```python
import torch

def _softmax(x, axis=-1):
    return torch.softmax(x, dim=axis)

def _gelu(x):
    return torch.nn.functional.gelu(x, approximate='tanh')

def _silu(x):
    return torch.nn.functional.silu(x)

def _sigmoid(x):
    return torch.sigmoid(x)

def _layernorm(x, axis=-1, eps=1e-05):
    m = x.mean(dim=axis, keepdim=True)
    v = x.var(dim=axis, keepdim=True, unbiased=False)
    return (x - m) / torch.sqrt(v + eps)

def _scatter_add(tgt, idx, src, axis=0):
    return tgt.clone().index_add_(axis, idx, src)

def _segment_sum(src, seg, n):
    out = torch.zeros((n,) + src.shape[1:], dtype=src.dtype)
    return out.index_add_(0, seg, src)

def _pad(x, pw):
    flat = tuple((v for pair in reversed(pw) for v in pair))
    return torch.nn.functional.pad(x, flat)
kernel_name = 'adaLN_cond__memory_aug_recurrent_mem_tr__moe_arch_mod__prompt'

def setup_inputs():

    _w = lambda a: (lambda t: t.to(torch.bfloat16) if t.is_floating_point() else t)(torch.as_tensor(a))

    def _A_setup():
        B, S, Dm = (1, 2048, 640)
        H, Dh = (32, 192)
        M, seg = (8, 32)
        seg = min(seg, S)
        S = S // seg * seg
        return {'x': _w((lambda *s: torch.randn(*s, dtype=torch.bfloat16) * 0.05)(B, S, Dm)), 'mem0': _w((lambda *s: torch.randn(*s, dtype=torch.bfloat16) * 0.4)(B, M, Dm)), 'Wq': _w((lambda *s: torch.randn(*s, dtype=torch.bfloat16) * 3.2)(Dm, H, Dh) * Dm ** (-0.5)), 'Wk': _w((lambda *s: torch.randn(*s, dtype=torch.bfloat16) * 3.2)(Dm, H, Dh) * Dm ** (-0.5)), 'Wv': _w((lambda *s: torch.randn(*s, dtype=torch.bfloat16) * 0.4)(Dm, H, Dh) * Dm ** (-0.5)), 'Wo': _w((lambda *s: torch.randn(*s, dtype=torch.bfloat16) * 0.4)(H, Dh, Dm) * (H * Dh) ** (-0.5)), 'seg_len': seg}
    _A_in = _A_setup()

    def _B_setup():
        B, S, D, F, C = (1, 2048, 640, 1536, 8)
        return {'x': _w((lambda *s: torch.randn(*s, dtype=torch.bfloat16) * 0.05)(B, S, D)), 'w_r': _w((lambda *s: torch.randn(*s, dtype=torch.bfloat16) * 0.05)(D)), 'w_gate': _w((lambda *s: torch.randn(*s, dtype=torch.bfloat16) * 0.05)(D, F)), 'w_up': _w((lambda *s: torch.randn(*s, dtype=torch.bfloat16) * 0.05)(D, F)), 'w_down': _w((lambda *s: torch.randn(*s, dtype=torch.bfloat16) * 0.05)(F, D))}
    _B_in = _B_setup()
    return {'A_x': _A_in['x'], 'A_mem0': _A_in['mem0'], 'A_Wq': _A_in['Wq'], 'A_Wk': _A_in['Wk'], 'A_Wv': _A_in['Wv'], 'A_Wo': _A_in['Wo'], 'A_seg_len': _A_in['seg_len'], 'B_x': _B_in['x'], 'B_w_r': _B_in['w_r'], 'B_w_gate': _B_in['w_gate'], 'B_w_up': _B_in['w_up'], 'B_w_down': _B_in['w_down'], 'c': _w((lambda *s: torch.randn(*s, dtype=torch.bfloat16) * 0.05)(1, 640) * 8.0), 'w_mod': _w((lambda *s: torch.randn(*s, dtype=torch.bfloat16) * 0.05)(640, 6 * 640) * 640 ** (-0.5) * 8.0)}

def reference(A_x, A_mem0, A_Wq, A_Wk, A_Wv, A_Wo, A_seg_len, B_x, B_w_r, B_w_gate, B_w_up, B_w_down, c, w_mod):

    def _A_ref(x, mem0, Wq, Wk, Wv, Wo, seg_len):
        B, S, Dm = x.shape
        H, Dh = (Wq.shape[1], Wq.shape[2])
        M = mem0.shape[1]
        scale = Dh ** (-0.5)
        n_seg = S // seg_len
        L = M + seg_len
        idx = torch.arange(L)
        mask = (idx[:, None] < M) | (idx[:, None] >= idx[None, :])
        mem = mem0
        outs = []
        for s in range(n_seg):
            xs = x[:, s * seg_len:(s + 1) * seg_len, :].clone()
            h = torch.concatenate([mem, xs], axis=1)
            q = torch.einsum('btd,dhe->bhte', h, Wq)
            k = torch.einsum('btd,dhe->bhte', h, Wk)
            v = torch.einsum('btd,dhe->bhte', h, Wv)
            scores = torch.einsum('bhqe,bhke->bhqk', q, k) * scale
            scores = torch.where(mask[None, None], scores, -1000000000.0)
            p = _softmax(scores, axis=-1)
            o = torch.einsum('bhqk,bhke->bhqe', p, v)
            o = torch.einsum('bhte,hed->btd', o, Wo)
            mem = o[:, :M, :].clone()
            outs.append(o[:, M:, :])
        return torch.concatenate(outs, axis=1)

    def _B_ref(x, w_r, w_gate, w_up, w_down):
        B, S, D = x.shape
        C = 8
        r = x @ w_r
        idx = torch.argsort(-r, axis=-1)[:, :C]
        idx_e = (lambda x, n, axis: torch.repeat_interleave(x, n, dim=axis))(idx.reshape(B, C, 1), D, axis=2)
        x_sel = (lambda x, i, axis: torch.take_along_dim(x, i, dim=axis))(x, idx_e, axis=1)
        g = _silu(x_sel @ w_gate)
        u = x_sel @ w_up
        y = g * u @ w_down
        r_sel = _sigmoid((lambda x, i, axis: torch.take_along_dim(x, i, dim=axis))(r, idx, axis=1))
        y = y * r_sel.reshape(B, C, 1)
        b_off = (torch.arange(B) * S).reshape(B, 1)
        flat_idx = (idx + b_off).reshape(B * C)
        zero = (x * 0.0).reshape(B * S, D)
        upd = _scatter_add(zero, flat_idx, y.reshape(B * C, D), axis=0)
        return x + upd.reshape(B, S, D)
    x = A_x
    mod = (_silu(c) @ w_mod).reshape(c.shape[0], 6, 1, -1)
    sa, ca, ga, sb, cb, gb = (mod[:, 0].clone(), mod[:, 1].clone(), mod[:, 2].clone(), mod[:, 3].clone(), mod[:, 4].clone(), mod[:, 5].clone())
    h = _layernorm(x, axis=-1) * (1 + ca) + sa
    x = x + ga * _A_ref(h, A_mem0, A_Wq, A_Wk, A_Wv, A_Wo, A_seg_len)
    h = _layernorm(x, axis=-1) * (1 + cb) + sb
    x = x + gb * _B_ref(h, B_w_r, B_w_gate, B_w_up, B_w_down)
    return x
```

```cpp
#include <cuda_runtime.h>
#include <cuda_bf16.h>
#include <cuda.h>
#include <stdint.h>
#include <stdio.h>
#include <string.h>
#include <stdlib.h>

typedef __nv_bfloat16 bf16;
constexpr int S_TOK = 2048, DM = 640, NH = 32, DH = 192, HD = NH * DH, NSEG = 64, SEG = 32, FF = 1536;

__device__ bf16 g_mod[6 * DM];
__device__ bf16 g_h[S_TOK * DM];
__device__ bf16 g_q[S_TOK * HD];
__device__ bf16 g_k[S_TOK * HD];
__device__ bf16 g_v[S_TOK * HD];
__device__ bf16 g_o[S_TOK * HD];
__device__ bf16 g_km[NSEG * NH * 8 * DH];
__device__ bf16 g_vm[NSEG * NH * 8 * DH];
__device__ bf16 g_A[S_TOK * DM];
__device__ bf16 g_x1[S_TOK * DM];
__device__ bf16 g_h2[S_TOK * DM];
__device__ bf16 g_r[S_TOK];
__device__ int g_idx[8];
__device__ __align__(128) uint32_t g_gu[FF / 8 * 32];
__device__ __align__(128) uint32_t g_memg[NSEG * 2560];
__device__ __align__(128) uint32_t g_part[80 * 32 * 32];
__device__ uint32_t g_stamp[NSEG * 96];
#define B_FINE 8
constexpr int KSPLIT = 16, SLABS = 3;
__device__ bf16 g_slab[SLABS * KSPLIT * 128 * DM];
struct __align__(128) BlockFlags {
    uint32_t qk, vb, c1, pad0;
    uint32_t at, c2, pad1[2];
    uint32_t o, c3, pad2[2];
    uint32_t ln, c0, pad3[18];
};
struct __align__(128) Flags {
    BlockFlags b[16];
    uint32_t v[16 * 32];
    uint32_t seg[64 * 32];
    uint32_t pair[16 * 16];
    uint32_t mod, h, pad1[30], gu, pad2[31], done, pad3[31];
};
__device__ Flags g_flags;

__device__ __forceinline__ uint32_t smem_u32(const void* p) { return (uint32_t)__cvta_generic_to_shared(p); }
__device__ __forceinline__ uint32_t pack2(float lo, float hi) {
    uint32_t r; asm("cvt.rn.bf16x2.f32 %0, %1, %2;" : "=r"(r) : "f"(hi), "f"(lo)); return r;
}
__device__ __forceinline__ float bfr(float x) { return __uint_as_float(pack2(0.f, x)); }
__device__ __forceinline__ float inv_std(float var) {
    float s, r; asm("sqrt.approx.f32 %0, %1;" : "=f"(s) : "f"(bfr(bfr(var) + 1e-5f))); asm("rcp.approx.f32 %0, %1;" : "=f"(r) : "f"(bfr(s))); return r;
}
__device__ __forceinline__ float lo_f(uint32_t v) { return __uint_as_float(v << 16); }
__device__ __forceinline__ float hi_f(uint32_t v) { return __uint_as_float(v & 0xffff0000u); }
__device__ __forceinline__ void mbar_init(uint32_t bar, int cnt) { asm volatile("mbarrier.init.shared::cta.b64 [%0], %1;" :: "r"(bar), "r"(cnt) : "memory"); }
__device__ __forceinline__ void mbar_expect(uint32_t bar, int bytes) { asm volatile("mbarrier.arrive.expect_tx.shared::cta.b64 _, [%0], %1;" :: "r"(bar), "r"(bytes) : "memory"); }
__device__ __forceinline__ void mbar_arrive(uint32_t bar) { asm volatile("mbarrier.arrive.shared::cta.b64 _, [%0];" :: "r"(bar) : "memory"); }
__device__ __forceinline__ bool mbar_try(uint32_t bar, int par) {
    uint32_t ok; asm volatile("{ .reg .pred p; mbarrier.try_wait.parity.shared::cta.b64 p, [%1], %2; selp.u32 %0, 1, 0, p; }" : "=r"(ok) : "r"(bar), "r"(par) : "memory"); return ok;
}
__device__ __forceinline__ bool mbar_try_cluster(uint32_t bar, int par) {
    uint32_t ok; asm volatile("{ .reg .pred p; mbarrier.try_wait.parity.acquire.cluster.shared::cta.b64 p, [%1], %2; selp.u32 %0, 1, 0, p; }" : "=r"(ok) : "r"(bar), "r"(par) : "memory"); return ok;
}
__device__ __forceinline__ bool mbar_test(uint32_t bar, uint32_t par) {
    uint32_t ok; asm volatile("{ .reg .pred p; mbarrier.test_wait.parity.shared::cta.b64 p, [%1], %2; selp.u32 %0, 1, 0, p; }" : "=r"(ok) : "r"(bar), "r"(par) : "memory"); return ok;
}
constexpr int SPIN_LIMIT = 1 << 18;
__device__ __forceinline__ void mbar_wait(uint32_t bar, uint32_t par) {
    asm volatile("{ .reg .pred p, q; .reg .u32 n; mov.u32 n, 0;\n"
                 "W_%=: mbarrier.try_wait.parity.shared::cta.b64 p, [%0], %1;\n"
                 "@p bra.uni D_%=;\n"
                 "add.u32 n, n, 1; setp.lt.u32 q, n, 0x200000; @q bra.uni W_%=;\n"
                 "trap;\n"
                 "D_%=: }" :: "r"(bar), "r"(par) : "memory");
}
__device__ __forceinline__ void tma2d(uint32_t dst, const CUtensorMap* m, int c0, int c1, uint32_t bar) {
    asm volatile("cp.async.bulk.tensor.2d.shared::cluster.global.mbarrier::complete_tx::bytes [%0], [%1, {%3, %4}], [%2];"
        :: "r"(dst), "l"((uint64_t)m), "r"(bar), "r"(c0), "r"(c1) : "memory");
}
__device__ __forceinline__ void tma2d_mc(uint32_t dst, const CUtensorMap* m, int c0, int c1, uint32_t bar, uint16_t mask) {
    asm volatile("cp.async.bulk.tensor.2d.shared::cluster.global.mbarrier::complete_tx::bytes.multicast::cluster [%0], [%1, {%3, %4}], [%2], %5;"
        :: "r"(dst), "l"((uint64_t)m), "r"(bar), "r"(c0), "r"(c1), "h"(mask) : "memory");
}
__device__ __forceinline__ uint64_t policy_stream() { uint64_t p; asm("createpolicy.fractional.L2::evict_first.b64 %0, 1.0;" : "=l"(p)); return p; }
__device__ __forceinline__ void tma2d_ef(uint32_t dst, const CUtensorMap* m, int c0, int c1, uint32_t bar, uint64_t pol) {
    asm volatile("cp.async.bulk.tensor.2d.shared::cluster.global.mbarrier::complete_tx::bytes.L2::cache_hint [%0], [%1, {%3, %4}], [%2], %5;"
        :: "r"(dst), "l"((uint64_t)m), "r"(bar), "r"(c0), "r"(c1), "l"(pol) : "memory");
}
__device__ __forceinline__ void tma3d(uint32_t dst, const CUtensorMap* m, int row, int chunk, uint32_t bar) {
    asm volatile("cp.async.bulk.tensor.3d.shared::cluster.global.mbarrier::complete_tx::bytes [%0], [%1, {0, %3, %4}], [%2];"
        :: "r"(dst), "l"((uint64_t)m), "r"(bar), "r"(row), "r"(chunk) : "memory");
}
__device__ __forceinline__ void tma3d_ef(uint32_t dst, const CUtensorMap* m, int row, int chunk, uint32_t bar, uint64_t pol) {
    asm volatile("cp.async.bulk.tensor.3d.shared::cluster.global.mbarrier::complete_tx::bytes.L2::cache_hint [%0], [%1, {0, %3, %4}], [%2], %5;"
        :: "r"(dst), "l"((uint64_t)m), "r"(bar), "r"(row), "r"(chunk), "l"(pol) : "memory");
}
__device__ __forceinline__ void tma3d_store(const CUtensorMap* m, int row, int chunk, uint32_t src, uint64_t pol, bool hint) {
    if (hint) asm volatile("cp.async.bulk.tensor.3d.global.shared::cta.bulk_group.L2::cache_hint [%0, {0, %2, %3}], [%1], %4;"
        :: "l"((uint64_t)m), "r"(src), "r"(row), "r"(chunk), "l"(pol) : "memory");
    else asm volatile("cp.async.bulk.tensor.3d.global.shared::cta.bulk_group [%0, {0, %2, %3}], [%1];"
        :: "l"((uint64_t)m), "r"(src), "r"(row), "r"(chunk) : "memory");
}
__device__ __forceinline__ bool elect() { uint32_t p; asm volatile("{ .reg .pred e; elect.sync _|e, -1; selp.u32 %0, 1, 0, e; }" : "=r"(p)); return p; }
__device__ __forceinline__ uint2 ld_ef(const void* p, uint64_t pol) {
    uint2 v; asm volatile("ld.relaxed.gpu.global.L2::cache_hint.v2.u32 {%0,%1}, [%2], %3;" : "=r"(v.x), "=r"(v.y) : "l"(p), "l"(pol)); return v;
}
__device__ __forceinline__ void st_ef(void* p, uint2 v, uint64_t pol) {
    asm volatile("st.global.L2::cache_hint.v2.u32 [%0], {%1,%2}, %3;" :: "l"(p), "r"(v.x), "r"(v.y), "l"(pol) : "memory");
}
__device__ __forceinline__ void tma2d_prefetch(const CUtensorMap* m, int c0, int c1) {
    asm volatile("cp.async.bulk.prefetch.tensor.2d.L2.global [%0, {%1, %2}];" :: "l"((uint64_t)m), "r"(c0), "r"(c1) : "memory");
}
__device__ __forceinline__ void mbar_arrive_remote(uint32_t bar) { asm volatile("mbarrier.arrive.relaxed.cluster.shared::cluster.b64 _, [%0];" :: "r"(bar) : "memory"); }
__device__ __forceinline__ void tma2d_store(const CUtensorMap* m, int c0, int c1, uint32_t src) {
    asm volatile("cp.async.bulk.tensor.2d.global.shared::cta.bulk_group [%0, {%2, %3}], [%1];"
        :: "l"((uint64_t)m), "r"(src), "r"(c0), "r"(c1) : "memory");
}
__device__ __forceinline__ void bulk_g2s(uint32_t dst, const void* src, int bytes, uint32_t bar) {
    asm volatile("cp.async.bulk.shared::cluster.global.mbarrier::complete_tx::bytes [%0], [%1], %2, [%3];" :: "r"(dst), "l"(src), "r"(bytes), "r"(bar) : "memory");
}
__device__ __forceinline__ void ldsm4(uint32_t (&r)[4], uint32_t a) {
    asm volatile("ldmatrix.sync.aligned.m8n8.x4.shared.b16 {%0,%1,%2,%3}, [%4];" : "=r"(r[0]), "=r"(r[1]), "=r"(r[2]), "=r"(r[3]) : "r"(a) : "memory");
}
__device__ __forceinline__ void ldsm4t(uint32_t (&r)[4], uint32_t a) {
    asm volatile("ldmatrix.sync.aligned.m8n8.x4.trans.shared.b16 {%0,%1,%2,%3}, [%4];" : "=r"(r[0]), "=r"(r[1]), "=r"(r[2]), "=r"(r[3]) : "r"(a) : "memory");
}
__device__ __forceinline__ void stsm4(uint32_t a, uint32_t r0, uint32_t r1, uint32_t r2, uint32_t r3) {
    asm volatile("stmatrix.sync.aligned.m8n8.x4.shared.b16 [%0], {%1,%2,%3,%4};" :: "r"(a), "r"(r0), "r"(r1), "r"(r2), "r"(r3) : "memory");
}
__device__ __forceinline__ void stsm4t(uint32_t a, uint32_t r0, uint32_t r1, uint32_t r2, uint32_t r3) {
    asm volatile("stmatrix.sync.aligned.m8n8.x4.trans.shared.b16 [%0], {%1,%2,%3,%4};" :: "r"(a), "r"(r0), "r"(r1), "r"(r2), "r"(r3) : "memory");
}
__device__ __forceinline__ void stsm2t(uint32_t a, uint32_t r0, uint32_t r1) {
    asm volatile("stmatrix.sync.aligned.m8n8.x2.trans.shared.b16 [%0], {%1,%2};" :: "r"(a), "r"(r0), "r"(r1) : "memory");
}
__device__ __forceinline__ uint32_t movm_t(uint32_t v) { uint32_t r; asm volatile("movmatrix.sync.aligned.m8n8.trans.b16 %0, %1;" : "=r"(r) : "r"(v)); return r; }
__device__ __forceinline__ void mma16(float (&d)[4], uint32_t a0, uint32_t a1, uint32_t a2, uint32_t a3, uint32_t b0, uint32_t b1) {
    asm volatile("mma.sync.aligned.m16n8k16.row.col.f32.bf16.bf16.f32 {%0,%1,%2,%3}, {%4,%5,%6,%7}, {%8,%9}, {%0,%1,%2,%3};"
        : "+f"(d[0]), "+f"(d[1]), "+f"(d[2]), "+f"(d[3]) : "r"(a0), "r"(a1), "r"(a2), "r"(a3), "r"(b0), "r"(b1));
}
__device__ __forceinline__ void mma8(float (&d)[4], uint32_t a0, uint32_t a1, uint32_t b0) {
    asm volatile("mma.sync.aligned.m16n8k8.row.col.f32.bf16.bf16.f32 {%0,%1,%2,%3}, {%4,%5}, {%6}, {%0,%1,%2,%3};"
        : "+f"(d[0]), "+f"(d[1]), "+f"(d[2]), "+f"(d[3]) : "r"(a0), "r"(a1), "r"(b0));
}
__device__ __forceinline__ uint32_t mapa(uint32_t a, uint32_t r) { uint32_t o; asm volatile("mapa.shared::cluster.u32 %0, %1, %2;" : "=r"(o) : "r"(a), "r"(r)); return o; }
__device__ __forceinline__ void bar_sync(int id, int n) { asm volatile("bar.sync %0, %1;" :: "r"(id), "r"(n) : "memory"); }
__device__ __forceinline__ void bar_arrive(int id, int n) { asm volatile("bar.arrive %0, %1;" :: "r"(id), "r"(n) : "memory"); }
__device__ __forceinline__ uint64_t mkdesc(uint32_t addr, uint32_t lbo, uint32_t sbo) {
    return (uint64_t)((addr & 0x3FFFF) >> 4) | ((uint64_t)(lbo >> 4) << 16) | ((uint64_t)(sbo >> 4) << 32) | (1ull << 62);
}
#define WG_FENCE()  asm volatile("wgmma.fence.sync.aligned;" ::: "memory")
#define WG_COMMIT() asm volatile("wgmma.commit_group.sync.aligned;" ::: "memory")
#define WG_WAIT(n)  asm volatile("wgmma.wait_group.sync.aligned %0;" :: "n"(n) : "memory")

__device__ __forceinline__ void wgmma_ss_n192_tb(float (&d)[96], uint64_t a, uint64_t b, int acc) {
    asm volatile("{ .reg .pred p; setp.ne.b32 p, %98, 0;\n"
        "wgmma.mma_async.sync.aligned.m64n192k16.f32.bf16.bf16 {%0,%1,%2,%3,%4,%5,%6,%7,%8,%9,%10,%11,%12,%13,%14,%15,%16,%17,%18,%19,%20,%21,%22,%23,%24,%25,%26,%27,%28,%29,%30,%31,%32,%33,%34,%35,%36,%37,%38,%39,%40,%41,%42,%43,%44,%45,%46,%47,%48,%49,%50,%51,%52,%53,%54,%55,%56,%57,%58,%59,%60,%61,%62,%63,%64,%65,%66,%67,%68,%69,%70,%71,%72,%73,%74,%75,%76,%77,%78,%79,%80,%81,%82,%83,%84,%85,%86,%87,%88,%89,%90,%91,%92,%93,%94,%95}, %96, %97, p, 1, 1, 0, 1; }"
        : "+f"(d[0]), "+f"(d[1]), "+f"(d[2]), "+f"(d[3]), "+f"(d[4]), "+f"(d[5]), "+f"(d[6]), "+f"(d[7]), "+f"(d[8]), "+f"(d[9]), "+f"(d[10]), "+f"(d[11]), "+f"(d[12]), "+f"(d[13]), "+f"(d[14]), "+f"(d[15]), "+f"(d[16]), "+f"(d[17]), "+f"(d[18]), "+f"(d[19]), "+f"(d[20]), "+f"(d[21]), "+f"(d[22]), "+f"(d[23]), "+f"(d[24]), "+f"(d[25]), "+f"(d[26]), "+f"(d[27]), "+f"(d[28]), "+f"(d[29]), "+f"(d[30]), "+f"(d[31]), "+f"(d[32]), "+f"(d[33]), "+f"(d[34]), "+f"(d[35]), "+f"(d[36]), "+f"(d[37]), "+f"(d[38]), "+f"(d[39]), "+f"(d[40]), "+f"(d[41]), "+f"(d[42]), "+f"(d[43]), "+f"(d[44]), "+f"(d[45]), "+f"(d[46]), "+f"(d[47]), "+f"(d[48]), "+f"(d[49]), "+f"(d[50]), "+f"(d[51]), "+f"(d[52]), "+f"(d[53]), "+f"(d[54]), "+f"(d[55]), "+f"(d[56]), "+f"(d[57]), "+f"(d[58]), "+f"(d[59]), "+f"(d[60]), "+f"(d[61]), "+f"(d[62]), "+f"(d[63]), "+f"(d[64]), "+f"(d[65]), "+f"(d[66]), "+f"(d[67]), "+f"(d[68]), "+f"(d[69]), "+f"(d[70]), "+f"(d[71]), "+f"(d[72]), "+f"(d[73]), "+f"(d[74]), "+f"(d[75]), "+f"(d[76]), "+f"(d[77]), "+f"(d[78]), "+f"(d[79]), "+f"(d[80]), "+f"(d[81]), "+f"(d[82]), "+f"(d[83]), "+f"(d[84]), "+f"(d[85]), "+f"(d[86]), "+f"(d[87]), "+f"(d[88]), "+f"(d[89]), "+f"(d[90]), "+f"(d[91]), "+f"(d[92]), "+f"(d[93]), "+f"(d[94]), "+f"(d[95])
        : "l"(a), "l"(b), "r"(acc));
}

__device__ __forceinline__ void wgmma_ss_n128_tb(float (&d)[64], uint64_t a, uint64_t b, int acc) {
    asm volatile("{ .reg .pred p; setp.ne.b32 p, %66, 0;\n"
        "wgmma.mma_async.sync.aligned.m64n128k16.f32.bf16.bf16 {%0,%1,%2,%3,%4,%5,%6,%7,%8,%9,%10,%11,%12,%13,%14,%15,%16,%17,%18,%19,%20,%21,%22,%23,%24,%25,%26,%27,%28,%29,%30,%31,%32,%33,%34,%35,%36,%37,%38,%39,%40,%41,%42,%43,%44,%45,%46,%47,%48,%49,%50,%51,%52,%53,%54,%55,%56,%57,%58,%59,%60,%61,%62,%63}, %64, %65, p, 1, 1, 0, 1; }"
        : "+f"(d[0]), "+f"(d[1]), "+f"(d[2]), "+f"(d[3]), "+f"(d[4]), "+f"(d[5]), "+f"(d[6]), "+f"(d[7]), "+f"(d[8]), "+f"(d[9]), "+f"(d[10]), "+f"(d[11]), "+f"(d[12]), "+f"(d[13]), "+f"(d[14]), "+f"(d[15]), "+f"(d[16]), "+f"(d[17]), "+f"(d[18]), "+f"(d[19]), "+f"(d[20]), "+f"(d[21]), "+f"(d[22]), "+f"(d[23]), "+f"(d[24]), "+f"(d[25]), "+f"(d[26]), "+f"(d[27]), "+f"(d[28]), "+f"(d[29]), "+f"(d[30]), "+f"(d[31]), "+f"(d[32]), "+f"(d[33]), "+f"(d[34]), "+f"(d[35]), "+f"(d[36]), "+f"(d[37]), "+f"(d[38]), "+f"(d[39]), "+f"(d[40]), "+f"(d[41]), "+f"(d[42]), "+f"(d[43]), "+f"(d[44]), "+f"(d[45]), "+f"(d[46]), "+f"(d[47]), "+f"(d[48]), "+f"(d[49]), "+f"(d[50]), "+f"(d[51]), "+f"(d[52]), "+f"(d[53]), "+f"(d[54]), "+f"(d[55]), "+f"(d[56]), "+f"(d[57]), "+f"(d[58]), "+f"(d[59]), "+f"(d[60]), "+f"(d[61]), "+f"(d[62]), "+f"(d[63])
        : "l"(a), "l"(b), "r"(acc));
}

__device__ __forceinline__ void wgmma_rs_n32(float (&d)[16], const uint32_t (&a)[4], uint64_t b, int acc) {
    asm volatile("{ .reg .pred p; setp.ne.b32 p, %21, 0;\n"
        "wgmma.mma_async.sync.aligned.m64n32k16.f32.bf16.bf16 {%0,%1,%2,%3,%4,%5,%6,%7,%8,%9,%10,%11,%12,%13,%14,%15}, {%16,%17,%18,%19}, %20, p, 1, 1, 0; }"
        : "+f"(d[0]), "+f"(d[1]), "+f"(d[2]), "+f"(d[3]), "+f"(d[4]), "+f"(d[5]), "+f"(d[6]), "+f"(d[7]), "+f"(d[8]), "+f"(d[9]), "+f"(d[10]), "+f"(d[11]), "+f"(d[12]), "+f"(d[13]), "+f"(d[14]), "+f"(d[15])
        : "r"(a[0]), "r"(a[1]), "r"(a[2]), "r"(a[3]), "l"(b), "r"(acc));
}

__device__ __forceinline__ float warp_sum(float v) {
#pragma unroll
    for (int o = 16; o; o >>= 1) v += __shfl_xor_sync(0xffffffffu, v, o);
    return v;
}
__device__ __forceinline__ void ln_mod(const float (&xv)[20], const uint32_t (&sv)[10], const uint32_t (&tv)[10], float (&hv)[20]) {
    float s = 0;
#pragma unroll
    for (int i = 0; i < 20; i++) s += xv[i];
    const float mean = warp_sum(s) * (1.f / DM);
    float q = 0;
#pragma unroll
    for (int i = 0; i < 20; i++) { float d = xv[i] - mean; q += d * d; }
    const float mb = bfr(mean), inv = inv_std(warp_sum(q) * (1.f / DM));
#pragma unroll
    for (int i = 0; i < 10; i++) {
        const float n0 = bfr(bfr(xv[2 * i] - mb) * inv), n1 = bfr(bfr(xv[2 * i + 1] - mb) * inv);
        hv[2 * i] = bfr(bfr(n0 * bfr(1.f + lo_f(sv[i]))) + lo_f(tv[i]));
        hv[2 * i + 1] = bfr(bfr(n1 * bfr(1.f + hi_f(sv[i]))) + hi_f(tv[i]));
    }
}
__device__ __forceinline__ uint32_t ld_rlx(const uint32_t* f) { uint32_t v; asm volatile("ld.relaxed.gpu.global.u32 %0, [%1];" : "=r"(v) : "l"(f) : "memory"); return v; }
__device__ __forceinline__ void bump(uint32_t* f) { asm volatile("red.relaxed.gpu.global.add.u32 [%0], 1;" :: "l"(f) : "memory"); }
__device__ __forceinline__ void flag_wait(const uint32_t* f, uint32_t target) {
    for (int n = 0;; n++) {
        uint32_t v; asm volatile("ld.relaxed.gpu.global.u32 %0, [%1];" : "=r"(v) : "l"(f) : "memory");
        if (v >= target) break;
        if (n > (1 << 23)) __trap();
    }
}
__device__ __forceinline__ void flag_add(uint32_t* f, uint32_t v = 1) { asm volatile("red.release.gpu.global.add.u32 [%0], %1;" :: "l"(f), "r"(v) : "memory"); }
constexpr int N_SIDE = 36;
__device__ __forceinline__ void flags_release() {
    uint32_t old; asm volatile("atom.acq_rel.gpu.global.add.u32 %0, [%1], 1;" : "=r"(old) : "l"(&g_flags.done) : "memory");
    if (old == 96 + N_SIDE - 1) for (int i = 0; i < (int)(sizeof(Flags) / 16); i++) ((uint4*)&g_flags)[i] = make_uint4(0, 0, 0, 0);
}

struct ChainMaps { CUtensorMap wq, wk, wv, wo, h32, q32, k32, v32, wgate, wup, wdown, wmod; };
struct ChainArgs { const bf16 *x, *mem0, *c, *wv, *wo; bf16* out; int D1, D2, DG; };
constexpr uint32_t SM_BASE = 1024;
#define NPRE 8
#define VGAP 20
#define XISS 4
#define XGAP 5
constexpr int NXR = 8;
constexpr int C_WV = 0, C_WO = 81920, C_XR = 167936, C_QX = C_XR + 2 * 4096, C_KX = C_XR + 3 * 4096, C_VX = C_XR + NXR * 4096, C_MEM = C_VX + 4096,
              C_QM = C_MEM + 10240, C_KM = C_QM + 1024, C_VP = C_KM + 1024, C_VM = C_VP + 4096, C_OX = C_VM + 1024, C_SC = C_OX + 3072, C_BAR = C_SC + 3840;
constexpr int CB_W = C_BAR, CB_W2 = C_BAR + 8, CB_SC = C_BAR + 16, CB_KX = C_BAR + 24, CB_VX = C_BAR + 32, CB_PRE = C_BAR + 40, CB_XD = C_BAR + 48, CB_OX = C_BAR + 56, CB_VP = C_BAR + 64,
              CB_MEM = C_BAR + 80, CB_XF = C_BAR + 112, CB_XE = C_BAR + 176, C_PACE = C_BAR + 192;
constexpr int C_SMEM = C_BAR + 256;
#define PROF(i)
#define PROFG(i)
#define PROFV(i, v)
static_assert(C_SMEM <= 232448, "chain shared memory");
__device__ __forceinline__ uint32_t umax3(uint32_t a, uint32_t b, uint32_t c) { return max(max(a, b), c); }
__device__ __forceinline__ void wait_until(uint32_t t) { while ((int32_t)((uint32_t)clock() - t) < 0) {} }
__device__ __forceinline__ uint32_t gtime() { uint32_t c; asm volatile("mov.u32 %0, %%globaltimer_lo;" : "=r"(c)); return c; }
__device__ __forceinline__ uint32_t opaque(uint32_t v) { uint32_t r; asm volatile("shfl.sync.bfly.b32 %0, %1, 0, 31, -1;" : "=r"(r) : "r"(v)); return r; }
__device__ __forceinline__ uint32_t lds32(uint32_t a) { uint32_t v; asm volatile("ld.shared.u32 %0, [%1];" : "=r"(v) : "r"(a) : "memory"); return v; }
__device__ __forceinline__ float2 lds64f(uint32_t a) { float2 v; asm volatile("ld.shared.v2.f32 {%0,%1}, [%2];" : "=f"(v.x), "=f"(v.y) : "r"(a) : "memory"); return v; }
__device__ __forceinline__ float4 lds128f(uint32_t a) { float4 v; asm volatile("ld.shared.v4.f32 {%0,%1,%2,%3}, [%4];" : "=f"(v.x), "=f"(v.y), "=f"(v.z), "=f"(v.w) : "r"(a) : "memory"); return v; }
__device__ __forceinline__ void sts128f(uint32_t a, float x, float y, float z, float w) { asm volatile("st.shared.v4.f32 [%0], {%1,%2,%3,%4};" :: "r"(a), "f"(x), "f"(y), "f"(z), "f"(w) : "memory"); }
__device__ __forceinline__ uint32_t xor_or(uint32_t a, uint32_t b, uint32_t t) { uint32_t r; asm("lop3.b32 %0, %1, %2, %3, 0x7e;" : "=r"(r) : "r"(a), "r"(b), "r"(t)); return r; }
__device__ __forceinline__ uint32_t or3(uint32_t a, uint32_t b, uint32_t c) { uint32_t r; asm("lop3.b32 %0, %1, %2, %3, 0xfe;" : "=r"(r) : "r"(a), "r"(b), "r"(c)); return r; }
__device__ __forceinline__ int mem_forward(uint32_t sm, int s, int j, uint32_t u, uint32_t t0, uint32_t g0) {
    const uint32_t off = j * 896 + u * 16;
    const bool mine = u < 56 && off < 2560;
    uint32_t todo = mine ? 15u : 0u, open = 15u;
    const uint8_t* src = (const uint8_t*)(g_memg + s * 2560) + off;
    const uint32_t r1 = mapa(sm, (j + 1) % 3), r2 = mapa(sm, (j + 2) % 3);
    uint4 v[4];
#pragma unroll
    for (int p = 0; p < 4; p++) v[p] = make_uint4(0, 0, 0, 0);
    auto send = [&](int p) {
        asm volatile("{ .reg .u32 a, b;\n"
            "add.u32 a, %0, %5; add.u32 b, %5, %8; st.async.shared::cluster.mbarrier::complete_tx::bytes.v4.b32 [a], {%1,%2,%3,%4}, [b];\n"
            "add.u32 a, %0, %6; add.u32 b, %6, %8; st.async.shared::cluster.mbarrier::complete_tx::bytes.v4.b32 [a], {%1,%2,%3,%4}, [b];\n"
            "add.u32 a, %0, %7; st.shared.v4.b32 [a], {%1,%2,%3,%4}; }"
            :: "r"(off + (C_MEM + p * 2560)), "r"(v[p].x), "r"(v[p].y), "r"(v[p].z), "r"(v[p].w), "r"(r1), "r"(r2), "r"(sm), "r"(CB_MEM + 8 * p) : "memory");
    };
    if (g0) { while ((int32_t)(gtime() - g0) < 0 && (int32_t)((uint32_t)clock() - t0) < 4000) {} }
    else wait_until(t0);
    for (int n = 0;; n++) {
#pragma unroll
        for (int p = 0; p < 4; p++)
            asm volatile("{ .reg .pred q; setp.ne.u32 q, %5, 0;\n@q ld.relaxed.gpu.global.v4.u32 {%0,%1,%2,%3}, [%4]; }"
                : "+r"(v[p].x), "+r"(v[p].y), "+r"(v[p].z), "+r"(v[p].w) : "l"(src + p * 2560), "r"(todo & (1u << p)) : "memory");
        uint32_t miss = 0;
#pragma unroll
        for (int p = 0; p < 4; p++) miss |= (umax3(umax3(v[p].x, v[p].y, v[p].z), v[p].w, 0u) == 0xffffffffu ? 1u : 0u) << p;
        if (n == 0 && !__any_sync(0xffffffffu, miss)) {
            if (mine) { send(0); send(1); send(2); send(3); }
            __syncwarp();
            if ((u & 31) < 4) mbar_arrive(sm + CB_MEM + 8 * (u & 31));
            return 0;
        }
        const uint32_t ok = todo & ~miss;
#pragma unroll
        for (int p = 0; p < 4; p++) if (ok & (1u << p)) send(p);
        todo &= miss;
        __syncwarp();
        const uint32_t left = __reduce_or_sync(0xffffffffu, todo);
        if ((u & 31) < 4 && ((open & ~left) >> (u & 31) & 1)) mbar_arrive(sm + CB_MEM + 8 * (u & 31));
        open = left;
        if (!left) return n;
        if (n > SPIN_LIMIT) __trap();
    }
}
__device__ __forceinline__ void wgmma_ss_n8_ta(float (&d)[4], uint64_t a, uint64_t b) {
    asm volatile("wgmma.mma_async.sync.aligned.m64n8k16.f32.bf16.bf16 {%0,%1,%2,%3}, %4, %5, 1, 1, 1, 1, 0;"
        : "+f"(d[0]), "+f"(d[1]), "+f"(d[2]), "+f"(d[3]) : "l"(a), "l"(b));
}
__device__ __forceinline__ void wgmma_ss_n8_ta_first(float (&d)[4], uint64_t a, uint64_t b) {
    asm volatile("wgmma.mma_async.sync.aligned.m64n8k16.f32.bf16.bf16 {%0,%1,%2,%3}, %4, %5, 0, 1, 1, 1, 0;"
        : "=f"(d[0]), "=f"(d[1]), "=f"(d[2]), "=f"(d[3]) : "l"(a), "l"(b));
}
__device__ __forceinline__ void score_tile(const uint32_t (&qa)[4][4], const uint32_t (&kb)[2][4], bool odd, float (&x)[4]) {
    float sc[2][4] = {{0, 0, 0, 0}, {0, 0, 0, 0}};
#pragma unroll
    for (int k = 0; k < 4; k++) mma16(sc[k & 1], qa[k][0], qa[k][1], qa[k][2], qa[k][3], kb[k >> 1][2 * (k & 1)], kb[k >> 1][2 * (k & 1) + 1]);
    float a = sc[0][0] + sc[1][0], b = sc[0][1] + sc[1][1];
    float c = __shfl_xor_sync(0xffffffffu, a, 1), d = __shfl_xor_sync(0xffffffffu, b, 1);
    x[0] = odd ? c : a; x[1] = odd ? d : b; x[2] = odd ? a : c; x[3] = odd ? b : d;
}
__device__ __forceinline__ void send_piece(const float (&x)[4], uint32_t rdst, uint32_t rbar, uint32_t ldst) {
    asm volatile("st.async.shared::cluster.mbarrier::complete_tx::bytes.v4.f32 [%0], {%1,%2,%3,%4}, [%5];"
        :: "r"(rdst), "f"(x[0]), "f"(x[1]), "f"(x[2]), "f"(x[3]), "r"(rbar) : "memory");
    sts128f(ldst, x[0], x[1], x[2], x[3]);
}

__device__ __forceinline__ void x_part(const uint32_t (&wa)[40][4], const ChainMaps& mp, uint32_t sm, int n, int wg, int w, uint32_t ln, int col0, int j) {
    const int s = n - 1; const bool lane0 = ln == 0; (void)s; (void)lane0;
    float acc[16];
#pragma unroll
    for (int i = 0; i < 16; i++) acc[i] = 0.f;
    const bool issuer = wg == 1 && w == 1 && ln == 0;
    const uint64_t xd = mkdesc(SM_BASE + C_XR, 16, 1024);
    if (wg == 0 && w == 0) PROF(12);
    mbar_wait(sm + CB_XF, n & 1);
#pragma unroll
    for (int c = 0; c < 10; c++) {
        if (c >= NXR) mbar_wait(sm + CB_XF + 8 * (1 + c - NXR), n & 1);
        if (c == XGAP && n > 0) bar_sync(9, 288);
        WG_FENCE();
#pragma unroll
        for (int ks = 0; ks < 4; ks++)
            wgmma_rs_n32(acc, wa[4 * c + ks], xd + (((c % NXR) * 4096 + ks * 32) >> 4), 1);
        if (c <= 10 - NXR) {
            WG_COMMIT();
            if (c >= 1) {
                WG_WAIT(1);
                if (w == 0 && ln == 0) mbar_arrive_remote(mapa(sm + CB_XE + 8 * (c - 1), c - 1));
                __syncwarp();
            }
        }
        if (c == XISS - 1) {
            if (issuer) {
#pragma unroll
                for (int f = 0; f < 10 - NXR; f++) mbar_expect(sm + CB_XF + 8 * (1 + f), 4096);
                if (j < 10 - NXR) {
                    mbar_wait(sm + CB_XE + 8 * j, n & 1);
                    tma2d_mc(sm + C_XR + j * 4096, &mp.h32, (j + NXR) * 64, n * SEG, sm + CB_XF + 8 * (1 + j), 7);
                }
            }
            __syncwarp();
        }
    }
    WG_COMMIT();
    WG_WAIT(0);
    if (wg == 0 && w == 0) PROF(30);
    bar_sync(8, 256);
    if (wg == 1 && w == 1 && ln < 3) mbar_arrive_remote(mapa(sm + CB_XD, ln));
    const uint32_t r = ln & 7, mi = ln >> 3, dst = sm + (wg == 0 ? C_QX : C_KX) + ((mi >> 1) * 8 + r) * 128 + (((2 * w + (mi & 1)) ^ r) << 4);
#pragma unroll
    for (int p = 0; p < 2; p++)
        stsm4t(dst + p * 2048, pack2(acc[8 * p], acc[8 * p + 1]), pack2(acc[8 * p + 2], acc[8 * p + 3]), pack2(acc[8 * p + 4], acc[8 * p + 5]), pack2(acc[8 * p + 6], acc[8 * p + 7]));
    asm volatile("fence.proxy.async.shared::cta;" ::: "memory");
    bar_sync(6 + wg, 128);
    if (w == 0 && ln == 0) {
        if (wg == 1) mbar_arrive(sm + CB_KX);
        tma2d_store(wg == 0 ? &mp.q32 : &mp.k32, col0, n * SEG, sm + (wg == 0 ? C_QX : C_KX));
        asm volatile("cp.async.bulk.commit_group;" ::: "memory");
    }
    if (issuer && n + 1 < NSEG) {
        mbar_wait(sm + CB_XD, n & 1);
#pragma unroll
        for (int c = 0; c < 2; c++) { const int sl = (j ? 2 * j + 2 : 0) + c; tma2d_mc(sm + C_XR + sl * 4096, &mp.h32, sl * 64, (n + 1) * SEG, sm + CB_XF, 7); }
    }
    __syncwarp();
}
__device__ __forceinline__ void x_prefetch(const ChainMaps& mp, uint32_t sm, int n, int j) {
    mbar_expect(sm + CB_XF, NXR * 4096);
    if (n == 0) {
#pragma unroll 1
        for (int c = 0; c < 2; c++) { const int sl = (j ? 2 * j + 2 : 0) + c; tma2d_mc(sm + C_XR + sl * 4096, &mp.h32, sl * 64, 0, sm + CB_XF, 7); }
    }
    if (j < 2) tma2d_mc(sm + C_XR + (2 + j) * 4096, &mp.h32, (2 + j) * 64, n * SEG, sm + CB_XF, 7);
    if (blockIdx.x < 10 - NXR)
        tma2d_prefetch(&mp.h32, (NXR + (int)blockIdx.x) * 64, n * SEG);
}

__global__ void __cluster_dims__(3, 1, 1) __launch_bounds__(384, 1) k_chain(const __grid_constant__ ChainMaps mp, const __grid_constant__ ChainArgs ar) {
    const int D1 = ar.D1, D2 = ar.D2, DG = ar.DG;
    extern __shared__ __align__(1024) uint8_t smraw[];
    const uint32_t sm = SM_BASE + ((blockIdx.x % 3) << 24);
    if (smem_u32(smraw) != sm) __trap();
    uint32_t tid; asm volatile("mov.u32 %0, %%tid.x;" : "=r"(tid));
    const int warp = __shfl_sync(0xffffffffu, tid >> 5, 0), lane = tid & 31, wg = warp >> 2, w = warp & 3;
    const int blk = blockIdx.x, head = blk / 3, j = blk % 3;
    const int col0 = head * DH + j * 64;
    const int mt0 = j == 0 ? 0 : j == 1 ? 14 : 27, nmt = j == 0 ? 14 : 13;
    asm volatile("griddepcontrol.launch_dependents;");
#define PPROF(i)
    {
        const int mc0 = (blk >> 1) * 80 + (blk & 1) * 32, mcn = (blk & 1) ? 24 : 16;
        const int nrow = blk < 74 ? 2 : blk == 74 ? (warp < 8 ? 2 : 1) : 1;
        if (tid == 0) {
            mbar_init(sm + CB_PRE, 1);
            asm volatile("fence.mbarrier_init.release.cluster;" ::: "memory");
            const int n1 = blk < 74 ? 15360 : blk == 74 ? 10240 : 0;
            mbar_expect(sm + CB_PRE, 61440 + 1280 + 15360 + n1);
            bulk_g2s(sm + C_QM, ar.c, 1280, sm + CB_PRE);
#pragma unroll 1
            for (int c = 0; c < 4; c++) tma2d(sm + C_WO + 24576 + c * 15360, &mp.wmod, mc0, c * 160, sm + CB_PRE);
            bulk_g2s(sm + C_XR, ar.x + blk * 12 * DM, 15360, sm + CB_PRE);
            if (n1) bulk_g2s(sm + C_XR + 15360, ar.x + (1152 + blk * 12) * DM, n1, sm + CB_PRE);
        }
        if (tid == 32) {
#pragma unroll 1
            for (int c = 0; c < 24; c++) if (c != 5) mbar_init(sm + C_BAR + 8 * c, c == 2 || c == 7 ? 5 : c == 8 ? 8 : (c == 6 || (c >= 10 && c < 14)) ? 3 : c >= 22 ? 6 : 1);
            asm volatile("fence.mbarrier_init.release.cluster;" ::: "memory");
            mbar_expect(sm + CB_SC, 2560); mbar_expect(sm + CB_OX, 2048);
#pragma unroll 1
            for (int c = 0; c < 4; c++) mbar_expect(sm + CB_MEM + 8 * c, j == 2 ? 2560 - 768 : 2560 - 896);
        }
#pragma unroll 1
        for (int i = blk * 384 + tid; i < NSEG * 640; i += 96 * 384)
            ((uint4*)g_memg)[i] = i < 640 ? __ldg((const uint4*)(ar.mem0 + (i & 7) * DM + (i >> 3) * 8)) : make_uint4(~0u, ~0u, ~0u, ~0u);
        if (blk * 384 + tid < 80 * 32 * 8) ((uint4*)g_part)[blk * 384 + tid] = make_uint4(0, 0, 0, 0);
        PPROF(8);
        asm volatile("barrier.cluster.arrive.release.aligned; barrier.cluster.wait.acquire.aligned;" ::: "memory");
        PPROF(9);
        mbar_wait(sm + CB_PRE, 0);
        PPROF(10);
        if (tid == 352) {
            const uint64_t ef = policy_stream();
            mbar_expect(sm + CB_W, 2 * 81920);
#pragma unroll 1
            for (int c = 0; c < 10; c++) tma2d_ef(sm + C_WV + c * 8192, &mp.wq, col0, c * 64, sm + CB_W, ef);
        }
        if (tid < 320) {
            const uint32_t cv = lds32(sm + C_QM + tid * 4);
            asm volatile("st.shared.v2.f32 [%0], {%1,%2};" :: "r"(sm + C_VP + tid * 8), "f"(bfr(__fdividef(lo_f(cv), 1.f + __expf(-lo_f(cv))))),
                         "f"(bfr(__fdividef(hi_f(cv), 1.f + __expf(-hi_f(cv))))) : "memory");
        }
        __syncthreads();
        {
            float a0 = 0, a1 = 0;
            const uint32_t k0 = (tid / 24) * 40, wa0 = sm + C_WO + 24576 + k0 * 96 + (tid % 24) * 4;
#pragma unroll 4
            for (int i = 0; i < 40; i++) {
                const float sc = __uint_as_float(lds32(sm + C_VP + (k0 + i) * 4));
                const uint32_t wv = lds32(wa0 + i * 96);
                a0 += sc * lo_f(wv); a1 += sc * hi_f(wv);
            }
            asm volatile("st.shared.v2.f32 [%0], {%1,%2};" :: "r"(sm + C_MEM + tid * 8), "f"(a0), "f"(a1) : "memory");
        }
        __syncthreads();
        PPROF(11);
        if (warp == 0) {
            float a0 = 0, a1 = 0;
            const int cp = lane < mcn ? lane : 0;
#pragma unroll 4
            for (int i = 0; i < 16; i++) { const float2 v = lds64f(sm + C_MEM + (i * 24 + cp) * 8); a0 += v.x; a1 += v.y; }
            uint32_t* dst = (uint32_t*)(g_mod + mc0) + cp;
            *dst = pack2(a0, a1);
            const uint32_t rb = ld_rlx(dst);
            PPROF(1);
            if (__all_sync(0xffffffffu, rb == pack2(a0, a1)) && tid == 0) bump(blk < 32 ? &g_flags.mod : &g_flags.h);
            if (tid == 0) flag_wait(&g_flags.mod, 32);
            PPROF(2);
        }
        __syncthreads();
        uint32_t sv[10], tv[10], bad = 0;
#pragma unroll
        for (int i = 0; i < 10; i++) { sv[i] = __ldcg((const uint32_t*)g_mod + DM / 2 + lane + 32 * i); tv[i] = __ldcg((const uint32_t*)g_mod + lane + 32 * i); }
#pragma unroll 1
        for (int q = 0; q < nrow; q++) {
            float xv[20], hv[20];
#pragma unroll
            for (int i = 0; i < 10; i++) { const uint32_t v = lds32(sm + C_XR + q * 15360 + warp * 1280 + lane * 4 + i * 128); xv[2 * i] = lo_f(v); xv[2 * i + 1] = hi_f(v); }
            ln_mod(xv, sv, tv, hv);
            uint32_t* dst = (uint32_t*)g_h + (q * 1152 + blk * 12 + warp) * (DM / 2) + lane;
#pragma unroll
            for (int i = 0; i < 10; i++) dst[32 * i] = pack2(hv[2 * i], hv[2 * i + 1]);
#pragma unroll
            for (int i = 0; i < 10; i++) bad |= ld_rlx(dst + 32 * i) ^ pack2(hv[2 * i], hv[2 * i + 1]);
        }
        if (__syncthreads_or(bad)) __trap();
        PPROF(3);
        if (tid == 0) {
            bump(&g_flags.h);
            flag_wait(&g_flags.h, 160);
            x_prefetch(mp, sm, 0, j);
            const uint64_t ef = policy_stream();
#pragma unroll 1
            for (int c = 0; c < 10; c++) tma2d_ef(sm + C_WO + c * 8192, &mp.wk, col0, c * 64, sm + CB_W, ef);
        }
        PPROF(4);
        __syncthreads();
        if (tid >= 64) {
#pragma unroll 1
            for (int i = tid - 64; i < 640 + 192 * 4; i += 320)
                asm volatile("prefetch.global.L2 [%0];" :: "l"(i < 640 ? ar.wv + (size_t)i * HD + col0 : ar.wo + (size_t)(head * DH + ((i - 640) >> 2)) * DM + mt0 * 16 + min((i & 3) * 64, 639 - mt0 * 16)));
        }
    }
    const int r = lane & 7, mi = lane >> 3;
    const uint32_t memrd = opaque(sm + C_MEM + lane * 16);
    const bool lane0 = (memrd & 0x1f0) == 0;
    if (wg < 2) {
        asm volatile("setmaxnreg.inc.sync.aligned.u32 208;");
        uint32_t wa[40][4];
        mbar_wait(sm + CB_W, 0);
#pragma unroll
        for (int ks = 0; ks < 40; ks++) ldsm4t(wa[ks], sm + (wg == 0 ? C_WV : C_WO) + ((mi >> 1) * 8 + r) * 128 + (((2 * w + (mi & 1)) ^ r) << 4) + ks * 2048);
        PPROF(5);
        bar_sync(1, 384);
        x_part(wa, mp, sm, 0, wg, w, lane, col0, j);
        PPROF(6);
        mbar_wait(sm + CB_W2, 0);
        PPROF(7);
        const uint32_t qst = opaque(sm + (wg == 0 ? C_QM : C_KM) + (2 * w + (mi & 1)) * 128 + r * 16);
        if (warp == 5 && lane0) {
            flag_wait(&g_flags.v[head], 2);
            mbar_expect(sm + CB_VX, 4096);
            tma2d(sm + C_VX, &mp.v32, col0, 0, sm + CB_VX);
        }
        __syncwarp();
        const uint64_t vda = mkdesc(SM_BASE + C_WV + wg * 40960, 8192, 1024);
        const uint64_t vdb = (uint64_t)(((SM_BASE + C_MEM + wg * 5120) & 0x3FFFF) >> 4) | ((uint64_t)(128 >> 4) << 16) | ((uint64_t)(256 >> 4) << 32);
        for (int s = 0; s < NSEG; s++) {
            float res[4];
            mbar_wait(sm + CB_MEM, s & 1);
            if (warp == 0) { PROF(0); PROFG(24); }
            {
                float d[4][4];
#pragma unroll
                for (int c = 0; c < 4; c++) { d[c][0] = d[c][1] = d[c][2] = d[c][3] = 0.f; }
                uint32_t b[4][4];
#pragma unroll
                for (int k = 0; k < 3; k++) ldsm4(b[k], memrd + k * 512);
                bool rdy = mbar_test(sm + CB_MEM + 8, s & 1);
#pragma unroll
                for (int k2 = 0; k2 < 20; k2++) {
                    if (k2 + 3 < 20) {
                        if ((k2 + 3) % 5 == 0) {
                            if (!rdy) mbar_wait(sm + CB_MEM + 8 * ((k2 + 3) / 5), s & 1);
                            if (k2 + 8 < 20) rdy = mbar_test(sm + CB_MEM + 8 * ((k2 + 8) / 5), s & 1);
                        }
                        ldsm4(b[(k2 + 3) & 3], memrd + (k2 + 3) * 512);
                    }
                    mma16(d[(2 * k2) & 3], wa[2 * k2][0], wa[2 * k2][1], wa[2 * k2][2], wa[2 * k2][3], b[k2 & 3][0], b[k2 & 3][1]);
                    mma16(d[(2 * k2 + 1) & 3], wa[2 * k2 + 1][0], wa[2 * k2 + 1][1], wa[2 * k2 + 1][2], wa[2 * k2 + 1][3], b[k2 & 3][2], b[k2 & 3][3]);
                }
#pragma unroll
                for (int i = 0; i < 4; i++) res[i] = (d[0][i] + d[1][i]) + (d[2][i] + d[3][i]);
            }
            const uint32_t p0 = pack2(res[0], res[1]), p1 = pack2(res[2], res[3]);
            stsm2t(qst, p0, p1);
            if (w == 0 && lane0) asm volatile("cp.async.bulk.wait_group.read 0;" ::: "memory");
            bar_arrive(2, 384);
            if (w == 0) PROF(1 + wg);
            {
                float d[2][4];
                asm volatile("fence.proxy.async.shared::cta;" ::: "memory");
                bar_sync(4, 384);
                WG_FENCE();
                wgmma_ss_n8_ta_first(d[0], vda, vdb); wgmma_ss_n8_ta_first(d[1], vda + (2048 >> 4), vdb + (256 >> 4));
#pragma unroll
                for (int ks = 2; ks < 20; ks++) {
                    if (ks == VGAP) { bar_sync(11, 384); WG_FENCE(); }
                    wgmma_ss_n8_ta(d[ks & 1], vda + ks * (2048 >> 4), vdb + ks * (256 >> 4));
                }
                WG_COMMIT(); WG_WAIT(0);
                sts128f(memrd + (C_VP - C_MEM) + warp * 512, d[0][0] + d[1][0], d[0][1] + d[1][1], d[0][2] + d[1][2], d[0][3] + d[1][3]);
                __syncwarp();
                if (lane0) mbar_arrive(sm + CB_VP);
            }
            if (warp == 0) PROF(7);
            const uint32_t ln = opaque(memrd) >> 4 & 31;
            if (ln == 0 && s + 1 < NSEG) {
                if (warp == 5) {
                    if ((s & 3) == 3) flag_wait(&g_flags.v[((s + 1) >> 2) * 32 + head], 2);
                    mbar_expect(sm + CB_VX, 4096);
                    tma2d(sm + C_VX, &mp.v32, col0, (s + 1) * SEG, sm + CB_VX);
                }
                if (warp == 1) {
                    mbar_wait(sm + CB_SC, s & 1);
                    x_prefetch(mp, sm, s + 1, j);
                }
            }
            if (w == 0 && ln == 0) {
                asm volatile("cp.async.bulk.wait_group 0;" ::: "memory");
            }
            bar_sync(5, 384);
            {
                uint32_t f0 = p0, f1 = p1;
                if (wg == 0) asm volatile("ld.shared.v2.u32 {%0,%1}, [%2];" : "=r"(f0), "=r"(f1) : "r"(sm + C_VM + w * 256 + ln * 8) : "memory");
                const uint32_t t0_ = movm_t(f0), t1_ = movm_t(f1);
                uint8_t* dst = (uint8_t*)(wg == 0 ? g_vm : g_km) + (size_t)s * (NH * 8 * DH * 2) + ((head * 8 + (ln >> 2)) * DH + j * 64 + 16 * w + (ln & 3) * 2) * 2;
                *(uint32_t*)dst = t0_; *(uint32_t*)(dst + 16) = t1_;
            }
            if (s + 1 < NSEG) x_part(wa, mp, sm, s + 1, wg, w, ln, col0, j);
            else {
                bar_sync(6 + wg, 128);
                if (w == 0 && ln == 0) flag_add(&g_flags.seg[63 * 32 + head], 1);
            }
            if (warp == 0) PROF(11);
        }
    } else {
        asm volatile("setmaxnreg.dec.sync.aligned.u32 88;");
        bar_sync(1, 384);
        if (tid == 256) {
            mbar_expect(sm + CB_W2, 81920 + 86016);
#pragma unroll 1
            for (int c = 0; c < 10; c++) tma2d(sm + C_WV + c * 8192, &mp.wv, col0, c * 64, sm + CB_W2);
#pragma unroll 1
            for (int c = 0; c < 7; c++) tma2d(sm + C_WO + c * 12288, &mp.wo, mt0 * 16 + c * 32, head * DH, sm + CB_W2);
        }
        mbar_wait(sm + CB_W2, 0);
        const int oc = blk % 80;
        const float scale = 0.07216878364870322f;
        if (w >= 2) mem_forward(sm, 0, j, tid - 320, clock(), 0);
        for (int s = 0; s < NSEG; s++) {
            const uint32_t l0 = opaque(memrd) >> 4 & 31, r0 = l0 & 7, m0 = l0 >> 3;
            const uint32_t vkey = 16 * (m0 >> 1) + 4 * (r0 >> 1) + 2 * (m0 & 1) + (r0 & 1);
            const uint32_t vxrd = sm + C_VX + vkey * 128 + (((2 * w) ^ (vkey & 7)) << 4);
            const uint32_t kxrd = sm + C_KX + (8 * w + r0) * 128 + ((m0 ^ r0) << 4);
            const uint32_t sco = (w >> 1) * 512 + (l0 >> 2) * 64 + (w & 1) * 32 + ((l0 >> 1) & 1) * 16, peer = (j + 1 + (l0 & 1)) % 3;
            const uint32_t word = opaque(sm + C_WO + (w >> 1) * 12288 + ((m0 >> 1) * 8 + r0) * 64 + ((((w & 1) * 2 + (m0 & 1)) ^ (r0 >> 1)) << 4));
            const uint32_t qrd = opaque(sm + C_QM + (m0 >> 1) * 128 + r0 * 16);
            const uint32_t scdst = opaque(sm + C_SC + j * 1280 + sco);
            const uint32_t rbase = opaque(mapa(sm, peer) - sm);
            const uint32_t scm = opaque(1024 + (l0 >> 1) * 16 - sco);
            const uint32_t oxrd = opaque(sm + C_OX + l0 * 8);
            const uint32_t poff = opaque(((2 * (mt0 + w) * 32 + head) * 32 + l0) * 4);
            uint32_t kb[2][4], vb[2][4];
            mbar_wait(sm + CB_KX, s & 1);
            ldsm4(kb[0], kxrd); ldsm4(kb[1], kxrd ^ 64);
            mbar_wait(sm + CB_VX, s & 1);
            ldsm4t(vb[0], vxrd); ldsm4t(vb[1], vxrd ^ 16);
            bar_sync(2, 384);
            const bool odd = memrd & 16;
            {
                uint32_t qa[4][4];
#pragma unroll
                for (int k = 0; k < 4; k++) ldsm4(qa[k], qrd + k * 256);
                float x[4];
                if (w == 3) {
                    uint32_t km[2][4]; float y[4];
                    ldsm4(km[0], memrd + (C_KM - C_MEM)); ldsm4(km[1], memrd + (C_KM - C_MEM) + 512);
                    score_tile(qa, kb, odd, x); score_tile(qa, km, odd, y);
                    if (s + 1 < NSEG) { send_piece(x, scdst + rbase, sm + CB_SC + rbase, scdst); send_piece(y, scdst + scm + rbase, sm + CB_SC + rbase, scdst + scm); }
                } else {
                    score_tile(qa, kb, odd, x);
                    if (s + 1 < NSEG) send_piece(x, scdst + rbase, sm + CB_SC + rbase, scdst);
                }
                bar_arrive(4, 384);
            }
            if (s + 1 == NSEG) {
                if (VGAP < 20) bar_arrive(11, 384);
                if (w == 1 && lane0) flag_add(&g_flags.seg[62 * 32 + head], 2);
                mbar_wait(sm + CB_VP, s & 1);
                const uint32_t vp = memrd + (C_VP - C_MEM) + w * 512;
                float4 y0 = lds128f(vp), y1 = lds128f(vp + 2048);
                asm volatile("st.shared.v2.u32 [%0], {%1,%2};" :: "r"(oxrd - (C_OX - C_VM) + w * 256), "r"(pack2(y0.x + y1.x, y0.y + y1.y)), "r"(pack2(y0.z + y1.z, y0.w + y1.w)) : "memory");
                bar_arrive(5, 384);
                break;
            }
            __syncwarp();
            if (lane0) mbar_arrive(sm + CB_SC);
            if (w == 0) PROF(4);
            mbar_wait(sm + CB_SC, s & 1);
            if (w == 0) PROF(8);
            float sv[10];
            {
                const uint32_t scrd = memrd + (C_SC - C_MEM);
                float4 x[3], y[3]; float2 z[3];
#pragma unroll
                for (int p = 0; p < 3; p++) { x[p] = lds128f(scrd + p * 1280); y[p] = lds128f(scrd + p * 1280 + 512); z[p] = lds64f(oxrd + (C_SC - C_OX) + p * 1280 + 1024); }
                sv[0] = (x[0].x + x[1].x) + x[2].x; sv[1] = (x[0].y + x[1].y) + x[2].y; sv[2] = (x[0].z + x[1].z) + x[2].z; sv[3] = (x[0].w + x[1].w) + x[2].w;
                sv[4] = (y[0].x + y[1].x) + y[2].x; sv[5] = (y[0].y + y[1].y) + y[2].y; sv[6] = (y[0].z + y[1].z) + y[2].z; sv[7] = (y[0].w + y[1].w) + y[2].w;
                sv[8] = (z[0].x + z[1].x) + z[2].x; sv[9] = (z[0].y + z[1].y) + z[2].y;
            }
            float mx = fmaxf(fmaxf(fmaxf(sv[0], sv[1]), fmaxf(sv[2], sv[3])), fmaxf(fmaxf(fmaxf(sv[4], sv[5]), fmaxf(sv[6], sv[7])), fmaxf(sv[8], sv[9])));
            mx = fmaxf(mx, __shfl_xor_sync(0xffffffffu, mx, 1)); mx = fmaxf(mx, __shfl_xor_sync(0xffffffffu, mx, 2));
            if (VGAP < 20) {
                asm volatile("st.shared.f32 [%0], %1; bar.arrive 11, 384;" :: "r"(qrd), "f"(mx) : "memory");
            }
            const float sl2e = scale * 1.4426950408889634f, mxl = mx * sl2e;
#pragma unroll
            for (int i = 0; i < 10; i++) asm("ex2.approx.ftz.f32 %0, %1;" : "=f"(sv[i]) : "f"(fmaf(sv[i], sl2e, -mxl)));
            uint32_t pa[5];
#pragma unroll
            for (int i = 0; i < 5; i++) pa[i] = pack2(sv[2 * i], sv[2 * i + 1]);
            float sum = ((sv[0] + sv[1]) + (sv[2] + sv[3])) + ((sv[4] + sv[5]) + (sv[6] + sv[7])) + (sv[8] + sv[9]);
            if (w == 0) PROF(6);
            uint32_t a[8][4];
            const uint32_t kb0 = j * 4096, kb1 = j == 2 ? 0 : kb0 + 4096, kb2 = j == 0 ? 8192 : kb0 - 4096;
            auto frag = [&](int i) { const int k = i / 3; return word + (i % 3) * 24576 + (k < 4 ? kb0 : k < 8 ? kb1 : kb2) + (k & 3) * 1024; };
            mbar_wait(sm + CB_VP, s & 1);
            uint32_t vm0, vm1;
            {
                const uint32_t vp = memrd + (C_VP - C_MEM) + w * 512;
                float4 y0 = lds128f(vp), y1 = lds128f(vp + 2048);
#pragma unroll
                for (int i = 0; i < NPRE; i++) ldsm4t(a[i], frag(i));
                float o[2][4] = {{0, 0, 0, 0}, {0, 0, 0, 0}}, o2[2][4] = {{0, 0, 0, 0}, {0, 0, 0, 0}};
#pragma unroll
                for (int u = 0; u < 2; u++) mma16(o[u], pa[0], pa[0], pa[1], pa[1], vb[u][0], vb[u][1]);
#pragma unroll
                for (int u = 0; u < 2; u++) mma16(o2[u], pa[2], pa[2], pa[3], pa[3], vb[u][2], vb[u][3]);
                sum += __shfl_xor_sync(0xffffffffu, sum, 1);
                vm0 = pack2(y0.x + y1.x, y0.y + y1.y); vm1 = pack2(y0.z + y1.z, y0.w + y1.w);
                sum += __shfl_xor_sync(0xffffffffu, sum, 2);
                mma8(o[0], pa[4], pa[4], vm0); mma8(o[1], pa[4], pa[4], vm1);
                float inv; asm("rcp.approx.ftz.f32 %0, %1;" : "=f"(inv) : "f"(sum));
                const uint32_t a = pack2((o[0][0] + o2[0][0]) * inv, (o[0][1] + o2[0][1]) * inv), b = pack2((o[1][0] + o2[1][0]) * inv, (o[1][1] + o2[1][1]) * inv);
                const uint32_t c = __shfl_xor_sync(0xffffffffu, a, 1), d = __shfl_xor_sync(0xffffffffu, b, 1);
                const float x[4] = {__uint_as_float(odd ? c : a), __uint_as_float(odd ? d : b), __uint_as_float(odd ? a : c), __uint_as_float(odd ? b : d)};
                const uint32_t od = (oxrd & ~8u) + (4 * j + w) * 256;
                send_piece(x, od + rbase, sm + CB_OX + rbase, od);
                __syncwarp();
                if (lane0) mbar_arrive(sm + CB_OX);
            }
            asm volatile("st.shared.v2.u32 [%0], {%1,%2};" :: "r"(oxrd - (C_OX - C_VM) + w * 256), "r"(vm0), "r"(vm1) : "memory");
            if (w == 0) PROF(10);
#pragma unroll
            for (int i = NPRE; i < 8; i++) ldsm4t(a[i], frag(i));
            bar_sync(3, 128);
            const uint32_t tag = (s & 1) ^ 1;
            uint8_t* pdst = (uint8_t*)g_part + poff;
            const uint32_t lp = memrd + (C_VP - C_MEM);
            const uint32_t wl = word + (6 - (w >> 1)) * 12288 + w * 3072;
            float e[3][4] = {{0, 0, 0, 0}, {0, 0, 0, 0}, {0, 0, 0, 0}};
            {
                uint32_t ob[4][2];
#pragma unroll
                for (int k = 0; k < 4; k++) asm volatile("ld.shared.v2.u32 {%0,%1}, [%2];" : "=r"(ob[k][0]), "=r"(ob[k][1]) : "r"(oxrd + (kb0 >> 2) + k * 256) : "memory");
#pragma unroll
                for (int i = 0; i < 12; i++) {
                    mma16(e[i % 3], a[i & 7][0], a[i & 7][1], a[i & 7][2], a[i & 7][3], ob[i / 3][0], ob[i / 3][1]);
                    ldsm4t(a[i & 7], frag(i + 8));
                }
            }
            {
                uint32_t al[6][4];
#pragma unroll
                for (int k = 0; k < 3; k++) { ldsm4t(al[k], wl + k * 1024); ldsm4t(al[3 + k], (wl ^ 32) + k * 1024); }
                mbar_wait(sm + CB_OX, s & 1);
                if (w == 0) PROF(9);
                uint32_t ol[3][2];
#pragma unroll
                for (int k = 0; k < 3; k++) asm volatile("ld.shared.v2.u32 {%0,%1}, [%2];" : "=r"(ol[k][0]), "=r"(ol[k][1]) : "r"(oxrd + w * 768 + k * 256) : "memory");
                float f[2][4] = {{0, 0, 0, 0}, {0, 0, 0, 0}};
#pragma unroll
                for (int k = 0; k < 3; k++) {
                    mma16(f[0], al[k][0], al[k][1], al[k][2], al[k][3], ol[k][0], ol[k][1]);
                    mma16(f[1], al[3 + k][0], al[3 + k][1], al[3 + k][2], al[3 + k][3], ol[k][0], ol[k][1]);
                }
                sts128f(lp + (w & 1) * 2048 + w * 512, f[0][0], f[0][1], f[0][2], f[0][3]);
                sts128f(lp + ((w & 1) ^ 1) * 2048 + w * 512, f[1][0], f[1][1], f[1][2], f[1][3]);
            }
#pragma unroll
            for (int h = 0; h < 2; h++) {
                uint32_t ob[4][2];
#pragma unroll
                for (int k = 0; k < 4; k++) asm volatile("ld.shared.v2.u32 {%0,%1}, [%2];" : "=r"(ob[k][0]), "=r"(ob[k][1]) : "r"(oxrd + ((h ? kb2 : kb1) >> 2) + k * 256) : "memory");
#pragma unroll
                for (int i = 12 + 12 * h; i < 24 + 12 * h; i++) {
                    mma16(e[i % 3], a[i & 7][0], a[i & 7][1], a[i & 7][2], a[i & 7][3], ob[(i / 3) & 3][0], ob[(i / 3) & 3][1]);
                    if (i + 8 < 36) ldsm4t(a[i & 7], frag(i + 8));
                }
                if (h == 0) {
                    bar_sync(3, 128);
                    if (12 + w < nmt) {
                        float4 y0 = lds128f(lp + w * 2048), y1 = lds128f(lp + w * 2048 + 512), y2 = lds128f(lp + w * 2048 + 1024), y3 = lds128f(lp + w * 2048 + 1536);
                        asm volatile("st.relaxed.gpu.global.u32 [%0], %1;" :: "l"(pdst + 24 * (32 * 128)), "r"((pack2((y0.x + y1.x) + (y2.x + y3.x), (y0.y + y1.y) + (y2.y + y3.y)) & ~1u) | tag) : "memory");
                        asm volatile("st.relaxed.gpu.global.u32 [%0], %1;" :: "l"(pdst + 25 * (32 * 128)), "r"((pack2((y0.z + y1.z) + (y2.z + y3.z), (y0.w + y1.w) + (y2.w + y3.w)) & ~1u) | tag) : "memory");
                    }
                }
            }
#pragma unroll
            for (int q = 0; q < 3; q++)
#pragma unroll
                for (int hf = 0; hf < 2; hf++)
                    asm volatile("st.relaxed.gpu.global.u32 [%0], %1;" :: "l"(pdst + (8 * q + hf) * (32 * 128)), "r"((pack2(e[q][2 * hf], e[q][2 * hf + 1]) & ~1u) | tag) : "memory");
            const uint32_t tw = clock();
            bar_arrive(5, 384);
            if (w == 0) { PROF(14); PROFG(25); }
            const uint32_t ln = opaque(memrd) >> 4 & 31, gg = ln >> 2, tt = ln & 3;
            if (w == 0) {
                const uint8_t* src = (const uint8_t*)g_part + ((oc * 32 + tt) * 8 + gg) * 16;
                uint32_t* mdst = g_memg + (s + 1) * 2560 + oc * 32 + ln;
                const uint32_t sel0 = gg == 0 ? 0x00003f80u : gg == 1 ? 0x3f800000u : 0u, sel1 = gg == 2 ? 0x00003f80u : gg == 3 ? 0x3f800000u : 0u;
                const uint32_t sl = (ln & 28) | (tt >> 1);
                wait_until(tw + D1);
                for (int n = 0;; n++) {
                    uint4 v[8];
#pragma unroll
                    for (int i = 0; i < 8; i++)
                        asm volatile("ld.relaxed.gpu.global.v4.u32 {%0,%1,%2,%3}, [%4];" : "=r"(v[i].x), "=r"(v[i].y), "=r"(v[i].z), "=r"(v[i].w) : "l"(src + i * 512) : "memory");
                    float e[4][4];
#pragma unroll
                    for (int i = 0; i < 4; i++) { e[i][0] = e[i][1] = e[i][2] = e[i][3] = 0.f; }
#pragma unroll
                    for (int i = 0; i < 8; i++) mma16(e[i & 3], v[i].x, v[i].y, v[i].z, v[i].w, sel0, sel1);
                    uint32_t bd[8];
#pragma unroll
                    for (int i = 0; i < 8; i++) bd[i] = or3(xor_or(v[i].x, v[i].y, tag), xor_or(v[i].z, v[i].w, tag), 0);
                    const bool bad = __any_sync(0xffffffffu, or3(or3(bd[0], bd[1], bd[2]), or3(bd[3], bd[4], bd[5]), or3(bd[6], bd[7], 0)) & 1);
                    const uint32_t p01 = pack2((e[0][0] + e[1][0]) + (e[2][0] + e[3][0]), (e[0][1] + e[1][1]) + (e[2][1] + e[3][1]));
                    const uint32_t p23 = pack2((e[0][2] + e[1][2]) + (e[2][2] + e[3][2]), (e[0][3] + e[1][3]) + (e[2][3] + e[3][3]));
                    const uint32_t x = __shfl_sync(0xffffffffu, p01, sl), y = __shfl_sync(0xffffffffu, p23, sl);
                    const uint32_t res = movm_t((tt & 1) ? y : x);
                    if (!bad) {
                        if (blk < 80) {
                            asm volatile("st.relaxed.gpu.global.u32 [%0], %1;" :: "l"(mdst), "r"(res) : "memory");
                            if (ln == 0) asm volatile("st.relaxed.gpu.global.u32 [%0], %1;" :: "l"(g_stamp + (s + 1) * 96 + oc), "r"(gtime()) : "memory");
                        }
                        PROFV(15, n);
                        break;
                    }
                    if (n > SPIN_LIMIT) __trap();
                }
                bar_arrive(9, 288);
                PROF(5); PROFG(26);
            } else if (w == 1) {
                const uint32_t now = gtime();
                int32_t a = -(1 << 30);
#pragma unroll
                for (int q = 0; q < 3; q++) {
                    const int32_t d = (int32_t)(__ldcg(g_stamp + s * 96 + (q * 32 + ln < 80 ? q * 32 + ln : ln)) - now);
                    if (d <= 0 && d > -100000) a = max(a, d);
                }
                a = __reduce_max_sync(0xffffffffu, a);
                const uint32_t an = now + a, ap = lds32(sm + C_PACE), pp = lds32(sm + C_PACE + 4);
                const uint32_t pn = s < 3 ? an - ap : (3 * pp + (an - ap)) >> 2;
                __syncwarp();
                if (ln == 0) {
                    asm volatile("st.shared.v4.u32 [%0], {%1,%2,%3,%3};" :: "r"(sm + C_PACE), "r"(an), "r"(pn), "r"(s < 3 || DG < -5000 ? 0u : (an + pn + DG) | 1u) : "memory");
                    mbar_expect(sm + CB_SC, 2560); mbar_expect(sm + CB_OX, 2048);
#pragma unroll
                    for (int c = 0; c < 4; c++) mbar_expect(sm + CB_MEM + 8 * c, j == 2 ? 2560 - 768 : 2560 - 896);
                }
                bar_arrive(10, 96);
                if (ln == 0) {
                    if (s + 3 < NSEG) asm volatile("prefetch.global.L2 [%0];" :: "l"(g_memg + (s + 3) * 2560 + oc * 32) : "memory");
                    if (s >= 4 * B_FINE + 1) flag_add(&g_flags.seg[(s - 1) * 32 + head], 2);
                    else if ((s & 3) == 0 && s > 0) flag_add(&g_flags.b[(s >> 2) - 1].qk, 2);
                }
                __syncwarp();
            } else {
                bar_sync(10, 96);
                const int nf = mem_forward(sm, s + 1, j, (w - 2) * 32 + ln, tw + D2, lds32(sm + C_PACE + 8));
                if (w == 2) { PROFV(20, nf); PROFG(29); }
            }
        }
    }
#define TPROF(i)
    __syncthreads();
    TPROF(0);
    constexpr int T_WG = 0, T_WU = 20480, T_WD = 40960, T_X = 65536, T_GU = 81920, T_RED = 106496, T_KEY = 122880;
    if (tid == 0) {
        mbar_expect(sm + CB_W, 40960 + (blk < 80 ? 24576 : 0));
        for (int c = 0; c < 5; c++) { tma2d(sm + T_WG + c * 4096, &mp.wgate, blk * 16, c * 128, sm + CB_W); tma2d(sm + T_WU + c * 4096, &mp.wup, blk * 16, c * 128, sm + CB_W); }
        if (blk < 80) for (int c = 0; c < 6; c++) tma2d(sm + T_WD + c * 4096, &mp.wdown, blk * 8, c * 256, sm + CB_W);
    }
    auto rkey = [](int idx) { uint32_t u = __ldcg((const unsigned short*)g_r + idx); u = (u & 0x8000u) ? (~u & 0xffffu) : (u | 0x8000u); return (u << 16) | (uint32_t)(S_TOK - 1 - idx); };
    if (warp < 8) {
        if (warp == 0 && lane == 0) for (int b = 0; b < 15; b++) flag_wait(&g_flags.b[b].ln, 128);
        bar_sync(1, 256);
        uint32_t k[8];
#pragma unroll
        for (int i = 0; i < 8; i++) { const int idx = warp * 240 + i * 32 + lane; k[i] = i * 32 + lane < 240 ? rkey(idx) : 0u; }
#pragma unroll 1
        for (int it = 0; it < 8; it++) {
            const uint32_t m = __reduce_max_sync(0xffffffffu, max(umax3(k[0], k[1], k[2]), max(umax3(k[3], k[4], k[5]), max(k[6], k[7]))));
#pragma unroll
            for (int i = 0; i < 8; i++) if (k[i] == m) k[i] = 0;
            if (lane == 0) asm volatile("st.shared.u32 [%0], %1;" :: "r"(sm + T_KEY + (warp * 8 + it) * 4), "r"(m) : "memory");
        }
    }
    __syncthreads();
    if (warp == 0) {
        uint32_t k[6];
        k[0] = lds32(sm + T_KEY + lane * 4); k[1] = lds32(sm + T_KEY + 128 + lane * 4);
        if (lane == 0) flag_wait(&g_flags.b[15].ln, 128);
        __syncwarp();
        TPROF(1);
#pragma unroll
        for (int i = 0; i < 4; i++) k[2 + i] = rkey(1920 + i * 32 + lane);
#pragma unroll 1
        for (int it = 0; it < 8; it++) {
            const uint32_t m = __reduce_max_sync(0xffffffffu, max(umax3(k[0], k[1], k[2]), umax3(k[3], k[4], k[5])));
#pragma unroll
            for (int i = 0; i < 6; i++) if (k[i] == m) k[i] = 0;
            if (lane == 0) asm volatile("st.shared.u32 [%0], %1;" :: "r"(sm + T_KEY + 256 + it * 4), "r"(S_TOK - 1 - (m & 0xffffu)) : "memory");
        }
    }
    __syncthreads();
    TPROF(2);
    for (int i = tid; i < 640; i += 384) {
        const uint4 v = __ldcg((const uint4*)(g_h2 + lds32(sm + T_KEY + 256 + (i & 7) * 4) * DM + (i >> 3) * 8));
        asm volatile("st.shared.v4.u32 [%0], {%1,%2,%3,%4};" :: "r"(sm + T_X + i * 16), "r"(v.x), "r"(v.y), "r"(v.z), "r"(v.w) : "memory");
    }
    const int trow = lds32(sm + T_KEY + 256 + (lane >> 2) * 4), tcol = (blk < 80 ? blk : 0) * 8 + (lane & 3) * 2;
    const uint32_t fx1 = __ldcg((const uint32_t*)(g_x1 + trow * DM + tcol)), fh2 = __ldcg((const uint32_t*)(g_h2 + trow * DM + tcol)),
                   fgb = __ldcg((const uint32_t*)(g_mod + 5 * DM + tcol));
    const float fr = __uint_as_float((uint32_t)__ldcg((const unsigned short*)g_r + trow) << 16);
    mbar_wait(sm + CB_W, 1);
    __syncthreads();
    TPROF(3);
    if (warp < 10) {
        float dg[4] = {0, 0, 0, 0}, du[4] = {0, 0, 0, 0};
#pragma unroll
        for (int k2 = 0; k2 < 2; k2++) {
            uint32_t b[4]; ldsm4(b, sm + T_X + (warp * 2 + k2) * 512 + lane * 16);
#pragma unroll
            for (int h = 0; h < 2; h++) {
                uint32_t ag[4], au[4];
                const uint32_t o = ((warp * 4 + k2 * 2 + h) * 16 + (mi >> 1) * 8 + r) * 32 + (mi & 1) * 16;
                ldsm4t(ag, sm + T_WG + o); ldsm4t(au, sm + T_WU + o);
                mma16(dg, ag[0], ag[1], ag[2], ag[3], b[2 * h], b[2 * h + 1]); mma16(du, au[0], au[1], au[2], au[3], b[2 * h], b[2 * h + 1]);
            }
        }
        sts128f(sm + T_RED + warp * 1024 + lane * 16, dg[0], dg[1], dg[2], dg[3]); sts128f(sm + T_RED + warp * 1024 + 512 + lane * 16, du[0], du[1], du[2], du[3]);
    }
    __syncthreads();
    if (warp == 0) {
        float g4[4] = {0, 0, 0, 0}, u4[4] = {0, 0, 0, 0};
#pragma unroll
        for (int i = 0; i < 10; i++) {
            const float4 a = lds128f(sm + T_RED + i * 1024 + lane * 16), b = lds128f(sm + T_RED + i * 1024 + 512 + lane * 16);
            g4[0] += a.x; g4[1] += a.y; g4[2] += a.z; g4[3] += a.w; u4[0] += b.x; u4[1] += b.y; u4[2] += b.z; u4[3] += b.w;
        }
        float y[4];
#pragma unroll
        for (int i = 0; i < 4; i++) { const float gq = bfr(g4[i]); y[i] = bfr(__fdividef(gq, 1.f + __expf(-gq))) * bfr(u4[i]); }
        g_gu[blk * 64 + lane] = movm_t(pack2(y[0], y[1])); g_gu[blk * 64 + 32 + lane] = movm_t(pack2(y[2], y[3]));
        __syncwarp();
        TPROF(4);
        if (lane == 0) {
            flag_add(&g_flags.gu);
            if (blk < 80) {
                flag_wait(&g_flags.gu, 96);
                mbar_expect(sm + CB_W2, 24576); bulk_g2s(sm + T_GU, g_gu, 24576, sm + CB_W2);
            }
        }
        __syncwarp();
    }
    if (blk < 80) {
        mbar_wait(sm + CB_W2, 1);
        TPROF(5);
        float d[4] = {0, 0, 0, 0};
#pragma unroll
        for (int k2 = 0; k2 < 4; k2++) {
            uint32_t b[4]; ldsm4t(b, sm + T_WD + (warp * 4 + k2) * 512 + lane * 16);
#pragma unroll
            for (int h = 0; h < 2; h++) {
                uint32_t a[4]; ldsm4(a, sm + T_GU + ((warp * 8 + k2 * 2 + h) * 2 + (mi >> 1)) * 128 + r * 16);
                mma16(d, a[0], a[1], a[2], a[3], b[2 * h], b[2 * h + 1]);
            }
        }
        asm volatile("st.shared.v2.f32 [%0], {%1,%2};" :: "r"(sm + T_RED + warp * 256 + lane * 8), "f"(d[0]), "f"(d[1]) : "memory");
        __syncthreads();
        if (warp == 0) {
            float y0 = 0, y1 = 0;
#pragma unroll
            for (int i = 0; i < 12; i++) { const float2 a = lds64f(sm + T_RED + i * 256 + lane * 8); y0 += a.x; y1 += a.y; }
            const float sg = bfr(__fdividef(1.f, 1.f + __expf(-fr)));
            const float b0 = bfr(lo_f(fh2) + bfr(bfr(y0) * sg)), b1 = bfr(hi_f(fh2) + bfr(bfr(y1) * sg));
            *(uint32_t*)(ar.out + trow * DM + tcol) = pack2(lo_f(fx1) + bfr(lo_f(fgb) * b0), hi_f(fx1) + bfr(hi_f(fgb) * b1));
        }
    }
    TPROF(6);
    if (tid == 0) flags_release();
}

struct SideMaps { CUtensorMap h, wv, vst, q32, k32, v32, km, vm, ost, o, wo, slab3, slab2; };
constexpr int SD_ST = 43008, SD_NST = 4, SD_EPI = SD_NST * SD_ST, SD_LN = SD_EPI + 2 * 24576, SD_BAR = SD_LN + 10240, SD_SMEM = SD_BAR + 256;
#define N_ATT 10
__device__ __forceinline__ int o_split(int b) { return b >= B_FINE ? 16 : 8; }
__device__ __forceinline__ int next_item(bool att, int (&cur)[4], int& fix) {
    for (int n = 0;; n++) {
        if (!att) { cur[1] = max(cur[1], cur[2]); cur[3] = max(cur[3], cur[2] - SLABS); }
        if (cur[3] >= B_FINE && (att || cur[0] > 15)) {
            const int b = fix >> 2, c = blockIdx.x;
            if (c >= 32 || b == 16) return -1;
            if ((fix & 3) == 0) { fix++; return 1 << 16 | b << 8 | c; }
            if ((fix & 3) == 1) { fix++; return 2 << 16 | b << 8 | c; }
            if ((fix & 3) == 3) { fix -= 2; return 3 << 16 | (b - 1) << 8 | c; }
            if (b == 14 || (b < 14 && ld_rlx(&g_flags.seg[(4 * b + 6) * 32 + c]) >= 6)) { fix += 5; return 1 << 16 | (b + 1) << 8 | c; }
            fix += 2; return 3 << 16 | b << 8 | c;
        }
        uint32_t f3, c3, f2, c2, f1, f1v, c1; [[maybe_unused]] uint32_t dummy;
        asm volatile("ld.relaxed.gpu.global.v2.u32 {%0,%1}, [%2];" : "=r"(f3), "=r"(c3) : "l"(&g_flags.b[cur[3] & 15].o) : "memory");
        asm volatile("ld.relaxed.gpu.global.v2.u32 {%0,%1}, [%2];" : "=r"(f2), "=r"(c2) : "l"(&g_flags.b[cur[2] & 15].at) : "memory");
        asm volatile("ld.relaxed.gpu.global.v4.u32 {%0,%1,%2,%3}, [%4];" : "=r"(f1), "=r"(f1v), "=r"(c1), "=r"(dummy) : "l"(&g_flags.b[cur[1] & 15].qk) : "memory");
        const uint32_t f2l = ld_rlx(&g_flags.b[(cur[2] - SLABS) & 15].ln);
        const bool e3 = cur[3] < B_FINE && c3 >= 2u * o_split(cur[3]), e2 = cur[2] < B_FINE && c2 >= 2u * o_split(cur[2]), e1 = cur[1] < B_FINE && c1 >= 32;
        const bool r3 = !e3 && cur[3] < B_FINE && f3 >= 4u * o_split(cur[3]), r2 = !e2 && cur[2] < B_FINE && f2 >= 64 && (cur[2] < SLABS || f2l >= 128),
                   r1 = !e1 && cur[1] < B_FINE && f1 >= 192 && f1v >= 64, r0 = cur[0] < 16;
        const int kind = att ? (r3 ? 3 : r2 ? 2 : r1 ? 1 : (cur[1] == 0 && r0) ? 0 : -1)
                             : r0 ? ((cur[0] > cur[2] + 3 && r2) ? 2 : 0) : (r3 ? 3 : r2 ? 2 : r1 ? 1 : -1);
        const int b = kind == 3 ? cur[3] : kind == 2 ? cur[2] : kind == 1 ? cur[1] : cur[0];
        cur[3] += e3; cur[2] += e2; cur[1] += e1;
        if (kind < 0) { if (n > (1 << 22)) __trap(); continue; }
        uint32_t i; asm volatile("atom.relaxed.gpu.global.add.u32 %0, [%1], 1;" : "=r"(i)
            : "l"(kind == 3 ? &g_flags.b[b].c3 : kind == 2 ? &g_flags.b[b].c2 : kind == 1 ? &g_flags.b[b].c1 : &g_flags.b[b].c0) : "memory");
        if (i < (kind < 2 ? 32u : 2u * o_split(b))) {
            return kind << 16 | b << 8 | i;
        }
        if (kind == 0) cur[0]++;
    }
}

template <int NP>
__device__ __forceinline__ void tile_out(const float (&acc)[8 * NP], uint32_t eb, uint32_t efull, uint32_t eempty, int& eph, int w, int lane) {
    const int r = lane & 7, mi = lane >> 3, row = w * 16 + (mi & 1) * 8 + r;
    mbar_wait(eempty, eph); eph ^= 1;
#pragma unroll
    for (int p = 0; p < NP; p++) {
        const int oc = 2 * p + (mi >> 1);
        stsm4(eb + (oc >> 3) * 8192 + row * 128 + (((oc & 7) ^ r) << 4), pack2(acc[8 * p], acc[8 * p + 1]), pack2(acc[8 * p + 2], acc[8 * p + 3]),
              pack2(acc[8 * p + 4], acc[8 * p + 5]), pack2(acc[8 * p + 6], acc[8 * p + 7]));
    }
    asm volatile("fence.proxy.async.shared::cta;" ::: "memory");
    __syncwarp();
    if (lane == 0) mbar_arrive(efull);
}

template <int MT>
__device__ __forceinline__ void attn_tile(uint32_t base, uint32_t dst, uint32_t eempty, int eph, int lane) {
    constexpr int NK = MT ? 5 : 3;
    const int r = lane & 7, mi = lane >> 3, g = lane >> 2, t = lane & 3;
    float sc[NK][4];
#pragma unroll
    for (int n = 0; n < NK; n++) sc[n][0] = sc[n][1] = sc[n][2] = sc[n][3] = 0.f;
#pragma unroll 1
    for (int k2 = 0; k2 < 6; k2++) {
        const uint32_t cb = (k2 >> 1) * 4096, c0 = (k2 & 1) * 4;
        uint32_t a0[4], a1[4], bb[NK][4];
        ldsm4(a0, base + cb + (16 * MT + (mi & 1) * 8 + r) * 128 + (((c0 + (mi >> 1)) ^ r) << 4));
        ldsm4(a1, base + cb + (16 * MT + (mi & 1) * 8 + r) * 128 + (((c0 + 2 + (mi >> 1)) ^ r) << 4));
#pragma unroll
        for (int n = 0; n < NK; n++)
            ldsm4(bb[n], (n < NK - 1 ? base + 12288 + cb + (8 * n + r) * 128 : base + 36864 + (k2 >> 1) * 1024 + r * 128) + (((c0 + mi) ^ r) << 4));
#pragma unroll
        for (int n = 0; n < NK; n++) mma16(sc[n], a0[0], a0[1], a0[2], a0[3], bb[n][0], bb[n][1]);
#pragma unroll
        for (int n = 0; n < NK; n++) mma16(sc[n], a1[0], a1[1], a1[2], a1[3], bb[n][2], bb[n][3]);
    }
    const float scale = 0.07216878364870322f, l2e = 1.4426950408889634f;
    float v[2][2 * NK], mx[2], sum[2];
#pragma unroll
    for (int hf = 0; hf < 2; hf++) {
        mx[hf] = -INFINITY;
#pragma unroll
        for (int n = 0; n < NK; n++) {
            uint32_t u = pack2(sc[n][2 * hf], sc[n][2 * hf + 1]);
            u = pack2(lo_f(u) * scale, hi_f(u) * scale);
            const int lim = 16 * MT + 8 * hf + g - 8 * n - 2 * t;
            v[hf][2 * n] = (n < NK - 1 && lim < 0) ? -1e9f : lo_f(u);
            v[hf][2 * n + 1] = (n < NK - 1 && lim < 1) ? -1e9f : hi_f(u);
            mx[hf] = fmaxf(mx[hf], fmaxf(v[hf][2 * n], v[hf][2 * n + 1]));
        }
    }
#pragma unroll
    for (int o = 1; o < 4; o <<= 1)
#pragma unroll
        for (int hf = 0; hf < 2; hf++) mx[hf] = fmaxf(mx[hf], __shfl_xor_sync(0xffffffffu, mx[hf], o));
#pragma unroll
    for (int hf = 0; hf < 2; hf++) {
        sum[hf] = 0;
#pragma unroll
        for (int q = 0; q < 2 * NK; q++) { asm("ex2.approx.ftz.f32 %0, %1;" : "=f"(v[hf][q]) : "f"((v[hf][q] - mx[hf]) * l2e)); sum[hf] += v[hf][q]; }
    }
#pragma unroll
    for (int o = 1; o < 4; o <<= 1)
#pragma unroll
        for (int hf = 0; hf < 2; hf++) sum[hf] += __shfl_xor_sync(0xffffffffu, sum[hf], o);
    uint32_t pa[NK][2];
#pragma unroll
    for (int hf = 0; hf < 2; hf++) {
        const float inv = __fdividef(1.f, sum[hf]);
#pragma unroll
        for (int n = 0; n < NK; n++) pa[n][hf] = pack2(v[hf][2 * n] * inv, v[hf][2 * n + 1] * inv);
    }
    mbar_wait(eempty, eph);
#pragma unroll 1
    for (int n4 = 0; n4 < 6; n4++) {
        const uint32_t cb = (n4 >> 1) * 4096, c0 = (n4 & 1) * 4;
        uint32_t bm[4], bb[4][4];
        ldsm4t(bm, base + 39936 + (n4 >> 1) * 1024 + r * 128 + (((c0 + mi) ^ r) << 4));
#pragma unroll
        for (int u = 0; u < 4; u++) ldsm4t(bb[u], base + 24576 + cb + (8 * mi + r) * 128 + (((c0 + u) ^ r) << 4));
        float o[4][4];
#pragma unroll
        for (int u = 0; u < 4; u++) { o[u][0] = o[u][1] = o[u][2] = o[u][3] = 0.f; mma8(o[u], pa[NK - 1][0], pa[NK - 1][1], bm[u]); }
#pragma unroll
        for (int u = 0; u < 4; u++) mma16(o[u], pa[0][0], pa[0][1], pa[1][0], pa[1][1], bb[u][0], bb[u][1]);
        if (MT) {
#pragma unroll
            for (int u = 0; u < 4; u++) mma16(o[u], pa[MT ? 2 : 0][0], pa[MT ? 2 : 0][1], pa[MT ? 3 : 0][0], pa[MT ? 3 : 0][1], bb[u][2], bb[u][3]);
        }
#pragma unroll
        for (int p = 0; p < 2; p++)
            stsm4(dst + (n4 >> 1) * 8192 + ((mi & 1) * 8 + r) * 128 + (((c0 + 2 * p + (mi >> 1)) ^ r) << 4), pack2(o[2 * p][0], o[2 * p][1]), pack2(o[2 * p][2], o[2 * p][3]),
                  pack2(o[2 * p + 1][0], o[2 * p + 1][1]), pack2(o[2 * p + 1][2], o[2 * p + 1][3]));
    }
}

__global__ void __launch_bounds__(384, 1) k_side(const __grid_constant__ SideMaps mp, const bf16* __restrict__ x, const bf16* __restrict__ wr,
                                                 bf16* __restrict__ out) {
    extern __shared__ __align__(1024) uint8_t smraw[];
    const uint32_t sm = smem_u32(smraw);
    if (sm & 1023) __trap();
    const uint32_t FULL = sm + SD_BAR, EMPTY = FULL + 32, EFULL = FULL + 64, EEMPTY = FULL + 80, IFULL = FULL + 96, IEMPTY = FULL + 128, IQ = FULL + 160, SCHED = FULL + 176, LNDONE = FULL + 184;
    const int tid = threadIdx.x, warp = __shfl_sync(0xffffffffu, tid >> 5, 0), lane = tid & 31;
    const uint64_t ef = policy_stream();
    if (tid == 0) {
        for (int i = 0; i < SD_NST; i++) { mbar_init(FULL + 8 * i, 1); mbar_init(EMPTY + 8 * i, 2); }
        for (int i = 0; i < 2; i++) { mbar_init(EFULL + 8 * i, 4); mbar_init(EEMPTY + 8 * i, 1); }
        for (int i = 0; i < 4; i++) { mbar_init(IFULL + 8 * i, 1); mbar_init(IEMPTY + 8 * i, 11); }
        mbar_init(SCHED, 1); mbar_init(LNDONE, 1);
        asm volatile("fence.mbarrier_init.release.cluster;" ::: "memory");
    }
    __syncthreads();
    if (warp >= 8) {
      asm volatile("setmaxnreg.dec.sync.aligned.u32 40;");
      if (warp == 8) {
        int st = 0, ph = 1;
        for (int q = 0;; q++) {
            mbar_wait(IFULL + 8 * (q & 3), (q >> 2) & 1);
            const int it = __shfl_sync(0xffffffffu, lds32(IQ + 4 * (q & 3)), 0);
            if (elect()) mbar_arrive(IEMPTY + 8 * (q & 3));
            if (it < 0) break;
            const int kind = it >> 16, b = (it >> 8) & 255, i = it & 255;
            if (kind == 3) { if (elect()) mbar_arrive(SCHED); continue; }
            const int nst = kind == 0 ? 10 : kind == 1 ? 4 : 192 / o_split(b);
            const int ksched = kind == 0 ? 4 : kind == 2 ? nst - (b < B_FINE ? 7 : 4) : 0;
            if (kind == 1 && b >= B_FINE) flag_wait(&g_flags.v[b * 32 + i], 2);
            for (int kb = 0; kb < nst; kb++) {
                mbar_wait(EMPTY + 8 * st, ph);
                const uint32_t base = sm + st * SD_ST, fb = FULL + 8 * st;
                if (kb == ksched && elect()) mbar_arrive(SCHED);
                if (kind == 0) {
                    if (elect()) {
                        mbar_expect(fb, 40960);
                        tma2d(base, &mp.h, kb * 64, b * 128, fb);
                        tma3d(base + 16384, &mp.wv, kb * 64, i * 3, fb);
                    }
                } else if (kind == 1) {
                    if (b >= B_FINE) flag_wait(&g_flags.seg[(b * 4 + kb) * 32 + i], 6);
                    if (elect()) {
                        mbar_expect(fb, 43008);
                        const int row = b * 128 + kb * 32, mrow = ((b * 4 + kb) * NH + i) * 8;
                        tma3d_ef(base, &mp.q32, row, i * 3, fb, ef);
                        tma3d_ef(base + 12288, &mp.k32, row, i * 3, fb, ef);
                        tma3d_ef(base + 36864, &mp.km, mrow, 0, fb, ef);
                        tma3d_ef(base + 24576, &mp.v32, row, i * 3, fb, ef);
                        tma3d_ef(base + 39936, &mp.vm, mrow, 0, fb, ef);
                    }
                } else {
                    const int k0 = ((i >> 1) * nst + kb) * 32;
                    if (elect()) { mbar_expect(fb, 28672); tma3d(base + 8192, &mp.wo, k0, (i & 1) * 5, fb); }
                    if (kb == 0 && b >= B_FINE) flag_wait(&g_flags.pair[b * 16 + (i >> 1)], 4);
                    if (elect()) tma2d_ef(base, &mp.o, k0, b * 128, fb, ef);
                }
                __syncwarp();
                if (++st == SD_NST) { st = 0; ph ^= 1; }
            }
        }
      } else if (warp == 11) {
        if (lane == 0) {
            int cur[4] = {0, 0, blockIdx.x < N_ATT ? B_FINE : 0, 0}, fix = 4 * B_FINE;
            flag_wait(&g_flags.h, 160);
            for (int q = 0;; q++) {
                if (q) mbar_wait(SCHED, (q - 1) & 1);
                const int it = next_item(blockIdx.x < N_ATT, cur, fix);
                if (it >> 16 == 3 && ((it >> 8) & 255) >= B_FINE) flag_wait(&g_flags.b[(it >> 8) & 255].o, 64);
                if (it >> 16 == 1)
                    asm volatile("cp.async.bulk.prefetch.L2.global [%0], 5120;" :: "l"(x + (((it >> 8) & 255) * 128 + (it & 31) * 4) * DM) : "memory");
                mbar_wait(IEMPTY + 8 * (q & 3), ((q >> 2) & 1) ^ 1);
                asm volatile("st.shared.u32 [%0], %1;" :: "r"(IQ + 4 * (q & 3)), "r"(it) : "memory");
                mbar_arrive(IFULL + 8 * (q & 3));
                if (it < 0) { flags_release(); break; }
            }
        }
      } else {
        if (lane == 0) {
            const int wg = warp - 9; int ph = 0, lph = 0;
            for (int q = 0;; q++) {
                mbar_wait(IFULL + 8 * (q & 3), (q >> 2) & 1);
                const int it = lds32(IQ + 4 * (q & 3));
                mbar_arrive(IEMPTY + 8 * (q & 3));
                if (it < 0) break;
                const int kind = it >> 16, b = (it >> 8) & 255, i = it & 255;
                if (kind > 2) {
                    if (wg == 0) { mbar_wait(LNDONE, lph); lph ^= 1; flag_add(&g_flags.b[b].ln, 64 / o_split(b)); }
                    continue;
                }
                if (kind == 2 && b >= B_FINE) { flag_wait(&g_flags.b[b - SLABS].ln, 128); }
                for (int rd = 0; rd < (kind == 2 ? 2 : 1); rd++) {
                    mbar_wait(EFULL + 8 * wg, ph); ph ^= 1;
                    const uint32_t src = sm + SD_EPI + wg * 24576;
                    if (kind == 2) tma3d_store(rd ? &mp.slab2 : &mp.slab3, ((b % SLABS) * KSPLIT + (i >> 1)) * 128 + wg * 64, (i & 1) * 5 + rd * 3, src, ef, false);
                    else tma3d_store(kind == 0 ? &mp.vst : &mp.ost, b * 128 + wg * 64, i * 3, src, ef, kind == 0 && b > 1);
                    asm volatile("cp.async.bulk.commit_group;" ::: "memory");
                    asm volatile("cp.async.bulk.wait_group.read 0;" ::: "memory");
                    mbar_arrive(EEMPTY + 8 * wg);
                }
                asm volatile("cp.async.bulk.wait_group 0;" ::: "memory");
                bump(kind == 0 ? &g_flags.v[b * 32 + i] : kind == 1 ? (b >= B_FINE ? &g_flags.pair[b * 16 + (i >> 1)] : &g_flags.b[b].at) : &g_flags.b[b].o);
                if (kind == 0) bump(&g_flags.b[b].vb);
            }
        }
      }
    } else {
        asm volatile("setmaxnreg.inc.sync.aligned.u32 232;");
        const int wg = warp >> 2, w = warp & 3;
        int st = 0, ph = 0, eph = 1;
        const uint32_t eb = sm + SD_EPI + wg * 24576;
        for (int q = 0;; q++) {
            mbar_wait(IFULL + 8 * (q & 3), (q >> 2) & 1);
            const int itc = lds32(IQ + 4 * (q & 3));
            __syncwarp();
            if (lane == 0) mbar_arrive(IEMPTY + 8 * (q & 3));
            if (itc < 0) break;
            const int kind = itc >> 16, b = (itc >> 8) & 255, i = itc & 255;
            if (kind == 0) {
                float acc[96];
#pragma unroll
                for (int n = 0; n < 96; n++) acc[n] = 0.f;
                int prev = -1;
                for (int kb = 0; kb < 10; kb++) {
                    mbar_wait(FULL + 8 * st, ph);
                    const uint32_t base = sm + st * SD_ST;
                    WG_FENCE();
#pragma unroll
                    for (int ks = 0; ks < 4; ks++)
                        wgmma_ss_n192_tb(acc, mkdesc(base + wg * 8192 + ks * 32, 16, 1024), mkdesc(base + 16384 + ks * 2048, 8192, 1024), (kb | ks) != 0);
                    WG_COMMIT();
                    if (prev >= 0) { WG_WAIT(1); if ((tid & 127) == 0) mbar_arrive(EMPTY + 8 * prev); }
                    prev = st;
                    if (++st == SD_NST) { st = 0; ph ^= 1; }
                }
                WG_WAIT(0);
                if ((tid & 127) == 0) mbar_arrive(EMPTY + 8 * prev);
                tile_out<12>(acc, eb, EFULL + 8 * wg, EEMPTY + 8 * wg, eph, w, lane);
            } else if (kind == 1) {
                const int seg = warp >> 1, mt = warp & 1;
                int sst = st + seg, sph = ph; if (sst >= SD_NST) { sst -= SD_NST; sph ^= 1; }
                ph ^= 1;
                mbar_wait(FULL + 8 * sst, sph);
                const uint32_t base = sm + sst * SD_ST;
                if (mt) attn_tile<1>(base, eb + (w * 16) * 128, EEMPTY + 8 * wg, eph, lane);
                else attn_tile<0>(base, eb + (w * 16) * 128, EEMPTY + 8 * wg, eph, lane);
                eph ^= 1;
                asm volatile("fence.proxy.async.shared::cta;" ::: "memory");
                __syncwarp();
                if (lane == 0) { mbar_arrive(EMPTY + 8 * sst); mbar_arrive(EFULL + 8 * wg); }
            } else if (kind == 2) {
                float acc[96], acc2[64];
#pragma unroll
                for (int n = 0; n < 96; n++) acc[n] = 0.f;
#pragma unroll
                for (int n = 0; n < 64; n++) acc2[n] = 0.f;
                int prev = -1;
                for (int kb = 192 / o_split(b); kb > 0; kb--) {
                    const uint32_t base = sm + st * SD_ST;
                    mbar_wait(FULL + 8 * st, ph);
                    WG_FENCE();
#pragma unroll
                    for (int ks = 0; ks < 2; ks++) {
                        const uint64_t da = (mkdesc(base + wg * 4096 + ks * 32, 16, 512) & ~(3ull << 62)) | (2ull << 62);
                        wgmma_ss_n192_tb(acc, da, mkdesc(base + 8192 + ks * 2048, 4096, 1024), 1);
                        wgmma_ss_n128_tb(acc2, da, mkdesc(base + 8192 + 3 * 4096 + ks * 2048, 4096, 1024), 1);
                    }
                    WG_COMMIT();
                    if (prev >= 0) { WG_WAIT(1); if ((tid & 127) == 0) mbar_arrive(EMPTY + 8 * prev); }
                    prev = st;
                    if (++st == SD_NST) { st = 0; ph ^= 1; }
                }
                WG_WAIT(0);
                if ((tid & 127) == 0) mbar_arrive(EMPTY + 8 * prev);
                tile_out<12>(acc, eb, EFULL + 8 * wg, EEMPTY + 8 * wg, eph, w, lane);
                tile_out<8>(acc2, eb, EFULL + 8 * wg, EEMPTY + 8 * wg, eph, w, lane);
            } else {
                const bool two = o_split(b) == 16;
                const int lrow = two ? i * 4 + w : i * 8 + warp, row = b * 128 + lrow;
                const bf16* sl = g_slab + ((size_t)((b % SLABS) * KSPLIT + (two ? wg * 8 : 0)) * 128 + lrow) * DM + lane * 4;
                uint2 ga[5], gb[5], sh[5], sc[5], wv[5], xin[5];
                float xv[20], hv[20];
                {
#pragma unroll
                    for (int q2 = 0; q2 < 5; q2++) {
                        const int c = lane * 4 + q2 * 128;
                        ga[q2] = __ldcg((const uint2*)(g_mod + 2 * DM + c)); sh[q2] = __ldcg((const uint2*)(g_mod + 3 * DM + c));
                        sc[q2] = __ldcg((const uint2*)(g_mod + 4 * DM + c)); gb[q2] = __ldcg((const uint2*)(g_mod + 5 * DM + c));
                        wv[q2] = __ldg((const uint2*)(wr + c)); xin[q2] = ld_ef(x + row * DM + c, ef);
                    }
                }
                {
                    uint2 z[5][8];
#pragma unroll
                    for (int q2 = 0; q2 < 5; q2++)
#pragma unroll
                        for (int k = 0; k < 8; k++) z[q2][k] = ld_ef(sl + (size_t)k * 128 * DM + q2 * 128, ef);
#pragma unroll
                    for (int q2 = 0; q2 < 5; q2++) {
                        xv[4 * q2] = xv[4 * q2 + 1] = xv[4 * q2 + 2] = xv[4 * q2 + 3] = 0.f;
#pragma unroll
                        for (int k = 0; k < 8; k++) { xv[4 * q2] += lo_f(z[q2][k].x); xv[4 * q2 + 1] += hi_f(z[q2][k].x); xv[4 * q2 + 2] += lo_f(z[q2][k].y); xv[4 * q2 + 3] += hi_f(z[q2][k].y); }
                    }
                }
                if (two) {
                    const uint32_t xb = sm + SD_LN + w * 2560 + lane * 16;
                    if (wg == 1) {
#pragma unroll
                        for (int q2 = 0; q2 < 5; q2++) sts128f(xb + q2 * 512, xv[4 * q2], xv[4 * q2 + 1], xv[4 * q2 + 2], xv[4 * q2 + 3]);
                        bar_arrive(2, 256);
                        continue;
                    }
                    bar_sync(2, 256);
#pragma unroll
                    for (int q2 = 0; q2 < 5; q2++) { const float4 z = lds128f(xb + q2 * 512); xv[4 * q2] += z.x; xv[4 * q2 + 1] += z.y; xv[4 * q2 + 2] += z.z; xv[4 * q2 + 3] += z.w; }
                }
                uint32_t sv[10], tv[10];
#pragma unroll
                for (int q2 = 0; q2 < 10; q2++) {
                    const uint32_t xi = q2 & 1 ? xin[q2 >> 1].y : xin[q2 >> 1].x, gi = q2 & 1 ? ga[q2 >> 1].y : ga[q2 >> 1].x;
                    xv[2 * q2] = bfr(lo_f(xi) + bfr(lo_f(gi) * bfr(xv[2 * q2]))); xv[2 * q2 + 1] = bfr(hi_f(xi) + bfr(hi_f(gi) * bfr(xv[2 * q2 + 1])));
                    sv[q2] = q2 & 1 ? sc[q2 >> 1].y : sc[q2 >> 1].x; tv[q2] = q2 & 1 ? sh[q2 >> 1].y : sh[q2 >> 1].x;
                }
                ln_mod(xv, sv, tv, hv);
                float rs = 0;
#pragma unroll
                for (int q2 = 0; q2 < 5; q2++) {
                    const int c = row * DM + lane * 4 + q2 * 128;
                    const float* xx = xv + 4 * q2; const float* hh = hv + 4 * q2;
                    rs += (hh[0] * lo_f(wv[q2].x) + hh[1] * hi_f(wv[q2].x)) + (hh[2] * lo_f(wv[q2].y) + hh[3] * hi_f(wv[q2].y));
                    st_ef(g_x1 + c, make_uint2(pack2(xx[0], xx[1]), pack2(xx[2], xx[3])), ef);
                    st_ef(g_h2 + c, make_uint2(pack2(hh[0], hh[1]), pack2(hh[2], hh[3])), ef);
                    st_ef(out + c, make_uint2(pack2(xx[0] + bfr(lo_f(gb[q2].x) * hh[0]), xx[1] + bfr(hi_f(gb[q2].x) * hh[1])),
                                              pack2(xx[2] + bfr(lo_f(gb[q2].y) * hh[2]), xx[3] + bfr(hi_f(gb[q2].y) * hh[3]))), ef);
                }
                rs = warp_sum(rs);
                if (lane == 0) g_r[row] = __float2bfloat16_rn(rs);
                bar_sync(1, two ? 128 : 256);
                if (tid == 0) mbar_arrive(LNDONE);
            }
        }
    }
    __syncwarp();
    asm volatile("griddepcontrol.wait;" ::: "memory");
}

#define P_D1 400
#define P_DL 700
#define P_DG 0
typedef CUresult (*EncodeFn)(CUtensorMap*, CUtensorMapDataType, cuuint32_t, void*, const cuuint64_t*, const cuuint64_t*, const cuuint32_t*, const cuuint32_t*,
                             CUtensorMapInterleave, CUtensorMapSwizzle, CUtensorMapL2promotion, CUtensorMapFloatOOBfill);
static EncodeFn s_encode = nullptr;
static void make_map(CUtensorMap* m, const void* p, int rows, int cols, int box_rows, int box_cols = 64) {
    cuuint64_t dims[2] = {(cuuint64_t)cols, (cuuint64_t)rows}, strides[1] = {(cuuint64_t)cols * 2};
    cuuint32_t box[2] = {(cuuint32_t)box_cols, (cuuint32_t)box_rows}, es[2] = {1, 1};
    s_encode(m, CU_TENSOR_MAP_DATA_TYPE_BFLOAT16, 2, (void*)p, dims, strides, box, es, CU_TENSOR_MAP_INTERLEAVE_NONE,
             box_cols == 64 ? CU_TENSOR_MAP_SWIZZLE_128B : box_cols == 32 ? CU_TENSOR_MAP_SWIZZLE_64B : CU_TENSOR_MAP_SWIZZLE_NONE, CU_TENSOR_MAP_L2_PROMOTION_L2_256B, CU_TENSOR_MAP_FLOAT_OOB_FILL_NONE);
}
static void make_map3(CUtensorMap* m, const void* p, int rows, int cols, int box_rows, int box_chunks) {
    cuuint64_t dims[3] = {64, (cuuint64_t)rows, (cuuint64_t)cols / 64}, strides[2] = {(cuuint64_t)cols * 2, 128};
    cuuint32_t box[3] = {64, (cuuint32_t)box_rows, (cuuint32_t)box_chunks}, es[3] = {1, 1, 1};
    s_encode(m, CU_TENSOR_MAP_DATA_TYPE_BFLOAT16, 3, (void*)p, dims, strides, box, es, CU_TENSOR_MAP_INTERLEAVE_NONE,
             CU_TENSOR_MAP_SWIZZLE_128B, CU_TENSOR_MAP_L2_PROMOTION_L2_256B, CU_TENSOR_MAP_FLOAT_OOB_FILL_NONE);
}
template <typename T> static void* sym(T& s) { void* p = nullptr; cudaGetSymbolAddress(&p, s); return p; }

extern "C" void kernel_launch(void* const* d_in, const int* in_sizes, int n_in, void* d_out, int out_size) {
    const bf16 *x = (const bf16*)d_in[0], *mem0 = (const bf16*)d_in[1], *Wq = (const bf16*)d_in[2], *Wk = (const bf16*)d_in[3],
               *Wv = (const bf16*)d_in[4], *Wo = (const bf16*)d_in[5], *wr = (const bf16*)d_in[8], *wgate = (const bf16*)d_in[9],
               *wup = (const bf16*)d_in[10], *wdown = (const bf16*)d_in[11], *c = (const bf16*)d_in[12], *wmod = (const bf16*)d_in[13];
    bf16* out = (bf16*)d_out;
    if (!s_encode) {
        cudaDriverEntryPointQueryResult qr;
        cudaGetDriverEntryPoint("cuTensorMapEncodeTiled", (void**)&s_encode, cudaEnableDefault, &qr);
        cudaFuncSetAttribute(k_side, cudaFuncAttributeMaxDynamicSharedMemorySize, SD_SMEM);
        cudaFuncSetAttribute(k_chain, cudaFuncAttributeMaxDynamicSharedMemorySize, C_SMEM);
    }
    ChainMaps cm; SideMaps sd;
    make_map(&sd.h, sym(g_h), S_TOK, DM, 128); make_map3(&sd.wv, Wv, DM, HD, 64, 3); make_map3(&sd.vst, sym(g_v), S_TOK, HD, 64, 3);
    make_map3(&sd.q32, sym(g_q), S_TOK, HD, 32, 3); make_map3(&sd.k32, sym(g_k), S_TOK, HD, 32, 3); make_map3(&sd.v32, sym(g_v), S_TOK, HD, 32, 3);
    make_map3(&sd.km, sym(g_km), NSEG * NH * 8, DH, 8, 3); make_map3(&sd.vm, sym(g_vm), NSEG * NH * 8, DH, 8, 3);
    make_map3(&sd.ost, sym(g_o), S_TOK, HD, 64, 3); make_map(&sd.o, sym(g_o), S_TOK, HD, 128, 32); make_map3(&sd.wo, Wo, HD, DM, 32, 5);
    make_map3(&sd.slab3, sym(g_slab), SLABS * KSPLIT * 128, DM, 64, 3); make_map3(&sd.slab2, sym(g_slab), SLABS * KSPLIT * 128, DM, 64, 2);
    make_map(&cm.wq, Wq, DM, HD, 64); make_map(&cm.wk, Wk, DM, HD, 64); make_map(&cm.wv, Wv, DM, HD, 64); make_map(&cm.wo, Wo, HD, DM, 192, 32);
    make_map(&cm.h32, sym(g_h), S_TOK, DM, 32);
    make_map(&cm.q32, sym(g_q), S_TOK, HD, 32); make_map(&cm.k32, sym(g_k), S_TOK, HD, 32); make_map(&cm.v32, sym(g_v), S_TOK, HD, 32);
    make_map(&cm.wgate, wgate, DM, FF, 128, 16); make_map(&cm.wup, wup, DM, FF, 128, 16); make_map(&cm.wdown, wdown, FF, DM, 256, 8);
    make_map(&cm.wmod, wmod, DM, 6 * DM, 160, 48);
    ChainArgs ar = {x, mem0, c, Wv, Wo, out, P_D1, P_DL, P_DG};
    k_chain<<<96, 384, C_SMEM>>>(cm, ar);
    cudaLaunchConfig_t cfg = {};
    cfg.gridDim = dim3(N_SIDE); cfg.blockDim = dim3(384); cfg.dynamicSmemBytes = SD_SMEM; cfg.stream = cudaStreamPerThread;
    cudaLaunchAttribute at[1]; at[0].id = cudaLaunchAttributeProgrammaticStreamSerialization; at[0].val.programmaticStreamSerializationAllowed = 1;
    cfg.attrs = at; cfg.numAttrs = 1;
    cudaLaunchKernelEx(&cfg, k_side, sd, x, wr, out);
}
```

```cpp
#include <cuda_runtime.h>
#include <cuda_bf16.h>
#include <cuda.h>
#include <stdint.h>
#include <stdio.h>
#include <string.h>
#include <stdlib.h>

typedef __nv_bfloat16 bf16;
constexpr int S_TOK = 2048, DM = 640, NH = 32, DH = 192, HD = NH * DH, NSEG = 64, SEG = 32, FF = 1536;

__device__ bf16 g_mod[6 * DM];
__device__ bf16 g_h[S_TOK * DM];
__device__ bf16 g_q[S_TOK * HD];
__device__ bf16 g_k[S_TOK * HD];
__device__ bf16 g_v[S_TOK * HD];
__device__ bf16 g_o[S_TOK * HD];
__device__ __align__(128) bf16 g_kvm[NSEG * NH * 2 * 8 * DH];
__device__ bf16 g_A[S_TOK * DM];
__device__ bf16 g_x1[S_TOK * DM];
__device__ bf16 g_h2[S_TOK * DM];
__device__ bf16 g_r[S_TOK];
__device__ int g_idx[8];
__device__ __align__(128) uint32_t g_gu[FF / 8 * 32];
constexpr int ACC_PAIR = 24 * 1024;
__device__ __align__(1024) uint8_t g_acc[2 * ACC_PAIR];
__device__ __align__(1024) uint32_t g_stamp[4 * 12 * 32];
constexpr int KSPLIT = 16;
__device__ bf16 g_slab[16 * KSPLIT * 128 * DM];
struct __align__(128) Flags {
    uint32_t qk[16], vb[16];
    uint32_t at[16], o[16];
    uint32_t c[4][16];
    uint32_t ln[16], pad0[16];
    uint32_t v[16 * 32];
    uint32_t seg[64 * 32];
    uint32_t pair[16 * 16];
    uint32_t mod, h, pad1[30], gu, pad2[31], done, pad3[31];
};
__device__ Flags g_flags;

__device__ __forceinline__ uint32_t smem_u32(const void* p) { return (uint32_t)__cvta_generic_to_shared(p); }
__device__ __forceinline__ uint32_t pack2(float lo, float hi) {
    uint32_t r; asm("cvt.rn.bf16x2.f32 %0, %1, %2;" : "=r"(r) : "f"(hi), "f"(lo)); return r;
}
__device__ __forceinline__ float bfr(float x) { return __uint_as_float(pack2(0.f, x)); }
__device__ __forceinline__ float inv_std(float var) {
    float s, r; asm("sqrt.approx.f32 %0, %1;" : "=f"(s) : "f"(bfr(bfr(var) + 1e-5f))); asm("rcp.approx.f32 %0, %1;" : "=f"(r) : "f"(bfr(s))); return r;
}
__device__ __forceinline__ float lo_f(uint32_t v) { return __uint_as_float(v << 16); }
__device__ __forceinline__ float hi_f(uint32_t v) { return __uint_as_float(v & 0xffff0000u); }
__device__ __forceinline__ void mbar_init(uint32_t bar, int cnt) { asm volatile("mbarrier.init.shared::cta.b64 [%0], %1;" :: "r"(bar), "r"(cnt) : "memory"); }
__device__ __forceinline__ void mbar_expect(uint32_t bar, int bytes) { asm volatile("mbarrier.arrive.expect_tx.shared::cta.b64 _, [%0], %1;" :: "r"(bar), "r"(bytes) : "memory"); }
__device__ __forceinline__ void mbar_arrive(uint32_t bar) { asm volatile("mbarrier.arrive.shared::cta.b64 _, [%0];" :: "r"(bar) : "memory"); }
__device__ __forceinline__ bool mbar_try(uint32_t bar, int par) {
    uint32_t ok; asm volatile("{ .reg .pred p; mbarrier.try_wait.parity.shared::cta.b64 p, [%1], %2; selp.u32 %0, 1, 0, p; }" : "=r"(ok) : "r"(bar), "r"(par) : "memory"); return ok;
}
__device__ __forceinline__ bool mbar_try_cluster(uint32_t bar, int par) {
    uint32_t ok; asm volatile("{ .reg .pred p; mbarrier.try_wait.parity.acquire.cluster.shared::cta.b64 p, [%1], %2; selp.u32 %0, 1, 0, p; }" : "=r"(ok) : "r"(bar), "r"(par) : "memory"); return ok;
}
__device__ __forceinline__ bool mbar_test(uint32_t bar, uint32_t par) {
    uint32_t ok; asm volatile("{ .reg .pred p; mbarrier.test_wait.parity.shared::cta.b64 p, [%1], %2; selp.u32 %0, 1, 0, p; }" : "=r"(ok) : "r"(bar), "r"(par) : "memory"); return ok;
}
constexpr int SPIN_LIMIT = 1 << 18;
__device__ __forceinline__ void mbar_wait(uint32_t bar, uint32_t par) {
    asm volatile("{ .reg .pred p, q; .reg .u32 n; mov.u32 n, 0;\n"
                 "W_%=: mbarrier.try_wait.parity.shared::cta.b64 p, [%0], %1;\n"
                 "@p bra.uni D_%=;\n"
                 "add.u32 n, n, 1; setp.lt.u32 q, n, 0x200000; @q bra.uni W_%=;\n"
                 "trap;\n"
                 "D_%=: }" :: "r"(bar), "r"(par) : "memory");
}
__device__ __forceinline__ void tma2d(uint32_t dst, const CUtensorMap* m, int c0, int c1, uint32_t bar) {
    asm volatile("cp.async.bulk.tensor.2d.shared::cluster.global.mbarrier::complete_tx::bytes [%0], [%1, {%3, %4}], [%2];"
        :: "r"(dst), "l"((uint64_t)m), "r"(bar), "r"(c0), "r"(c1) : "memory");
}
__device__ __forceinline__ void tma2d_mc(uint32_t dst, const CUtensorMap* m, int c0, int c1, uint32_t bar, uint16_t mask) {
    asm volatile("cp.async.bulk.tensor.2d.shared::cluster.global.mbarrier::complete_tx::bytes.multicast::cluster [%0], [%1, {%3, %4}], [%2], %5;"
        :: "r"(dst), "l"((uint64_t)m), "r"(bar), "r"(c0), "r"(c1), "h"(mask) : "memory");
}
__device__ __forceinline__ uint64_t policy_stream() { uint64_t p; asm("createpolicy.fractional.L2::evict_first.b64 %0, 1.0;" : "=l"(p)); return p; }
__device__ __forceinline__ void tma2d_ef(uint32_t dst, const CUtensorMap* m, int c0, int c1, uint32_t bar, uint64_t pol) {
    asm volatile("cp.async.bulk.tensor.2d.shared::cluster.global.mbarrier::complete_tx::bytes.L2::cache_hint [%0], [%1, {%3, %4}], [%2], %5;"
        :: "r"(dst), "l"((uint64_t)m), "r"(bar), "r"(c0), "r"(c1), "l"(pol) : "memory");
}
__device__ __forceinline__ void tma3d(uint32_t dst, const CUtensorMap* m, int row, int chunk, uint32_t bar) {
    asm volatile("cp.async.bulk.tensor.3d.shared::cluster.global.mbarrier::complete_tx::bytes [%0], [%1, {0, %3, %4}], [%2];"
        :: "r"(dst), "l"((uint64_t)m), "r"(bar), "r"(row), "r"(chunk) : "memory");
}
__device__ __forceinline__ void tma3d_ef(uint32_t dst, const CUtensorMap* m, int row, int chunk, uint32_t bar, uint64_t pol) {
    asm volatile("cp.async.bulk.tensor.3d.shared::cluster.global.mbarrier::complete_tx::bytes.L2::cache_hint [%0], [%1, {0, %3, %4}], [%2], %5;"
        :: "r"(dst), "l"((uint64_t)m), "r"(bar), "r"(row), "r"(chunk), "l"(pol) : "memory");
}
__device__ __forceinline__ void tma3d_store(const CUtensorMap* m, int row, int chunk, uint32_t src, uint64_t pol, bool hint) {
    if (hint) asm volatile("cp.async.bulk.tensor.3d.global.shared::cta.bulk_group.L2::cache_hint [%0, {0, %2, %3}], [%1], %4;"
        :: "l"((uint64_t)m), "r"(src), "r"(row), "r"(chunk), "l"(pol) : "memory");
    else asm volatile("cp.async.bulk.tensor.3d.global.shared::cta.bulk_group [%0, {0, %2, %3}], [%1];"
        :: "l"((uint64_t)m), "r"(src), "r"(row), "r"(chunk) : "memory");
}
__device__ __forceinline__ bool elect() { uint32_t p; asm volatile("{ .reg .pred e; elect.sync _|e, -1; selp.u32 %0, 1, 0, e; }" : "=r"(p)); return p; }
__device__ __forceinline__ uint2 ld_ef(const void* p, uint64_t pol) {
    uint2 v; asm volatile("ld.relaxed.gpu.global.L2::cache_hint.v2.u32 {%0,%1}, [%2], %3;" : "=r"(v.x), "=r"(v.y) : "l"(p), "l"(pol)); return v;
}
__device__ __forceinline__ void st_ef(void* p, uint2 v, uint64_t pol) {
    asm volatile("st.global.L2::cache_hint.v2.u32 [%0], {%1,%2}, %3;" :: "l"(p), "r"(v.x), "r"(v.y), "l"(pol) : "memory");
}
__device__ __forceinline__ void tma2d_prefetch(const CUtensorMap* m, int c0, int c1) {
    asm volatile("cp.async.bulk.prefetch.tensor.2d.L2.global [%0, {%1, %2}];" :: "l"((uint64_t)m), "r"(c0), "r"(c1) : "memory");
}
__device__ __forceinline__ void mbar_arrive_remote(uint32_t bar) { asm volatile("mbarrier.arrive.relaxed.cluster.shared::cluster.b64 _, [%0];" :: "r"(bar) : "memory"); }
__device__ __forceinline__ void tma2d_store(const CUtensorMap* m, int c0, int c1, uint32_t src) {
    asm volatile("cp.async.bulk.tensor.2d.global.shared::cta.bulk_group [%0, {%2, %3}], [%1];"
        :: "l"((uint64_t)m), "r"(src), "r"(c0), "r"(c1) : "memory");
}
__device__ __forceinline__ void bulk_g2s(uint32_t dst, const void* src, int bytes, uint32_t bar) {
    asm volatile("cp.async.bulk.shared::cluster.global.mbarrier::complete_tx::bytes [%0], [%1], %2, [%3];" :: "r"(dst), "l"(src), "r"(bytes), "r"(bar) : "memory");
}
__device__ __forceinline__ void ldsm4(uint32_t (&r)[4], uint32_t a) {
    asm volatile("ldmatrix.sync.aligned.m8n8.x4.shared.b16 {%0,%1,%2,%3}, [%4];" : "=r"(r[0]), "=r"(r[1]), "=r"(r[2]), "=r"(r[3]) : "r"(a) : "memory");
}
__device__ __forceinline__ void ldsm4t(uint32_t (&r)[4], uint32_t a) {
    asm volatile("ldmatrix.sync.aligned.m8n8.x4.trans.shared.b16 {%0,%1,%2,%3}, [%4];" : "=r"(r[0]), "=r"(r[1]), "=r"(r[2]), "=r"(r[3]) : "r"(a) : "memory");
}
__device__ __forceinline__ void stsm4(uint32_t a, uint32_t r0, uint32_t r1, uint32_t r2, uint32_t r3) {
    asm volatile("stmatrix.sync.aligned.m8n8.x4.shared.b16 [%0], {%1,%2,%3,%4};" :: "r"(a), "r"(r0), "r"(r1), "r"(r2), "r"(r3) : "memory");
}
__device__ __forceinline__ void stsm4t(uint32_t a, uint32_t r0, uint32_t r1, uint32_t r2, uint32_t r3) {
    asm volatile("stmatrix.sync.aligned.m8n8.x4.trans.shared.b16 [%0], {%1,%2,%3,%4};" :: "r"(a), "r"(r0), "r"(r1), "r"(r2), "r"(r3) : "memory");
}
__device__ __forceinline__ void stsm2t(uint32_t a, uint32_t r0, uint32_t r1) {
    asm volatile("stmatrix.sync.aligned.m8n8.x2.trans.shared.b16 [%0], {%1,%2};" :: "r"(a), "r"(r0), "r"(r1) : "memory");
}
__device__ __forceinline__ uint32_t movm_t(uint32_t v) { uint32_t r; asm volatile("movmatrix.sync.aligned.m8n8.trans.b16 %0, %1;" : "=r"(r) : "r"(v)); return r; }
__device__ __forceinline__ void mma16(float (&d)[4], uint32_t a0, uint32_t a1, uint32_t a2, uint32_t a3, uint32_t b0, uint32_t b1) {
    asm volatile("mma.sync.aligned.m16n8k16.row.col.f32.bf16.bf16.f32 {%0,%1,%2,%3}, {%4,%5,%6,%7}, {%8,%9}, {%0,%1,%2,%3};"
        : "+f"(d[0]), "+f"(d[1]), "+f"(d[2]), "+f"(d[3]) : "r"(a0), "r"(a1), "r"(a2), "r"(a3), "r"(b0), "r"(b1));
}
__device__ __forceinline__ void mma8(float (&d)[4], uint32_t a0, uint32_t a1, uint32_t b0) {
    asm volatile("mma.sync.aligned.m16n8k8.row.col.f32.bf16.bf16.f32 {%0,%1,%2,%3}, {%4,%5}, {%6}, {%0,%1,%2,%3};"
        : "+f"(d[0]), "+f"(d[1]), "+f"(d[2]), "+f"(d[3]) : "r"(a0), "r"(a1), "r"(b0));
}
__device__ __forceinline__ uint32_t mapa(uint32_t a, uint32_t r) { uint32_t o; asm volatile("mapa.shared::cluster.u32 %0, %1, %2;" : "=r"(o) : "r"(a), "r"(r)); return o; }
__device__ __forceinline__ void bar_sync(int id, int n) { asm volatile("bar.sync %0, %1;" :: "r"(id), "r"(n) : "memory"); }
__device__ __forceinline__ void bar_arrive(int id, int n) { asm volatile("bar.arrive %0, %1;" :: "r"(id), "r"(n) : "memory"); }
__device__ __forceinline__ uint64_t mkdesc(uint32_t addr, uint32_t lbo, uint32_t sbo) {
    return (uint64_t)((addr & 0x3FFFF) >> 4) | ((uint64_t)(lbo >> 4) << 16) | ((uint64_t)(sbo >> 4) << 32) | (1ull << 62);
}
#define WG_FENCE()  asm volatile("wgmma.fence.sync.aligned;" ::: "memory")
#define WG_COMMIT() asm volatile("wgmma.commit_group.sync.aligned;" ::: "memory")
#define WG_WAIT(n)  asm volatile("wgmma.wait_group.sync.aligned %0;" :: "n"(n) : "memory")

__device__ __forceinline__ void wgmma_ss_n192_tb(float (&d)[96], uint64_t a, uint64_t b, int acc) {
    asm volatile("{ .reg .pred p; setp.ne.b32 p, %98, 0;\n"
        "wgmma.mma_async.sync.aligned.m64n192k16.f32.bf16.bf16 {%0,%1,%2,%3,%4,%5,%6,%7,%8,%9,%10,%11,%12,%13,%14,%15,%16,%17,%18,%19,%20,%21,%22,%23,%24,%25,%26,%27,%28,%29,%30,%31,%32,%33,%34,%35,%36,%37,%38,%39,%40,%41,%42,%43,%44,%45,%46,%47,%48,%49,%50,%51,%52,%53,%54,%55,%56,%57,%58,%59,%60,%61,%62,%63,%64,%65,%66,%67,%68,%69,%70,%71,%72,%73,%74,%75,%76,%77,%78,%79,%80,%81,%82,%83,%84,%85,%86,%87,%88,%89,%90,%91,%92,%93,%94,%95}, %96, %97, p, 1, 1, 0, 1; }"
        : "+f"(d[0]), "+f"(d[1]), "+f"(d[2]), "+f"(d[3]), "+f"(d[4]), "+f"(d[5]), "+f"(d[6]), "+f"(d[7]), "+f"(d[8]), "+f"(d[9]), "+f"(d[10]), "+f"(d[11]), "+f"(d[12]), "+f"(d[13]), "+f"(d[14]), "+f"(d[15]), "+f"(d[16]), "+f"(d[17]), "+f"(d[18]), "+f"(d[19]), "+f"(d[20]), "+f"(d[21]), "+f"(d[22]), "+f"(d[23]), "+f"(d[24]), "+f"(d[25]), "+f"(d[26]), "+f"(d[27]), "+f"(d[28]), "+f"(d[29]), "+f"(d[30]), "+f"(d[31]), "+f"(d[32]), "+f"(d[33]), "+f"(d[34]), "+f"(d[35]), "+f"(d[36]), "+f"(d[37]), "+f"(d[38]), "+f"(d[39]), "+f"(d[40]), "+f"(d[41]), "+f"(d[42]), "+f"(d[43]), "+f"(d[44]), "+f"(d[45]), "+f"(d[46]), "+f"(d[47]), "+f"(d[48]), "+f"(d[49]), "+f"(d[50]), "+f"(d[51]), "+f"(d[52]), "+f"(d[53]), "+f"(d[54]), "+f"(d[55]), "+f"(d[56]), "+f"(d[57]), "+f"(d[58]), "+f"(d[59]), "+f"(d[60]), "+f"(d[61]), "+f"(d[62]), "+f"(d[63]), "+f"(d[64]), "+f"(d[65]), "+f"(d[66]), "+f"(d[67]), "+f"(d[68]), "+f"(d[69]), "+f"(d[70]), "+f"(d[71]), "+f"(d[72]), "+f"(d[73]), "+f"(d[74]), "+f"(d[75]), "+f"(d[76]), "+f"(d[77]), "+f"(d[78]), "+f"(d[79]), "+f"(d[80]), "+f"(d[81]), "+f"(d[82]), "+f"(d[83]), "+f"(d[84]), "+f"(d[85]), "+f"(d[86]), "+f"(d[87]), "+f"(d[88]), "+f"(d[89]), "+f"(d[90]), "+f"(d[91]), "+f"(d[92]), "+f"(d[93]), "+f"(d[94]), "+f"(d[95])
        : "l"(a), "l"(b), "r"(acc));
}

__device__ __forceinline__ void wgmma_ss_n128_tb(float (&d)[64], uint64_t a, uint64_t b, int acc) {
    asm volatile("{ .reg .pred p; setp.ne.b32 p, %66, 0;\n"
        "wgmma.mma_async.sync.aligned.m64n128k16.f32.bf16.bf16 {%0,%1,%2,%3,%4,%5,%6,%7,%8,%9,%10,%11,%12,%13,%14,%15,%16,%17,%18,%19,%20,%21,%22,%23,%24,%25,%26,%27,%28,%29,%30,%31,%32,%33,%34,%35,%36,%37,%38,%39,%40,%41,%42,%43,%44,%45,%46,%47,%48,%49,%50,%51,%52,%53,%54,%55,%56,%57,%58,%59,%60,%61,%62,%63}, %64, %65, p, 1, 1, 0, 1; }"
        : "+f"(d[0]), "+f"(d[1]), "+f"(d[2]), "+f"(d[3]), "+f"(d[4]), "+f"(d[5]), "+f"(d[6]), "+f"(d[7]), "+f"(d[8]), "+f"(d[9]), "+f"(d[10]), "+f"(d[11]), "+f"(d[12]), "+f"(d[13]), "+f"(d[14]), "+f"(d[15]), "+f"(d[16]), "+f"(d[17]), "+f"(d[18]), "+f"(d[19]), "+f"(d[20]), "+f"(d[21]), "+f"(d[22]), "+f"(d[23]), "+f"(d[24]), "+f"(d[25]), "+f"(d[26]), "+f"(d[27]), "+f"(d[28]), "+f"(d[29]), "+f"(d[30]), "+f"(d[31]), "+f"(d[32]), "+f"(d[33]), "+f"(d[34]), "+f"(d[35]), "+f"(d[36]), "+f"(d[37]), "+f"(d[38]), "+f"(d[39]), "+f"(d[40]), "+f"(d[41]), "+f"(d[42]), "+f"(d[43]), "+f"(d[44]), "+f"(d[45]), "+f"(d[46]), "+f"(d[47]), "+f"(d[48]), "+f"(d[49]), "+f"(d[50]), "+f"(d[51]), "+f"(d[52]), "+f"(d[53]), "+f"(d[54]), "+f"(d[55]), "+f"(d[56]), "+f"(d[57]), "+f"(d[58]), "+f"(d[59]), "+f"(d[60]), "+f"(d[61]), "+f"(d[62]), "+f"(d[63])
        : "l"(a), "l"(b), "r"(acc));
}

__device__ __forceinline__ void wgmma_rs_n32(float (&d)[16], const uint32_t (&a)[4], uint64_t b, int acc) {
    asm volatile("{ .reg .pred p; setp.ne.b32 p, %21, 0;\n"
        "wgmma.mma_async.sync.aligned.m64n32k16.f32.bf16.bf16 {%0,%1,%2,%3,%4,%5,%6,%7,%8,%9,%10,%11,%12,%13,%14,%15}, {%16,%17,%18,%19}, %20, p, 1, 1, 0; }"
        : "+f"(d[0]), "+f"(d[1]), "+f"(d[2]), "+f"(d[3]), "+f"(d[4]), "+f"(d[5]), "+f"(d[6]), "+f"(d[7]), "+f"(d[8]), "+f"(d[9]), "+f"(d[10]), "+f"(d[11]), "+f"(d[12]), "+f"(d[13]), "+f"(d[14]), "+f"(d[15])
        : "r"(a[0]), "r"(a[1]), "r"(a[2]), "r"(a[3]), "l"(b), "r"(acc));
}

__device__ __forceinline__ float warp_sum(float v) {
#pragma unroll
    for (int o = 16; o; o >>= 1) v += __shfl_xor_sync(0xffffffffu, v, o);
    return v;
}
__device__ __forceinline__ void ln_mod(const float (&xv)[20], const uint32_t (&sv)[10], const uint32_t (&tv)[10], float (&hv)[20]) {
    float s = 0;
#pragma unroll
    for (int i = 0; i < 20; i++) s += xv[i];
    const float mean = warp_sum(s) * (1.f / DM);
    float q = 0;
#pragma unroll
    for (int i = 0; i < 20; i++) { float d = xv[i] - mean; q += d * d; }
    const float mb = bfr(mean), inv = inv_std(warp_sum(q) * (1.f / DM));
#pragma unroll
    for (int i = 0; i < 10; i++) {
        const float n0 = bfr(bfr(xv[2 * i] - mb) * inv), n1 = bfr(bfr(xv[2 * i + 1] - mb) * inv);
        hv[2 * i] = bfr(bfr(n0 * bfr(1.f + lo_f(sv[i]))) + lo_f(tv[i]));
        hv[2 * i + 1] = bfr(bfr(n1 * bfr(1.f + hi_f(sv[i]))) + hi_f(tv[i]));
    }
}
__device__ __forceinline__ uint32_t ld_rlx(const uint32_t* f) { uint32_t v; asm volatile("ld.relaxed.gpu.global.u32 %0, [%1];" : "=r"(v) : "l"(f) : "memory"); return v; }
__device__ __forceinline__ void bump(uint32_t* f) { asm volatile("red.relaxed.gpu.global.add.u32 [%0], 1;" :: "l"(f) : "memory"); }
__device__ __forceinline__ void flag_wait(const uint32_t* f, uint32_t target) {
    for (int n = 0;; n++) {
        uint32_t v; asm volatile("ld.relaxed.gpu.global.u32 %0, [%1];" : "=r"(v) : "l"(f) : "memory");
        if (v >= target) break;
        if (n > (1 << 23)) __trap();
    }
}
__device__ __forceinline__ void flag_add(uint32_t* f, uint32_t v = 1) { asm volatile("red.release.gpu.global.add.u32 [%0], %1;" :: "l"(f), "r"(v) : "memory"); }
constexpr int N_SIDE = 36;
__device__ __forceinline__ void flags_release() {
    uint32_t old; asm volatile("atom.acq_rel.gpu.global.add.u32 %0, [%1], 1;" : "=r"(old) : "l"(&g_flags.done) : "memory");
    if (old == 96 + N_SIDE - 1) for (int i = 0; i < (int)(sizeof(Flags) / 16); i++) ((uint4*)&g_flags)[i] = make_uint4(0, 0, 0, 0);
}

struct ChainMaps { CUtensorMap wq, wk, wv, wo, h2, q32, k32, v32, wgate, wup, wdown, wmod; };
struct ChainArgs { const bf16 *x, *mem0, *c, *wv, *wo; bf16* out; int D1, D2, DG; };
constexpr uint32_t SM_BASE = 1024;
#define NRING 11
#define FILL_AT 1
#define VF 6
#define VPRE 2
#define XORD 0
#define B5AT 41
#define QCUT 0x7f
#define NCH 2
#define ALA 1
#define VPOS 0
#define NPRE 9
#define REG_P 208
#define REG_L (504 - 2 * REG_P)
constexpr int WO_BLK = 7 * 4096;
constexpr int C_WV = 0, C_WO = 81920, C_XR = 167936, C_VP = C_XR + 7 * 4096, C_VX = C_XR + 8 * 4096, C_QX = C_VX + 4096, C_KX = C_QX + 4096,
              C_MEM = C_KX + 4096, C_OX = C_MEM + 9216, C_VM = C_OX + 3072, C_QM = C_VM + 1024, C_KM = C_QM + 1024, C_SC = C_KM + 1024, C_BAR = C_SC + 3840;
constexpr int CB_W = C_BAR, CB_W2 = C_BAR + 8, CB_SC = C_BAR + 16, CB_XD = C_BAR + 24, CB_VX = C_BAR + 32, CB_PRE = C_BAR + 40, CB_XM = C_BAR + 48, CB_OX = C_BAR + 56,
              CB_XF = C_BAR + 64, C_LAG = C_BAR + 96;
constexpr int C_SMEM = C_BAR + 128;
#define PROF(i)
#define PROFG(i)
#define PROFV(i, v)
static_assert(C_SMEM <= 232448, "chain shared memory");
__device__ __forceinline__ uint32_t umax3(uint32_t a, uint32_t b, uint32_t c) { return max(max(a, b), c); }
__device__ __forceinline__ void wait_until(uint32_t t) {
    asm volatile("{ .reg .pred p; .reg .s32 c;\nU_%=: mov.u32 c, %%clock; sub.s32 c, c, %0; setp.lt.s32 p, c, 0; @p bra.uni U_%=; }" :: "r"(t) : "memory");
}
__device__ __forceinline__ uint32_t gtime() { uint32_t c; asm volatile("mov.u32 %0, %%globaltimer_lo;" : "=r"(c)); return c; }
__device__ __forceinline__ uint32_t opaque(uint32_t v) { uint32_t r; asm volatile("shfl.sync.bfly.b32 %0, %1, 0, 31, -1;" : "=r"(r) : "r"(v)); return r; }
__device__ __forceinline__ uint32_t lds32(uint32_t a) { uint32_t v; asm volatile("ld.shared.u32 %0, [%1];" : "=r"(v) : "r"(a) : "memory"); return v; }
__device__ __forceinline__ float2 lds64f(uint32_t a) { float2 v; asm volatile("ld.shared.v2.f32 {%0,%1}, [%2];" : "=f"(v.x), "=f"(v.y) : "r"(a) : "memory"); return v; }
__device__ __forceinline__ float4 lds128f(uint32_t a) { float4 v; asm volatile("ld.shared.v4.f32 {%0,%1,%2,%3}, [%4];" : "=f"(v.x), "=f"(v.y), "=f"(v.z), "=f"(v.w) : "r"(a) : "memory"); return v; }
__device__ __forceinline__ void sts128f(uint32_t a, float x, float y, float z, float w) { asm volatile("st.shared.v4.f32 [%0], {%1,%2,%3,%4};" :: "r"(a), "f"(x), "f"(y), "f"(z), "f"(w) : "memory"); }
__device__ __forceinline__ void lds64(uint32_t (&v)[2], uint32_t a) { asm volatile("ld.shared.v2.u32 {%0,%1}, [%2];" : "=r"(v[0]), "=r"(v[1]) : "r"(a) : "memory"); }
__device__ __forceinline__ void mma16q(float (&d)[4], const uint32_t (&a)[4], uint32_t b0, uint32_t b1) { mma16(d, a[0], a[1], a[2], a[3], b0, b1); }
__device__ __forceinline__ uint32_t f16_to_bf16(uint32_t v) {
    float lo, hi; asm("{ .reg .f16 l, h; mov.b32 {l, h}, %2; cvt.f32.f16 %0, l; cvt.f32.f16 %1, h; }" : "=f"(lo), "=f"(hi) : "r"(v));
    return pack2(lo, hi);
}
__device__ __forceinline__ uint32_t pack2h(float lo, float hi) { uint32_t r; asm("cvt.rn.f16x2.f32 %0, %1, %2;" : "=r"(r) : "f"(hi), "f"(lo)); return r; }
#define SPLIT 1
__device__ __forceinline__ void cut(uint32_t never, int n) {
    asm volatile("{ .reg .pred p; setp.ne.u32 p, %0, %1; @p bra.uni C_%=; trap; C_%=: }" :: "r"(never), "r"(n) : "memory");
}
__device__ __forceinline__ void pin(uint32_t never, uint32_t a, uint32_t b, uint32_t c, uint32_t d) {
    asm volatile("{ .reg .pred p; setp.eq.u32 p, %0, 0; @p st.shared.v4.u32 [%0], {%1,%2,%3,%4}; }" :: "r"(never), "r"(a), "r"(b), "r"(c), "r"(d) : "memory");
}
__device__ __forceinline__ void pin0(uint32_t never) {
    asm volatile("{ .reg .pred p; setp.eq.u32 p, %0, 0; @p st.shared.u32 [%0], 0; }" :: "r"(never) : "memory");
}
#define ELECTED(txt) "{ .reg .pred e; elect.sync _|e, -1; @e " txt " }"
__device__ __forceinline__ void w_bulk_s2g(void* dst, uint32_t src, int bytes) {
    asm volatile(ELECTED("cp.async.bulk.global.shared::cta.bulk_group [%0], [%1], %2;") :: "l"(dst), "r"(src), "r"(bytes) : "memory");
}
__device__ __forceinline__ void w_tma2d_store(const CUtensorMap* m, int c0, int c1, uint32_t src) {
    asm volatile(ELECTED("cp.async.bulk.tensor.2d.global.shared::cta.bulk_group [%0, {%2, %3}], [%1];") :: "l"((uint64_t)m), "r"(src), "r"(c0), "r"(c1) : "memory");
}
__device__ __forceinline__ void w_bump(uint32_t* f) { asm volatile(ELECTED("red.relaxed.gpu.global.add.u32 [%0], 1;") :: "l"(f) : "memory"); }
__device__ __forceinline__ void w_expect(uint32_t bar, int bytes) { asm volatile(ELECTED("mbarrier.arrive.expect_tx.shared::cta.b64 _, [%0], %1;") :: "r"(bar), "r"(bytes) : "memory"); }
__device__ __forceinline__ void w_flag_wait(const uint32_t* f, uint32_t target) {
    asm volatile("{ .reg .pred p; .reg .u32 n, v; mov.u32 n, 0;\n"
                 "F_%=: ld.relaxed.gpu.global.u32 v, [%0]; setp.ge.u32 p, v, %1; vote.sync.all.pred p, p, -1; @p bra.uni G_%=;\n"
                 "add.u32 n, n, 1; setp.lt.u32 p, n, 0x800000; @p bra.uni F_%=;\ntrap;\nG_%=: }" :: "l"(f), "r"(target) : "memory");
}
#define BULK_COMMIT()    asm volatile("cp.async.bulk.commit_group;" ::: "memory")
#define BULK_WAIT()      asm volatile("cp.async.bulk.wait_group 0;" ::: "memory")
#define BULK_WAIT_READ() asm volatile("cp.async.bulk.wait_group.read 0;" ::: "memory")
#define PROXY_FENCE()    asm volatile("fence.proxy.async.shared::cta;" ::: "memory")
__device__ __forceinline__ void score_tile(const uint32_t (&qa)[2][4], const uint32_t (&kb)[2][4], bool odd, float (&x)[4]) {
    float sc[2][4] = {{0, 0, 0, 0}, {0, 0, 0, 0}};
#pragma unroll
    for (int k = 0; k < 4; k++) mma16q(sc[k & 1], qa[k >> 1], kb[k >> 1][2 * (k & 1)], kb[k >> 1][2 * (k & 1) + 1]);
    float a = sc[0][0] + sc[1][2], b = sc[0][1] + sc[1][3];
    float c = __shfl_xor_sync(0xffffffffu, a, 1), d = __shfl_xor_sync(0xffffffffu, b, 1);
    x[0] = odd ? c : a; x[1] = odd ? d : b; x[2] = odd ? a : c; x[3] = odd ? b : d;
}
__device__ __forceinline__ void send_piece(const float (&x)[4], uint32_t rdst, uint32_t rbar, uint32_t ldst) {
    asm volatile("st.async.shared::cluster.mbarrier::complete_tx::bytes.v4.f32 [%0], {%1,%2,%3,%4}, [%5];"
        :: "r"(rdst), "f"(x[0]), "f"(x[1]), "f"(x[2]), "f"(x[3]), "r"(rbar) : "memory");
    sts128f(ldst, x[0], x[1], x[2], x[3]);
}

__device__ __forceinline__ void seg_done(int n, int head) {
    w_bump(&g_flags.seg[n * 32 + head]);
    if ((n & 3) == 3) w_bump(&g_flags.qk[n >> 2]);
}
__device__ __forceinline__ void x_part(const uint32_t (&wa)[40][4], uint32_t sm, int n, int wg, int w, uint32_t ln, int head) {
    const int s = n - 1; (void)s;
    float acc[16]; uint32_t giv[8];
#pragma unroll
    for (int i = 0; i < 16; i++) acc[i] = 0.f;
    const uint32_t x0 = (uint32_t)mkdesc(SM_BASE + C_XR + wg * 4096, 16, 1024) + ln, xl[2] = {__shfl_sync(0xffffffffu, x0, 0), __shfl_sync(0xffffffffu, x0, 1)};
    auto chunk = [&](int a0, int i, int first) {
#pragma unroll
        for (int ks = 0; ks < 4; ks++)
            wgmma_rs_n32(acc, wa[a0 + 4 * i + ks], (mkdesc(0, 0, 1024) | (uint32_t)(xl[!a0] + ((((i ? (i - 1) * 8192 : C_MEM - C_XR) + ks * 32) >> 4) - !a0))), !(first && ks == 0));
    };
    mbar_wait(sm + CB_XF, n & 1);
    if (n) bar_sync(5, 384);
    if (wg == 0 && w == 0) PROF(12);
    WG_FENCE();
    chunk(20, 1, 1); chunk(20, 2, 0); chunk(20, 3, 0);
    mbar_wait(sm + CB_XM, n & 1);
    if (wg == 0 && w == 0) PROF(13);
    WG_FENCE();
    chunk(20, 0, 0);
    mbar_wait(sm + CB_XF + 8, n & 1);
    if (wg == 0 && w == 0) PROF(17);
    WG_FENCE();
    chunk(20, 4, 0);
    WG_COMMIT();
    if (n) {
        if (wg == 1 && w == 1) { BULK_WAIT(); seg_done(n - 1, head); }
        bar_sync(8, 256);
    }
    if (wg == 0 && w == 0) PROF(18);
    const uint32_t xb = sm + w * 512 + ln * 16, xw = xb + C_KX - wg * 4096, xr = xb + C_QX + wg * 4096;
    WG_WAIT(0);
#pragma unroll
    for (int i = 0; i < 8; i++) asm volatile("cvt.rn.bf16x2.f32 %0, %1, %2;" : "=r"(giv[i]) : "f"(acc[2 * i + 1]), "f"(acc[2 * i]));
#pragma unroll
    for (int p = 0; p < 2; p++) asm volatile("st.shared.v4.u32 [%0], {%1,%2,%3,%4};" :: "r"(xw + p * 2048), "r"(giv[4 * p]), "r"(giv[4 * p + 1]), "r"(giv[4 * p + 2]), "r"(giv[4 * p + 3]) : "memory");
    bar_arrive(12 + wg, 256);
    WG_FENCE();
    chunk(0, 0, 1);
    WG_COMMIT();
    chunk(0, 1, 0);
    if (XORD) chunk(0, 2, 0);
    bar_sync(13 - wg, 256);
#pragma unroll
    for (int p = 0; p < 2; p++) asm volatile("ld.shared.v4.u32 {%0,%1,%2,%3}, [%4];" : "=r"(giv[4 * p]), "=r"(giv[4 * p + 1]), "=r"(giv[4 * p + 2]), "=r"(giv[4 * p + 3]) : "r"(xr + p * 2048) : "memory");
    WG_COMMIT(); WG_WAIT(1); bar_arrive(9, 384);
    WG_FENCE();
    if (!XORD) chunk(0, 2, 0);
    chunk(0, 3, 0); chunk(0, 4, 0);
    WG_COMMIT();
    const uint32_t r = ln & 7, mi = ln >> 3, dst = sm + (wg == 0 ? C_QX : C_KX) + ((mi >> 1) * 8 + r) * 128 + (((2 * w + (mi & 1)) ^ r) << 4);
    pin(xb, giv[0], giv[4], dst, 0);
    bar_sync(10 + wg, 128);
    WG_WAIT(0);
    if (wg == 0 && w == 0) PROF(30);
    if (w == 0 && ln < 3) mbar_arrive_remote(mapa(sm + CB_XD, ln));
#pragma unroll
    for (int i = 0; i < 8; i++) { acc[2 * i] += lo_f(giv[i]); acc[2 * i + 1] += hi_f(giv[i]); }
#pragma unroll
    for (int p = 0; p < 2; p++)
        stsm4t(dst + p * 2048, pack2(acc[8 * p], acc[8 * p + 1]), pack2(acc[8 * p + 2], acc[8 * p + 3]), pack2(acc[8 * p + 4], acc[8 * p + 5]), pack2(acc[8 * p + 6], acc[8 * p + 7]));
}
__device__ __forceinline__ void x_fill(const ChainMaps& mp, uint32_t sm, int n, int j, int g) {
    mbar_expect(sm + CB_XF + 8 * g, g ? 8192 : 24576);
    const int c = g ? 6 : 2 * j;
    if (!g || j == 2)
        asm volatile("cp.async.bulk.tensor.3d.shared::cluster.global.mbarrier::complete_tx::bytes.multicast::cluster [%0], [%1, {0, %3, %4}], [%2], %5;"
            :: "r"(sm + C_XR + c * 4096), "l"((uint64_t)&mp.h2), "r"(sm + CB_XF + 8 * g), "r"(n * SEG), "r"(2 + c), "h"((uint16_t)7) : "memory");
}

__global__ void __cluster_dims__(3, 1, 1) __launch_bounds__(384, 1) k_chain(const __grid_constant__ ChainMaps mp, const __grid_constant__ ChainArgs ar) {
    const int D1 = ar.D1, DG = ar.DG;
    extern __shared__ __align__(1024) uint8_t smraw[];
    const uint32_t sm = SM_BASE + ((blockIdx.x % 3) << 24);
    if (smem_u32(smraw) != sm) __trap();
    uint32_t tid; asm volatile("mov.u32 %0, %%tid.x;" : "=r"(tid));
    const int warp = __shfl_sync(0xffffffffu, tid >> 5, 0), lane = tid & 31, wg = warp >> 2, w = warp & 3;
    const int blk = blockIdx.x, head = blk / 3, j = blk % 3;
    const int col0 = head * DH + j * 64;
    asm volatile("griddepcontrol.launch_dependents;");
#define PPROF(i)
    {
        const int mc0 = (blk >> 1) * 80 + (blk & 1) * 32, mcn = (blk & 1) ? 24 : 16;
        const int nrow = blk < 74 ? 2 : blk == 74 ? (warp < 8 ? 2 : 1) : 1;
        if (tid == 0) {
            mbar_init(sm + CB_PRE, 1);
            asm volatile("fence.mbarrier_init.release.cluster;" ::: "memory");
            const int n1 = blk < 74 ? 15360 : blk == 74 ? 10240 : 0;
            mbar_expect(sm + CB_PRE, 61440 + 1280 + 15360 + n1);
            bulk_g2s(sm + C_QM, ar.c, 1280, sm + CB_PRE);
#pragma unroll 1
            for (int c = 0; c < 4; c++) tma2d(sm + C_WO + 24576 + c * 15360, &mp.wmod, mc0, c * 160, sm + CB_PRE);
            bulk_g2s(sm + C_XR, ar.x + blk * 12 * DM, 15360, sm + CB_PRE);
            if (n1) bulk_g2s(sm + C_XR + 15360, ar.x + (1152 + blk * 12) * DM, n1, sm + CB_PRE);
        }
        if (tid == 32) {
#pragma unroll 1
            for (int c = 0; c < 11; c++) if (c != 5) mbar_init(sm + C_BAR + 8 * c, c == 2 ? 5 : c == 3 ? 6 : 1);
            asm volatile("fence.mbarrier_init.release.cluster;" ::: "memory");
            mbar_expect(sm + CB_SC, 2560); mbar_expect(sm + CB_OX, 2048);
        }
        if (warp == 2) {
            ((uint4*)g_acc)[blk * 32 + lane] = make_uint4(0, 0, 0, 0);
            if (blk < 12) ((uint4*)g_stamp)[blk * 32 + lane] = make_uint4(0, 0, 0, 0);
            __threadfence();
        }
        PPROF(8);
        asm volatile("barrier.cluster.arrive.release.aligned; barrier.cluster.wait.acquire.aligned;" ::: "memory");
        PPROF(9);
        mbar_wait(sm + CB_PRE, 0);
        PPROF(10);
        if (tid == 352) {
            const uint64_t ef = policy_stream();
            mbar_expect(sm + CB_W, 2 * 81920);
#pragma unroll 1
            for (int c = 0; c < 10; c++) tma2d_ef(sm + C_WV + c * 8192, &mp.wq, col0, c * 64, sm + CB_W, ef);
        }
        if (tid < 320) {
            const uint32_t cv = lds32(sm + C_QM + tid * 4);
            asm volatile("st.shared.v2.f32 [%0], {%1,%2};" :: "r"(sm + C_QX + tid * 8), "f"(bfr(__fdividef(lo_f(cv), 1.f + __expf(-lo_f(cv))))),
                         "f"(bfr(__fdividef(hi_f(cv), 1.f + __expf(-hi_f(cv))))) : "memory");
        }
        __syncthreads();
        {
            float a0 = 0, a1 = 0;
            const uint32_t k0 = (tid / 24) * 40, wa0 = sm + C_WO + 24576 + k0 * 96 + (tid % 24) * 4;
#pragma unroll 4
            for (int i = 0; i < 40; i++) {
                const float sc = __uint_as_float(lds32(sm + C_QX + (k0 + i) * 4));
                const uint32_t wv = lds32(wa0 + i * 96);
                a0 += sc * lo_f(wv); a1 += sc * hi_f(wv);
            }
            asm volatile("st.shared.v2.f32 [%0], {%1,%2};" :: "r"(sm + C_MEM + tid * 8), "f"(a0), "f"(a1) : "memory");
        }
        __syncthreads();
        PPROF(11);
        if (warp == 0) {
            float a0 = 0, a1 = 0;
            const int cp = lane < mcn ? lane : 0;
#pragma unroll 4
            for (int i = 0; i < 16; i++) { const float2 v = lds64f(sm + C_MEM + (i * 24 + cp) * 8); a0 += v.x; a1 += v.y; }
            uint32_t* dst = (uint32_t*)(g_mod + mc0) + cp;
            *dst = pack2(a0, a1);
            const uint32_t rb = ld_rlx(dst);
            PPROF(1);
            if (__all_sync(0xffffffffu, rb == pack2(a0, a1)) && tid == 0) bump(blk < 32 ? &g_flags.mod : &g_flags.h);
            if (tid == 0) flag_wait(&g_flags.mod, 32);
            PPROF(2);
        }
        __syncthreads();
        uint32_t sv[10], tv[10], bad = 0;
#pragma unroll
        for (int i = 0; i < 10; i++) { sv[i] = __ldcg((const uint32_t*)g_mod + DM / 2 + lane + 32 * i); tv[i] = __ldcg((const uint32_t*)g_mod + lane + 32 * i); }
#pragma unroll 1
        for (int q = 0; q < nrow; q++) {
            float xv[20], hv[20];
#pragma unroll
            for (int i = 0; i < 10; i++) { const uint32_t v = lds32(sm + C_XR + q * 15360 + warp * 1280 + lane * 4 + i * 128); xv[2 * i] = lo_f(v); xv[2 * i + 1] = hi_f(v); }
            ln_mod(xv, sv, tv, hv);
            uint32_t* dst = (uint32_t*)g_h + (q * 1152 + blk * 12 + warp) * (DM / 2) + lane;
#pragma unroll
            for (int i = 0; i < 10; i++) dst[32 * i] = pack2(hv[2 * i], hv[2 * i + 1]);
#pragma unroll
            for (int i = 0; i < 10; i++) bad |= ld_rlx(dst + 32 * i) ^ pack2(hv[2 * i], hv[2 * i + 1]);
        }
        if (__syncthreads_or(bad)) __trap();
        PPROF(3);
        if (tid == 0) {
            bump(&g_flags.h);
            flag_wait(&g_flags.h, 160);
            mbar_expect(sm + CB_XM, 8192); tma3d(sm + C_MEM, &mp.h2, 0, 0, sm + CB_XM);
            x_fill(mp, sm, 0, j, 0); x_fill(mp, sm, 0, j, 1);
            const uint64_t ef = policy_stream();
#pragma unroll 1
            for (int c = 0; c < 10; c++) tma2d_ef(sm + C_WO + c * 8192, &mp.wk, col0, c * 64, sm + CB_W, ef);
        }
        PPROF(4);
        __syncthreads();
        if (tid >= 64) {
#pragma unroll 1
            for (int i = tid - 64; i < 640 + 192 * 4; i += 320)
                asm volatile("prefetch.global.L2 [%0];" :: "l"(i < 640 ? ar.wv + (size_t)i * HD + col0 : ar.wo + (size_t)(head * DH + ((i - 640) >> 2)) * DM + j * 224 + min((i & 3) * 64, 639 - j * 224)));
        }
    }
    const int r = lane & 7, mi = lane >> 3;
    const uint32_t memrd = opaque(sm + C_MEM + lane * 16);
    constexpr float S_ACC = 64.f;
    if (wg < 2) {
        asm volatile("setmaxnreg.inc.sync.aligned.u32 %0;" :: "n"(REG_P));
        uint32_t wa[40][4];
        mbar_wait(sm + CB_W, 0);
#pragma unroll
        for (int ks = 0; ks < 40; ks++)
            ldsm4t(wa[ks], sm + ((wg == 0) == (ks < 20) ? C_WV : C_WO) + ((mi >> 1) * 8 + r) * 128 + (((2 * w + (mi & 1)) ^ r) << 4) + (ks % 20 / 4 * 8 + 4 * wg + (ks & 3)) * 2048);
        PPROF(5);
        bar_sync(1, 384);
        x_part(wa, sm, 0, wg, w, lane, head);
        PPROF(6);
        mbar_wait(sm + CB_W2, 0);
        PPROF(7);
        const uint32_t qst = opaque(sm + (wg == 0 ? C_QM : C_KM) + (2 * w + (mi & 1)) * 128 + r * 16);
        const uint32_t vrd = opaque(sm + C_WV + ((mi >> 1) * 8 + r) * 128 + (((2 * w + (mi & 1)) ^ r) << 4) + 4 * wg * 2048);
        const uint32_t mrd = opaque(memrd + wg * 1024);
        for (int s = 0; s < NSEG; s++) {
            const float un = s ? 1.f / S_ACC : 1.f;
            cut(s + ar.D2, 0);
            bar_sync(1, 384);
            if (warp == 0) { PROF(0); PROFG(24); }
            uint32_t b[3][4], a[5][4];
            float dv[2][4] = {{0, 0, 0, 0}, {0, 0, 0, 0}};
            auto fb = [&](int n) { return mrd + (n >> 1) * 2048 + (n & 1) * 512; };
            auto fa = [&](int k) { return vrd + (k >> 2) * 16384 + (k & 3) * 2048; };
            {
                float d[2][4] = {{0, 0, 0, 0}, {0, 0, 0, 0}}, g[2][4] = {{0, 0, 0, 0}, {0, 0, 0, 0}};
                ldsm4t(b[0], fb(0)); pin0(mrd); ldsm4t(b[1], fb(1)); pin0(mrd);
#pragma unroll
                for (int n = 0; n < 10; n++) {
                    const int c1 = (NCH == 2 || n >= 8);
                    if (n < 8) ldsm4t(b[(n + 2) % 3], fb(n + 2));
                    if (n + ALA >= 2 && n + ALA < 2 + VF) ldsm4t(a[2 + (n + ALA) % 3], fa(2 * (n + ALA)));
                    if (!VPOS && n >= 9 - VPRE && n < 9) ldsm4t(a[n - 9 + VPRE], fa(16 + n - 9 + VPRE));
                    mma16q(g[0], wa[20 + 2 * n], b[n % 3][0], b[n % 3][1]); mma16q(d[0], wa[2 * n], b[n % 3][0], b[n % 3][1]);
                    if (n >= 2 && n < 2 + VF) mma16q(dv[0], a[2 + n % 3], b[n % 3][0], b[n % 3][1]);
                    mma16q(g[c1], wa[21 + 2 * n], b[n % 3][2], b[n % 3][3]); mma16q(d[c1], wa[2 * n + 1], b[n % 3][2], b[n % 3][3]);
                    if (QCUT >> n & 1) cut(s + ar.D2, 1 + n);
                }
                const uint32_t xb = mrd - wg * 1024 - (C_MEM - C_VP) + w * 512;
                sts128f(xb + wg * 2048, g[0][0] + g[1][0], g[0][1] + g[1][1], g[0][2] + g[1][2], g[0][3] + g[1][3]);
                bar_sync(8, 256);
                const float4 z = lds128f(xb + (wg ^ 1) * 2048);
                if (VPOS) {
                    pin0(mrd);
#pragma unroll
                    for (int i = 0; i < VPRE; i++) ldsm4t(a[i], fa(16 + i));
                }
                stsm2t(qst, pack2((d[0][0] + d[1][0] + z.x) * un, (d[0][1] + d[1][1] + z.y) * un), pack2((d[0][2] + d[1][2] + z.z) * un, (d[0][3] + d[1][3] + z.w) * un));
            }
            bar_arrive(2, 384);
            if (w == 0) PROF(1 + wg);
            {
                if (warp == 3)
                    asm volatile(ELECTED("st.relaxed.gpu.global.u32 [%0], %1;") :: "l"(g_stamp + (s & 3) * 384 + (blk >> 3) * 32 + (blk & 7)), "r"((gtime() & ~31u) | ((s >> 2) + 1)) : "memory");
                PROXY_FENCE();
                bar_sync(7, 384);
                constexpr int NR = 16 - VF, NB = 4 + 12 - 2 * VF;
                auto kst = [&](int i) { return i < 4 ? 16 + i : i < NB ? i + 2 * VF : 5 + 2 * (i - NB); };
                const uint32_t mo = mrd + 256 + (mrd & 256);
                auto fc = [&](int p) { return 2 * p < NB ? fb(p + VF) : mo + (1 + (2 * p - NB) / 2) * 2048; };
#pragma unroll
                for (int i = VPRE; i < 4; i++) ldsm4t(a[i], fa(kst(i)));
#pragma unroll
                for (int i = 0; i < NR; i++) {
                    if (i + 4 < NR) ldsm4t(a[(i + 4) % 5], fa(kst(i + 4)));
                    if (!(i & 1) && i + 4 < NR) ldsm4t(b[(i / 2 + 1) % 3], fc(i / 2 + 2));
                    mma16q(dv[~i & 1], a[i % 5], b[(i / 2 + 2) % 3][2 * (i & 1)], b[(i / 2 + 2) % 3][2 * (i & 1) + 1]);
                }
                sts128f(mrd - (C_MEM - C_VP) + wg * 1024 + w * 512, dv[0][0] + dv[1][0], dv[0][1] + dv[1][1], dv[0][2] + dv[1][2], dv[0][3] + dv[1][3]);
            }
            if (warp == 0) bar_sync(4, 384);
            else bar_arrive(4, 384);
            if (warp == 0) {
                PROF(7);
                if (s + 1 < NSEG && elect()) {
                    mbar_expect(sm + CB_XM, 8192); tma3d(sm + C_MEM, &mp.h2, (s + 1) * SEG, 0, sm + CB_XM);
                }
            } else {
                if (wg == 1) {
                    if (w == 1) {
                        w_tma2d_store(&mp.k32, col0, s * SEG, sm + C_KX); w_tma2d_store(&mp.q32, col0, s * SEG, sm + C_QX);
                        w_bulk_s2g((uint8_t*)g_kvm + (s * NH + head) * 6144 + j * 1024, sm + C_KM, 1024);
                        BULK_COMMIT();
                        if (s + 1 == NSEG) { BULK_WAIT(); seg_done(s, head); }
                    }
                    if (w == 2 && blk < 10 && s + 3 < NSEG)
                        asm volatile(ELECTED("cp.async.bulk.prefetch.L2.global [%0], 4096;") :: "l"((const uint8_t*)g_h + (s + 3) * (SEG * DM * 2) + blk * 4096) : "memory");
                } else if (w == 3) {
                    const uint32_t l = opaque(mrd) >> 4 & 31, tag = (s >> 2) + 1, now = gtime();
                    const uint32_t* sp = g_stamp + (s & 3) * 384 + (l >> 3) * 32 + (l & 7);
                    uint32_t t[3];
                    for (int n = 0;; n++) {
#pragma unroll
                        for (int i = 0; i < 3; i++) t[i] = ld_rlx(sp + i * 128);
                        if (!__any_sync(0xffffffffu, ((t[0] ^ tag) | (t[1] ^ tag) | (t[2] ^ tag)) & 31) || n > SPIN_LIMIT) break;
                    }
                    int all = -(1 << 30), own = all;
#pragma unroll
                    for (int i = 0; i < 3; i++) { const int d = t[i] - now; all = max(all, d); if ((i * 32 + l) / 3 == head) own = d; }
                    const int lag = min(__reduce_max_sync(0xffffffffu, all) - __reduce_max_sync(0xffffffffu, own), 8000);
                    PROFV(15, lag);
                    asm volatile("st.shared.u32 [%0], %1;" :: "r"(sm + C_LAG), "r"(D1 + ((lag * DG) >> 4)) : "memory");
                    if (s + 1 < NSEG) bar_arrive(6, 160);
                } else if (w == 2) {
                    if (s + 1 < NSEG) {
                        if ((s & 3) == 3) w_flag_wait(&g_flags.v[((s + 1) >> 2) * 32 + head], 2);
                        if (elect()) { mbar_expect(sm + CB_VX, 4096); tma2d(sm + C_VX, &mp.v32, col0, (s + 1) * SEG, sm + CB_VX); }
                    }
                    if ((s & 3) == 1 && s + 3 < NSEG) asm volatile("prefetch.global.L2 [%0];" :: "l"(&g_flags.v[((s + 3) >> 2) * 32]));
                    if (s + 2 < NSEG && ((s & 3) != 2 || __all_sync(0xffffffffu, ld_rlx(&g_flags.v[((s + 2) >> 2) * 32 + head]) >= 2)))
                        asm volatile("prefetch.global.L2 [%0];" :: "l"(g_v + (size_t)((s + 2) * SEG + (opaque(mrd) >> 4 & 31)) * HD + col0));
                } else if (s + 1 < NSEG) {
                    mbar_wait(sm + CB_OX, s & 1);
                    if (elect()) x_fill(mp, sm, s + 1, j, 1);
                }
            }
            if (s + 1 == NSEG) break;
            x_part(wa, sm, s + 1, wg, w, opaque(mrd) >> 4 & 31, head);
            if (warp == 0) PROF(11);
        }
    } else {
        asm volatile("setmaxnreg.dec.sync.aligned.u32 %0;" :: "n"(REG_L));
        bar_sync(1, 384);
        if (tid == 256) {
            mbar_expect(sm + CB_W2, 81920 + 3 * WO_BLK);
#pragma unroll 1
            for (int c = 0; c < 10; c++) tma2d(sm + C_WV + c * 8192, &mp.wv, col0, c * 64, sm + CB_W2);
#pragma unroll 1
            for (int c = 0; c < 3; c++) tma3d(sm + C_WO + c * WO_BLK, &mp.wo, head * DH + (j + c) % 3 * 64, 7 * j, sm + CB_W2);
        }
        bar_sync(9, 384);
#pragma unroll 1
        for (int c = tid - 256; c < DM; c += 128) {
            uint32_t u[8];
#pragma unroll
            for (int i = 0; i < 8; i++) u[i] = __ldg((const unsigned short*)ar.mem0 + i * DM + c);
            asm volatile("st.shared.v4.u32 [%0], {%1,%2,%3,%4};" :: "r"(sm + C_MEM + c * 16), "r"(u[0] | u[1] << 16), "r"(u[2] | u[3] << 16), "r"(u[4] | u[5] << 16), "r"(u[6] | u[7] << 16) : "memory");
        }
        __syncwarp();
        if (w == 1) {
            w_flag_wait(&g_flags.v[head], 2);
            if (elect()) { mbar_expect(sm + CB_VX, 4096); tma2d(sm + C_VX, &mp.v32, col0, 0, sm + CB_VX); }
        }
        mbar_wait(sm + CB_W2, 0);
        const float scale = 0.07216878364870322f;
        uint32_t va[8][4], mr = memrd;
#pragma unroll
        for (int i = 0; i < 8; i++) ldsm4t(va[i], sm + C_WV + ((mi >> 1) * 8 + r) * 128 + (((2 * w + (mi & 1)) ^ r) << 4) + i * 2048);
        for (int s = 0; s < NSEG; s++) {
            const float un = s ? 1.f / S_ACC : 1.f;
            bar_sync(1, 384);
            if (w == 0) {
                mbar_wait(sm + CB_XD, s & 1);
                if (s + 1 < NSEG && elect()) x_fill(mp, sm, s + 1, j, 0);
            } else if (w == 1 && s > 0) { BULK_WAIT(); seg_done(s - 1, head); }
            const uint32_t l0 = mr >> 4 & 31, r0 = l0 & 7, m0 = l0 >> 3;
            uint32_t kb[2][4];
            {
                const uint32_t k7 = (4 * (w & 1) + (r0 >> 2) * 2 + (r0 & 1)) ^ (r0 << 1 & 4);
                const uint32_t kxrd = sm + C_KX + (16 * (w >> 1) + (r0 << 2 & 8) + k7) * 128 + ((m0 ^ k7) << 4);
                ldsm4(kb[0], kxrd); ldsm4(kb[1], kxrd ^ 64);
            }
            float vd[4];
            {
                uint32_t c[4][4];
#pragma unroll
                for (int i = 0; i < 4; i++) ldsm4t(c[i], mr + i * 512);
                float d[2][4] = {{0, 0, 0, 0}, {0, 0, 0, 0}};
#pragma unroll
                for (int i = 0; i < 8; i++) mma16q(d[i & 1], va[i], c[i >> 1][2 * (i & 1)], c[i >> 1][2 * (i & 1) + 1]);
#pragma unroll
                for (int i = 0; i < 4; i++) vd[i] = d[0][i] + d[1][i];
            }
            uint32_t zr = 0;
            if (w == 2)
                asm volatile("atom.relaxed.gpu.global.exch.b32 %0, [%1], 0;" : "=r"(zr)
                    : "l"(g_acc + ((s & 2) ^ 2) * (ACC_PAIR / 2) + (s & 1) * 512 + (blk >> 2) * 1024 + (blk & 3) * 128 + l0 * 4) : "memory");
            __syncwarp();
            const uint32_t sco = (w >> 1) * 512 + (l0 >> 2) * 64 + (w & 1) * 32 + ((l0 >> 1) & 1) * 16;
            const uint32_t qrd = sm + C_QM + ((m0 & 1) * 2 + (m0 >> 1)) * 128 + r0 * 16;
            const uint32_t scdst = sm + C_SC + j * 1280 + sco;
            const uint32_t rbase = mapa(sm, (j + 1 + (l0 & 1)) % 3) - sm;
            const uint32_t scm = 1024 + (l0 >> 1) * 16 - sco;
            const uint32_t v7 = r0 ^ (m0 << 2 & 4), vxrd = sm + C_VX + (8 * m0 + v7) * 128 + (((2 * w) ^ v7) << 4);
            mbar_wait(sm + CB_VX, s & 1);
            uint32_t vb[2][4];
            ldsm4t(vb[0], vxrd); ldsm4t(vb[1], vxrd ^ 16);
            const uint32_t word = sm + C_WO + (m0 & 1) * 4096 + ((m0 >> 1) * 8 + r0) * 64 + ((w ^ (r0 >> 1)) << 4);
            const uint32_t word6 = word + 6 * 4096 - (m0 & 1) * 3072;
            const uint32_t oxrd = sm + C_OX + l0 * 8;
            const uint32_t ord = sm + C_OX + (l0 >> 1) * 16 + w * 256 + (2 - (l0 & 1)) * 1024 + rbase;
            pin(mr, qrd, scdst, rbase, scm); pin(mr, scdst + scm + rbase, scdst + rbase, sm + CB_SC + rbase, scdst + scm); pin(mr, word, word6, oxrd, ord);
            pin(mr, __float_as_uint(vd[0]), __float_as_uint(vd[1]), __float_as_uint(vd[2]), __float_as_uint(vd[3]));
            bar_sync(2, 384);
            const bool odd = mr & 16;
            {
                uint32_t qa[2][4];
                ldsm4(qa[0], qrd); ldsm4(qa[1], qrd + 512);
                float x[4];
                if (w == 3) {
                    uint32_t km[2][4]; float y[4];
                    ldsm4(km[0], mr + (C_KM - C_MEM)); ldsm4(km[1], mr + (C_KM - C_MEM) + 512);
                    score_tile(qa, kb, odd, x); score_tile(qa, km, odd, y);
                    send_piece(x, scdst + rbase, sm + CB_SC + rbase, scdst); send_piece(y, scdst + scm + rbase, sm + CB_SC + rbase, scdst + scm);
                } else {
                    score_tile(qa, kb, odd, x);
                    send_piece(x, scdst + rbase, sm + CB_SC + rbase, scdst);
                }
            }
            bar_arrive(7, 384);
            if (elect()) mbar_arrive(sm + CB_SC);
            if (w == 0) PROF(4);
            const uint32_t vp = mr - (C_MEM - C_VP) + w * 512, vmst = mr + (C_VM - C_MEM) + w * 256;
            if (s + 1 == NSEG) {
                mbar_wait(sm + CB_SC, s & 1);
                bar_sync(4, 384);
                const float4 y0 = lds128f(vp), y1 = lds128f(vp + 2048);
                stsm2t(vmst, pack2((vd[0] + y0.x + y1.x) * un, (vd[1] + y0.y + y1.y) * un), pack2((vd[2] + y0.z + y1.z) * un, (vd[3] + y0.w + y1.w) * un));
                PROXY_FENCE();
                bar_sync(3, 128);
                if (w == 1) {
                    w_bulk_s2g((uint8_t*)g_kvm + (s * NH + head) * 6144 + 3072 + j * 1024, sm + C_VM, 1024);
                    BULK_COMMIT(); BULK_WAIT(); seg_done(s, head);
                }
                __syncwarp();
                break;
            }
            pin(mr, vp, vmst, oxrd + w * 256, sm + CB_OX + rbase);
            cut(s + ar.D2, 0);
            mbar_wait(sm + CB_SC, s & 1);
            if (w == 0) PROF(8);
            float sv[10];
            {
                const uint32_t scrd = mr + (C_SC - C_MEM);
                float4 x[3], y[3]; float2 z[3];
#pragma unroll
                for (int p = 0; p < 3; p++) { x[p] = lds128f(scrd + p * 1280); y[p] = lds128f(scrd + p * 1280 + 512); z[p] = lds64f(oxrd + (C_SC - C_OX) + p * 1280 + 1024); }
                sv[0] = (x[0].x + x[1].x) + x[2].x; sv[1] = (x[0].y + x[1].y) + x[2].y; sv[2] = (x[0].z + x[1].z) + x[2].z; sv[3] = (x[0].w + x[1].w) + x[2].w;
                sv[4] = (y[0].x + y[1].x) + y[2].x; sv[5] = (y[0].y + y[1].y) + y[2].y; sv[6] = (y[0].z + y[1].z) + y[2].z; sv[7] = (y[0].w + y[1].w) + y[2].w;
                sv[8] = (z[0].x + z[1].x) + z[2].x; sv[9] = (z[0].y + z[1].y) + z[2].y;
            }
            float mx = fmaxf(fmaxf(fmaxf(sv[0], sv[1]), fmaxf(sv[2], sv[3])), fmaxf(fmaxf(fmaxf(sv[4], sv[5]), fmaxf(sv[6], sv[7])), fmaxf(sv[8], sv[9])));
            uint32_t a[NRING][4];
            auto frag = [&](int i) { const int p = i / 7, u = i % 7, o = (p >> 1) * WO_BLK + (p & 1) * 2048;
                                     return u == 3 ? word6 + o : word + o + (u > 3 ? 1024 + (u - 4) * 8192 : u * 8192); };
            mx = fmaxf(fmaxf(mx, __shfl_xor_sync(0xffffffffu, mx, 1)), fmaxf(__shfl_xor_sync(0xffffffffu, mx, 2), __shfl_xor_sync(0xffffffffu, mx, 3)));
            pin(mr, __float_as_uint(mx), 0, 0, 0);
            bar_sync(4, 384);
            {
                const float4 y0 = lds128f(vp), y1 = lds128f(vp + 2048);
                pin0(mr);
#pragma unroll
                for (int i = 0; i < NPRE; i++) ldsm4t(a[i], frag(i));
                pin0(mr);
                const float sl2e = scale * 1.4426950408889634f, mxl = mx * sl2e;
#pragma unroll
                for (int i = 9; i >= 0; i--) asm volatile("ex2.approx.ftz.f32 %0, %1;" : "=f"(sv[i]) : "f"(fmaf(sv[i], sl2e, -mxl)));
                const uint32_t pq[4] = {pack2(sv[0], sv[1]), pack2(sv[4], sv[5]), pack2(sv[2], sv[3]), pack2(sv[6], sv[7])}, pm = pack2(sv[8], sv[9]);
                if (w == 0) PROF(6);
                float o[2][4] = {{0, 0, 0, 0}, {0, 0, 0, 0}}, o2[2][4] = {{0, 0, 0, 0}, {0, 0, 0, 0}}, sx[4] = {0, 0, 0, 0};
                const uint32_t vm0 = pack2((vd[0] + y0.x + y1.x) * un, (vd[1] + y0.y + y1.y) * un), vm1 = pack2((vd[2] + y0.z + y1.z) * un, (vd[3] + y0.w + y1.w) * un);
                mma8(sx, pm, 0, 0x3f803f80u); mma8(o[0], pm, 0, vm0); mma8(o[1], pm, 0, vm1);
                mma16q(sx, pq, 0x3f803f80u, 0x3f803f80u);
#pragma unroll
                for (int u = 0; u < 2; u++) { mma16q(o[u], pq, vb[u][0], vb[u][1]); mma16q(o2[u], pq, vb[u][2], vb[u][3]); }
                float inv; asm("rcp.approx.ftz.f32 %0, %1;" : "=f"(inv) : "f"((sx[0] + sx[2]) * (1.f / S_ACC)));
                const uint32_t f0 = pack2((o[0][0] + o2[0][2]) * inv, (o[0][1] + o2[0][3]) * inv), f1 = pack2((o[1][0] + o2[1][2]) * inv, (o[1][1] + o2[1][3]) * inv);
                const uint32_t c = __shfl_xor_sync(0xffffffffu, f0, 1), d = __shfl_xor_sync(0xffffffffu, f1, 1);
                asm volatile("st.shared.v2.u32 [%0], {%1,%2};" :: "r"(oxrd + w * 256), "r"(f0), "r"(f1) : "memory");
                asm volatile("st.async.shared::cluster.mbarrier::complete_tx::bytes.v4.b32 [%0], {%1,%2,%3,%4}, [%5];"
                    :: "r"(ord), "r"(odd ? c : f0), "r"(odd ? d : f1), "r"(odd ? f0 : c), "r"(odd ? f1 : d), "r"(sm + CB_OX + rbase) : "memory");
                stsm2t(vmst, vm0, vm1);
            }
            if (w == 0) PROF(10);
#pragma unroll
            for (int i = NPRE; i < NRING; i++) ldsm4t(a[i], frag(i));
            bar_sync(3, 128);
            float e[5][4];
#pragma unroll
            for (int q = 0; q < 5; q++) e[q][0] = e[q][1] = e[q][2] = e[q][3] = 0.f;
            constexpr int LAG = 2;
            uint8_t* pdst = g_acc + ((s & 2) * (ACC_PAIR / 2) + (s & 1) * 512 + w * 2048 + j * 8192 - C_MEM - sm + mr);
#pragma unroll
            for (int h = 0; h < 3; h++) {
                uint32_t ob[4][2];
                if (h == 1) {
#pragma unroll
                    for (int i = 14 - LAG; i < 14; i++) ldsm4t(a[i % NRING], frag(i + NRING));
                    pin(mr, zr, (uint32_t)(uint64_t)pdst, (uint32_t)((uint64_t)pdst >> 32), 0);
                    mbar_wait(sm + CB_OX, s & 1);
                    if (w == 0) PROF(9);
                }
#pragma unroll
                for (int k = 0; k < 4; k++) lds64(ob[k], oxrd + h * 1024 + k * 256);
#pragma unroll
                for (int i = 14 * h; i < 14 * h + 14; i++) {
                    const int u = i % 7, k = 2 * (i / 7 & 1);
                    if (u == 3) { mma16q(e[3], a[i % NRING], ob[k][0], ob[k][1]); mma16q(e[4], a[i % NRING], ob[k + 1][0], ob[k + 1][1]); }
                    else mma16q(e[u & 3], a[i % NRING], ob[k + (u >> 2)][0], ob[k + (u >> 2)][1]);
                    if (i == B5AT) { pin(mr, a[i % NRING][0], a[i % NRING][1], a[i % NRING][2], a[i % NRING][3]); bar_arrive(5, 384); }
                    if (i >= LAG && !(i >= 14 && i < 14 + LAG) && i - LAG + NRING < 42) ldsm4t(a[(i - LAG) % NRING], frag(i - LAG + NRING));
                }
            }
            {
                const uint32_t w6 = pack2h(e[3][0] + e[4][2], e[3][1] + e[4][3]), one = 0x3c003c00u;
                asm volatile("red.relaxed.gpu.global.add.noftz.v4.f16x2 [%0], {%1,%2,%3,%4};"
                    :: "l"(pdst), "r"(pack2h(e[0][0], e[0][1])), "r"(pack2h(e[0][2], e[0][3])), "r"(pack2h(e[1][0], e[1][1])), "r"(odd ? w6 : one) : "memory");
                asm volatile("red.relaxed.gpu.global.add.noftz.v4.f16x2 [%0], {%1,%2,%3,%4};"
                    :: "l"(pdst + 1024), "r"(pack2h(e[1][2], e[1][3])), "r"(pack2h(e[2][0], e[2][1])), "r"(pack2h(e[2][2], e[2][3])), "r"(odd ? one : w6) : "memory");
            }
            const uint32_t tw = clock();
            if (w == 0) { PROF(14); PROFG(25); }
            PROXY_FENCE();
            bar_sync(6, 160);
            mr = opaque(mr);
            const uint32_t ln = mr >> 4 & 31, due = tw + lds32(sm + C_LAG);
            const uint32_t vr = sm + C_WV + ((ln >> 4) * 8 + (ln & 7)) * 128 + (((2 * w + (ln >> 3 & 1)) ^ (ln & 7)) << 4);
            const uint32_t ms0 = sm + C_MEM + w * 128 + (ln & 7) * 16 + (ln >> 3) * 512, ms1 = ms0 + (ln < 24 ? 2048 : 1536);
            if (w == 2) { w_expect(sm + CB_SC, 2560); w_expect(sm + CB_OX, 2048); }
            if (w == 1) { w_bulk_s2g((uint8_t*)g_kvm + (s * NH + head) * 6144 + 3072 + j * 1024, sm + C_VM, 1024); BULK_COMMIT(); }
            const uint8_t* src = pdst - j * 8192;
            pin(mr, ms0, ms1, (uint32_t)(uint64_t)src, (uint32_t)((uint64_t)src >> 32));
            pin(mr, vr, due, 0, 0);
            cut(s + ar.D2, 1);
#pragma unroll
            for (int i = 0; i < 8; i++) ldsm4t(va[i], vr + i * 2048);
            wait_until(due);
            if (w == 0) { PROF(5); PROFG(26); }
            uint4 v[6];
            auto fetch = [&]() {
#pragma unroll
                for (int k = 0; k < 6; k++)
                    asm volatile("ld.relaxed.gpu.global.v4.u32 {%0,%1,%2,%3}, [%4];" : "=r"(v[k].x), "=r"(v[k].y), "=r"(v[k].z), "=r"(v[k].w) : "l"(src + (k >> 1) * 8192 + (k & 1) * 1024) : "memory");
            };
            fetch();
            bar_sync(9, 384);
#pragma unroll 1
            for (int n = 0;; n++) {
                uint32_t all = 0x50005000u;
#pragma unroll
                for (int k = 0; k < 3; k++) {
                    const uint4 x = v[2 * k], y = v[2 * k + 1];
                    all &= odd ? y.w : x.w;
                    stsm4(ms0 + k * 3584, f16_to_bf16(x.x), f16_to_bf16(x.y), f16_to_bf16(x.z), f16_to_bf16(y.x));
                    if (k < 2) { const uint32_t w6 = f16_to_bf16(odd ? x.w : y.w); stsm4(ms1 + k * 3584, f16_to_bf16(y.y), f16_to_bf16(y.z), w6, w6); }
                    else asm volatile("stmatrix.sync.aligned.m8n8.x2.shared.b16 [%0], {%1,%2};" :: "r"(ms1 + k * 3584), "r"(f16_to_bf16(y.y)), "r"(f16_to_bf16(y.z)) : "memory");
                }
                if (!__any_sync(0xffffffffu, all != 0x50005000u)) { PROFV(20 + w, n); break; }
                cut(n, SPIN_LIMIT);
                fetch();
            }
            if (w == 0) PROF(16);
        }
    }
#define TPROF(i)
    __syncthreads();
    TPROF(0);
    constexpr int T_WG = 0, T_WU = 20480, T_WD = 40960, T_X = 65536, T_GU = 81920, T_RED = 106496, T_KEY = 122880;
    if (tid == 0) {
        mbar_expect(sm + CB_W, 40960 + (blk < 80 ? 24576 : 0));
        for (int c = 0; c < 5; c++) { tma2d(sm + T_WG + c * 4096, &mp.wgate, blk * 16, c * 128, sm + CB_W); tma2d(sm + T_WU + c * 4096, &mp.wup, blk * 16, c * 128, sm + CB_W); }
        if (blk < 80) for (int c = 0; c < 6; c++) tma2d(sm + T_WD + c * 4096, &mp.wdown, blk * 8, c * 256, sm + CB_W);
    }
    auto rkey = [](int idx) { uint32_t u = __ldcg((const unsigned short*)g_r + idx); u = (u & 0x8000u) ? (~u & 0xffffu) : (u | 0x8000u); return (u << 16) | (uint32_t)(S_TOK - 1 - idx); };
    if (warp < 8) {
        if (warp == 0 && lane == 0) for (int b = 0; b < 15; b++) flag_wait(&g_flags.ln[b], 128);
        bar_sync(1, 256);
        uint32_t k[8];
#pragma unroll
        for (int i = 0; i < 8; i++) { const int idx = warp * 240 + i * 32 + lane; k[i] = i * 32 + lane < 240 ? rkey(idx) : 0u; }
#pragma unroll 1
        for (int it = 0; it < 8; it++) {
            const uint32_t m = __reduce_max_sync(0xffffffffu, max(umax3(k[0], k[1], k[2]), max(umax3(k[3], k[4], k[5]), max(k[6], k[7]))));
#pragma unroll
            for (int i = 0; i < 8; i++) if (k[i] == m) k[i] = 0;
            if (lane == 0) asm volatile("st.shared.u32 [%0], %1;" :: "r"(sm + T_KEY + (warp * 8 + it) * 4), "r"(m) : "memory");
        }
    }
    __syncthreads();
    if (warp == 0) {
        uint32_t k[6];
        k[0] = lds32(sm + T_KEY + lane * 4); k[1] = lds32(sm + T_KEY + 128 + lane * 4);
        if (lane == 0) flag_wait(&g_flags.ln[15], 128);
        __syncwarp();
        TPROF(1);
#pragma unroll
        for (int i = 0; i < 4; i++) k[2 + i] = rkey(1920 + i * 32 + lane);
#pragma unroll 1
        for (int it = 0; it < 8; it++) {
            const uint32_t m = __reduce_max_sync(0xffffffffu, max(umax3(k[0], k[1], k[2]), umax3(k[3], k[4], k[5])));
#pragma unroll
            for (int i = 0; i < 6; i++) if (k[i] == m) k[i] = 0;
            if (lane == 0) asm volatile("st.shared.u32 [%0], %1;" :: "r"(sm + T_KEY + 256 + it * 4), "r"(S_TOK - 1 - (m & 0xffffu)) : "memory");
        }
    }
    __syncthreads();
    TPROF(2);
    for (int i = tid; i < 640; i += 384) {
        const uint4 v = __ldcg((const uint4*)(g_h2 + lds32(sm + T_KEY + 256 + (i & 7) * 4) * DM + (i >> 3) * 8));
        asm volatile("st.shared.v4.u32 [%0], {%1,%2,%3,%4};" :: "r"(sm + T_X + i * 16), "r"(v.x), "r"(v.y), "r"(v.z), "r"(v.w) : "memory");
    }
    const int trow = lds32(sm + T_KEY + 256 + (lane >> 2) * 4), tcol = (blk < 80 ? blk : 0) * 8 + (lane & 3) * 2;
    const uint32_t fx1 = __ldcg((const uint32_t*)(g_x1 + trow * DM + tcol)), fh2 = __ldcg((const uint32_t*)(g_h2 + trow * DM + tcol)),
                   fgb = __ldcg((const uint32_t*)(g_mod + 5 * DM + tcol));
    const float fr = __uint_as_float((uint32_t)__ldcg((const unsigned short*)g_r + trow) << 16);
    mbar_wait(sm + CB_W, 1);
    __syncthreads();
    TPROF(3);
    if (warp < 10) {
        float dg[4] = {0, 0, 0, 0}, du[4] = {0, 0, 0, 0};
#pragma unroll
        for (int k2 = 0; k2 < 2; k2++) {
            uint32_t b[4]; ldsm4(b, sm + T_X + (warp * 2 + k2) * 512 + lane * 16);
#pragma unroll
            for (int h = 0; h < 2; h++) {
                uint32_t ag[4], au[4];
                const uint32_t o = ((warp * 4 + k2 * 2 + h) * 16 + (mi >> 1) * 8 + r) * 32 + (mi & 1) * 16;
                ldsm4t(ag, sm + T_WG + o); ldsm4t(au, sm + T_WU + o);
                mma16(dg, ag[0], ag[1], ag[2], ag[3], b[2 * h], b[2 * h + 1]); mma16(du, au[0], au[1], au[2], au[3], b[2 * h], b[2 * h + 1]);
            }
        }
        sts128f(sm + T_RED + warp * 1024 + lane * 16, dg[0], dg[1], dg[2], dg[3]); sts128f(sm + T_RED + warp * 1024 + 512 + lane * 16, du[0], du[1], du[2], du[3]);
    }
    __syncthreads();
    if (warp == 0) {
        float g4[4] = {0, 0, 0, 0}, u4[4] = {0, 0, 0, 0};
#pragma unroll
        for (int i = 0; i < 10; i++) {
            const float4 a = lds128f(sm + T_RED + i * 1024 + lane * 16), b = lds128f(sm + T_RED + i * 1024 + 512 + lane * 16);
            g4[0] += a.x; g4[1] += a.y; g4[2] += a.z; g4[3] += a.w; u4[0] += b.x; u4[1] += b.y; u4[2] += b.z; u4[3] += b.w;
        }
        float y[4];
#pragma unroll
        for (int i = 0; i < 4; i++) { const float gq = bfr(g4[i]); y[i] = bfr(__fdividef(gq, 1.f + __expf(-gq))) * bfr(u4[i]); }
        g_gu[blk * 64 + lane] = movm_t(pack2(y[0], y[1])); g_gu[blk * 64 + 32 + lane] = movm_t(pack2(y[2], y[3]));
        __syncwarp();
        TPROF(4);
        if (lane == 0) {
            flag_add(&g_flags.gu);
            if (blk < 80) {
                flag_wait(&g_flags.gu, 96);
                mbar_expect(sm + CB_W2, 24576); bulk_g2s(sm + T_GU, g_gu, 24576, sm + CB_W2);
            }
        }
        __syncwarp();
    }
    if (blk < 80) {
        mbar_wait(sm + CB_W2, 1);
        TPROF(5);
        float d[4] = {0, 0, 0, 0};
#pragma unroll
        for (int k2 = 0; k2 < 4; k2++) {
            uint32_t b[4]; ldsm4t(b, sm + T_WD + (warp * 4 + k2) * 512 + lane * 16);
#pragma unroll
            for (int h = 0; h < 2; h++) {
                uint32_t a[4]; ldsm4(a, sm + T_GU + ((warp * 8 + k2 * 2 + h) * 2 + (mi >> 1)) * 128 + r * 16);
                mma16(d, a[0], a[1], a[2], a[3], b[2 * h], b[2 * h + 1]);
            }
        }
        asm volatile("st.shared.v2.f32 [%0], {%1,%2};" :: "r"(sm + T_RED + warp * 256 + lane * 8), "f"(d[0]), "f"(d[1]) : "memory");
        __syncthreads();
        if (warp == 0) {
            float y0 = 0, y1 = 0;
#pragma unroll
            for (int i = 0; i < 12; i++) { const float2 a = lds64f(sm + T_RED + i * 256 + lane * 8); y0 += a.x; y1 += a.y; }
            const float sg = bfr(__fdividef(1.f, 1.f + __expf(-fr)));
            const float b0 = bfr(lo_f(fh2) + bfr(bfr(y0) * sg)), b1 = bfr(hi_f(fh2) + bfr(bfr(y1) * sg));
            *(uint32_t*)(ar.out + trow * DM + tcol) = pack2(lo_f(fx1) + bfr(lo_f(fgb) * b0), hi_f(fx1) + bfr(hi_f(fgb) * b1));
        }
    }
    TPROF(6);
    if (tid == 0) flags_release();
}

struct SideMaps { CUtensorMap h, wv, vst, q32, k32, v32, ost, o, wo, slab3, slab2, lnp[3]; };
constexpr int SD_ST = 43008, SD_NST = 4, SD_EPI = SD_NST * SD_ST, SD_PAR = SD_EPI + 2 * 24576, SD_BAR = SD_PAR + 6400, SD_SMEM = SD_BAR + 256;
#define VLEAD 2
#define KSO 6
#define KSA 3
#define B_8 8
#define B_16 13
__device__ __forceinline__ int o_shift(int b) { return b >= B_16 ? 4 : b >= B_8 ? 3 : 2; }
__device__ __forceinline__ int o_split(int b) { return 1 << o_shift(b); }
__device__ __forceinline__ int next_item(int lane) {
    const int b0 = lane & 15, hi = lane >> 4;
    for (int n = 0;; n++) {
        const uint32_t w0 = ld_rlx(g_flags.qk + lane), w1 = ld_rlx(g_flags.at + lane), w2 = ld_rlx(&g_flags.c[0][0] + lane), w3 = ld_rlx(&g_flags.c[2][0] + lane);
        const uint32_t o01 = __ballot_sync(0xffffffffu, w2 < 32), o23 = __ballot_sync(0xffffffffu, w3 < 2u * o_split(b0));
        const uint32_t ra = __ballot_sync(0xffffffffu, w0 >= (hi ? 64u : 192u)), rb = __ballot_sync(0xffffffffu, w1 >= (hi ? 4u * o_split(b0) : 64u));
        const int bv = __ffs(o01 | 0x10000) - 1, ba = __ffs(o01 >> 16 | 0x10000) - 1, bo = __ffs(o23 | 0x10000) - 1, bl = __ffs(o23 >> 16 | 0x10000) - 1;
        if (bl == 16) return -1;
        const int bc = __ffs(~ra | 0x10000) - 1;
        const int kind = bv < 16 && bv <= bc + VLEAD ? 0 : (rb >> 16 >> bl & 1) ? 3 : ((ra & ra >> 16) >> ba & 1) ? 1 : ((rb & 0xffff) >> bo & 1) ? 2 : bv < 16 ? 0 :
                         bo < ba ? 2 : bl < bo ? (bl >= B_16 ? 3 : -1) : ba >= B_16 ? 1 : -1;
        if (kind < 0) { if (n > (1 << 20)) __trap(); __nanosleep(300); continue; }
        const int b = kind == 3 ? bl : kind == 2 ? bo : kind == 1 ? ba : bv;
        uint32_t i = 0;
        if (lane == 0) asm volatile("atom.relaxed.gpu.global.add.u32 %0, [%1], 1;" : "=r"(i) : "l"(&g_flags.c[kind][b]) : "memory");
        i = __shfl_sync(0xffffffffu, i, 0);
        if (i < (kind < 2 ? 32u : 2u * o_split(b))) return kind << 16 | b << 8 | i;
    }
}

template <int NP>
__device__ __forceinline__ void tile_out(const float (&acc)[8 * NP], uint32_t eb, uint32_t efull, uint32_t eempty, int& eph, int w, int lane) {
    const int r = lane & 7, mi = lane >> 3, row = w * 16 + (mi & 1) * 8 + r;
    mbar_wait(eempty, eph); eph ^= 1;
#pragma unroll
    for (int p = 0; p < NP; p++) {
        const int oc = 2 * p + (mi >> 1);
        stsm4(eb + (oc >> 3) * 8192 + row * 128 + (((oc & 7) ^ r) << 4), pack2(acc[8 * p], acc[8 * p + 1]), pack2(acc[8 * p + 2], acc[8 * p + 3]),
              pack2(acc[8 * p + 4], acc[8 * p + 5]), pack2(acc[8 * p + 6], acc[8 * p + 7]));
    }
    asm volatile("fence.proxy.async.shared::cta;" ::: "memory");
    __syncwarp();
    if (lane == 0) mbar_arrive(efull);
}

template <int MT>
__device__ __forceinline__ void attn_tile(uint32_t base, uint32_t dst, uint32_t eempty, int eph, int lane) {
    constexpr int NK = MT ? 5 : 3;
    const int r = lane & 7, mi = lane >> 3, g = lane >> 2, t = lane & 3;
    float sc[NK][4];
#pragma unroll
    for (int n = 0; n < NK; n++) sc[n][0] = sc[n][1] = sc[n][2] = sc[n][3] = 0.f;
#pragma unroll 1
    for (int k2 = 0; k2 < 6; k2++) {
        const uint32_t cb = (k2 >> 1) * 4096, c0 = (k2 & 1) * 4;
        uint32_t a0[4], a1[4], bb[NK][4];
        ldsm4(a0, base + cb + (16 * MT + (mi & 1) * 8 + r) * 128 + (((c0 + (mi >> 1)) ^ r) << 4));
        ldsm4(a1, base + cb + (16 * MT + (mi & 1) * 8 + r) * 128 + (((c0 + 2 + (mi >> 1)) ^ r) << 4));
#pragma unroll
        for (int n = 0; n < NK; n++)
            ldsm4(bb[n], n < NK - 1 ? base + 12288 + cb + (8 * n + r) * 128 + (((c0 + mi) ^ r) << 4) : base + 36864 + k2 * 512 + lane * 16);
#pragma unroll
        for (int n = 0; n < NK; n++) mma16(sc[n], a0[0], a0[1], a0[2], a0[3], bb[n][0], bb[n][1]);
#pragma unroll
        for (int n = 0; n < NK; n++) mma16(sc[n], a1[0], a1[1], a1[2], a1[3], bb[n][2], bb[n][3]);
    }
    const float scale = 0.07216878364870322f, l2e = 1.4426950408889634f;
    float v[2][2 * NK], mx[2], sum[2];
#pragma unroll
    for (int hf = 0; hf < 2; hf++) {
        mx[hf] = -INFINITY;
#pragma unroll
        for (int n = 0; n < NK; n++) {
            uint32_t u = pack2(sc[n][2 * hf], sc[n][2 * hf + 1]);
            u = pack2(lo_f(u) * scale, hi_f(u) * scale);
            const int lim = 16 * MT + 8 * hf + g - 8 * n - 2 * t;
            v[hf][2 * n] = (n < NK - 1 && lim < 0) ? -1e9f : lo_f(u);
            v[hf][2 * n + 1] = (n < NK - 1 && lim < 1) ? -1e9f : hi_f(u);
            mx[hf] = fmaxf(mx[hf], fmaxf(v[hf][2 * n], v[hf][2 * n + 1]));
        }
    }
#pragma unroll
    for (int o = 1; o < 4; o <<= 1)
#pragma unroll
        for (int hf = 0; hf < 2; hf++) mx[hf] = fmaxf(mx[hf], __shfl_xor_sync(0xffffffffu, mx[hf], o));
#pragma unroll
    for (int hf = 0; hf < 2; hf++) {
        sum[hf] = 0;
#pragma unroll
        for (int q = 0; q < 2 * NK; q++) { asm("ex2.approx.ftz.f32 %0, %1;" : "=f"(v[hf][q]) : "f"((v[hf][q] - mx[hf]) * l2e)); sum[hf] += v[hf][q]; }
    }
#pragma unroll
    for (int o = 1; o < 4; o <<= 1)
#pragma unroll
        for (int hf = 0; hf < 2; hf++) sum[hf] += __shfl_xor_sync(0xffffffffu, sum[hf], o);
    uint32_t pa[NK][2];
#pragma unroll
    for (int hf = 0; hf < 2; hf++) {
        const float inv = __fdividef(1.f, sum[hf]);
#pragma unroll
        for (int n = 0; n < NK; n++) pa[n][hf] = pack2(v[hf][2 * n] * inv, v[hf][2 * n + 1] * inv);
    }
    mbar_wait(eempty, eph);
#pragma unroll 1
    for (int n4 = 0; n4 < 6; n4++) {
        const uint32_t cb = (n4 >> 1) * 4096, c0 = (n4 & 1) * 4;
        uint32_t bm[4], bb[4][4];
        ldsm4t(bm, base + 39936 + n4 * 512 + lane * 16);
#pragma unroll
        for (int u = 0; u < 4; u++) ldsm4t(bb[u], base + 24576 + cb + (8 * mi + r) * 128 + (((c0 + u) ^ r) << 4));
        float o[4][4];
#pragma unroll
        for (int u = 0; u < 4; u++) { o[u][0] = o[u][1] = o[u][2] = o[u][3] = 0.f; mma8(o[u], pa[NK - 1][0], pa[NK - 1][1], bm[u]); }
#pragma unroll
        for (int u = 0; u < 4; u++) mma16(o[u], pa[0][0], pa[0][1], pa[1][0], pa[1][1], bb[u][0], bb[u][1]);
        if (MT) {
#pragma unroll
            for (int u = 0; u < 4; u++) mma16(o[u], pa[MT ? 2 : 0][0], pa[MT ? 2 : 0][1], pa[MT ? 3 : 0][0], pa[MT ? 3 : 0][1], bb[u][2], bb[u][3]);
        }
#pragma unroll
        for (int p = 0; p < 2; p++)
            stsm4(dst + (n4 >> 1) * 8192 + ((mi & 1) * 8 + r) * 128 + (((c0 + 2 * p + (mi >> 1)) ^ r) << 4), pack2(o[2 * p][0], o[2 * p][1]), pack2(o[2 * p][2], o[2 * p][3]),
                  pack2(o[2 * p + 1][0], o[2 * p + 1][1]), pack2(o[2 * p + 1][2], o[2 * p + 1][3]));
    }
}

__global__ void __launch_bounds__(384, 1) k_side(const __grid_constant__ SideMaps mp, const bf16* __restrict__ x, const bf16* __restrict__ wr,
                                                 bf16* __restrict__ out) {
    extern __shared__ __align__(1024) uint8_t smraw[];
    const uint32_t sm = smem_u32(smraw);
    if (sm & 1023) __trap();
    const uint32_t FULL = sm + SD_BAR, EMPTY = FULL + 32, EFULL = FULL + 64, EEMPTY = FULL + 80, IFULL = FULL + 96, IEMPTY = FULL + 128, IQ = FULL + 160, SCHED = FULL + 176, PARAM = FULL + 184;
    const int tid = threadIdx.x, warp = __shfl_sync(0xffffffffu, tid >> 5, 0), lane = tid & 31;
    const uint64_t ef = policy_stream();
    if (tid == 0) {
        for (int i = 0; i < SD_NST; i++) { mbar_init(FULL + 8 * i, 1); mbar_init(EMPTY + 8 * i, 2); }
        for (int i = 0; i < 2; i++) { mbar_init(EFULL + 8 * i, 4); mbar_init(EEMPTY + 8 * i, 1); }
        for (int i = 0; i < 4; i++) { mbar_init(IFULL + 8 * i, 1); mbar_init(IEMPTY + 8 * i, 11); }
        mbar_init(SCHED, 1); mbar_init(PARAM, 1);
        asm volatile("fence.mbarrier_init.release.cluster;" ::: "memory");
    }
    __syncthreads();
    if (warp >= 8) {
      asm volatile("setmaxnreg.dec.sync.aligned.u32 40;");
      if (warp == 8) {
        int st = 0, ph = 1;
        for (int q = 0;; q++) {
            mbar_wait(IFULL + 8 * (q & 3), (q >> 2) & 1);
            const int it = __shfl_sync(0xffffffffu, lds32(IQ + 4 * (q & 3)), 0);
            if (elect()) mbar_arrive(IEMPTY + 8 * (q & 3));
            if (it < 0) break;
            const int kind = it >> 16, b = (it >> 8) & 255, i = it & 255;
            const int nst = kind == 0 ? 10 : kind == 1 ? 4 : kind == 2 ? 192 >> o_shift(b) : 2;
            const int ksched = kind == 0 ? 4 : kind == 2 ? nst - KSO : kind == 1 && b >= B_16 ? KSA : 0;
            if (kind == 1) flag_wait(&g_flags.v[b * 32 + i], 2);
            if (kind == 3) flag_wait(&g_flags.o[b], 4 << o_shift(b));
            for (int kb = 0; kb < nst; kb++) {
                mbar_wait(EMPTY + 8 * st, ph);
                const uint32_t base = sm + st * SD_ST, fb = FULL + 8 * st;
                if (kind == 1) flag_wait(&g_flags.seg[(b * 4 + kb) * 32 + i], 6);
                if (kb == ksched && elect()) mbar_arrive(SCHED);
                if (kind == 0) {
                    if (elect()) {
                        mbar_expect(fb, 40960);
                        tma2d(base, &mp.h, kb * 64, b * 128, fb);
                        tma3d(base + 16384, &mp.wv, kb * 64, i * 3, fb);
                    }
                } else if (kind == 1) {
                    if (elect()) {
                        mbar_expect(fb, 43008);
                        const int row = b * 128 + kb * 32;
                        tma3d_ef(base, &mp.q32, row, i * 3, fb, ef);
                        tma3d_ef(base + 12288, &mp.k32, row, i * 3, fb, ef);
                        bulk_g2s(base + 36864, g_kvm + ((b * 4 + kb) * NH + i) * (2 * 8 * DH), 6144, fb);
                        tma3d_ef(base + 24576, &mp.v32, row, i * 3, fb, ef);
                    }
                } else if (kind == 3) {
                    if (elect()) { mbar_expect(fb, 40960); tma3d_ef(base, &mp.lnp[o_shift(b) - 2], i * (160 >> o_shift(b)), b * KSPLIT + (kb << o_shift(b) >> 1), fb, ef); }
                } else {
                    const int k0 = ((i >> 1) * nst + kb) * 32;
                    if (elect()) { mbar_expect(fb, 28672); tma3d(base + 8192, &mp.wo, k0, (i & 1) * 5, fb); }
                    if (kb % 12 == 0) flag_wait(&g_flags.pair[b * 16 + k0 / 384], 4);
                    if (elect()) tma2d_ef(base, &mp.o, k0, b * 128, fb, ef);
                }
                __syncwarp();
                if (++st == SD_NST) { st = 0; ph ^= 1; }
            }
        }
      } else if (warp == 11) {
        flag_wait(&g_flags.h, 160);
        if (lane == 0) { mbar_expect(PARAM, 6400); bulk_g2s(sm + SD_PAR, g_mod + 2 * DM, 5120, PARAM); bulk_g2s(sm + SD_PAR + 5120, wr, 1280, PARAM); }
        for (int q = 0;; q++) {
            if (q) mbar_wait(SCHED, (q - 1) & 1);
            const int it = next_item(lane);
            if (lane == 0) {
                if (it >> 16 == 2) {
                    const int b = (it >> 8) & 255, nr = 64 >> o_shift(b);
                    asm volatile("cp.async.bulk.prefetch.L2.global [%0], %1;" :: "l"(x + (b * 128 + (it & 255) * nr) * DM), "r"(nr * DM * 2) : "memory");
                }
                mbar_wait(IEMPTY + 8 * (q & 3), ((q >> 2) & 1) ^ 1);
                asm volatile("st.shared.u32 [%0], %1;" :: "r"(IQ + 4 * (q & 3)), "r"(it) : "memory");
                mbar_arrive(IFULL + 8 * (q & 3));
                if (it < 0) flags_release();
            }
            __syncwarp();
            if (it < 0) break;
        }
      } else {
        if (lane == 0) {
            const int wg = warp - 9; int ph = 0;
            for (int q = 0;; q++) {
                mbar_wait(IFULL + 8 * (q & 3), (q >> 2) & 1);
                const int it = lds32(IQ + 4 * (q & 3));
                mbar_arrive(IEMPTY + 8 * (q & 3));
                if (it < 0) break;
                const int kind = it >> 16, b = (it >> 8) & 255, i = it & 255;
                if (kind > 2) {
                    if (wg == 0) { mbar_wait(EFULL, ph); ph ^= 1; mbar_arrive(EEMPTY); flag_add(&g_flags.ln[b], 64 >> o_shift(b)); }
                    continue;
                }
                for (int rd = 0; rd < (kind == 2 ? 2 : 1); rd++) {
                    mbar_wait(EFULL + 8 * wg, ph); ph ^= 1;
                    const uint32_t src = sm + SD_EPI + wg * 24576;
                    if (kind == 2) tma3d_store(rd ? &mp.slab2 : &mp.slab3, (b * KSPLIT + (i >> 1)) * 128 + wg * 64, (i & 1) * 5 + rd * 3, src, ef, false);
                    else tma3d_store(kind == 0 ? &mp.vst : &mp.ost, b * 128 + wg * 64, i * 3, src, ef, kind == 0 && b > 1);
                    asm volatile("cp.async.bulk.commit_group;" ::: "memory");
                    asm volatile("cp.async.bulk.wait_group.read 0;" ::: "memory");
                    mbar_arrive(EEMPTY + 8 * wg);
                }
                asm volatile("cp.async.bulk.wait_group 0;" ::: "memory");
                bump(kind == 0 ? &g_flags.v[b * 32 + i] : kind == 1 ? &g_flags.pair[b * 16 + (i >> 1)] : &g_flags.o[b]);
                if (kind < 2) bump(kind ? &g_flags.at[b] : &g_flags.vb[b]);
            }
        }
      }
    } else {
        asm volatile("setmaxnreg.inc.sync.aligned.u32 232;");
        const int wg = warp >> 2, w = warp & 3;
        int st = 0, ph = 0, eph = 1;
        const uint32_t eb = sm + SD_EPI + wg * 24576;
        for (int q = 0;; q++) {
            mbar_wait(IFULL + 8 * (q & 3), (q >> 2) & 1);
            const int itc = lds32(IQ + 4 * (q & 3));
            __syncwarp();
            if (lane == 0) mbar_arrive(IEMPTY + 8 * (q & 3));
            if (itc < 0) break;
            const int kind = itc >> 16, b = (itc >> 8) & 255, i = itc & 255;
            if (kind == 0) {
                float acc[96];
#pragma unroll
                for (int n = 0; n < 96; n++) acc[n] = 0.f;
                int prev = -1;
                for (int kb = 0; kb < 10; kb++) {
                    mbar_wait(FULL + 8 * st, ph);
                    const uint32_t base = sm + st * SD_ST;
                    WG_FENCE();
#pragma unroll
                    for (int ks = 0; ks < 4; ks++)
                        wgmma_ss_n192_tb(acc, mkdesc(base + wg * 8192 + ks * 32, 16, 1024), mkdesc(base + 16384 + ks * 2048, 8192, 1024), (kb | ks) != 0);
                    WG_COMMIT();
                    if (prev >= 0) { WG_WAIT(1); if ((tid & 127) == 0) mbar_arrive(EMPTY + 8 * prev); }
                    prev = st;
                    if (++st == SD_NST) { st = 0; ph ^= 1; }
                }
                WG_WAIT(0);
                if ((tid & 127) == 0) mbar_arrive(EMPTY + 8 * prev);
                tile_out<12>(acc, eb, EFULL + 8 * wg, EEMPTY + 8 * wg, eph, w, lane);
            } else if (kind == 1) {
                const int seg = warp >> 1, mt = warp & 1;
                int sst = st + seg, sph = ph; if (sst >= SD_NST) { sst -= SD_NST; sph ^= 1; }
                ph ^= 1;
                mbar_wait(FULL + 8 * sst, sph);
                const uint32_t base = sm + sst * SD_ST;
                if (mt) attn_tile<1>(base, eb + (w * 16) * 128, EEMPTY + 8 * wg, eph, lane);
                else attn_tile<0>(base, eb + (w * 16) * 128, EEMPTY + 8 * wg, eph, lane);
                eph ^= 1;
                asm volatile("fence.proxy.async.shared::cta;" ::: "memory");
                __syncwarp();
                if (lane == 0) { mbar_arrive(EMPTY + 8 * sst); mbar_arrive(EFULL + 8 * wg); }
            } else if (kind == 2) {
                float acc[96], acc2[64];
#pragma unroll
                for (int n = 0; n < 96; n++) acc[n] = 0.f;
#pragma unroll
                for (int n = 0; n < 64; n++) acc2[n] = 0.f;
                int prev = -1;
                for (int kb = 192 >> o_shift(b); kb > 0; kb--) {
                    const uint32_t base = sm + st * SD_ST;
                    mbar_wait(FULL + 8 * st, ph);
                    WG_FENCE();
#pragma unroll
                    for (int ks = 0; ks < 2; ks++) {
                        const uint64_t da = (mkdesc(base + wg * 4096 + ks * 32, 16, 512) & ~(3ull << 62)) | (2ull << 62);
                        wgmma_ss_n192_tb(acc, da, mkdesc(base + 8192 + ks * 2048, 4096, 1024), 1);
                        wgmma_ss_n128_tb(acc2, da, mkdesc(base + 8192 + 3 * 4096 + ks * 2048, 4096, 1024), 1);
                    }
                    WG_COMMIT();
                    if (prev >= 0) { WG_WAIT(1); if ((tid & 127) == 0) mbar_arrive(EMPTY + 8 * prev); }
                    prev = st;
                    if (++st == SD_NST) { st = 0; ph ^= 1; }
                }
                WG_WAIT(0);
                if ((tid & 127) == 0) mbar_arrive(EMPTY + 8 * prev);
                tile_out<12>(acc, eb, EFULL + 8 * wg, EEMPTY + 8 * wg, eph, w, lane);
                tile_out<8>(acc2, eb, EFULL + 8 * wg, EEMPTY + 8 * wg, eph, w, lane);
            } else {
                const int sh = o_shift(b), nr = 64 >> sh;
                int st1 = st + 1, ph1 = ph; if (st1 == SD_NST) { st1 = 0; ph1 ^= 1; }
                uint2 xin[2][5];
                uint32_t as[2][10];
#pragma unroll
                for (int q2 = 0; q2 < 10; q2++) xin[q2 & 1][q2 >> 1] = ld_ef(x + (b * 128 + i * nr + ((warp + 8 * (q2 & 1)) & (nr - 1))) * DM + lane * 4 + (q2 >> 1) * 128, ef);
                mbar_wait(PARAM, 0); mbar_wait(FULL + 8 * st, ph); mbar_wait(FULL + 8 * st1, ph1);
#pragma unroll
                for (int u2 = 0; u2 < 2; u2++) {
                    float a[20];
#pragma unroll
                    for (int q2 = 0; q2 < 20; q2++) a[q2] = 0.f;
                    if (warp + 8 * u2 < nr) {
#pragma unroll 2
                        for (int k = 0; k < (1 << sh); k++) {
                            const uint32_t ad = sm + ((k >> (sh - 1)) ? st1 : st) * SD_ST + (((k & ((1 << sh >> 1) - 1)) << (6 - sh)) + warp + 8 * u2) * 1280 + lane * 8;
                            uint32_t z[5][2];
#pragma unroll
                            for (int q2 = 0; q2 < 5; q2++) lds64(z[q2], ad + q2 * 256);
#pragma unroll
                            for (int q2 = 0; q2 < 5; q2++) { a[4 * q2] += lo_f(z[q2][0]); a[4 * q2 + 1] += hi_f(z[q2][0]); a[4 * q2 + 2] += lo_f(z[q2][1]); a[4 * q2 + 3] += hi_f(z[q2][1]); }
                        }
                    }
#pragma unroll
                    for (int q2 = 0; q2 < 10; q2++) as[u2][q2] = pack2(a[2 * q2], a[2 * q2 + 1]);
                }
                bar_sync(2 + wg, 128);
                if ((tid & 127) == 0) { mbar_arrive(EMPTY + 8 * st); mbar_arrive(EMPTY + 8 * st1); }
#pragma unroll 1
                for (int lrow = warp; lrow < nr; lrow += 8) {
                    const int row = b * 128 + i * nr + lrow;
                    const uint32_t pa = sm + SD_PAR + lane * 8;
                    float xv[20], hv[20];
                    uint32_t sv[10], tv[10];
#pragma unroll
                    for (int q2 = 0; q2 < 5; q2++) {
                        uint32_t ga[2], t[2], u[2];
                        lds64(ga, pa + q2 * 256); lds64(t, pa + 1280 + q2 * 256); lds64(u, pa + 2560 + q2 * 256);
#pragma unroll
                        for (int e = 0; e < 2; e++) {
                            const uint32_t xi = e ? xin[0][q2].y : xin[0][q2].x, ai = as[0][2 * q2 + e];
                            xv[4 * q2 + 2 * e] = bfr(lo_f(xi) + bfr(lo_f(ga[e]) * lo_f(ai))); xv[4 * q2 + 2 * e + 1] = bfr(hi_f(xi) + bfr(hi_f(ga[e]) * hi_f(ai)));
                            tv[2 * q2 + e] = t[e]; sv[2 * q2 + e] = u[e]; as[0][2 * q2 + e] = as[1][2 * q2 + e];
                        }
                        xin[0][q2] = xin[1][q2];
                    }
                    ln_mod(xv, sv, tv, hv);
                    float rs = 0;
#pragma unroll
                    for (int q2 = 0; q2 < 5; q2++) {
                        const int c = row * DM + lane * 4 + q2 * 128;
                        const float* xx = xv + 4 * q2; const float* hh = hv + 4 * q2;
                        uint32_t gb[2], wv[2];
                        lds64(gb, pa + 3840 + q2 * 256); lds64(wv, pa + 5120 + q2 * 256);
                        rs += (hh[0] * lo_f(wv[0]) + hh[1] * hi_f(wv[0])) + (hh[2] * lo_f(wv[1]) + hh[3] * hi_f(wv[1]));
                        st_ef(g_x1 + c, make_uint2(pack2(xx[0], xx[1]), pack2(xx[2], xx[3])), ef);
                        st_ef(g_h2 + c, make_uint2(pack2(hh[0], hh[1]), pack2(hh[2], hh[3])), ef);
                        st_ef(out + c, make_uint2(pack2(xx[0] + bfr(lo_f(gb[0]) * hh[0]), xx[1] + bfr(hi_f(gb[0]) * hh[1])),
                                                  pack2(xx[2] + bfr(lo_f(gb[1]) * hh[2]), xx[3] + bfr(hi_f(gb[1]) * hh[3]))), ef);
                    }
                    rs = warp_sum(rs);
                    if (lane == 0) g_r[row] = __float2bfloat16_rn(rs);
                }
                bar_sync(1, 256);
                if (wg == 0) { mbar_wait(EEMPTY, eph); eph ^= 1; if (lane == 0) mbar_arrive(EFULL); }
                st = st1 + 1; ph = ph1; if (st == SD_NST) { st = 0; ph ^= 1; }
            }
        }
    }
    __syncwarp();
    asm volatile("griddepcontrol.wait;" ::: "memory");
}

#define P_D1 650
#define P_DL 700
#define P_DG 29
typedef CUresult (*EncodeFn)(CUtensorMap*, CUtensorMapDataType, cuuint32_t, void*, const cuuint64_t*, const cuuint64_t*, const cuuint32_t*, const cuuint32_t*,
                             CUtensorMapInterleave, CUtensorMapSwizzle, CUtensorMapL2promotion, CUtensorMapFloatOOBfill);
static EncodeFn s_encode = nullptr;
static void make_map(CUtensorMap* m, const void* p, int rows, int cols, int box_rows, int box_cols = 64) {
    cuuint64_t dims[2] = {(cuuint64_t)cols, (cuuint64_t)rows}, strides[1] = {(cuuint64_t)cols * 2};
    cuuint32_t box[2] = {(cuuint32_t)box_cols, (cuuint32_t)box_rows}, es[2] = {1, 1};
    s_encode(m, CU_TENSOR_MAP_DATA_TYPE_BFLOAT16, 2, (void*)p, dims, strides, box, es, CU_TENSOR_MAP_INTERLEAVE_NONE,
             box_cols == 64 ? CU_TENSOR_MAP_SWIZZLE_128B : box_cols == 32 ? CU_TENSOR_MAP_SWIZZLE_64B : CU_TENSOR_MAP_SWIZZLE_NONE, CU_TENSOR_MAP_L2_PROMOTION_L2_256B, CU_TENSOR_MAP_FLOAT_OOB_FILL_NONE);
}
static void make_map3(CUtensorMap* m, const void* p, int rows, int cols, int box_rows, int box_chunks, int cw = 64) {
    cuuint64_t dims[3] = {(cuuint64_t)cw, (cuuint64_t)rows, (cuuint64_t)(cols / cw)}, strides[2] = {(cuuint64_t)cols * 2, (cuuint64_t)cw * 2};
    cuuint32_t box[3] = {(cuuint32_t)cw, (cuuint32_t)box_rows, (cuuint32_t)box_chunks}, es[3] = {1, 1, 1};
    s_encode(m, CU_TENSOR_MAP_DATA_TYPE_BFLOAT16, 3, (void*)p, dims, strides, box, es, CU_TENSOR_MAP_INTERLEAVE_NONE,
             cw == 64 ? CU_TENSOR_MAP_SWIZZLE_128B : CU_TENSOR_MAP_SWIZZLE_64B, CU_TENSOR_MAP_L2_PROMOTION_L2_256B, CU_TENSOR_MAP_FLOAT_OOB_FILL_NONE);
}
template <typename T> static void* sym(T& s) { void* p = nullptr; cudaGetSymbolAddress(&p, s); return p; }

extern "C" void kernel_launch(void* const* d_in, const int* in_sizes, int n_in, void* d_out, int out_size) {
    const bf16 *x = (const bf16*)d_in[0], *mem0 = (const bf16*)d_in[1], *Wq = (const bf16*)d_in[2], *Wk = (const bf16*)d_in[3],
               *Wv = (const bf16*)d_in[4], *Wo = (const bf16*)d_in[5], *wr = (const bf16*)d_in[8], *wgate = (const bf16*)d_in[9],
               *wup = (const bf16*)d_in[10], *wdown = (const bf16*)d_in[11], *c = (const bf16*)d_in[12], *wmod = (const bf16*)d_in[13];
    bf16* out = (bf16*)d_out;
    if (!s_encode) {
        cudaDriverEntryPointQueryResult qr;
        cudaGetDriverEntryPoint("cuTensorMapEncodeTiled", (void**)&s_encode, cudaEnableDefault, &qr);
        cudaFuncSetAttribute(k_side, cudaFuncAttributeMaxDynamicSharedMemorySize, SD_SMEM);
        cudaFuncSetAttribute(k_chain, cudaFuncAttributeMaxDynamicSharedMemorySize, C_SMEM);
    }
    ChainMaps cm; SideMaps sd;
    make_map(&sd.h, sym(g_h), S_TOK, DM, 128); make_map3(&sd.wv, Wv, DM, HD, 64, 3); make_map3(&sd.vst, sym(g_v), S_TOK, HD, 64, 3);
    make_map3(&sd.q32, sym(g_q), S_TOK, HD, 32, 3); make_map3(&sd.k32, sym(g_k), S_TOK, HD, 32, 3); make_map3(&sd.v32, sym(g_v), S_TOK, HD, 32, 3);
    make_map3(&sd.ost, sym(g_o), S_TOK, HD, 64, 3); make_map(&sd.o, sym(g_o), S_TOK, HD, 128, 32); make_map3(&sd.wo, Wo, HD, DM, 32, 5);
    make_map3(&sd.slab3, sym(g_slab), 16 * KSPLIT * 128, DM, 64, 3); make_map3(&sd.slab2, sym(g_slab), 16 * KSPLIT * 128, DM, 64, 2);
    for (int i = 0; i < 3; i++) {
        cuuint64_t dims[3] = {256, 320, 16 * KSPLIT}, strides[2] = {512, 128 * DM * 2};
        cuuint32_t box[3] = {256, 40u >> i, 2u << i}, es[3] = {1, 1, 1};
        s_encode(&sd.lnp[i], CU_TENSOR_MAP_DATA_TYPE_BFLOAT16, 3, sym(g_slab), dims, strides, box, es, CU_TENSOR_MAP_INTERLEAVE_NONE,
                 CU_TENSOR_MAP_SWIZZLE_NONE, CU_TENSOR_MAP_L2_PROMOTION_L2_256B, CU_TENSOR_MAP_FLOAT_OOB_FILL_NONE);
    }
    make_map(&cm.wq, Wq, DM, HD, 64); make_map(&cm.wk, Wk, DM, HD, 64); make_map(&cm.wv, Wv, DM, HD, 64); make_map3(&cm.wo, Wo, HD, DM, 64, 7, 32);
    make_map3(&cm.h2, sym(g_h), S_TOK, DM, 32, 2);
    make_map(&cm.q32, sym(g_q), S_TOK, HD, 32); make_map(&cm.k32, sym(g_k), S_TOK, HD, 32); make_map(&cm.v32, sym(g_v), S_TOK, HD, 32);
    make_map(&cm.wgate, wgate, DM, FF, 128, 16); make_map(&cm.wup, wup, DM, FF, 128, 16); make_map(&cm.wdown, wdown, FF, DM, 256, 8);
    make_map(&cm.wmod, wmod, DM, 6 * DM, 160, 48);
    ChainArgs ar = {x, mem0, c, Wv, Wo, out, P_D1, P_DL, P_DG};
    k_chain<<<96, 384, C_SMEM>>>(cm, ar);
    cudaLaunchConfig_t cfg = {};
    cfg.gridDim = dim3(N_SIDE); cfg.blockDim = dim3(384); cfg.dynamicSmemBytes = SD_SMEM; cfg.stream = cudaStreamPerThread;
    cudaLaunchAttribute at[1]; at[0].id = cudaLaunchAttributeProgrammaticStreamSerialization; at[0].val.programmaticStreamSerializationAllowed = 1;
    cfg.attrs = at; cfg.numAttrs = 1;
    cudaLaunchKernelEx(&cfg, k_side, sd, x, wr, out);
}
```

```cpp
#include <cuda_runtime.h>
#include <cuda_bf16.h>
#include <cuda.h>
#include <stdint.h>
#include <stdio.h>
#include <string.h>
#include <stdlib.h>

typedef __nv_bfloat16 bf16;
constexpr int S_TOK = 2048, DM = 640, NH = 32, DH = 192, HD = NH * DH, NSEG = 64, SEG = 32, FF = 1536;

__device__ bf16 g_mod[6 * DM];
__device__ bf16 g_h[S_TOK * DM];
__device__ bf16 g_q[S_TOK * HD];
__device__ bf16 g_k[S_TOK * HD];
__device__ bf16 g_v[S_TOK * HD];
__device__ bf16 g_o[S_TOK * HD];
__device__ __align__(128) bf16 g_kvm[NSEG * NH * 2 * 8 * DH];
__device__ bf16 g_A[S_TOK * DM];
__device__ bf16 g_x1[S_TOK * DM];
__device__ bf16 g_h2[S_TOK * DM];
__device__ bf16 g_r[S_TOK];
__device__ int g_idx[8];
__device__ __align__(128) uint32_t g_gu[FF / 8 * 32];
constexpr int ACC_PAIR = 24 * 1024;
__device__ __align__(1024) uint8_t g_acc[2 * ACC_PAIR];
__device__ __align__(1024) uint32_t g_stamp[4 * 12 * 32];
constexpr int KSPLIT = 16;
__device__ bf16 g_slab[16 * KSPLIT * 128 * DM];
struct __align__(128) Flags {
    uint32_t qk[16], vb[16];
    uint32_t at[16], o[16];
    uint32_t c[4][16];
    uint32_t ln[16], pad0[16];
    uint32_t v[16 * 32];
    uint32_t seg[64 * 32];
    uint32_t pair[16 * 16];
    uint32_t mod, h, pad1[30], gu, pad2[31], done, pad3[31];
};
__device__ Flags g_flags;

__device__ __forceinline__ uint32_t smem_u32(const void* p) { return (uint32_t)__cvta_generic_to_shared(p); }
__device__ __forceinline__ uint32_t pack2(float lo, float hi) {
    uint32_t r; asm("cvt.rn.bf16x2.f32 %0, %1, %2;" : "=r"(r) : "f"(hi), "f"(lo)); return r;
}
__device__ __forceinline__ float bfr(float x) { return __uint_as_float(pack2(0.f, x)); }
__device__ __forceinline__ float inv_std(float var) {
    float s, r; asm("sqrt.approx.f32 %0, %1;" : "=f"(s) : "f"(bfr(bfr(var) + 1e-5f))); asm("rcp.approx.f32 %0, %1;" : "=f"(r) : "f"(bfr(s))); return r;
}
__device__ __forceinline__ float lo_f(uint32_t v) { return __uint_as_float(v << 16); }
__device__ __forceinline__ float hi_f(uint32_t v) { return __uint_as_float(v & 0xffff0000u); }
__device__ __forceinline__ void mbar_init(uint32_t bar, int cnt) { asm volatile("mbarrier.init.shared::cta.b64 [%0], %1;" :: "r"(bar), "r"(cnt) : "memory"); }
__device__ __forceinline__ void mbar_expect(uint32_t bar, int bytes) { asm volatile("mbarrier.arrive.expect_tx.shared::cta.b64 _, [%0], %1;" :: "r"(bar), "r"(bytes) : "memory"); }
__device__ __forceinline__ void mbar_arrive(uint32_t bar) { asm volatile("mbarrier.arrive.shared::cta.b64 _, [%0];" :: "r"(bar) : "memory"); }
__device__ __forceinline__ bool mbar_try(uint32_t bar, int par) {
    uint32_t ok; asm volatile("{ .reg .pred p; mbarrier.try_wait.parity.shared::cta.b64 p, [%1], %2; selp.u32 %0, 1, 0, p; }" : "=r"(ok) : "r"(bar), "r"(par) : "memory"); return ok;
}
__device__ __forceinline__ bool mbar_try_cluster(uint32_t bar, int par) {
    uint32_t ok; asm volatile("{ .reg .pred p; mbarrier.try_wait.parity.acquire.cluster.shared::cta.b64 p, [%1], %2; selp.u32 %0, 1, 0, p; }" : "=r"(ok) : "r"(bar), "r"(par) : "memory"); return ok;
}
__device__ __forceinline__ bool mbar_test(uint32_t bar, uint32_t par) {
    uint32_t ok; asm volatile("{ .reg .pred p; mbarrier.test_wait.parity.shared::cta.b64 p, [%1], %2; selp.u32 %0, 1, 0, p; }" : "=r"(ok) : "r"(bar), "r"(par) : "memory"); return ok;
}
constexpr int SPIN_LIMIT = 1 << 18;
__device__ __forceinline__ void mbar_wait(uint32_t bar, uint32_t par) {
    asm volatile("{ .reg .pred p, q; .reg .u32 n; mov.u32 n, 0;\n"
                 "W_%=: mbarrier.try_wait.parity.shared::cta.b64 p, [%0], %1;\n"
                 "@p bra.uni D_%=;\n"
                 "add.u32 n, n, 1; setp.lt.u32 q, n, 0x200000; @q bra.uni W_%=;\n"
                 "trap;\n"
                 "D_%=: }" :: "r"(bar), "r"(par) : "memory");
}
__device__ __forceinline__ void tma2d(uint32_t dst, const CUtensorMap* m, int c0, int c1, uint32_t bar) {
    asm volatile("cp.async.bulk.tensor.2d.shared::cluster.global.mbarrier::complete_tx::bytes [%0], [%1, {%3, %4}], [%2];"
        :: "r"(dst), "l"((uint64_t)m), "r"(bar), "r"(c0), "r"(c1) : "memory");
}
__device__ __forceinline__ void tma2d_mc(uint32_t dst, const CUtensorMap* m, int c0, int c1, uint32_t bar, uint16_t mask) {
    asm volatile("cp.async.bulk.tensor.2d.shared::cluster.global.mbarrier::complete_tx::bytes.multicast::cluster [%0], [%1, {%3, %4}], [%2], %5;"
        :: "r"(dst), "l"((uint64_t)m), "r"(bar), "r"(c0), "r"(c1), "h"(mask) : "memory");
}
__device__ __forceinline__ uint64_t policy_stream() { uint64_t p; asm("createpolicy.fractional.L2::evict_first.b64 %0, 1.0;" : "=l"(p)); return p; }
__device__ __forceinline__ void tma2d_ef(uint32_t dst, const CUtensorMap* m, int c0, int c1, uint32_t bar, uint64_t pol) {
    asm volatile("cp.async.bulk.tensor.2d.shared::cluster.global.mbarrier::complete_tx::bytes.L2::cache_hint [%0], [%1, {%3, %4}], [%2], %5;"
        :: "r"(dst), "l"((uint64_t)m), "r"(bar), "r"(c0), "r"(c1), "l"(pol) : "memory");
}
__device__ __forceinline__ void tma3d(uint32_t dst, const CUtensorMap* m, int row, int chunk, uint32_t bar) {
    asm volatile("cp.async.bulk.tensor.3d.shared::cluster.global.mbarrier::complete_tx::bytes [%0], [%1, {0, %3, %4}], [%2];"
        :: "r"(dst), "l"((uint64_t)m), "r"(bar), "r"(row), "r"(chunk) : "memory");
}
__device__ __forceinline__ void tma3d_ef(uint32_t dst, const CUtensorMap* m, int row, int chunk, uint32_t bar, uint64_t pol) {
    asm volatile("cp.async.bulk.tensor.3d.shared::cluster.global.mbarrier::complete_tx::bytes.L2::cache_hint [%0], [%1, {0, %3, %4}], [%2], %5;"
        :: "r"(dst), "l"((uint64_t)m), "r"(bar), "r"(row), "r"(chunk), "l"(pol) : "memory");
}
__device__ __forceinline__ void tma3d_store(const CUtensorMap* m, int row, int chunk, uint32_t src, uint64_t pol, bool hint) {
    if (hint) asm volatile("cp.async.bulk.tensor.3d.global.shared::cta.bulk_group.L2::cache_hint [%0, {0, %2, %3}], [%1], %4;"
        :: "l"((uint64_t)m), "r"(src), "r"(row), "r"(chunk), "l"(pol) : "memory");
    else asm volatile("cp.async.bulk.tensor.3d.global.shared::cta.bulk_group [%0, {0, %2, %3}], [%1];"
        :: "l"((uint64_t)m), "r"(src), "r"(row), "r"(chunk) : "memory");
}
__device__ __forceinline__ bool elect() { uint32_t p; asm volatile("{ .reg .pred e; elect.sync _|e, -1; selp.u32 %0, 1, 0, e; }" : "=r"(p)); return p; }
__device__ __forceinline__ uint2 ld_ef(const void* p, uint64_t pol) {
    uint2 v; asm volatile("ld.relaxed.gpu.global.L2::cache_hint.v2.u32 {%0,%1}, [%2], %3;" : "=r"(v.x), "=r"(v.y) : "l"(p), "l"(pol)); return v;
}
__device__ __forceinline__ void st_ef(void* p, uint2 v, uint64_t pol) {
    asm volatile("st.global.L2::cache_hint.v2.u32 [%0], {%1,%2}, %3;" :: "l"(p), "r"(v.x), "r"(v.y), "l"(pol) : "memory");
}
__device__ __forceinline__ void tma2d_prefetch(const CUtensorMap* m, int c0, int c1) {
    asm volatile("cp.async.bulk.prefetch.tensor.2d.L2.global [%0, {%1, %2}];" :: "l"((uint64_t)m), "r"(c0), "r"(c1) : "memory");
}
__device__ __forceinline__ void mbar_arrive_remote(uint32_t bar) { asm volatile("mbarrier.arrive.relaxed.cluster.shared::cluster.b64 _, [%0];" :: "r"(bar) : "memory"); }
__device__ __forceinline__ void tma2d_store(const CUtensorMap* m, int c0, int c1, uint32_t src) {
    asm volatile("cp.async.bulk.tensor.2d.global.shared::cta.bulk_group [%0, {%2, %3}], [%1];"
        :: "l"((uint64_t)m), "r"(src), "r"(c0), "r"(c1) : "memory");
}
__device__ __forceinline__ void bulk_g2s(uint32_t dst, const void* src, int bytes, uint32_t bar) {
    asm volatile("cp.async.bulk.shared::cluster.global.mbarrier::complete_tx::bytes [%0], [%1], %2, [%3];" :: "r"(dst), "l"(src), "r"(bytes), "r"(bar) : "memory");
}
__device__ __forceinline__ void ldsm4(uint32_t (&r)[4], uint32_t a) {
    asm volatile("ldmatrix.sync.aligned.m8n8.x4.shared.b16 {%0,%1,%2,%3}, [%4];" : "=r"(r[0]), "=r"(r[1]), "=r"(r[2]), "=r"(r[3]) : "r"(a) : "memory");
}
__device__ __forceinline__ void ldsm4t(uint32_t (&r)[4], uint32_t a) {
    asm volatile("ldmatrix.sync.aligned.m8n8.x4.trans.shared.b16 {%0,%1,%2,%3}, [%4];" : "=r"(r[0]), "=r"(r[1]), "=r"(r[2]), "=r"(r[3]) : "r"(a) : "memory");
}
__device__ __forceinline__ void stsm4(uint32_t a, uint32_t r0, uint32_t r1, uint32_t r2, uint32_t r3) {
    asm volatile("stmatrix.sync.aligned.m8n8.x4.shared.b16 [%0], {%1,%2,%3,%4};" :: "r"(a), "r"(r0), "r"(r1), "r"(r2), "r"(r3) : "memory");
}
__device__ __forceinline__ void stsm4t(uint32_t a, uint32_t r0, uint32_t r1, uint32_t r2, uint32_t r3) {
    asm volatile("stmatrix.sync.aligned.m8n8.x4.trans.shared.b16 [%0], {%1,%2,%3,%4};" :: "r"(a), "r"(r0), "r"(r1), "r"(r2), "r"(r3) : "memory");
}
__device__ __forceinline__ void stsm2t(uint32_t a, uint32_t r0, uint32_t r1) {
    asm volatile("stmatrix.sync.aligned.m8n8.x2.trans.shared.b16 [%0], {%1,%2};" :: "r"(a), "r"(r0), "r"(r1) : "memory");
}
__device__ __forceinline__ uint32_t movm_t(uint32_t v) { uint32_t r; asm volatile("movmatrix.sync.aligned.m8n8.trans.b16 %0, %1;" : "=r"(r) : "r"(v)); return r; }
__device__ __forceinline__ void mma16(float (&d)[4], uint32_t a0, uint32_t a1, uint32_t a2, uint32_t a3, uint32_t b0, uint32_t b1) {
    asm volatile("mma.sync.aligned.m16n8k16.row.col.f32.bf16.bf16.f32 {%0,%1,%2,%3}, {%4,%5,%6,%7}, {%8,%9}, {%0,%1,%2,%3};"
        : "+f"(d[0]), "+f"(d[1]), "+f"(d[2]), "+f"(d[3]) : "r"(a0), "r"(a1), "r"(a2), "r"(a3), "r"(b0), "r"(b1));
}
__device__ __forceinline__ void mma8(float (&d)[4], uint32_t a0, uint32_t a1, uint32_t b0) {
    asm volatile("mma.sync.aligned.m16n8k8.row.col.f32.bf16.bf16.f32 {%0,%1,%2,%3}, {%4,%5}, {%6}, {%0,%1,%2,%3};"
        : "+f"(d[0]), "+f"(d[1]), "+f"(d[2]), "+f"(d[3]) : "r"(a0), "r"(a1), "r"(b0));
}
__device__ __forceinline__ uint32_t mapa(uint32_t a, uint32_t r) { uint32_t o; asm volatile("mapa.shared::cluster.u32 %0, %1, %2;" : "=r"(o) : "r"(a), "r"(r)); return o; }
__device__ __forceinline__ void bar_sync(int id, int n) { asm volatile("bar.sync %0, %1;" :: "r"(id), "r"(n) : "memory"); }
__device__ __forceinline__ void bar_arrive(int id, int n) { asm volatile("bar.arrive %0, %1;" :: "r"(id), "r"(n) : "memory"); }
__device__ __forceinline__ uint64_t mkdesc(uint32_t addr, uint32_t lbo, uint32_t sbo) {
    return (uint64_t)((addr & 0x3FFFF) >> 4) | ((uint64_t)(lbo >> 4) << 16) | ((uint64_t)(sbo >> 4) << 32) | (1ull << 62);
}
#define WG_FENCE()  asm volatile("wgmma.fence.sync.aligned;" ::: "memory")
#define WG_COMMIT() asm volatile("wgmma.commit_group.sync.aligned;" ::: "memory")
#define WG_WAIT(n)  asm volatile("wgmma.wait_group.sync.aligned %0;" :: "n"(n) : "memory")

__device__ __forceinline__ void wgmma_ss_n192_tb(float (&d)[96], uint64_t a, uint64_t b, int acc) {
    asm volatile("{ .reg .pred p; setp.ne.b32 p, %98, 0;\n"
        "wgmma.mma_async.sync.aligned.m64n192k16.f32.bf16.bf16 {%0,%1,%2,%3,%4,%5,%6,%7,%8,%9,%10,%11,%12,%13,%14,%15,%16,%17,%18,%19,%20,%21,%22,%23,%24,%25,%26,%27,%28,%29,%30,%31,%32,%33,%34,%35,%36,%37,%38,%39,%40,%41,%42,%43,%44,%45,%46,%47,%48,%49,%50,%51,%52,%53,%54,%55,%56,%57,%58,%59,%60,%61,%62,%63,%64,%65,%66,%67,%68,%69,%70,%71,%72,%73,%74,%75,%76,%77,%78,%79,%80,%81,%82,%83,%84,%85,%86,%87,%88,%89,%90,%91,%92,%93,%94,%95}, %96, %97, p, 1, 1, 0, 1; }"
        : "+f"(d[0]), "+f"(d[1]), "+f"(d[2]), "+f"(d[3]), "+f"(d[4]), "+f"(d[5]), "+f"(d[6]), "+f"(d[7]), "+f"(d[8]), "+f"(d[9]), "+f"(d[10]), "+f"(d[11]), "+f"(d[12]), "+f"(d[13]), "+f"(d[14]), "+f"(d[15]), "+f"(d[16]), "+f"(d[17]), "+f"(d[18]), "+f"(d[19]), "+f"(d[20]), "+f"(d[21]), "+f"(d[22]), "+f"(d[23]), "+f"(d[24]), "+f"(d[25]), "+f"(d[26]), "+f"(d[27]), "+f"(d[28]), "+f"(d[29]), "+f"(d[30]), "+f"(d[31]), "+f"(d[32]), "+f"(d[33]), "+f"(d[34]), "+f"(d[35]), "+f"(d[36]), "+f"(d[37]), "+f"(d[38]), "+f"(d[39]), "+f"(d[40]), "+f"(d[41]), "+f"(d[42]), "+f"(d[43]), "+f"(d[44]), "+f"(d[45]), "+f"(d[46]), "+f"(d[47]), "+f"(d[48]), "+f"(d[49]), "+f"(d[50]), "+f"(d[51]), "+f"(d[52]), "+f"(d[53]), "+f"(d[54]), "+f"(d[55]), "+f"(d[56]), "+f"(d[57]), "+f"(d[58]), "+f"(d[59]), "+f"(d[60]), "+f"(d[61]), "+f"(d[62]), "+f"(d[63]), "+f"(d[64]), "+f"(d[65]), "+f"(d[66]), "+f"(d[67]), "+f"(d[68]), "+f"(d[69]), "+f"(d[70]), "+f"(d[71]), "+f"(d[72]), "+f"(d[73]), "+f"(d[74]), "+f"(d[75]), "+f"(d[76]), "+f"(d[77]), "+f"(d[78]), "+f"(d[79]), "+f"(d[80]), "+f"(d[81]), "+f"(d[82]), "+f"(d[83]), "+f"(d[84]), "+f"(d[85]), "+f"(d[86]), "+f"(d[87]), "+f"(d[88]), "+f"(d[89]), "+f"(d[90]), "+f"(d[91]), "+f"(d[92]), "+f"(d[93]), "+f"(d[94]), "+f"(d[95])
        : "l"(a), "l"(b), "r"(acc));
}

__device__ __forceinline__ void wgmma_ss_n128_tb(float (&d)[64], uint64_t a, uint64_t b, int acc) {
    asm volatile("{ .reg .pred p; setp.ne.b32 p, %66, 0;\n"
        "wgmma.mma_async.sync.aligned.m64n128k16.f32.bf16.bf16 {%0,%1,%2,%3,%4,%5,%6,%7,%8,%9,%10,%11,%12,%13,%14,%15,%16,%17,%18,%19,%20,%21,%22,%23,%24,%25,%26,%27,%28,%29,%30,%31,%32,%33,%34,%35,%36,%37,%38,%39,%40,%41,%42,%43,%44,%45,%46,%47,%48,%49,%50,%51,%52,%53,%54,%55,%56,%57,%58,%59,%60,%61,%62,%63}, %64, %65, p, 1, 1, 0, 1; }"
        : "+f"(d[0]), "+f"(d[1]), "+f"(d[2]), "+f"(d[3]), "+f"(d[4]), "+f"(d[5]), "+f"(d[6]), "+f"(d[7]), "+f"(d[8]), "+f"(d[9]), "+f"(d[10]), "+f"(d[11]), "+f"(d[12]), "+f"(d[13]), "+f"(d[14]), "+f"(d[15]), "+f"(d[16]), "+f"(d[17]), "+f"(d[18]), "+f"(d[19]), "+f"(d[20]), "+f"(d[21]), "+f"(d[22]), "+f"(d[23]), "+f"(d[24]), "+f"(d[25]), "+f"(d[26]), "+f"(d[27]), "+f"(d[28]), "+f"(d[29]), "+f"(d[30]), "+f"(d[31]), "+f"(d[32]), "+f"(d[33]), "+f"(d[34]), "+f"(d[35]), "+f"(d[36]), "+f"(d[37]), "+f"(d[38]), "+f"(d[39]), "+f"(d[40]), "+f"(d[41]), "+f"(d[42]), "+f"(d[43]), "+f"(d[44]), "+f"(d[45]), "+f"(d[46]), "+f"(d[47]), "+f"(d[48]), "+f"(d[49]), "+f"(d[50]), "+f"(d[51]), "+f"(d[52]), "+f"(d[53]), "+f"(d[54]), "+f"(d[55]), "+f"(d[56]), "+f"(d[57]), "+f"(d[58]), "+f"(d[59]), "+f"(d[60]), "+f"(d[61]), "+f"(d[62]), "+f"(d[63])
        : "l"(a), "l"(b), "r"(acc));
}

__device__ __forceinline__ void wgmma_rs_n32(float (&d)[16], const uint32_t (&a)[4], uint64_t b, int acc) {
    asm volatile("{ .reg .pred p; setp.ne.b32 p, %21, 0;\n"
        "wgmma.mma_async.sync.aligned.m64n32k16.f32.bf16.bf16 {%0,%1,%2,%3,%4,%5,%6,%7,%8,%9,%10,%11,%12,%13,%14,%15}, {%16,%17,%18,%19}, %20, p, 1, 1, 0; }"
        : "+f"(d[0]), "+f"(d[1]), "+f"(d[2]), "+f"(d[3]), "+f"(d[4]), "+f"(d[5]), "+f"(d[6]), "+f"(d[7]), "+f"(d[8]), "+f"(d[9]), "+f"(d[10]), "+f"(d[11]), "+f"(d[12]), "+f"(d[13]), "+f"(d[14]), "+f"(d[15])
        : "r"(a[0]), "r"(a[1]), "r"(a[2]), "r"(a[3]), "l"(b), "r"(acc));
}

__device__ __forceinline__ float warp_sum(float v) {
#pragma unroll
    for (int o = 16; o; o >>= 1) v += __shfl_xor_sync(0xffffffffu, v, o);
    return v;
}
__device__ __forceinline__ void ln_mod(const float (&xv)[20], const uint32_t (&sv)[10], const uint32_t (&tv)[10], float (&hv)[20]) {
    float s = 0;
#pragma unroll
    for (int i = 0; i < 20; i++) s += xv[i];
    const float mean = warp_sum(s) * (1.f / DM);
    float q = 0;
#pragma unroll
    for (int i = 0; i < 20; i++) { float d = xv[i] - mean; q += d * d; }
    const float mb = bfr(mean), inv = inv_std(warp_sum(q) * (1.f / DM));
#pragma unroll
    for (int i = 0; i < 10; i++) {
        const float n0 = bfr(bfr(xv[2 * i] - mb) * inv), n1 = bfr(bfr(xv[2 * i + 1] - mb) * inv);
        hv[2 * i] = bfr(bfr(n0 * bfr(1.f + lo_f(sv[i]))) + lo_f(tv[i]));
        hv[2 * i + 1] = bfr(bfr(n1 * bfr(1.f + hi_f(sv[i]))) + hi_f(tv[i]));
    }
}
__device__ __forceinline__ uint32_t ld_rlx(const uint32_t* f) { uint32_t v; asm volatile("ld.relaxed.gpu.global.u32 %0, [%1];" : "=r"(v) : "l"(f) : "memory"); return v; }
__device__ __forceinline__ void bump(uint32_t* f) { asm volatile("red.relaxed.gpu.global.add.u32 [%0], 1;" :: "l"(f) : "memory"); }
__device__ __forceinline__ void flag_wait(const uint32_t* f, uint32_t target) {
    for (int n = 0;; n++) {
        uint32_t v; asm volatile("ld.relaxed.gpu.global.u32 %0, [%1];" : "=r"(v) : "l"(f) : "memory");
        if (v >= target) break;
        if (n > (1 << 23)) __trap();
    }
}
__device__ __forceinline__ void flag_add(uint32_t* f, uint32_t v = 1) { asm volatile("red.release.gpu.global.add.u32 [%0], %1;" :: "l"(f), "r"(v) : "memory"); }
constexpr int N_SIDE = 36;
__device__ __forceinline__ void flags_release(int lane) {
    uint32_t old = 0;
    if (lane == 0) asm volatile("atom.relaxed.gpu.global.add.u32 %0, [%1], 1;" : "=r"(old) : "l"(&g_flags.done) : "memory");
    if (__shfl_sync(0xffffffffu, old, 0) == 96 + N_SIDE - 1)
        for (int i = lane; i < (int)(sizeof(Flags) / 16); i += 32) ((uint4*)&g_flags)[i] = make_uint4(0, 0, 0, 0);
}

struct ChainMaps { CUtensorMap wq, wk, wv, wo, h2, q32, k32, v32, wmod; };
struct ChainArgs { const bf16 *x, *mem0, *c, *wv, *wo; bf16* out; int D1, D2, DG; };
constexpr uint32_t SM_BASE = 1024;
#define NRING 11
#define FILL_AT 1
#define VF 6
#define VPRE 2
#define XORD 0
#define B5AT 41
#define QCUT 0x7f
#define NCH 2
#define ALA 1
#define VPOS 0
#define NPRE 9
#define REG_P 208
#define REG_L (504 - 2 * REG_P)
constexpr int WO_BLK = 7 * 4096;
constexpr int C_WV = 0, C_WO = 81920, C_XR = 167936, C_VP = C_XR + 7 * 4096, C_VX = C_XR + 8 * 4096, C_QX = C_VX + 4096, C_KX = C_QX + 4096,
              C_MEM = C_KX + 4096, C_OX = C_MEM + 9216, C_VM = C_OX + 3072, C_QM = C_VM + 1024, C_KM = C_QM + 1024, C_SC = C_KM + 1024, C_BAR = C_SC + 3840;
constexpr int CB_W = C_BAR, CB_W2 = C_BAR + 8, CB_SC = C_BAR + 16, CB_XD = C_BAR + 24, CB_VX = C_BAR + 32, CB_PRE = C_BAR + 40, CB_XM = C_BAR + 48, CB_OX = C_BAR + 56,
              CB_XF = C_BAR + 64, C_LAG = C_BAR + 96;
constexpr int C_SMEM = C_BAR + 128;
#define PROF(i)
#define PROFG(i)
#define PROFV(i, v)
static_assert(C_SMEM <= 232448, "chain shared memory");
__device__ __forceinline__ uint32_t umax3(uint32_t a, uint32_t b, uint32_t c) { return max(max(a, b), c); }
__device__ __forceinline__ void wait_until(uint32_t t) {
    asm volatile("{ .reg .pred p; .reg .s32 c;\nU_%=: mov.u32 c, %%clock; sub.s32 c, c, %0; setp.lt.s32 p, c, 0; @p bra.uni U_%=; }" :: "r"(t) : "memory");
}
__device__ __forceinline__ uint32_t gtime() { uint32_t c; asm volatile("mov.u32 %0, %%globaltimer_lo;" : "=r"(c)); return c; }
__device__ __forceinline__ uint32_t opaque(uint32_t v) { uint32_t r; asm volatile("shfl.sync.bfly.b32 %0, %1, 0, 31, -1;" : "=r"(r) : "r"(v)); return r; }
__device__ __forceinline__ uint32_t lds32(uint32_t a) { uint32_t v; asm volatile("ld.shared.u32 %0, [%1];" : "=r"(v) : "r"(a) : "memory"); return v; }
__device__ __forceinline__ float2 lds64f(uint32_t a) { float2 v; asm volatile("ld.shared.v2.f32 {%0,%1}, [%2];" : "=f"(v.x), "=f"(v.y) : "r"(a) : "memory"); return v; }
__device__ __forceinline__ float4 lds128f(uint32_t a) { float4 v; asm volatile("ld.shared.v4.f32 {%0,%1,%2,%3}, [%4];" : "=f"(v.x), "=f"(v.y), "=f"(v.z), "=f"(v.w) : "r"(a) : "memory"); return v; }
__device__ __forceinline__ void sts128f(uint32_t a, float x, float y, float z, float w) { asm volatile("st.shared.v4.f32 [%0], {%1,%2,%3,%4};" :: "r"(a), "f"(x), "f"(y), "f"(z), "f"(w) : "memory"); }
__device__ __forceinline__ void lds64(uint32_t (&v)[2], uint32_t a) { asm volatile("ld.shared.v2.u32 {%0,%1}, [%2];" : "=r"(v[0]), "=r"(v[1]) : "r"(a) : "memory"); }
__device__ __forceinline__ void mma16q(float (&d)[4], const uint32_t (&a)[4], uint32_t b0, uint32_t b1) { mma16(d, a[0], a[1], a[2], a[3], b0, b1); }
__device__ __forceinline__ uint32_t f16_to_bf16(uint32_t v) {
    float lo, hi; asm("{ .reg .f16 l, h; mov.b32 {l, h}, %2; cvt.f32.f16 %0, l; cvt.f32.f16 %1, h; }" : "=f"(lo), "=f"(hi) : "r"(v));
    return pack2(lo, hi);
}
__device__ __forceinline__ uint32_t pack2h(float lo, float hi) { uint32_t r; asm("cvt.rn.f16x2.f32 %0, %1, %2;" : "=r"(r) : "f"(hi), "f"(lo)); return r; }
#define SPLIT 1
__device__ __forceinline__ void cut(uint32_t never, int n) {
    asm volatile("{ .reg .pred p; setp.ne.u32 p, %0, %1; @p bra.uni C_%=; trap; C_%=: }" :: "r"(never), "r"(n) : "memory");
}
__device__ __forceinline__ void pin(uint32_t never, uint32_t a, uint32_t b, uint32_t c, uint32_t d) {
    asm volatile("{ .reg .pred p; setp.eq.u32 p, %0, 0; @p st.shared.v4.u32 [%0], {%1,%2,%3,%4}; }" :: "r"(never), "r"(a), "r"(b), "r"(c), "r"(d) : "memory");
}
__device__ __forceinline__ void pin0(uint32_t never) {
    asm volatile("{ .reg .pred p; setp.eq.u32 p, %0, 0; @p st.shared.u32 [%0], 0; }" :: "r"(never) : "memory");
}
#define ELECTED(txt) "{ .reg .pred e; elect.sync _|e, -1; @e " txt " }"
__device__ __forceinline__ void w_bulk_s2g(void* dst, uint32_t src, int bytes) {
    asm volatile(ELECTED("cp.async.bulk.global.shared::cta.bulk_group [%0], [%1], %2;") :: "l"(dst), "r"(src), "r"(bytes) : "memory");
}
__device__ __forceinline__ void w_tma2d_store(const CUtensorMap* m, int c0, int c1, uint32_t src) {
    asm volatile(ELECTED("cp.async.bulk.tensor.2d.global.shared::cta.bulk_group [%0, {%2, %3}], [%1];") :: "l"((uint64_t)m), "r"(src), "r"(c0), "r"(c1) : "memory");
}
__device__ __forceinline__ void w_bump(uint32_t* f) { asm volatile(ELECTED("red.relaxed.gpu.global.add.u32 [%0], 1;") :: "l"(f) : "memory"); }
__device__ __forceinline__ void w_expect(uint32_t bar, int bytes) { asm volatile(ELECTED("mbarrier.arrive.expect_tx.shared::cta.b64 _, [%0], %1;") :: "r"(bar), "r"(bytes) : "memory"); }
__device__ __forceinline__ void w_flag_wait(const uint32_t* f, uint32_t target) {
    asm volatile("{ .reg .pred p; .reg .u32 n, v; mov.u32 n, 0;\n"
                 "F_%=: ld.relaxed.gpu.global.u32 v, [%0]; setp.ge.u32 p, v, %1; vote.sync.all.pred p, p, -1; @p bra.uni G_%=;\n"
                 "add.u32 n, n, 1; setp.lt.u32 p, n, 0x800000; @p bra.uni F_%=;\ntrap;\nG_%=: }" :: "l"(f), "r"(target) : "memory");
}
#define BULK_COMMIT()    asm volatile("cp.async.bulk.commit_group;" ::: "memory")
#define BULK_WAIT()      asm volatile("cp.async.bulk.wait_group 0;" ::: "memory")
#define BULK_WAIT_READ() asm volatile("cp.async.bulk.wait_group.read 0;" ::: "memory")
#define PROXY_FENCE()    asm volatile("fence.proxy.async.shared::cta;" ::: "memory")
__device__ __forceinline__ void score_tile(const uint32_t (&qa)[2][4], const uint32_t (&kb)[2][4], bool odd, float (&x)[4]) {
    float sc[2][4] = {{0, 0, 0, 0}, {0, 0, 0, 0}};
#pragma unroll
    for (int k = 0; k < 4; k++) mma16q(sc[k & 1], qa[k >> 1], kb[k >> 1][2 * (k & 1)], kb[k >> 1][2 * (k & 1) + 1]);
    float a = sc[0][0] + sc[1][2], b = sc[0][1] + sc[1][3];
    float c = __shfl_xor_sync(0xffffffffu, a, 1), d = __shfl_xor_sync(0xffffffffu, b, 1);
    x[0] = odd ? c : a; x[1] = odd ? d : b; x[2] = odd ? a : c; x[3] = odd ? b : d;
}
__device__ __forceinline__ void send_piece(const float (&x)[4], uint32_t rdst, uint32_t rbar, uint32_t ldst) {
    asm volatile("st.async.shared::cluster.mbarrier::complete_tx::bytes.v4.f32 [%0], {%1,%2,%3,%4}, [%5];"
        :: "r"(rdst), "f"(x[0]), "f"(x[1]), "f"(x[2]), "f"(x[3]), "r"(rbar) : "memory");
    sts128f(ldst, x[0], x[1], x[2], x[3]);
}

__device__ __forceinline__ void seg_done(int n, int head) {
    w_bump(&g_flags.seg[n * 32 + head]);
    if ((n & 3) == 3) w_bump(&g_flags.qk[n >> 2]);
}
__device__ __forceinline__ void x_part(const uint32_t (&wa)[40][4], uint32_t sm, int n, int wg, int w, uint32_t ln, int head) {
    const int s = n - 1; (void)s;
    float acc[16]; uint32_t giv[8];
#pragma unroll
    for (int i = 0; i < 16; i++) acc[i] = 0.f;
    const uint32_t x0 = (uint32_t)mkdesc(SM_BASE + C_XR + wg * 4096, 16, 1024) + ln, xl[2] = {__shfl_sync(0xffffffffu, x0, 0), __shfl_sync(0xffffffffu, x0, 1)};
    auto chunk = [&](int a0, int i, int first) {
#pragma unroll
        for (int ks = 0; ks < 4; ks++)
            wgmma_rs_n32(acc, wa[a0 + 4 * i + ks], (mkdesc(0, 0, 1024) | (uint32_t)(xl[!a0] + ((((i ? (i - 1) * 8192 : C_MEM - C_XR) + ks * 32) >> 4) - !a0))), !(first && ks == 0));
    };
    mbar_wait(sm + CB_XF, n & 1);
    if (n) bar_sync(5, 384);
    if (wg == 0 && w == 0) PROF(12);
    WG_FENCE();
    chunk(20, 1, 1); chunk(20, 2, 0); chunk(20, 3, 0);
    mbar_wait(sm + CB_XM, n & 1);
    if (wg == 0 && w == 0) PROF(13);
    WG_FENCE();
    chunk(20, 0, 0);
    mbar_wait(sm + CB_XF + 8, n & 1);
    if (wg == 0 && w == 0) PROF(17);
    WG_FENCE();
    chunk(20, 4, 0);
    WG_COMMIT();
    if (n) {
        if (wg == 1 && w == 1) { BULK_WAIT(); seg_done(n - 1, head); }
        bar_sync(8, 256);
    }
    if (wg == 0 && w == 0) PROF(18);
    const uint32_t xb = sm + w * 512 + ln * 16, xw = xb + C_KX - wg * 4096, xr = xb + C_QX + wg * 4096;
    WG_WAIT(0);
#pragma unroll
    for (int i = 0; i < 8; i++) asm volatile("cvt.rn.bf16x2.f32 %0, %1, %2;" : "=r"(giv[i]) : "f"(acc[2 * i + 1]), "f"(acc[2 * i]));
#pragma unroll
    for (int p = 0; p < 2; p++) asm volatile("st.shared.v4.u32 [%0], {%1,%2,%3,%4};" :: "r"(xw + p * 2048), "r"(giv[4 * p]), "r"(giv[4 * p + 1]), "r"(giv[4 * p + 2]), "r"(giv[4 * p + 3]) : "memory");
    bar_arrive(12 + wg, 256);
    WG_FENCE();
    chunk(0, 0, 1);
    WG_COMMIT();
    chunk(0, 1, 0);
    if (XORD) chunk(0, 2, 0);
    bar_sync(13 - wg, 256);
#pragma unroll
    for (int p = 0; p < 2; p++) asm volatile("ld.shared.v4.u32 {%0,%1,%2,%3}, [%4];" : "=r"(giv[4 * p]), "=r"(giv[4 * p + 1]), "=r"(giv[4 * p + 2]), "=r"(giv[4 * p + 3]) : "r"(xr + p * 2048) : "memory");
    WG_COMMIT(); WG_WAIT(1); bar_arrive(9, 384);
    WG_FENCE();
    if (!XORD) chunk(0, 2, 0);
    chunk(0, 3, 0); chunk(0, 4, 0);
    WG_COMMIT();
    const uint32_t r = ln & 7, mi = ln >> 3, dst = sm + (wg == 0 ? C_QX : C_KX) + ((mi >> 1) * 8 + r) * 128 + (((2 * w + (mi & 1)) ^ r) << 4);
    pin(xb, giv[0], giv[4], dst, 0);
    bar_sync(10 + wg, 128);
    WG_WAIT(0);
    if (wg == 0 && w == 0) PROF(30);
    if (w == 0 && ln < 3) mbar_arrive_remote(mapa(sm + CB_XD, ln));
#pragma unroll
    for (int i = 0; i < 8; i++) { acc[2 * i] += lo_f(giv[i]); acc[2 * i + 1] += hi_f(giv[i]); }
#pragma unroll
    for (int p = 0; p < 2; p++)
        stsm4t(dst + p * 2048, pack2(acc[8 * p], acc[8 * p + 1]), pack2(acc[8 * p + 2], acc[8 * p + 3]), pack2(acc[8 * p + 4], acc[8 * p + 5]), pack2(acc[8 * p + 6], acc[8 * p + 7]));
}
__device__ __forceinline__ void x_fill(const ChainMaps& mp, uint32_t sm, int n, int j, int g) {
    mbar_expect(sm + CB_XF + 8 * g, g ? 8192 : 24576);
    const int c = g ? 6 : 2 * j;
    if (!g || j == 2)
        asm volatile("cp.async.bulk.tensor.3d.shared::cluster.global.mbarrier::complete_tx::bytes.multicast::cluster [%0], [%1, {0, %3, %4}], [%2], %5;"
            :: "r"(sm + C_XR + c * 4096), "l"((uint64_t)&mp.h2), "r"(sm + CB_XF + 8 * g), "r"(n * SEG), "r"(2 + c), "h"((uint16_t)7) : "memory");
}

__global__ void __cluster_dims__(3, 1, 1) __launch_bounds__(384, 1) k_chain(const __grid_constant__ ChainMaps mp, const __grid_constant__ ChainArgs ar) {
    const int D1 = ar.D1, DG = ar.DG;
    extern __shared__ __align__(1024) uint8_t smraw[];
    const uint32_t sm = SM_BASE + ((blockIdx.x % 3) << 24);
    if (smem_u32(smraw) != sm) __trap();
    uint32_t tid; asm volatile("mov.u32 %0, %%tid.x;" : "=r"(tid));
    const int warp = __shfl_sync(0xffffffffu, tid >> 5, 0), lane = tid & 31, wg = warp >> 2, w = warp & 3;
    const int blk = blockIdx.x, head = blk / 3, j = blk % 3;
    const int col0 = head * DH + j * 64;
    asm volatile("griddepcontrol.launch_dependents;");
#define PPROF(i)
    {
        const int mc0 = (blk >> 1) * 80 + (blk & 1) * 32, mcn = (blk & 1) ? 24 : 16;
        const int nrow = blk < 74 ? 2 : blk == 74 ? (warp < 8 ? 2 : 1) : 1;
        if (tid == 0) {
            mbar_init(sm + CB_PRE, 1);
            asm volatile("fence.mbarrier_init.release.cluster;" ::: "memory");
            const int n1 = blk < 74 ? 15360 : blk == 74 ? 10240 : 0;
            mbar_expect(sm + CB_PRE, 61440 + 1280 + 15360 + n1);
            bulk_g2s(sm + C_QM, ar.c, 1280, sm + CB_PRE);
#pragma unroll 1
            for (int c = 0; c < 4; c++) tma2d(sm + C_WO + 24576 + c * 15360, &mp.wmod, mc0, c * 160, sm + CB_PRE);
            bulk_g2s(sm + C_XR, ar.x + blk * 12 * DM, 15360, sm + CB_PRE);
            if (n1) bulk_g2s(sm + C_XR + 15360, ar.x + (1152 + blk * 12) * DM, n1, sm + CB_PRE);
        }
        if (tid == 32) {
#pragma unroll 1
            for (int c = 0; c < 11; c++) if (c != 5) mbar_init(sm + C_BAR + 8 * c, c == 2 ? 5 : c == 3 ? 6 : 1);
            asm volatile("fence.mbarrier_init.release.cluster;" ::: "memory");
            mbar_expect(sm + CB_SC, 2560); mbar_expect(sm + CB_OX, 2048);
        }
        if (warp == 2) {
            ((uint4*)g_acc)[blk * 32 + lane] = make_uint4(0, 0, 0, 0);
            if (blk < 12) ((uint4*)g_stamp)[blk * 32 + lane] = make_uint4(0, 0, 0, 0);
            __threadfence();
        }
        PPROF(8);
        asm volatile("barrier.cluster.arrive.release.aligned; barrier.cluster.wait.acquire.aligned;" ::: "memory");
        PPROF(9);
        mbar_wait(sm + CB_PRE, 0);
        PPROF(10);
        if (tid == 352) {
            const uint64_t ef = policy_stream();
            mbar_expect(sm + CB_W, 2 * 81920);
#pragma unroll 1
            for (int c = 0; c < 10; c++) tma2d_ef(sm + C_WV + c * 8192, &mp.wq, col0, c * 64, sm + CB_W, ef);
        }
        if (tid < 320) {
            const uint32_t cv = lds32(sm + C_QM + tid * 4);
            asm volatile("st.shared.v2.f32 [%0], {%1,%2};" :: "r"(sm + C_QX + tid * 8), "f"(bfr(__fdividef(lo_f(cv), 1.f + __expf(-lo_f(cv))))),
                         "f"(bfr(__fdividef(hi_f(cv), 1.f + __expf(-hi_f(cv))))) : "memory");
        }
        __syncthreads();
        {
            float a0 = 0, a1 = 0;
            const uint32_t k0 = (tid / 24) * 40, wa0 = sm + C_WO + 24576 + k0 * 96 + (tid % 24) * 4;
#pragma unroll 4
            for (int i = 0; i < 40; i++) {
                const float sc = __uint_as_float(lds32(sm + C_QX + (k0 + i) * 4));
                const uint32_t wv = lds32(wa0 + i * 96);
                a0 += sc * lo_f(wv); a1 += sc * hi_f(wv);
            }
            asm volatile("st.shared.v2.f32 [%0], {%1,%2};" :: "r"(sm + C_MEM + tid * 8), "f"(a0), "f"(a1) : "memory");
        }
        __syncthreads();
        PPROF(11);
        if (warp == 0) {
            float a0 = 0, a1 = 0;
            const int cp = lane < mcn ? lane : 0;
#pragma unroll 4
            for (int i = 0; i < 16; i++) { const float2 v = lds64f(sm + C_MEM + (i * 24 + cp) * 8); a0 += v.x; a1 += v.y; }
            uint32_t* dst = (uint32_t*)(g_mod + mc0) + cp;
            *dst = pack2(a0, a1);
            const uint32_t rb = ld_rlx(dst);
            PPROF(1);
            if (__all_sync(0xffffffffu, rb == pack2(a0, a1)) && tid == 0) bump(blk < 32 ? &g_flags.mod : &g_flags.h);
            if (tid == 0) flag_wait(&g_flags.mod, 32);
            PPROF(2);
        }
        __syncthreads();
        uint32_t sv[10], tv[10], bad = 0;
#pragma unroll
        for (int i = 0; i < 10; i++) { sv[i] = __ldcg((const uint32_t*)g_mod + DM / 2 + lane + 32 * i); tv[i] = __ldcg((const uint32_t*)g_mod + lane + 32 * i); }
#pragma unroll 1
        for (int q = 0; q < nrow; q++) {
            float xv[20], hv[20];
#pragma unroll
            for (int i = 0; i < 10; i++) { const uint32_t v = lds32(sm + C_XR + q * 15360 + warp * 1280 + lane * 4 + i * 128); xv[2 * i] = lo_f(v); xv[2 * i + 1] = hi_f(v); }
            ln_mod(xv, sv, tv, hv);
            uint32_t* dst = (uint32_t*)g_h + (q * 1152 + blk * 12 + warp) * (DM / 2) + lane;
#pragma unroll
            for (int i = 0; i < 10; i++) dst[32 * i] = pack2(hv[2 * i], hv[2 * i + 1]);
#pragma unroll
            for (int i = 0; i < 10; i++) bad |= ld_rlx(dst + 32 * i) ^ pack2(hv[2 * i], hv[2 * i + 1]);
        }
        if (__syncthreads_or(bad)) __trap();
        PPROF(3);
        if (tid == 0) {
            bump(&g_flags.h);
            flag_wait(&g_flags.h, 160);
            mbar_expect(sm + CB_XM, 8192); tma3d(sm + C_MEM, &mp.h2, 0, 0, sm + CB_XM);
            x_fill(mp, sm, 0, j, 0); x_fill(mp, sm, 0, j, 1);
            const uint64_t ef = policy_stream();
#pragma unroll 1
            for (int c = 0; c < 10; c++) tma2d_ef(sm + C_WO + c * 8192, &mp.wk, col0, c * 64, sm + CB_W, ef);
        }
        PPROF(4);
        __syncthreads();
        if (tid >= 64) {
#pragma unroll 1
            for (int i = tid - 64; i < 640 + 192 * 4; i += 320)
                asm volatile("prefetch.global.L2 [%0];" :: "l"(i < 640 ? ar.wv + (size_t)i * HD + col0 : ar.wo + (size_t)(head * DH + ((i - 640) >> 2)) * DM + j * 224 + min((i & 3) * 64, 639 - j * 224)));
        }
    }
    const int r = lane & 7, mi = lane >> 3;
    const uint32_t memrd = opaque(sm + C_MEM + lane * 16);
    constexpr float S_ACC = 64.f;
    if (wg < 2) {
        asm volatile("setmaxnreg.inc.sync.aligned.u32 %0;" :: "n"(REG_P));
        uint32_t wa[40][4];
        mbar_wait(sm + CB_W, 0);
#pragma unroll
        for (int ks = 0; ks < 40; ks++)
            ldsm4t(wa[ks], sm + ((wg == 0) == (ks < 20) ? C_WV : C_WO) + ((mi >> 1) * 8 + r) * 128 + (((2 * w + (mi & 1)) ^ r) << 4) + (ks % 20 / 4 * 8 + 4 * wg + (ks & 3)) * 2048);
        PPROF(5);
        bar_sync(1, 384);
        x_part(wa, sm, 0, wg, w, lane, head);
        PPROF(6);
        mbar_wait(sm + CB_W2, 0);
        PPROF(7);
        const uint32_t qst = opaque(sm + (wg == 0 ? C_QM : C_KM) + (2 * w + (mi & 1)) * 128 + r * 16);
        const uint32_t vrd = opaque(sm + C_WV + ((mi >> 1) * 8 + r) * 128 + (((2 * w + (mi & 1)) ^ r) << 4) + 4 * wg * 2048);
        const uint32_t mrd = opaque(memrd + wg * 1024);
        for (int s = 0; s < NSEG; s++) {
            const float un = s ? 1.f / S_ACC : 1.f;
            cut(s + ar.D2, 0);
            bar_sync(1, 384);
            if (warp == 0) { PROF(0); PROFG(24); }
            uint32_t b[3][4], a[5][4];
            float dv[2][4] = {{0, 0, 0, 0}, {0, 0, 0, 0}};
            auto fb = [&](int n) { return mrd + (n >> 1) * 2048 + (n & 1) * 512; };
            auto fa = [&](int k) { return vrd + (k >> 2) * 16384 + (k & 3) * 2048; };
            {
                float d[2][4] = {{0, 0, 0, 0}, {0, 0, 0, 0}}, g[2][4] = {{0, 0, 0, 0}, {0, 0, 0, 0}};
                ldsm4t(b[0], fb(0)); pin0(mrd); ldsm4t(b[1], fb(1)); pin0(mrd);
#pragma unroll
                for (int n = 0; n < 10; n++) {
                    const int c1 = (NCH == 2 || n >= 8);
                    if (n < 8) ldsm4t(b[(n + 2) % 3], fb(n + 2));
                    if (n + ALA >= 2 && n + ALA < 2 + VF) ldsm4t(a[2 + (n + ALA) % 3], fa(2 * (n + ALA)));
                    if (!VPOS && n >= 9 - VPRE && n < 9) ldsm4t(a[n - 9 + VPRE], fa(16 + n - 9 + VPRE));
                    mma16q(g[0], wa[20 + 2 * n], b[n % 3][0], b[n % 3][1]); mma16q(d[0], wa[2 * n], b[n % 3][0], b[n % 3][1]);
                    if (n >= 2 && n < 2 + VF) mma16q(dv[0], a[2 + n % 3], b[n % 3][0], b[n % 3][1]);
                    mma16q(g[c1], wa[21 + 2 * n], b[n % 3][2], b[n % 3][3]); mma16q(d[c1], wa[2 * n + 1], b[n % 3][2], b[n % 3][3]);
                    if (QCUT >> n & 1) cut(s + ar.D2, 1 + n);
                }
                const uint32_t xb = mrd - wg * 1024 - (C_MEM - C_VP) + w * 512;
                sts128f(xb + wg * 2048, g[0][0] + g[1][0], g[0][1] + g[1][1], g[0][2] + g[1][2], g[0][3] + g[1][3]);
                bar_sync(8, 256);
                const float4 z = lds128f(xb + (wg ^ 1) * 2048);
                if (VPOS) {
                    pin0(mrd);
#pragma unroll
                    for (int i = 0; i < VPRE; i++) ldsm4t(a[i], fa(16 + i));
                }
                stsm2t(qst, pack2((d[0][0] + d[1][0] + z.x) * un, (d[0][1] + d[1][1] + z.y) * un), pack2((d[0][2] + d[1][2] + z.z) * un, (d[0][3] + d[1][3] + z.w) * un));
            }
            bar_arrive(2, 384);
            if (w == 0) PROF(1 + wg);
            {
                if (warp == 3)
                    asm volatile(ELECTED("st.relaxed.gpu.global.u32 [%0], %1;") :: "l"(g_stamp + (s & 3) * 384 + (blk >> 3) * 32 + (blk & 7)), "r"((gtime() & ~31u) | ((s >> 2) + 1)) : "memory");
                PROXY_FENCE();
                bar_sync(7, 384);
                constexpr int NR = 16 - VF, NB = 4 + 12 - 2 * VF;
                auto kst = [&](int i) { return i < 4 ? 16 + i : i < NB ? i + 2 * VF : 5 + 2 * (i - NB); };
                const uint32_t mo = mrd + 256 + (mrd & 256);
                auto fc = [&](int p) { return 2 * p < NB ? fb(p + VF) : mo + (1 + (2 * p - NB) / 2) * 2048; };
#pragma unroll
                for (int i = VPRE; i < 4; i++) ldsm4t(a[i], fa(kst(i)));
#pragma unroll
                for (int i = 0; i < NR; i++) {
                    if (i + 4 < NR) ldsm4t(a[(i + 4) % 5], fa(kst(i + 4)));
                    if (!(i & 1) && i + 4 < NR) ldsm4t(b[(i / 2 + 1) % 3], fc(i / 2 + 2));
                    mma16q(dv[~i & 1], a[i % 5], b[(i / 2 + 2) % 3][2 * (i & 1)], b[(i / 2 + 2) % 3][2 * (i & 1) + 1]);
                }
                sts128f(mrd - (C_MEM - C_VP) + wg * 1024 + w * 512, dv[0][0] + dv[1][0], dv[0][1] + dv[1][1], dv[0][2] + dv[1][2], dv[0][3] + dv[1][3]);
            }
            if (warp == 0) bar_sync(4, 384);
            else bar_arrive(4, 384);
            if (warp == 0) {
                PROF(7);
                if (s + 1 < NSEG && elect()) {
                    mbar_expect(sm + CB_XM, 8192); tma3d(sm + C_MEM, &mp.h2, (s + 1) * SEG, 0, sm + CB_XM);
                }
            } else {
                if (wg == 1) {
                    if (w == 1) {
                        w_tma2d_store(&mp.k32, col0, s * SEG, sm + C_KX); w_tma2d_store(&mp.q32, col0, s * SEG, sm + C_QX);
                        w_bulk_s2g((uint8_t*)g_kvm + (s * NH + head) * 6144 + j * 1024, sm + C_KM, 1024);
                        BULK_COMMIT();
                        if (s + 1 == NSEG) { BULK_WAIT(); seg_done(s, head); }
                    }
                    if (w == 2 && blk < 10 && s + 3 < NSEG)
                        asm volatile(ELECTED("cp.async.bulk.prefetch.L2.global [%0], 4096;") :: "l"((const uint8_t*)g_h + (s + 3) * (SEG * DM * 2) + blk * 4096) : "memory");
                } else if (w == 3) {
                    const uint32_t l = opaque(mrd) >> 4 & 31, tag = (s >> 2) + 1, now = gtime();
                    const uint32_t* sp = g_stamp + (s & 3) * 384 + (l >> 3) * 32 + (l & 7);
                    uint32_t t[3];
                    for (int n = 0;; n++) {
#pragma unroll
                        for (int i = 0; i < 3; i++) t[i] = ld_rlx(sp + i * 128);
                        if (!__any_sync(0xffffffffu, ((t[0] ^ tag) | (t[1] ^ tag) | (t[2] ^ tag)) & 31) || n > SPIN_LIMIT) break;
                    }
                    int all = -(1 << 30), own = all;
#pragma unroll
                    for (int i = 0; i < 3; i++) { const int d = t[i] - now; all = max(all, d); if ((i * 32 + l) / 3 == head) own = d; }
                    const int lag = min(__reduce_max_sync(0xffffffffu, all) - __reduce_max_sync(0xffffffffu, own), 8000);
                    PROFV(15, lag);
                    asm volatile("st.shared.u32 [%0], %1;" :: "r"(sm + C_LAG), "r"(D1 + ((lag * DG) >> 4)) : "memory");
                    if (s + 1 < NSEG) bar_arrive(6, 160);
                } else if (w == 2) {
                    if (s + 1 < NSEG) {
                        if ((s & 3) == 3) w_flag_wait(&g_flags.v[((s + 1) >> 2) * 32 + head], 2);
                        if (elect()) { mbar_expect(sm + CB_VX, 4096); tma2d(sm + C_VX, &mp.v32, col0, (s + 1) * SEG, sm + CB_VX); }
                    }
                    if ((s & 3) == 1 && s + 3 < NSEG) asm volatile("prefetch.global.L2 [%0];" :: "l"(&g_flags.v[((s + 3) >> 2) * 32]));
                    if (s + 2 < NSEG && ((s & 3) != 2 || __all_sync(0xffffffffu, ld_rlx(&g_flags.v[((s + 2) >> 2) * 32 + head]) >= 2)))
                        asm volatile("prefetch.global.L2 [%0];" :: "l"(g_v + (size_t)((s + 2) * SEG + (opaque(mrd) >> 4 & 31)) * HD + col0));
                } else if (s + 1 < NSEG) {
                    mbar_wait(sm + CB_OX, s & 1);
                    if (elect()) x_fill(mp, sm, s + 1, j, 1);
                }
            }
            if (s + 1 == NSEG) break;
            x_part(wa, sm, s + 1, wg, w, opaque(mrd) >> 4 & 31, head);
            if (warp == 0) PROF(11);
        }
    } else {
        asm volatile("setmaxnreg.dec.sync.aligned.u32 %0;" :: "n"(REG_L));
        bar_sync(1, 384);
        if (tid == 256) {
            mbar_expect(sm + CB_W2, 81920 + 3 * WO_BLK);
#pragma unroll 1
            for (int c = 0; c < 10; c++) tma2d(sm + C_WV + c * 8192, &mp.wv, col0, c * 64, sm + CB_W2);
#pragma unroll 1
            for (int c = 0; c < 3; c++) tma3d(sm + C_WO + c * WO_BLK, &mp.wo, head * DH + (j + c) % 3 * 64, 7 * j, sm + CB_W2);
        }
        bar_sync(9, 384);
#pragma unroll 1
        for (int c = tid - 256; c < DM; c += 128) {
            uint32_t u[8];
#pragma unroll
            for (int i = 0; i < 8; i++) u[i] = __ldg((const unsigned short*)ar.mem0 + i * DM + c);
            asm volatile("st.shared.v4.u32 [%0], {%1,%2,%3,%4};" :: "r"(sm + C_MEM + c * 16), "r"(u[0] | u[1] << 16), "r"(u[2] | u[3] << 16), "r"(u[4] | u[5] << 16), "r"(u[6] | u[7] << 16) : "memory");
        }
        __syncwarp();
        if (w == 1) {
            w_flag_wait(&g_flags.v[head], 2);
            if (elect()) { mbar_expect(sm + CB_VX, 4096); tma2d(sm + C_VX, &mp.v32, col0, 0, sm + CB_VX); }
        }
        mbar_wait(sm + CB_W2, 0);
        const float scale = 0.07216878364870322f;
        uint32_t va[8][4], mr = memrd;
#pragma unroll
        for (int i = 0; i < 8; i++) ldsm4t(va[i], sm + C_WV + ((mi >> 1) * 8 + r) * 128 + (((2 * w + (mi & 1)) ^ r) << 4) + i * 2048);
        for (int s = 0; s < NSEG; s++) {
            const float un = s ? 1.f / S_ACC : 1.f;
            bar_sync(1, 384);
            if (w == 0) {
                mbar_wait(sm + CB_XD, s & 1);
                if (s + 1 < NSEG && elect()) x_fill(mp, sm, s + 1, j, 0);
            } else if (w == 1 && s > 0) { BULK_WAIT(); seg_done(s - 1, head); }
            const uint32_t l0 = mr >> 4 & 31, r0 = l0 & 7, m0 = l0 >> 3;
            uint32_t kb[2][4];
            {
                const uint32_t k7 = (4 * (w & 1) + (r0 >> 2) * 2 + (r0 & 1)) ^ (r0 << 1 & 4);
                const uint32_t kxrd = sm + C_KX + (16 * (w >> 1) + (r0 << 2 & 8) + k7) * 128 + ((m0 ^ k7) << 4);
                ldsm4(kb[0], kxrd); ldsm4(kb[1], kxrd ^ 64);
            }
            float vd[4];
            {
                uint32_t c[4][4];
#pragma unroll
                for (int i = 0; i < 4; i++) ldsm4t(c[i], mr + i * 512);
                float d[2][4] = {{0, 0, 0, 0}, {0, 0, 0, 0}};
#pragma unroll
                for (int i = 0; i < 8; i++) mma16q(d[i & 1], va[i], c[i >> 1][2 * (i & 1)], c[i >> 1][2 * (i & 1) + 1]);
#pragma unroll
                for (int i = 0; i < 4; i++) vd[i] = d[0][i] + d[1][i];
            }
            uint32_t zr = 0;
            if (w == 2)
                asm volatile("atom.relaxed.gpu.global.exch.b32 %0, [%1], 0;" : "=r"(zr)
                    : "l"(g_acc + ((s & 2) ^ 2) * (ACC_PAIR / 2) + (s & 1) * 512 + (blk >> 2) * 1024 + (blk & 3) * 128 + l0 * 4) : "memory");
            __syncwarp();
            const uint32_t sco = (w >> 1) * 512 + (l0 >> 2) * 64 + (w & 1) * 32 + ((l0 >> 1) & 1) * 16;
            const uint32_t qrd = sm + C_QM + ((m0 & 1) * 2 + (m0 >> 1)) * 128 + r0 * 16;
            const uint32_t scdst = sm + C_SC + j * 1280 + sco;
            const uint32_t rbase = mapa(sm, (j + 1 + (l0 & 1)) % 3) - sm;
            const uint32_t scm = 1024 + (l0 >> 1) * 16 - sco;
            const uint32_t v7 = r0 ^ (m0 << 2 & 4), vxrd = sm + C_VX + (8 * m0 + v7) * 128 + (((2 * w) ^ v7) << 4);
            mbar_wait(sm + CB_VX, s & 1);
            uint32_t vb[2][4];
            ldsm4t(vb[0], vxrd); ldsm4t(vb[1], vxrd ^ 16);
            const uint32_t word = sm + C_WO + (m0 & 1) * 4096 + ((m0 >> 1) * 8 + r0) * 64 + ((w ^ (r0 >> 1)) << 4);
            const uint32_t word6 = word + 6 * 4096 - (m0 & 1) * 3072;
            const uint32_t oxrd = sm + C_OX + l0 * 8;
            const uint32_t ord = sm + C_OX + (l0 >> 1) * 16 + w * 256 + (2 - (l0 & 1)) * 1024 + rbase;
            pin(mr, qrd, scdst, rbase, scm); pin(mr, scdst + scm + rbase, scdst + rbase, sm + CB_SC + rbase, scdst + scm); pin(mr, word, word6, oxrd, ord);
            pin(mr, __float_as_uint(vd[0]), __float_as_uint(vd[1]), __float_as_uint(vd[2]), __float_as_uint(vd[3]));
            bar_sync(2, 384);
            const bool odd = mr & 16;
            {
                uint32_t qa[2][4];
                ldsm4(qa[0], qrd); ldsm4(qa[1], qrd + 512);
                float x[4];
                if (w == 3) {
                    uint32_t km[2][4]; float y[4];
                    ldsm4(km[0], mr + (C_KM - C_MEM)); ldsm4(km[1], mr + (C_KM - C_MEM) + 512);
                    score_tile(qa, kb, odd, x); score_tile(qa, km, odd, y);
                    send_piece(x, scdst + rbase, sm + CB_SC + rbase, scdst); send_piece(y, scdst + scm + rbase, sm + CB_SC + rbase, scdst + scm);
                } else {
                    score_tile(qa, kb, odd, x);
                    send_piece(x, scdst + rbase, sm + CB_SC + rbase, scdst);
                }
            }
            bar_arrive(7, 384);
            if (elect()) mbar_arrive(sm + CB_SC);
            if (w == 0) PROF(4);
            const uint32_t vp = mr - (C_MEM - C_VP) + w * 512, vmst = mr + (C_VM - C_MEM) + w * 256;
            if (s + 1 == NSEG) {
                mbar_wait(sm + CB_SC, s & 1);
                bar_sync(4, 384);
                const float4 y0 = lds128f(vp), y1 = lds128f(vp + 2048);
                stsm2t(vmst, pack2((vd[0] + y0.x + y1.x) * un, (vd[1] + y0.y + y1.y) * un), pack2((vd[2] + y0.z + y1.z) * un, (vd[3] + y0.w + y1.w) * un));
                PROXY_FENCE();
                bar_sync(3, 128);
                if (w == 1) {
                    w_bulk_s2g((uint8_t*)g_kvm + (s * NH + head) * 6144 + 3072 + j * 1024, sm + C_VM, 1024);
                    BULK_COMMIT(); BULK_WAIT(); seg_done(s, head);
                }
                __syncwarp();
                break;
            }
            pin(mr, vp, vmst, oxrd + w * 256, sm + CB_OX + rbase);
            cut(s + ar.D2, 0);
            mbar_wait(sm + CB_SC, s & 1);
            if (w == 0) PROF(8);
            float sv[10];
            {
                const uint32_t scrd = mr + (C_SC - C_MEM);
                float4 x[3], y[3]; float2 z[3];
#pragma unroll
                for (int p = 0; p < 3; p++) { x[p] = lds128f(scrd + p * 1280); y[p] = lds128f(scrd + p * 1280 + 512); z[p] = lds64f(oxrd + (C_SC - C_OX) + p * 1280 + 1024); }
                sv[0] = (x[0].x + x[1].x) + x[2].x; sv[1] = (x[0].y + x[1].y) + x[2].y; sv[2] = (x[0].z + x[1].z) + x[2].z; sv[3] = (x[0].w + x[1].w) + x[2].w;
                sv[4] = (y[0].x + y[1].x) + y[2].x; sv[5] = (y[0].y + y[1].y) + y[2].y; sv[6] = (y[0].z + y[1].z) + y[2].z; sv[7] = (y[0].w + y[1].w) + y[2].w;
                sv[8] = (z[0].x + z[1].x) + z[2].x; sv[9] = (z[0].y + z[1].y) + z[2].y;
            }
            float mx = fmaxf(fmaxf(fmaxf(sv[0], sv[1]), fmaxf(sv[2], sv[3])), fmaxf(fmaxf(fmaxf(sv[4], sv[5]), fmaxf(sv[6], sv[7])), fmaxf(sv[8], sv[9])));
            uint32_t a[NRING][4];
            auto frag = [&](int i) { const int p = i / 7, u = i % 7, o = (p >> 1) * WO_BLK + (p & 1) * 2048;
                                     return u == 3 ? word6 + o : word + o + (u > 3 ? 1024 + (u - 4) * 8192 : u * 8192); };
            mx = fmaxf(fmaxf(mx, __shfl_xor_sync(0xffffffffu, mx, 1)), fmaxf(__shfl_xor_sync(0xffffffffu, mx, 2), __shfl_xor_sync(0xffffffffu, mx, 3)));
            pin(mr, __float_as_uint(mx), 0, 0, 0);
            bar_sync(4, 384);
            {
                const float4 y0 = lds128f(vp), y1 = lds128f(vp + 2048);
                pin0(mr);
#pragma unroll
                for (int i = 0; i < NPRE; i++) ldsm4t(a[i], frag(i));
                pin0(mr);
                const float sl2e = scale * 1.4426950408889634f, mxl = mx * sl2e;
#pragma unroll
                for (int i = 9; i >= 0; i--) asm volatile("ex2.approx.ftz.f32 %0, %1;" : "=f"(sv[i]) : "f"(fmaf(sv[i], sl2e, -mxl)));
                const uint32_t pq[4] = {pack2(sv[0], sv[1]), pack2(sv[4], sv[5]), pack2(sv[2], sv[3]), pack2(sv[6], sv[7])}, pm = pack2(sv[8], sv[9]);
                if (w == 0) PROF(6);
                float o[2][4] = {{0, 0, 0, 0}, {0, 0, 0, 0}}, o2[2][4] = {{0, 0, 0, 0}, {0, 0, 0, 0}}, sx[4] = {0, 0, 0, 0};
                const uint32_t vm0 = pack2((vd[0] + y0.x + y1.x) * un, (vd[1] + y0.y + y1.y) * un), vm1 = pack2((vd[2] + y0.z + y1.z) * un, (vd[3] + y0.w + y1.w) * un);
                mma8(sx, pm, 0, 0x3f803f80u); mma8(o[0], pm, 0, vm0); mma8(o[1], pm, 0, vm1);
                mma16q(sx, pq, 0x3f803f80u, 0x3f803f80u);
#pragma unroll
                for (int u = 0; u < 2; u++) { mma16q(o[u], pq, vb[u][0], vb[u][1]); mma16q(o2[u], pq, vb[u][2], vb[u][3]); }
                float inv; asm("rcp.approx.ftz.f32 %0, %1;" : "=f"(inv) : "f"((sx[0] + sx[2]) * (1.f / S_ACC)));
                const uint32_t f0 = pack2((o[0][0] + o2[0][2]) * inv, (o[0][1] + o2[0][3]) * inv), f1 = pack2((o[1][0] + o2[1][2]) * inv, (o[1][1] + o2[1][3]) * inv);
                const uint32_t c = __shfl_xor_sync(0xffffffffu, f0, 1), d = __shfl_xor_sync(0xffffffffu, f1, 1);
                asm volatile("st.shared.v2.u32 [%0], {%1,%2};" :: "r"(oxrd + w * 256), "r"(f0), "r"(f1) : "memory");
                asm volatile("st.async.shared::cluster.mbarrier::complete_tx::bytes.v4.b32 [%0], {%1,%2,%3,%4}, [%5];"
                    :: "r"(ord), "r"(odd ? c : f0), "r"(odd ? d : f1), "r"(odd ? f0 : c), "r"(odd ? f1 : d), "r"(sm + CB_OX + rbase) : "memory");
                stsm2t(vmst, vm0, vm1);
            }
            if (w == 0) PROF(10);
#pragma unroll
            for (int i = NPRE; i < NRING; i++) ldsm4t(a[i], frag(i));
            bar_sync(3, 128);
            float e[5][4];
#pragma unroll
            for (int q = 0; q < 5; q++) e[q][0] = e[q][1] = e[q][2] = e[q][3] = 0.f;
            constexpr int LAG = 2;
            uint8_t* pdst = g_acc + ((s & 2) * (ACC_PAIR / 2) + (s & 1) * 512 + w * 2048 + j * 8192 - C_MEM - sm + mr);
#pragma unroll
            for (int h = 0; h < 3; h++) {
                uint32_t ob[4][2];
                if (h == 1) {
#pragma unroll
                    for (int i = 14 - LAG; i < 14; i++) ldsm4t(a[i % NRING], frag(i + NRING));
                    pin(mr, zr, (uint32_t)(uint64_t)pdst, (uint32_t)((uint64_t)pdst >> 32), 0);
                    mbar_wait(sm + CB_OX, s & 1);
                    if (w == 0) PROF(9);
                }
#pragma unroll
                for (int k = 0; k < 4; k++) lds64(ob[k], oxrd + h * 1024 + k * 256);
#pragma unroll
                for (int i = 14 * h; i < 14 * h + 14; i++) {
                    const int u = i % 7, k = 2 * (i / 7 & 1);
                    if (u == 3) { mma16q(e[3], a[i % NRING], ob[k][0], ob[k][1]); mma16q(e[4], a[i % NRING], ob[k + 1][0], ob[k + 1][1]); }
                    else mma16q(e[u & 3], a[i % NRING], ob[k + (u >> 2)][0], ob[k + (u >> 2)][1]);
                    if (i == B5AT) { pin(mr, a[i % NRING][0], a[i % NRING][1], a[i % NRING][2], a[i % NRING][3]); bar_arrive(5, 384); }
                    if (i >= LAG && !(i >= 14 && i < 14 + LAG) && i - LAG + NRING < 42) ldsm4t(a[(i - LAG) % NRING], frag(i - LAG + NRING));
                }
            }
            {
                const uint32_t w6 = pack2h(e[3][0] + e[4][2], e[3][1] + e[4][3]), one = 0x3c003c00u;
                asm volatile("red.relaxed.gpu.global.add.noftz.v4.f16x2 [%0], {%1,%2,%3,%4};"
                    :: "l"(pdst), "r"(pack2h(e[0][0], e[0][1])), "r"(pack2h(e[0][2], e[0][3])), "r"(pack2h(e[1][0], e[1][1])), "r"(odd ? w6 : one) : "memory");
                asm volatile("red.relaxed.gpu.global.add.noftz.v4.f16x2 [%0], {%1,%2,%3,%4};"
                    :: "l"(pdst + 1024), "r"(pack2h(e[1][2], e[1][3])), "r"(pack2h(e[2][0], e[2][1])), "r"(pack2h(e[2][2], e[2][3])), "r"(odd ? one : w6) : "memory");
            }
            const uint32_t tw = clock();
            if (w == 0) { PROF(14); PROFG(25); }
            PROXY_FENCE();
            bar_sync(6, 160);
            mr = opaque(mr);
            const uint32_t ln = mr >> 4 & 31, due = tw + lds32(sm + C_LAG);
            const uint32_t vr = sm + C_WV + ((ln >> 4) * 8 + (ln & 7)) * 128 + (((2 * w + (ln >> 3 & 1)) ^ (ln & 7)) << 4);
            const uint32_t ms0 = sm + C_MEM + w * 128 + (ln & 7) * 16 + (ln >> 3) * 512, ms1 = ms0 + (ln < 24 ? 2048 : 1536);
            if (w == 2) { w_expect(sm + CB_SC, 2560); w_expect(sm + CB_OX, 2048); }
            if (w == 1) { w_bulk_s2g((uint8_t*)g_kvm + (s * NH + head) * 6144 + 3072 + j * 1024, sm + C_VM, 1024); BULK_COMMIT(); }
            const uint8_t* src = pdst - j * 8192;
            pin(mr, ms0, ms1, (uint32_t)(uint64_t)src, (uint32_t)((uint64_t)src >> 32));
            pin(mr, vr, due, 0, 0);
            cut(s + ar.D2, 1);
#pragma unroll
            for (int i = 0; i < 8; i++) ldsm4t(va[i], vr + i * 2048);
            wait_until(due);
            if (w == 0) { PROF(5); PROFG(26); }
            uint4 v[6];
            auto fetch = [&]() {
#pragma unroll
                for (int k = 0; k < 6; k++)
                    asm volatile("ld.relaxed.gpu.global.v4.u32 {%0,%1,%2,%3}, [%4];" : "=r"(v[k].x), "=r"(v[k].y), "=r"(v[k].z), "=r"(v[k].w) : "l"(src + (k >> 1) * 8192 + (k & 1) * 1024) : "memory");
            };
            fetch();
            bar_sync(9, 384);
#pragma unroll 1
            for (int n = 0;; n++) {
                uint32_t all = 0x50005000u;
#pragma unroll
                for (int k = 0; k < 3; k++) {
                    const uint4 x = v[2 * k], y = v[2 * k + 1];
                    all &= odd ? y.w : x.w;
                    stsm4(ms0 + k * 3584, f16_to_bf16(x.x), f16_to_bf16(x.y), f16_to_bf16(x.z), f16_to_bf16(y.x));
                    if (k < 2) { const uint32_t w6 = f16_to_bf16(odd ? x.w : y.w); stsm4(ms1 + k * 3584, f16_to_bf16(y.y), f16_to_bf16(y.z), w6, w6); }
                    else asm volatile("stmatrix.sync.aligned.m8n8.x2.shared.b16 [%0], {%1,%2};" :: "r"(ms1 + k * 3584), "r"(f16_to_bf16(y.y)), "r"(f16_to_bf16(y.z)) : "memory");
                }
                if (!__any_sync(0xffffffffu, all != 0x50005000u)) { PROFV(20 + w, n); break; }
                cut(n, SPIN_LIMIT);
                fetch();
            }
            if (w == 0) PROF(16);
        }
    }
}

struct SideMaps { CUtensorMap h, wv, vst, q32, k32, v32, ost, o, wo, slab3, slab2, lnp[3], wgate, wup, wdown; };
constexpr int SD_ST = 43008, SD_NST = 4, SD_EPI = SD_NST * SD_ST, SD_PAR = SD_EPI + 2 * 24576, SD_BAR = SD_PAR + 6400, SD_SMEM = SD_BAR + 256;
#define VLEAD 16
#define SEG_LAST 60
#define B_LATE 14
#define N_LIGHT 6
#define B_HELP 13
#define KSO 6
#define KSA 3
#define B_8 10
#define B_16 13
__device__ __forceinline__ int o_shift(int b) { return b >= B_16 ? 4 : b >= B_8 ? 3 : 2; }
__device__ __forceinline__ int o_split(int b) { return 1 << o_shift(b); }
__device__ __forceinline__ int next_item(int lane, bool late) {
    const int b0 = lane & 15, hi = lane >> 4;
    for (int n = 0;; n++) {
        const uint32_t w0 = ld_rlx(g_flags.qk + lane), w1 = ld_rlx(g_flags.at + lane), w2 = ld_rlx(&g_flags.c[0][0] + lane), w3 = ld_rlx(&g_flags.c[2][0] + lane), w4 = ld_rlx(&g_flags.seg[SEG_LAST * 32]);
        const uint32_t o01 = __ballot_sync(0xffffffffu, w2 < 32), o23 = __ballot_sync(0xffffffffu, b0 < B_LATE && w3 < 2u * o_split(b0));
        const uint32_t ra = __ballot_sync(0xffffffffu, w0 >= (hi ? 64u : 192u)), rb = __ballot_sync(0xffffffffu, w1 >= (hi ? 4u * o_split(b0) : 256u));
        const int bv = __ffs(o01 | 0x10000) - 1, ba = __ffs(o01 >> 16 | 0x10000) - 1, bo = __ffs(o23 | 0x10000) - 1, bl = __ffs(o23 >> 16 | 0x10000) - 1;
        if (bl == 16 && (late || ba == 16)) return -1;
        const int bc = __ffs(~ra | 0x10000) - 1;
        const bool last = ba == 15 && w4 >= 6;
        const bool r1 = (ra & ra >> 16) >> ba & 1, r2 = (rb & 0xffff) >> bo & 1, r3 = rb >> 16 >> bl & 1;
        const int kind = late || ba == 16 ? (bo < ba ? 2 : bl < bo ? 3 : -1) : last ? 1 :
                         blockIdx.x < N_LIGHT ? (r1 ? 1 : r3 ? 3 : bv < 16 ? 0 : -1) :
                         bv < 16 && (bv <= bc + VLEAD || !r2) ? 0 : r1 && ba >= B_HELP ? 1 : r2 ? 2 : r1 ? 1 : r3 ? 3 : bo < ba ? 2 : -1;
        if (kind < 0) { if (n > (1 << 20)) __trap(); __nanosleep(300); continue; }
        const int b = kind == 3 ? bl : kind == 2 ? bo : kind == 1 ? ba : bv;
        uint32_t i = 0;
        if (lane == 0) asm volatile("atom.relaxed.gpu.global.add.u32 %0, [%1], 1;" : "=r"(i) : "l"(&g_flags.c[kind][b]) : "memory");
        i = __shfl_sync(0xffffffffu, i, 0);
        if (i < (kind < 2 ? 32u : 2u * o_split(b))) return kind << 16 | b << 8 | i | ((kind == 1 ? r1 : kind == 2 ? r2 : r3) ? 128 : 0);
    }
}

template <int NP>
__device__ __forceinline__ void tile_out(const float (&acc)[8 * NP], uint32_t eb, uint32_t efull, uint32_t eempty, int& eph, int w, int lane) {
    const int r = lane & 7, mi = lane >> 3, row = w * 16 + (mi & 1) * 8 + r;
    mbar_wait(eempty, eph); eph ^= 1;
#pragma unroll
    for (int p = 0; p < NP; p++) {
        const int oc = 2 * p + (mi >> 1);
        stsm4(eb + (oc >> 3) * 8192 + row * 128 + (((oc & 7) ^ r) << 4), pack2(acc[8 * p], acc[8 * p + 1]), pack2(acc[8 * p + 2], acc[8 * p + 3]),
              pack2(acc[8 * p + 4], acc[8 * p + 5]), pack2(acc[8 * p + 6], acc[8 * p + 7]));
    }
    asm volatile("fence.proxy.async.shared::cta;" ::: "memory");
    __syncwarp();
    if (lane == 0) mbar_arrive(efull);
}

template <int MT>
__device__ __forceinline__ void attn_tile(uint32_t base, uint32_t dst, uint32_t eempty, int eph, int lane) {
    constexpr int NK = MT ? 5 : 3;
    const int r = lane & 7, mi = lane >> 3, g = lane >> 2, t = lane & 3;
    float sc[NK][4];
#pragma unroll
    for (int n = 0; n < NK; n++) sc[n][0] = sc[n][1] = sc[n][2] = sc[n][3] = 0.f;
#pragma unroll 1
    for (int k2 = 0; k2 < 6; k2++) {
        const uint32_t cb = (k2 >> 1) * 4096, c0 = (k2 & 1) * 4;
        uint32_t a0[4], a1[4], bb[NK][4];
        ldsm4(a0, base + cb + (16 * MT + (mi & 1) * 8 + r) * 128 + (((c0 + (mi >> 1)) ^ r) << 4));
        ldsm4(a1, base + cb + (16 * MT + (mi & 1) * 8 + r) * 128 + (((c0 + 2 + (mi >> 1)) ^ r) << 4));
#pragma unroll
        for (int n = 0; n < NK; n++)
            ldsm4(bb[n], n < NK - 1 ? base + 12288 + cb + (8 * n + r) * 128 + (((c0 + mi) ^ r) << 4) : base + 36864 + k2 * 512 + lane * 16);
#pragma unroll
        for (int n = 0; n < NK; n++) mma16(sc[n], a0[0], a0[1], a0[2], a0[3], bb[n][0], bb[n][1]);
#pragma unroll
        for (int n = 0; n < NK; n++) mma16(sc[n], a1[0], a1[1], a1[2], a1[3], bb[n][2], bb[n][3]);
    }
    const float scale = 0.07216878364870322f, l2e = 1.4426950408889634f;
    float v[2][2 * NK], mx[2], sum[2];
#pragma unroll
    for (int hf = 0; hf < 2; hf++) {
        mx[hf] = -INFINITY;
#pragma unroll
        for (int n = 0; n < NK; n++) {
            uint32_t u = pack2(sc[n][2 * hf], sc[n][2 * hf + 1]);
            u = pack2(lo_f(u) * scale, hi_f(u) * scale);
            const int lim = 16 * MT + 8 * hf + g - 8 * n - 2 * t;
            v[hf][2 * n] = (n < NK - 1 && lim < 0) ? -1e9f : lo_f(u);
            v[hf][2 * n + 1] = (n < NK - 1 && lim < 1) ? -1e9f : hi_f(u);
            mx[hf] = fmaxf(mx[hf], fmaxf(v[hf][2 * n], v[hf][2 * n + 1]));
        }
    }
#pragma unroll
    for (int o = 1; o < 4; o <<= 1)
#pragma unroll
        for (int hf = 0; hf < 2; hf++) mx[hf] = fmaxf(mx[hf], __shfl_xor_sync(0xffffffffu, mx[hf], o));
#pragma unroll
    for (int hf = 0; hf < 2; hf++) {
        sum[hf] = 0;
#pragma unroll
        for (int q = 0; q < 2 * NK; q++) { asm("ex2.approx.ftz.f32 %0, %1;" : "=f"(v[hf][q]) : "f"((v[hf][q] - mx[hf]) * l2e)); sum[hf] += v[hf][q]; }
    }
#pragma unroll
    for (int o = 1; o < 4; o <<= 1)
#pragma unroll
        for (int hf = 0; hf < 2; hf++) sum[hf] += __shfl_xor_sync(0xffffffffu, sum[hf], o);
    uint32_t pa[NK][2];
#pragma unroll
    for (int hf = 0; hf < 2; hf++) {
        const float inv = __fdividef(1.f, sum[hf]);
#pragma unroll
        for (int n = 0; n < NK; n++) pa[n][hf] = pack2(v[hf][2 * n] * inv, v[hf][2 * n + 1] * inv);
    }
    mbar_wait(eempty, eph);
#pragma unroll 1
    for (int n4 = 0; n4 < 6; n4++) {
        const uint32_t cb = (n4 >> 1) * 4096, c0 = (n4 & 1) * 4;
        uint32_t bm[4], bb[4][4];
        ldsm4t(bm, base + 39936 + n4 * 512 + lane * 16);
#pragma unroll
        for (int u = 0; u < 4; u++) ldsm4t(bb[u], base + 24576 + cb + (8 * mi + r) * 128 + (((c0 + u) ^ r) << 4));
        float o[4][4];
#pragma unroll
        for (int u = 0; u < 4; u++) { o[u][0] = o[u][1] = o[u][2] = o[u][3] = 0.f; mma8(o[u], pa[NK - 1][0], pa[NK - 1][1], bm[u]); }
#pragma unroll
        for (int u = 0; u < 4; u++) mma16(o[u], pa[0][0], pa[0][1], pa[1][0], pa[1][1], bb[u][0], bb[u][1]);
        if (MT) {
#pragma unroll
            for (int u = 0; u < 4; u++) mma16(o[u], pa[MT ? 2 : 0][0], pa[MT ? 2 : 0][1], pa[MT ? 3 : 0][0], pa[MT ? 3 : 0][1], bb[u][2], bb[u][3]);
        }
#pragma unroll
        for (int p = 0; p < 2; p++)
            stsm4(dst + (n4 >> 1) * 2048 + ((mi & 1) * 8 + r) * 128 + (((c0 + 2 * p + (mi >> 1)) ^ r) << 4), pack2(o[2 * p][0], o[2 * p][1]), pack2(o[2 * p][2], o[2 * p][3]),
                  pack2(o[2 * p + 1][0], o[2 * p + 1][1]), pack2(o[2 * p + 1][2], o[2 * p + 1][3]));
    }
}

__device__ __forceinline__ void mod_tail(const SideMaps& mp, bf16* out, const uint32_t sm, const uint32_t bar, const int blk, const int tid) {
#define TPROF(i)
    const int warp = __shfl_sync(0xffffffffu, tid >> 5, 0), lane = tid & 31, r = lane & 7, mi = lane >> 3;
    constexpr int T_WG = 0, T_WU = 20480, T_WD = 40960, T_X = 65536, T_GU = 81920, T_RED = 106496, T_KEY = 122880;
    bar_sync(1, 256);
    if (tid == 32) {
        mbar_expect(bar, 40960 + (blk < 80 ? 24576 : 0));
#pragma unroll 1
        for (int c = 0; c < 8; c++) tma2d(sm + T_WG + c * 5120, c < 4 ? &mp.wgate : &mp.wup, blk * 16, (c & 3) * 160, bar);
#pragma unroll 1
        for (int c = 0; c < 6 && blk < 80; c++) tma2d(sm + T_WD + c * 4096, &mp.wdown, blk * 8, c * 256, bar);
    }
    if (warp == 0) w_flag_wait(&g_flags.ln[lane & 15], 128);
    bar_sync(1, 256);
    TPROF(1);
    {
        const uint4 u = __ldcg((const uint4*)g_r + tid);
        const uint32_t uu[4] = {u.x, u.y, u.z, u.w};
        uint32_t k[8];
#pragma unroll
        for (int i = 0; i < 8; i++) { const uint32_t v = i & 1 ? uu[i >> 1] & 0xffff0000u : uu[i >> 1] << 16; k[i] = (((int)v < 0 ? ~v : v | 0x80000000u) & 0xffff0000u) | (uint32_t)(S_TOK - 1 - (tid * 8 + i)); }
#pragma unroll 1
        for (int pass = 0; pass < 2; pass++) {
#pragma unroll 1
            for (int it = 0; it < 8; it++) {
                const uint32_t m = __reduce_max_sync(0xffffffffu, max(umax3(k[0], k[1], k[2]), max(umax3(k[3], k[4], k[5]), max(k[6], k[7]))));
#pragma unroll
                for (int i = 0; i < 8; i++) if (k[i] == m) k[i] = 0;
                asm volatile("st.shared.u32 [%0], %1;" :: "r"(sm + T_KEY + pass * 256 + (warp * 8 + it) * 4), "r"(m) : "memory");
            }
            if (pass) break;
            bar_sync(1, 256);
#pragma unroll
            for (int i = 2; i < 8; i++) k[i] = 0;
            k[0] = lds32(sm + T_KEY + lane * 4); k[1] = lds32(sm + T_KEY + 128 + lane * 4);
        }
        __syncwarp();
    }
    auto sel = [&](int i) { return S_TOK - 1 - (int)(lds32(sm + T_KEY + 256 + (warp * 8 + i) * 4) & 0xffffu); };
    TPROF(2);
    {
        const bf16* src = g_h2 + sel(r) * DM + warp * 80 + mi * 8;
        uint4 v[3];
#pragma unroll
        for (int i = 0; i < 3; i++) v[i] = __ldcg((const uint4*)(src + (i < 2 || mi < 2 ? i * 32 : 0)));
#pragma unroll
        for (int i = 0; i < 3; i++) asm volatile("st.shared.v4.u32 [%0], {%1,%2,%3,%4};" :: "r"(sm + T_X + warp * 1536 + i * 512 + lane * 16), "r"(v[i].x), "r"(v[i].y), "r"(v[i].z), "r"(v[i].w) : "memory");
    }
    const int trow = sel(lane >> 2), tcol = (blk < 80 ? blk : 0) * 8 + (lane & 3) * 2;
    const uint32_t fx1 = __ldcg((const uint32_t*)(g_x1 + trow * DM + tcol)), fh2 = __ldcg((const uint32_t*)(g_h2 + trow * DM + tcol)),
                   fgb = __ldcg((const uint32_t*)(g_mod + 5 * DM + tcol));
    const float fr = __uint_as_float((uint32_t)__ldcg((const unsigned short*)g_r + trow) << 16);
    mbar_wait(bar, 0);
    __syncwarp();
    TPROF(3);
    {
        float dg[4] = {0, 0, 0, 0}, du[4] = {0, 0, 0, 0};
        uint32_t b[3][4];
#pragma unroll
        for (int i = 0; i < 3; i++) ldsm4(b[i], sm + T_X + warp * 1536 + i * 512 + lane * 16);
#pragma unroll
        for (int h = 0; h < 5; h++) {
            uint32_t ag[4], au[4];
            const uint32_t o = ((warp * 5 + h) * 16 + (mi >> 1) * 8 + r) * 32 + (mi & 1) * 16;
            ldsm4t(ag, sm + T_WG + o); ldsm4t(au, sm + T_WU + o);
            mma16q(dg, ag, b[h >> 1][2 * (h & 1)], b[h >> 1][2 * (h & 1) + 1]); mma16q(du, au, b[h >> 1][2 * (h & 1)], b[h >> 1][2 * (h & 1) + 1]);
        }
        sts128f(sm + T_RED + warp * 1024 + lane * 16, dg[0], dg[1], dg[2], dg[3]); sts128f(sm + T_RED + warp * 1024 + 512 + lane * 16, du[0], du[1], du[2], du[3]);
    }
    bar_sync(1, 256);
    if (warp == 0) {
        float g4[4] = {0, 0, 0, 0}, u4[4] = {0, 0, 0, 0};
#pragma unroll
        for (int i = 0; i < 8; i++) {
            const float4 a = lds128f(sm + T_RED + i * 1024 + lane * 16), b = lds128f(sm + T_RED + i * 1024 + 512 + lane * 16);
            g4[0] += a.x; g4[1] += a.y; g4[2] += a.z; g4[3] += a.w; u4[0] += b.x; u4[1] += b.y; u4[2] += b.z; u4[3] += b.w;
        }
        float y[4];
#pragma unroll
        for (int i = 0; i < 4; i++) { const float gq = bfr(g4[i]); y[i] = bfr(__fdividef(gq, 1.f + __expf(-gq))) * bfr(u4[i]); }
        g_gu[blk * 64 + lane] = movm_t(pack2(y[0], y[1])); g_gu[blk * 64 + 32 + lane] = movm_t(pack2(y[2], y[3]));
        __syncwarp();
        TPROF(4);
        if (lane == 0) {
            flag_add(&g_flags.gu);
            if (blk < 80) {
                flag_wait(&g_flags.gu, 96);
                mbar_expect(bar + 8, 24576); bulk_g2s(sm + T_GU, g_gu, 24576, bar + 8);
            }
        }
        __syncwarp();
    }
    if (warp == 0 && blk >= 80) flags_release(lane);
    if (blk < 80) {
        mbar_wait(bar + 8, 0);
        TPROF(5);
        float d[2][4] = {{0, 0, 0, 0}, {0, 0, 0, 0}};
#pragma unroll
        for (int k2 = 0; k2 < 6; k2++) {
            uint32_t a[4], b[4];
            ldsm4t(b, sm + T_WD + (warp * 6 + k2) * 512 + lane * 16);
            ldsm4(a, sm + T_GU + ((warp * 6 + k2) * 4 + (mi & 1) * 2 + (mi >> 1)) * 128 + r * 16);
            mma16q(d[0], a, b[0], b[1]); mma16q(d[1], a, b[2], b[3]);
        }
        asm volatile("st.shared.v2.f32 [%0], {%1,%2};" :: "r"(sm + T_RED + warp * 256 + lane * 8), "f"(d[0][0] + d[1][2]), "f"(d[0][1] + d[1][3]) : "memory");
        bar_sync(1, 256);
        if (warp == 0) {
            float y0 = 0, y1 = 0;
#pragma unroll
            for (int i = 0; i < 8; i++) { const float2 a = lds64f(sm + T_RED + i * 256 + lane * 8); y0 += a.x; y1 += a.y; }
            const float sg = bfr(__fdividef(1.f, 1.f + __expf(-fr)));
            const float b0 = bfr(lo_f(fh2) + bfr(bfr(y0) * sg)), b1 = bfr(hi_f(fh2) + bfr(bfr(y1) * sg));
            *(uint32_t*)(out + trow * DM + tcol) = pack2(lo_f(fx1) + bfr(lo_f(fgb) * b0), hi_f(fx1) + bfr(hi_f(fgb) * b1));
        }
    }
    TPROF(6);
}

__global__ void __launch_bounds__(384, 1) k_side(const __grid_constant__ SideMaps mp, const bf16* __restrict__ x, const bf16* __restrict__ wr,
                                                 bf16* __restrict__ out) {
    extern __shared__ __align__(1024) uint8_t smraw[];
    const uint32_t sm = smem_u32(smraw);
    if (sm & 1023) __trap();
    const uint32_t FULL = sm + SD_BAR, EMPTY = FULL + 32, EFULL = FULL + 64, EEMPTY = FULL + 80, IFULL = FULL + 96, IEMPTY = FULL + 128, IQ = FULL + 160, SCHED = FULL + 176, PARAM = FULL + 184, TAILB = FULL + 192;
    const int tid = threadIdx.x, warp = __shfl_sync(0xffffffffu, tid >> 5, 0), lane = tid & 31;
    const uint64_t ef = policy_stream();
    if (tid == 0) {
        for (int i = 0; i < SD_NST; i++) { mbar_init(FULL + 8 * i, 1); mbar_init(EMPTY + 8 * i, 2); }
        for (int i = 0; i < 2; i++) { mbar_init(EFULL + 8 * i, 4); mbar_init(EEMPTY + 8 * i, 1); }
        for (int i = 0; i < 4; i++) { mbar_init(IFULL + 8 * i, 1); mbar_init(IEMPTY + 8 * i, 11); }
        mbar_init(SCHED, 1); mbar_init(PARAM, 1); mbar_init(TAILB, 1); mbar_init(TAILB + 8, 1);
        asm volatile("fence.mbarrier_init.release.cluster;" ::: "memory");
    }
    __syncthreads();
    if (warp >= 8) {
      asm volatile("setmaxnreg.dec.sync.aligned.u32 40;");
      if (warp == 8) {
        int st = 0, ph = 1;
        for (int q = 0;; q++) {
            mbar_wait(IFULL + 8 * (q & 3), (q >> 2) & 1);
            const int it = __shfl_sync(0xffffffffu, lds32(IQ + 4 * (q & 3)), 0);
            if (elect()) mbar_arrive(IEMPTY + 8 * (q & 3));
            if (it < 0) break;
            const int kind = it >> 16, b = (it >> 8) & 255, i = it & 127;
            const int nst = kind == 0 ? 10 : kind == 1 ? 4 : kind == 2 ? 192 >> o_shift(b) : 2;
            const int ksched = kind == 0 ? 4 : kind == 2 ? nst - KSO : kind == 1 && !(it & 128) ? KSA : 0;
            const bool look = !(it & 128);
            if (look && kind == 1) flag_wait(&g_flags.v[b * 32 + i], 2);
            if (look && kind == 3) flag_wait(&g_flags.o[b], 4 << o_shift(b));
            for (int kb = 0; kb < nst; kb++) {
                mbar_wait(EMPTY + 8 * st, ph);
                const uint32_t base = sm + st * SD_ST, fb = FULL + 8 * st;
                if (look && kind == 1) flag_wait(&g_flags.seg[(b * 4 + kb) * 32 + i], 6);
                if (kb == ksched && elect()) mbar_arrive(SCHED);
                if (kind == 0) {
                    if (q == 0 && kb == 0) {
                        if (elect()) {
#pragma unroll 1
                            for (int c = 0; c < SD_NST; c++) tma3d(sm + c * SD_ST + 16384, &mp.wv, c * 64, i * 3, FULL + 8 * c);
#pragma unroll 1
                            for (int c = SD_NST; c < 10; c++)
                                asm volatile("cp.async.bulk.prefetch.tensor.3d.L2.global [%0, {0, %1, %2}];" :: "l"((uint64_t)&mp.wv), "r"(c * 64), "r"(i * 3) : "memory");
                        }
                        flag_wait(&g_flags.h, 160);
                    }
                    if (elect()) {
                        mbar_expect(fb, 40960);
                        tma2d(base, &mp.h, kb * 64, b * 128, fb);
                        if (q || kb >= SD_NST) tma3d(base + 16384, &mp.wv, kb * 64, i * 3, fb);
                    }
                } else if (kind == 1) {
                    if (elect()) {
                        mbar_expect(fb, 43008);
                        const int row = b * 128 + kb * 32;
                        tma3d_ef(base, &mp.q32, row, i * 3, fb, ef);
                        tma3d_ef(base + 12288, &mp.k32, row, i * 3, fb, ef);
                        bulk_g2s(base + 36864, g_kvm + ((b * 4 + kb) * NH + i) * (2 * 8 * DH), 6144, fb);
                        tma3d_ef(base + 24576, &mp.v32, row, i * 3, fb, ef);
                    }
                } else if (kind == 3) {
                    if (elect()) { mbar_expect(fb, 40960); tma3d_ef(base, &mp.lnp[o_shift(b) - 2], i * (160 >> o_shift(b)), b * KSPLIT + (kb << o_shift(b) >> 1), fb, ef); }
                } else {
                    const int k0 = ((i >> 1) * nst + kb) * 32;
                    if (elect()) { mbar_expect(fb, 28672); tma3d(base + 8192, &mp.wo, k0, (i & 1) * 5, fb); }
                    if (look && kb % 12 == 0) flag_wait(&g_flags.pair[b * 16 + k0 / 384], 16);
                    if (elect()) tma2d_ef(base, &mp.o, k0, b * 128, fb, ef);
                }
                __syncwarp();
                if (++st == SD_NST) { st = 0; ph ^= 1; }
            }
        }
      } else if (warp == 11) {
        const int lt = (int)blockIdx.x - N_SIDE;
        int own = lt >= 0 && lt < 32 * (16 - B_LATE) ? (15 - (lt >> 5)) << 8 | (lt & 31) : -1;
        for (int q = 0;; q++) {
            if (q) mbar_wait(SCHED, (q - 1) & 1);
            int it = own >= 0 && q == 0 ? 2 << 16 | own : own == -2 ? -1 : next_item(lane, lt >= 0);
            if (it < 0 && own >= 0) { it = 3 << 16 | own; own = -2; }

            if (lane == 0) {
                if (it >> 16 == 3) {
                    const int b = (it >> 8) & 255, nr = 64 >> o_shift(b);
                    asm volatile("cp.async.bulk.prefetch.L2.global [%0], %1;" :: "l"(x + (b * 128 + (it & 127) * nr) * DM), "r"(nr * DM * 2) : "memory");
                }
                mbar_wait(IEMPTY + 8 * (q & 3), ((q >> 2) & 1) ^ 1);
                asm volatile("st.shared.u32 [%0], %1;" :: "r"(IQ + 4 * (q & 3)), "r"(it) : "memory");
                mbar_arrive(IFULL + 8 * (q & 3));
            }
            if (q == 0) {
                flag_wait(&g_flags.h, 160);
                if (lane == 0) { mbar_expect(PARAM, 6400); bulk_g2s(sm + SD_PAR, g_mod + 2 * DM, 5120, PARAM); bulk_g2s(sm + SD_PAR + 5120, wr, 1280, PARAM); mbar_wait(PARAM, 0); }
            }
            __syncwarp();
            if (it < 0) break;
        }
        if (blockIdx.x >= N_SIDE && blockIdx.x < N_SIDE + 80) mbar_wait(TAILB + 8, 0);
        if (blockIdx.x < N_SIDE + 80) flags_release(lane);
      } else {
        if (lane == 0) {
            if (blockIdx.x >= N_SIDE) {
                const int blk = blockIdx.x - N_SIDE;
#pragma unroll 1
                for (int c = 0; c < 4; c++) tma2d_prefetch(warp == 9 ? &mp.wgate : &mp.wup, blk * 16, c * 160);
#pragma unroll 1
                for (int c = (warp - 9) * 3; c < (warp - 8) * 3 && blk < 80; c++) tma2d_prefetch(&mp.wdown, blk * 8, c * 256);
            }
            const int wg = warp - 9; int ph = 0;
            for (int q = 0;; q++) {
                mbar_wait(IFULL + 8 * (q & 3), (q >> 2) & 1);
                const int it = lds32(IQ + 4 * (q & 3));
                mbar_arrive(IEMPTY + 8 * (q & 3));
                if (it < 0) break;
                const int kind = it >> 16, b = (it >> 8) & 255, i = it & 127;
                if (kind == 1) continue;
                if (kind > 2) {
                    if (wg == 0) { mbar_wait(EFULL, ph); ph ^= 1; mbar_arrive(EEMPTY); flag_add(&g_flags.ln[b], 64 >> o_shift(b)); }
                    continue;
                }
                for (int rd = 0; rd < (kind == 2 ? 2 : 1); rd++) {
                    mbar_wait(EFULL + 8 * wg, ph); ph ^= 1;
                    const uint32_t src = sm + SD_EPI + wg * 24576;
                    if (kind == 2) tma3d_store(rd ? &mp.slab2 : &mp.slab3, (b * KSPLIT + (i >> 1)) * 128 + wg * 64, (i & 1) * 5 + rd * 3, src, ef, false);
                    else tma3d_store(&mp.vst, b * 128 + wg * 64, i * 3, src, ef, b > 1);
                    asm volatile("cp.async.bulk.commit_group;" ::: "memory");
                    asm volatile("cp.async.bulk.wait_group.read 0;" ::: "memory");
                    mbar_arrive(EEMPTY + 8 * wg);
                }
                asm volatile("cp.async.bulk.wait_group 0;" ::: "memory");
                bump(kind == 0 ? &g_flags.v[b * 32 + i] : &g_flags.o[b]);
                if (kind == 0) bump(&g_flags.vb[b]);
            }
        }
      }
    } else {
        asm volatile("setmaxnreg.inc.sync.aligned.u32 232;");
        const int wg = warp >> 2, w = warp & 3;
        int st = 0, ph = 0, eph = 1;
        bool att = false;
        const uint32_t eb = sm + SD_EPI + wg * 24576;
        for (int q = 0;; q++) {
            mbar_wait(IFULL + 8 * (q & 3), (q >> 2) & 1);
            const int itc = lds32(IQ + 4 * (q & 3));
            __syncwarp();
            if (lane == 0) mbar_arrive(IEMPTY + 8 * (q & 3));
            if (itc < 0) break;
            const int kind = itc >> 16, b = (itc >> 8) & 255, i = itc & 127;
            if (att && kind != 1) { bar_sync(2 + wg, 128); att = false; }
            if (kind == 0) {
                float acc[96];
#pragma unroll
                for (int n = 0; n < 96; n++) acc[n] = 0.f;
                int prev = -1;
                for (int kb = 0; kb < 10; kb++) {
                    mbar_wait(FULL + 8 * st, ph);
                    const uint32_t base = sm + st * SD_ST;
                    WG_FENCE();
#pragma unroll
                    for (int ks = 0; ks < 4; ks++)
                        wgmma_ss_n192_tb(acc, mkdesc(base + wg * 8192 + ks * 32, 16, 1024), mkdesc(base + 16384 + ks * 2048, 8192, 1024), (kb | ks) != 0);
                    WG_COMMIT();
                    if (prev >= 0) { WG_WAIT(1); if ((tid & 127) == 0) mbar_arrive(EMPTY + 8 * prev); }
                    prev = st;
                    if (++st == SD_NST) { st = 0; ph ^= 1; }
                }
                WG_WAIT(0);
                if ((tid & 127) == 0) mbar_arrive(EMPTY + 8 * prev);
                tile_out<12>(acc, eb, EFULL + 8 * wg, EEMPTY + 8 * wg, eph, w, lane);
            } else if (kind == 1) {
                const int seg = warp >> 1, mt = warp & 1;
                int sst = st + seg, sph = ph; if (sst >= SD_NST) { sst -= SD_NST; sph ^= 1; }
                ph ^= 1;
                mbar_wait(FULL + 8 * sst, sph);
                const uint32_t base = sm + sst * SD_ST;
                if (mt) attn_tile<1>(base, eb + w * 6144, EEMPTY + 8 * wg, eph, lane);
                else attn_tile<0>(base, eb + w * 6144, EEMPTY + 8 * wg, eph, lane);
                asm volatile("fence.proxy.async.shared::cta;" ::: "memory");
                __syncwarp();
                if (lane == 0) {
                    mbar_arrive(EMPTY + 8 * sst);
                    tma3d_store(&mp.ost, b * 128 + warp * 16, i * 3, eb + w * 6144, ef, false);
                    BULK_COMMIT(); BULK_WAIT();
                    bump(&g_flags.pair[b * 16 + (i >> 1)]); bump(&g_flags.at[b]);
                }
                __syncwarp();
                att = true;
            } else if (kind == 2) {
                float acc[96], acc2[64];
#pragma unroll
                for (int n = 0; n < 96; n++) acc[n] = 0.f;
#pragma unroll
                for (int n = 0; n < 64; n++) acc2[n] = 0.f;
                int prev = -1;
                for (int kb = 192 >> o_shift(b); kb > 0; kb--) {
                    const uint32_t base = sm + st * SD_ST;
                    mbar_wait(FULL + 8 * st, ph);
                    WG_FENCE();
#pragma unroll
                    for (int ks = 0; ks < 2; ks++) {
                        const uint64_t da = (mkdesc(base + wg * 4096 + ks * 32, 16, 512) & ~(3ull << 62)) | (2ull << 62);
                        wgmma_ss_n192_tb(acc, da, mkdesc(base + 8192 + ks * 2048, 4096, 1024), 1);
                        wgmma_ss_n128_tb(acc2, da, mkdesc(base + 8192 + 3 * 4096 + ks * 2048, 4096, 1024), 1);
                    }
                    WG_COMMIT();
                    if (prev >= 0) { WG_WAIT(1); if ((tid & 127) == 0) mbar_arrive(EMPTY + 8 * prev); }
                    prev = st;
                    if (++st == SD_NST) { st = 0; ph ^= 1; }
                }
                WG_WAIT(0);
                if ((tid & 127) == 0) mbar_arrive(EMPTY + 8 * prev);
                tile_out<12>(acc, eb, EFULL + 8 * wg, EEMPTY + 8 * wg, eph, w, lane);
                tile_out<8>(acc2, eb, EFULL + 8 * wg, EEMPTY + 8 * wg, eph, w, lane);
            } else {
                const int sh = o_shift(b), nr = 64 >> sh;
                int st1 = st + 1, ph1 = ph; if (st1 == SD_NST) { st1 = 0; ph1 ^= 1; }
                uint2 xin[2][5];
                uint32_t as[2][10];
#pragma unroll
                for (int q2 = 0; q2 < 10; q2++) xin[q2 & 1][q2 >> 1] = ld_ef(x + (b * 128 + i * nr + ((warp + 8 * (q2 & 1)) & (nr - 1))) * DM + lane * 4 + (q2 >> 1) * 128, ef);
                mbar_wait(PARAM, 0); mbar_wait(FULL + 8 * st, ph); mbar_wait(FULL + 8 * st1, ph1);
#pragma unroll
                for (int u2 = 0; u2 < 2; u2++) {
                    float a[20];
#pragma unroll
                    for (int q2 = 0; q2 < 20; q2++) a[q2] = 0.f;
                    if (warp + 8 * u2 < nr) {
#pragma unroll 2
                        for (int k = 0; k < (1 << sh); k++) {
                            const uint32_t ad = sm + ((k >> (sh - 1)) ? st1 : st) * SD_ST + (((k & ((1 << sh >> 1) - 1)) << (6 - sh)) + warp + 8 * u2) * 1280 + lane * 8;
                            uint32_t z[5][2];
#pragma unroll
                            for (int q2 = 0; q2 < 5; q2++) lds64(z[q2], ad + q2 * 256);
#pragma unroll
                            for (int q2 = 0; q2 < 5; q2++) { a[4 * q2] += lo_f(z[q2][0]); a[4 * q2 + 1] += hi_f(z[q2][0]); a[4 * q2 + 2] += lo_f(z[q2][1]); a[4 * q2 + 3] += hi_f(z[q2][1]); }
                        }
                    }
#pragma unroll
                    for (int q2 = 0; q2 < 10; q2++) as[u2][q2] = pack2(a[2 * q2], a[2 * q2 + 1]);
                }
                bar_sync(2 + wg, 128);
                if ((tid & 127) == 0) { mbar_arrive(EMPTY + 8 * st); mbar_arrive(EMPTY + 8 * st1); }
#pragma unroll 1
                for (int lrow = warp; lrow < nr; lrow += 8) {
                    const int row = b * 128 + i * nr + lrow;
                    const uint32_t pa = sm + SD_PAR + lane * 8;
                    float xv[20], hv[20];
                    uint32_t sv[10], tv[10];
#pragma unroll
                    for (int q2 = 0; q2 < 5; q2++) {
                        uint32_t ga[2], t[2], u[2];
                        lds64(ga, pa + q2 * 256); lds64(t, pa + 1280 + q2 * 256); lds64(u, pa + 2560 + q2 * 256);
#pragma unroll
                        for (int e = 0; e < 2; e++) {
                            const uint32_t xi = e ? xin[0][q2].y : xin[0][q2].x, ai = as[0][2 * q2 + e];
                            xv[4 * q2 + 2 * e] = bfr(lo_f(xi) + bfr(lo_f(ga[e]) * lo_f(ai))); xv[4 * q2 + 2 * e + 1] = bfr(hi_f(xi) + bfr(hi_f(ga[e]) * hi_f(ai)));
                            tv[2 * q2 + e] = t[e]; sv[2 * q2 + e] = u[e]; as[0][2 * q2 + e] = as[1][2 * q2 + e];
                        }
                        xin[0][q2] = xin[1][q2];
                    }
                    ln_mod(xv, sv, tv, hv);
                    float rs = 0;
#pragma unroll
                    for (int q2 = 0; q2 < 5; q2++) {
                        const int c = row * DM + lane * 4 + q2 * 128;
                        const float* xx = xv + 4 * q2; const float* hh = hv + 4 * q2;
                        uint32_t gb[2], wv[2];
                        lds64(gb, pa + 3840 + q2 * 256); lds64(wv, pa + 5120 + q2 * 256);
                        rs += (hh[0] * lo_f(wv[0]) + hh[1] * hi_f(wv[0])) + (hh[2] * lo_f(wv[1]) + hh[3] * hi_f(wv[1]));
                        st_ef(g_x1 + c, make_uint2(pack2(xx[0], xx[1]), pack2(xx[2], xx[3])), ef);
                        st_ef(g_h2 + c, make_uint2(pack2(hh[0], hh[1]), pack2(hh[2], hh[3])), ef);
                        st_ef(out + c, make_uint2(pack2(xx[0] + bfr(lo_f(gb[0]) * hh[0]), xx[1] + bfr(hi_f(gb[0]) * hh[1])),
                                                  pack2(xx[2] + bfr(lo_f(gb[1]) * hh[2]), xx[3] + bfr(hi_f(gb[1]) * hh[3]))), ef);
                    }
                    rs = warp_sum(rs);
                    if (lane == 0) g_r[row] = __float2bfloat16_rn(rs);
                }
                bar_sync(1, 256);
                if (wg == 0) { mbar_wait(EEMPTY, eph); eph ^= 1; if (lane == 0) mbar_arrive(EFULL); }
                st = st1 + 1; ph = ph1; if (st == SD_NST) { st = 0; ph ^= 1; }
            }
        }
        if (blockIdx.x >= N_SIDE) mod_tail(mp, out, sm, TAILB, blockIdx.x - N_SIDE, tid);
    }
    __syncwarp();
    asm volatile("griddepcontrol.wait;" ::: "memory");
}

#define P_D1 650
#define P_DL 700
#define P_DG 29
typedef CUresult (*EncodeFn)(CUtensorMap*, CUtensorMapDataType, cuuint32_t, void*, const cuuint64_t*, const cuuint64_t*, const cuuint32_t*, const cuuint32_t*,
                             CUtensorMapInterleave, CUtensorMapSwizzle, CUtensorMapL2promotion, CUtensorMapFloatOOBfill);
static EncodeFn s_encode = nullptr;
static void make_map(CUtensorMap* m, const void* p, int rows, int cols, int box_rows, int box_cols = 64) {
    cuuint64_t dims[2] = {(cuuint64_t)cols, (cuuint64_t)rows}, strides[1] = {(cuuint64_t)cols * 2};
    cuuint32_t box[2] = {(cuuint32_t)box_cols, (cuuint32_t)box_rows}, es[2] = {1, 1};
    s_encode(m, CU_TENSOR_MAP_DATA_TYPE_BFLOAT16, 2, (void*)p, dims, strides, box, es, CU_TENSOR_MAP_INTERLEAVE_NONE,
             box_cols == 64 ? CU_TENSOR_MAP_SWIZZLE_128B : box_cols == 32 ? CU_TENSOR_MAP_SWIZZLE_64B : CU_TENSOR_MAP_SWIZZLE_NONE, CU_TENSOR_MAP_L2_PROMOTION_L2_256B, CU_TENSOR_MAP_FLOAT_OOB_FILL_NONE);
}
static void make_map3(CUtensorMap* m, const void* p, int rows, int cols, int box_rows, int box_chunks, int cw = 64) {
    cuuint64_t dims[3] = {(cuuint64_t)cw, (cuuint64_t)rows, (cuuint64_t)(cols / cw)}, strides[2] = {(cuuint64_t)cols * 2, (cuuint64_t)cw * 2};
    cuuint32_t box[3] = {(cuuint32_t)cw, (cuuint32_t)box_rows, (cuuint32_t)box_chunks}, es[3] = {1, 1, 1};
    s_encode(m, CU_TENSOR_MAP_DATA_TYPE_BFLOAT16, 3, (void*)p, dims, strides, box, es, CU_TENSOR_MAP_INTERLEAVE_NONE,
             cw == 64 ? CU_TENSOR_MAP_SWIZZLE_128B : CU_TENSOR_MAP_SWIZZLE_64B, CU_TENSOR_MAP_L2_PROMOTION_L2_256B, CU_TENSOR_MAP_FLOAT_OOB_FILL_NONE);
}
template <typename T> static void* sym(T& s) { void* p = nullptr; cudaGetSymbolAddress(&p, s); return p; }

extern "C" void kernel_launch(void* const* d_in, const int* in_sizes, int n_in, void* d_out, int out_size) {
    const bf16 *x = (const bf16*)d_in[0], *mem0 = (const bf16*)d_in[1], *Wq = (const bf16*)d_in[2], *Wk = (const bf16*)d_in[3],
               *Wv = (const bf16*)d_in[4], *Wo = (const bf16*)d_in[5], *wr = (const bf16*)d_in[8], *wgate = (const bf16*)d_in[9],
               *wup = (const bf16*)d_in[10], *wdown = (const bf16*)d_in[11], *c = (const bf16*)d_in[12], *wmod = (const bf16*)d_in[13];
    bf16* out = (bf16*)d_out;
    if (!s_encode) {
        cudaDriverEntryPointQueryResult qr;
        cudaGetDriverEntryPoint("cuTensorMapEncodeTiled", (void**)&s_encode, cudaEnableDefault, &qr);
        cudaFuncSetAttribute(k_side, cudaFuncAttributeMaxDynamicSharedMemorySize, SD_SMEM);
        cudaFuncSetAttribute(k_chain, cudaFuncAttributeMaxDynamicSharedMemorySize, C_SMEM);
    }
    ChainMaps cm; SideMaps sd;
    make_map(&sd.h, sym(g_h), S_TOK, DM, 128); make_map3(&sd.wv, Wv, DM, HD, 64, 3); make_map3(&sd.vst, sym(g_v), S_TOK, HD, 64, 3);
    make_map3(&sd.q32, sym(g_q), S_TOK, HD, 32, 3); make_map3(&sd.k32, sym(g_k), S_TOK, HD, 32, 3); make_map3(&sd.v32, sym(g_v), S_TOK, HD, 32, 3);
    make_map3(&sd.ost, sym(g_o), S_TOK, HD, 16, 3); make_map(&sd.o, sym(g_o), S_TOK, HD, 128, 32); make_map3(&sd.wo, Wo, HD, DM, 32, 5);
    make_map3(&sd.slab3, sym(g_slab), 16 * KSPLIT * 128, DM, 64, 3); make_map3(&sd.slab2, sym(g_slab), 16 * KSPLIT * 128, DM, 64, 2);
    for (int i = 0; i < 3; i++) {
        cuuint64_t dims[3] = {256, 320, 16 * KSPLIT}, strides[2] = {512, 128 * DM * 2};
        cuuint32_t box[3] = {256, 40u >> i, 2u << i}, es[3] = {1, 1, 1};
        s_encode(&sd.lnp[i], CU_TENSOR_MAP_DATA_TYPE_BFLOAT16, 3, sym(g_slab), dims, strides, box, es, CU_TENSOR_MAP_INTERLEAVE_NONE,
                 CU_TENSOR_MAP_SWIZZLE_NONE, CU_TENSOR_MAP_L2_PROMOTION_L2_256B, CU_TENSOR_MAP_FLOAT_OOB_FILL_NONE);
    }
    make_map(&cm.wq, Wq, DM, HD, 64); make_map(&cm.wk, Wk, DM, HD, 64); make_map(&cm.wv, Wv, DM, HD, 64); make_map3(&cm.wo, Wo, HD, DM, 64, 7, 32);
    make_map3(&cm.h2, sym(g_h), S_TOK, DM, 32, 2);
    make_map(&cm.q32, sym(g_q), S_TOK, HD, 32); make_map(&cm.k32, sym(g_k), S_TOK, HD, 32); make_map(&cm.v32, sym(g_v), S_TOK, HD, 32);
    make_map(&sd.wgate, wgate, DM, FF, 160, 16); make_map(&sd.wup, wup, DM, FF, 160, 16); make_map(&sd.wdown, wdown, FF, DM, 256, 8);
    make_map(&cm.wmod, wmod, DM, 6 * DM, 160, 48);
    ChainArgs ar = {x, mem0, c, Wv, Wo, out, P_D1, P_DL, P_DG};
    k_chain<<<96, 384, C_SMEM>>>(cm, ar);
    cudaLaunchConfig_t cfg = {};
    cfg.gridDim = dim3(N_SIDE + 96); cfg.blockDim = dim3(384); cfg.dynamicSmemBytes = SD_SMEM; cfg.stream = cudaStreamPerThread;
    cudaLaunchAttribute at[1]; at[0].id = cudaLaunchAttributeProgrammaticStreamSerialization; at[0].val.programmaticStreamSerializationAllowed = 1;
    cfg.attrs = at; cfg.numAttrs = 1;
    cudaLaunchKernelEx(&cfg, k_side, sd, x, wr, out);
}
```

```cpp
#include <cuda_runtime.h>
#include <cuda_bf16.h>
#include <cuda.h>
#include <stdint.h>
#include <stdio.h>
#include <string.h>
#include <stdlib.h>

typedef __nv_bfloat16 bf16;
constexpr int S_TOK = 2048, DM = 640, NH = 32, DH = 192, HD = NH * DH, NSEG = 64, SEG = 32, FF = 1536;

__device__ bf16 g_mod[6 * DM];
__device__ bf16 g_h[S_TOK * DM];
constexpr int AT_REC = 43008, AT_V = 24576, AT_KM = 36864, AT_VM = 39936;
__device__ __align__(1024) uint8_t g_att[NSEG * NH * AT_REC];
__device__ bf16 g_o[S_TOK * HD];
__device__ bf16 g_A[S_TOK * DM];
__device__ bf16 g_x1[S_TOK * DM];
__device__ bf16 g_h2[S_TOK * DM];
__device__ bf16 g_r[S_TOK];
__device__ int g_idx[8];
__device__ __align__(128) uint32_t g_gu[FF / 8 * 32];
constexpr int ACC_PAIR = 24 * 1024;
__device__ __align__(1024) uint8_t g_acc[2 * ACC_PAIR];
__device__ __align__(1024) uint32_t g_stamp[4 * 12 * 32];
constexpr int KSPLIT = 16;
__device__ bf16 g_slab[16 * KSPLIT * 128 * DM];
struct __align__(128) Flags {
    uint32_t qk[16], vb[16];
    uint32_t at[16], o[16];
    uint32_t c[4][16];
    uint32_t ln[16], pad0[16];
    uint32_t v[16 * 32];
    uint32_t seg[64 * 32];
    uint32_t pair[16 * 16];
    uint32_t mod, h, pad1[30], gu, pad2[31], done, pad3[31];
};
__device__ Flags g_flags;

__device__ __forceinline__ uint32_t smem_u32(const void* p) { return (uint32_t)__cvta_generic_to_shared(p); }
__device__ __forceinline__ uint32_t pack2(float lo, float hi) {
    uint32_t r; asm("cvt.rn.bf16x2.f32 %0, %1, %2;" : "=r"(r) : "f"(hi), "f"(lo)); return r;
}
__device__ __forceinline__ float bfr(float x) { return __uint_as_float(pack2(0.f, x)); }
__device__ __forceinline__ float inv_std(float var) {
    float s, r; asm("sqrt.approx.f32 %0, %1;" : "=f"(s) : "f"(bfr(bfr(var) + 1e-5f))); asm("rcp.approx.f32 %0, %1;" : "=f"(r) : "f"(bfr(s))); return r;
}
__device__ __forceinline__ float lo_f(uint32_t v) { return __uint_as_float(v << 16); }
__device__ __forceinline__ float hi_f(uint32_t v) { return __uint_as_float(v & 0xffff0000u); }
__device__ __forceinline__ void mbar_init(uint32_t bar, int cnt) { asm volatile("mbarrier.init.shared::cta.b64 [%0], %1;" :: "r"(bar), "r"(cnt) : "memory"); }
__device__ __forceinline__ void mbar_expect(uint32_t bar, int bytes) { asm volatile("mbarrier.arrive.expect_tx.shared::cta.b64 _, [%0], %1;" :: "r"(bar), "r"(bytes) : "memory"); }
__device__ __forceinline__ void mbar_arrive(uint32_t bar) { asm volatile("mbarrier.arrive.shared::cta.b64 _, [%0];" :: "r"(bar) : "memory"); }
__device__ __forceinline__ bool mbar_try(uint32_t bar, int par) {
    uint32_t ok; asm volatile("{ .reg .pred p; mbarrier.try_wait.parity.shared::cta.b64 p, [%1], %2; selp.u32 %0, 1, 0, p; }" : "=r"(ok) : "r"(bar), "r"(par) : "memory"); return ok;
}
__device__ __forceinline__ bool mbar_try_cluster(uint32_t bar, int par) {
    uint32_t ok; asm volatile("{ .reg .pred p; mbarrier.try_wait.parity.acquire.cluster.shared::cta.b64 p, [%1], %2; selp.u32 %0, 1, 0, p; }" : "=r"(ok) : "r"(bar), "r"(par) : "memory"); return ok;
}
__device__ __forceinline__ bool mbar_test(uint32_t bar, uint32_t par) {
    uint32_t ok; asm volatile("{ .reg .pred p; mbarrier.test_wait.parity.shared::cta.b64 p, [%1], %2; selp.u32 %0, 1, 0, p; }" : "=r"(ok) : "r"(bar), "r"(par) : "memory"); return ok;
}
constexpr int SPIN_LIMIT = 1 << 18;
__device__ __forceinline__ void mbar_wait(uint32_t bar, uint32_t par) {
    asm volatile("{ .reg .pred p, q; .reg .u32 n; mov.u32 n, 0;\n"
                 "W_%=: mbarrier.try_wait.parity.shared::cta.b64 p, [%0], %1;\n"
                 "@p bra.uni D_%=;\n"
                 "add.u32 n, n, 1; setp.lt.u32 q, n, 0x200000; @q bra.uni W_%=;\n"
                 "trap;\n"
                 "D_%=: }" :: "r"(bar), "r"(par) : "memory");
}
__device__ __forceinline__ void tma2d(uint32_t dst, const CUtensorMap* m, int c0, int c1, uint32_t bar) {
    asm volatile("cp.async.bulk.tensor.2d.shared::cluster.global.mbarrier::complete_tx::bytes [%0], [%1, {%3, %4}], [%2];"
        :: "r"(dst), "l"((uint64_t)m), "r"(bar), "r"(c0), "r"(c1) : "memory");
}
__device__ __forceinline__ void tma2d_mc(uint32_t dst, const CUtensorMap* m, int c0, int c1, uint32_t bar, uint16_t mask) {
    asm volatile("cp.async.bulk.tensor.2d.shared::cluster.global.mbarrier::complete_tx::bytes.multicast::cluster [%0], [%1, {%3, %4}], [%2], %5;"
        :: "r"(dst), "l"((uint64_t)m), "r"(bar), "r"(c0), "r"(c1), "h"(mask) : "memory");
}
__device__ __forceinline__ uint64_t policy_stream() { uint64_t p; asm("createpolicy.fractional.L2::evict_first.b64 %0, 1.0;" : "=l"(p)); return p; }
__device__ __forceinline__ void tma2d_ef(uint32_t dst, const CUtensorMap* m, int c0, int c1, uint32_t bar, uint64_t pol) {
    asm volatile("cp.async.bulk.tensor.2d.shared::cluster.global.mbarrier::complete_tx::bytes.L2::cache_hint [%0], [%1, {%3, %4}], [%2], %5;"
        :: "r"(dst), "l"((uint64_t)m), "r"(bar), "r"(c0), "r"(c1), "l"(pol) : "memory");
}
__device__ __forceinline__ void tma3d(uint32_t dst, const CUtensorMap* m, int row, int chunk, uint32_t bar) {
    asm volatile("cp.async.bulk.tensor.3d.shared::cluster.global.mbarrier::complete_tx::bytes [%0], [%1, {0, %3, %4}], [%2];"
        :: "r"(dst), "l"((uint64_t)m), "r"(bar), "r"(row), "r"(chunk) : "memory");
}
__device__ __forceinline__ void tma3d_ef(uint32_t dst, const CUtensorMap* m, int row, int chunk, uint32_t bar, uint64_t pol) {
    asm volatile("cp.async.bulk.tensor.3d.shared::cluster.global.mbarrier::complete_tx::bytes.L2::cache_hint [%0], [%1, {0, %3, %4}], [%2], %5;"
        :: "r"(dst), "l"((uint64_t)m), "r"(bar), "r"(row), "r"(chunk), "l"(pol) : "memory");
}
__device__ __forceinline__ void tma3d_store(const CUtensorMap* m, int row, int chunk, uint32_t src, uint64_t pol, bool hint) {
    if (hint) asm volatile("cp.async.bulk.tensor.3d.global.shared::cta.bulk_group.L2::cache_hint [%0, {0, %2, %3}], [%1], %4;"
        :: "l"((uint64_t)m), "r"(src), "r"(row), "r"(chunk), "l"(pol) : "memory");
    else asm volatile("cp.async.bulk.tensor.3d.global.shared::cta.bulk_group [%0, {0, %2, %3}], [%1];"
        :: "l"((uint64_t)m), "r"(src), "r"(row), "r"(chunk) : "memory");
}
__device__ __forceinline__ bool elect() { uint32_t p; asm volatile("{ .reg .pred e; elect.sync _|e, -1; selp.u32 %0, 1, 0, e; }" : "=r"(p)); return p; }
__device__ __forceinline__ uint2 ld_ef(const void* p, uint64_t pol) {
    uint2 v; asm volatile("ld.relaxed.gpu.global.L2::cache_hint.v2.u32 {%0,%1}, [%2], %3;" : "=r"(v.x), "=r"(v.y) : "l"(p), "l"(pol)); return v;
}
__device__ __forceinline__ void st_ef(void* p, uint2 v, uint64_t pol) {
    asm volatile("st.global.L2::cache_hint.v2.u32 [%0], {%1,%2}, %3;" :: "l"(p), "r"(v.x), "r"(v.y), "l"(pol) : "memory");
}
__device__ __forceinline__ void tma2d_prefetch(const CUtensorMap* m, int c0, int c1) {
    asm volatile("cp.async.bulk.prefetch.tensor.2d.L2.global [%0, {%1, %2}];" :: "l"((uint64_t)m), "r"(c0), "r"(c1) : "memory");
}
__device__ __forceinline__ void mbar_arrive_remote(uint32_t bar) { asm volatile("mbarrier.arrive.relaxed.cluster.shared::cluster.b64 _, [%0];" :: "r"(bar) : "memory"); }
__device__ __forceinline__ void tma2d_store(const CUtensorMap* m, int c0, int c1, uint32_t src) {
    asm volatile("cp.async.bulk.tensor.2d.global.shared::cta.bulk_group [%0, {%2, %3}], [%1];"
        :: "l"((uint64_t)m), "r"(src), "r"(c0), "r"(c1) : "memory");
}
__device__ __forceinline__ void bulk_g2s(uint32_t dst, const void* src, int bytes, uint32_t bar) {
    asm volatile("cp.async.bulk.shared::cluster.global.mbarrier::complete_tx::bytes [%0], [%1], %2, [%3];" :: "r"(dst), "l"(src), "r"(bytes), "r"(bar) : "memory");
}
__device__ __forceinline__ void ldsm4(uint32_t (&r)[4], uint32_t a) {
    asm volatile("ldmatrix.sync.aligned.m8n8.x4.shared.b16 {%0,%1,%2,%3}, [%4];" : "=r"(r[0]), "=r"(r[1]), "=r"(r[2]), "=r"(r[3]) : "r"(a) : "memory");
}
__device__ __forceinline__ void ldsm4t(uint32_t (&r)[4], uint32_t a) {
    asm volatile("ldmatrix.sync.aligned.m8n8.x4.trans.shared.b16 {%0,%1,%2,%3}, [%4];" : "=r"(r[0]), "=r"(r[1]), "=r"(r[2]), "=r"(r[3]) : "r"(a) : "memory");
}
__device__ __forceinline__ void stsm4(uint32_t a, uint32_t r0, uint32_t r1, uint32_t r2, uint32_t r3) {
    asm volatile("stmatrix.sync.aligned.m8n8.x4.shared.b16 [%0], {%1,%2,%3,%4};" :: "r"(a), "r"(r0), "r"(r1), "r"(r2), "r"(r3) : "memory");
}
__device__ __forceinline__ void stsm4t(uint32_t a, uint32_t r0, uint32_t r1, uint32_t r2, uint32_t r3) {
    asm volatile("stmatrix.sync.aligned.m8n8.x4.trans.shared.b16 [%0], {%1,%2,%3,%4};" :: "r"(a), "r"(r0), "r"(r1), "r"(r2), "r"(r3) : "memory");
}
__device__ __forceinline__ void stsm2t(uint32_t a, uint32_t r0, uint32_t r1) {
    asm volatile("stmatrix.sync.aligned.m8n8.x2.trans.shared.b16 [%0], {%1,%2};" :: "r"(a), "r"(r0), "r"(r1) : "memory");
}
__device__ __forceinline__ uint32_t movm_t(uint32_t v) { uint32_t r; asm volatile("movmatrix.sync.aligned.m8n8.trans.b16 %0, %1;" : "=r"(r) : "r"(v)); return r; }
__device__ __forceinline__ void mma16(float (&d)[4], uint32_t a0, uint32_t a1, uint32_t a2, uint32_t a3, uint32_t b0, uint32_t b1) {
    asm volatile("mma.sync.aligned.m16n8k16.row.col.f32.bf16.bf16.f32 {%0,%1,%2,%3}, {%4,%5,%6,%7}, {%8,%9}, {%0,%1,%2,%3};"
        : "+f"(d[0]), "+f"(d[1]), "+f"(d[2]), "+f"(d[3]) : "r"(a0), "r"(a1), "r"(a2), "r"(a3), "r"(b0), "r"(b1));
}
__device__ __forceinline__ void mma8(float (&d)[4], uint32_t a0, uint32_t a1, uint32_t b0) {
    asm volatile("mma.sync.aligned.m16n8k8.row.col.f32.bf16.bf16.f32 {%0,%1,%2,%3}, {%4,%5}, {%6}, {%0,%1,%2,%3};"
        : "+f"(d[0]), "+f"(d[1]), "+f"(d[2]), "+f"(d[3]) : "r"(a0), "r"(a1), "r"(b0));
}
__device__ __forceinline__ uint32_t mapa(uint32_t a, uint32_t r) { uint32_t o; asm volatile("mapa.shared::cluster.u32 %0, %1, %2;" : "=r"(o) : "r"(a), "r"(r)); return o; }
__device__ __forceinline__ void bar_sync(int id, int n) { asm volatile("bar.sync %0, %1;" :: "r"(id), "r"(n) : "memory"); }
__device__ __forceinline__ void bar_arrive(int id, int n) { asm volatile("bar.arrive %0, %1;" :: "r"(id), "r"(n) : "memory"); }
__device__ __forceinline__ uint64_t mkdesc(uint32_t addr, uint32_t lbo, uint32_t sbo) {
    return (uint64_t)((addr & 0x3FFFF) >> 4) | ((uint64_t)(lbo >> 4) << 16) | ((uint64_t)(sbo >> 4) << 32) | (1ull << 62);
}
#define WG_FENCE()  asm volatile("wgmma.fence.sync.aligned;" ::: "memory")
#define WG_COMMIT() asm volatile("wgmma.commit_group.sync.aligned;" ::: "memory")
#define WG_WAIT(n)  asm volatile("wgmma.wait_group.sync.aligned %0;" :: "n"(n) : "memory")

__device__ __forceinline__ void wgmma_ss_n192_tb(float (&d)[96], uint64_t a, uint64_t b, int acc) {
    asm volatile("{ .reg .pred p; setp.ne.b32 p, %98, 0;\n"
        "wgmma.mma_async.sync.aligned.m64n192k16.f32.bf16.bf16 {%0,%1,%2,%3,%4,%5,%6,%7,%8,%9,%10,%11,%12,%13,%14,%15,%16,%17,%18,%19,%20,%21,%22,%23,%24,%25,%26,%27,%28,%29,%30,%31,%32,%33,%34,%35,%36,%37,%38,%39,%40,%41,%42,%43,%44,%45,%46,%47,%48,%49,%50,%51,%52,%53,%54,%55,%56,%57,%58,%59,%60,%61,%62,%63,%64,%65,%66,%67,%68,%69,%70,%71,%72,%73,%74,%75,%76,%77,%78,%79,%80,%81,%82,%83,%84,%85,%86,%87,%88,%89,%90,%91,%92,%93,%94,%95}, %96, %97, p, 1, 1, 0, 1; }"
        : "+f"(d[0]), "+f"(d[1]), "+f"(d[2]), "+f"(d[3]), "+f"(d[4]), "+f"(d[5]), "+f"(d[6]), "+f"(d[7]), "+f"(d[8]), "+f"(d[9]), "+f"(d[10]), "+f"(d[11]), "+f"(d[12]), "+f"(d[13]), "+f"(d[14]), "+f"(d[15]), "+f"(d[16]), "+f"(d[17]), "+f"(d[18]), "+f"(d[19]), "+f"(d[20]), "+f"(d[21]), "+f"(d[22]), "+f"(d[23]), "+f"(d[24]), "+f"(d[25]), "+f"(d[26]), "+f"(d[27]), "+f"(d[28]), "+f"(d[29]), "+f"(d[30]), "+f"(d[31]), "+f"(d[32]), "+f"(d[33]), "+f"(d[34]), "+f"(d[35]), "+f"(d[36]), "+f"(d[37]), "+f"(d[38]), "+f"(d[39]), "+f"(d[40]), "+f"(d[41]), "+f"(d[42]), "+f"(d[43]), "+f"(d[44]), "+f"(d[45]), "+f"(d[46]), "+f"(d[47]), "+f"(d[48]), "+f"(d[49]), "+f"(d[50]), "+f"(d[51]), "+f"(d[52]), "+f"(d[53]), "+f"(d[54]), "+f"(d[55]), "+f"(d[56]), "+f"(d[57]), "+f"(d[58]), "+f"(d[59]), "+f"(d[60]), "+f"(d[61]), "+f"(d[62]), "+f"(d[63]), "+f"(d[64]), "+f"(d[65]), "+f"(d[66]), "+f"(d[67]), "+f"(d[68]), "+f"(d[69]), "+f"(d[70]), "+f"(d[71]), "+f"(d[72]), "+f"(d[73]), "+f"(d[74]), "+f"(d[75]), "+f"(d[76]), "+f"(d[77]), "+f"(d[78]), "+f"(d[79]), "+f"(d[80]), "+f"(d[81]), "+f"(d[82]), "+f"(d[83]), "+f"(d[84]), "+f"(d[85]), "+f"(d[86]), "+f"(d[87]), "+f"(d[88]), "+f"(d[89]), "+f"(d[90]), "+f"(d[91]), "+f"(d[92]), "+f"(d[93]), "+f"(d[94]), "+f"(d[95])
        : "l"(a), "l"(b), "r"(acc));
}

__device__ __forceinline__ void wgmma_ss_n128_tb(float (&d)[64], uint64_t a, uint64_t b, int acc) {
    asm volatile("{ .reg .pred p; setp.ne.b32 p, %66, 0;\n"
        "wgmma.mma_async.sync.aligned.m64n128k16.f32.bf16.bf16 {%0,%1,%2,%3,%4,%5,%6,%7,%8,%9,%10,%11,%12,%13,%14,%15,%16,%17,%18,%19,%20,%21,%22,%23,%24,%25,%26,%27,%28,%29,%30,%31,%32,%33,%34,%35,%36,%37,%38,%39,%40,%41,%42,%43,%44,%45,%46,%47,%48,%49,%50,%51,%52,%53,%54,%55,%56,%57,%58,%59,%60,%61,%62,%63}, %64, %65, p, 1, 1, 0, 1; }"
        : "+f"(d[0]), "+f"(d[1]), "+f"(d[2]), "+f"(d[3]), "+f"(d[4]), "+f"(d[5]), "+f"(d[6]), "+f"(d[7]), "+f"(d[8]), "+f"(d[9]), "+f"(d[10]), "+f"(d[11]), "+f"(d[12]), "+f"(d[13]), "+f"(d[14]), "+f"(d[15]), "+f"(d[16]), "+f"(d[17]), "+f"(d[18]), "+f"(d[19]), "+f"(d[20]), "+f"(d[21]), "+f"(d[22]), "+f"(d[23]), "+f"(d[24]), "+f"(d[25]), "+f"(d[26]), "+f"(d[27]), "+f"(d[28]), "+f"(d[29]), "+f"(d[30]), "+f"(d[31]), "+f"(d[32]), "+f"(d[33]), "+f"(d[34]), "+f"(d[35]), "+f"(d[36]), "+f"(d[37]), "+f"(d[38]), "+f"(d[39]), "+f"(d[40]), "+f"(d[41]), "+f"(d[42]), "+f"(d[43]), "+f"(d[44]), "+f"(d[45]), "+f"(d[46]), "+f"(d[47]), "+f"(d[48]), "+f"(d[49]), "+f"(d[50]), "+f"(d[51]), "+f"(d[52]), "+f"(d[53]), "+f"(d[54]), "+f"(d[55]), "+f"(d[56]), "+f"(d[57]), "+f"(d[58]), "+f"(d[59]), "+f"(d[60]), "+f"(d[61]), "+f"(d[62]), "+f"(d[63])
        : "l"(a), "l"(b), "r"(acc));
}

__device__ __forceinline__ void wgmma_rs_n32(float (&d)[16], const uint32_t (&a)[4], uint64_t b, int acc) {
    asm volatile("{ .reg .pred p; setp.ne.b32 p, %21, 0;\n"
        "wgmma.mma_async.sync.aligned.m64n32k16.f32.bf16.bf16 {%0,%1,%2,%3,%4,%5,%6,%7,%8,%9,%10,%11,%12,%13,%14,%15}, {%16,%17,%18,%19}, %20, p, 1, 1, 0; }"
        : "+f"(d[0]), "+f"(d[1]), "+f"(d[2]), "+f"(d[3]), "+f"(d[4]), "+f"(d[5]), "+f"(d[6]), "+f"(d[7]), "+f"(d[8]), "+f"(d[9]), "+f"(d[10]), "+f"(d[11]), "+f"(d[12]), "+f"(d[13]), "+f"(d[14]), "+f"(d[15])
        : "r"(a[0]), "r"(a[1]), "r"(a[2]), "r"(a[3]), "l"(b), "r"(acc));
}

__device__ __forceinline__ float warp_sum(float v) {
#pragma unroll
    for (int o = 16; o; o >>= 1) v += __shfl_xor_sync(0xffffffffu, v, o);
    return v;
}
__device__ __forceinline__ void ln_mod(const float (&xv)[20], const uint32_t (&sv)[10], const uint32_t (&tv)[10], float (&hv)[20]) {
    float s = 0;
#pragma unroll
    for (int i = 0; i < 20; i++) s += xv[i];
    const float mean = warp_sum(s) * (1.f / DM);
    float q = 0;
#pragma unroll
    for (int i = 0; i < 20; i++) { float d = xv[i] - mean; q += d * d; }
    const float mb = bfr(mean), inv = inv_std(warp_sum(q) * (1.f / DM));
#pragma unroll
    for (int i = 0; i < 10; i++) {
        const float n0 = bfr(bfr(xv[2 * i] - mb) * inv), n1 = bfr(bfr(xv[2 * i + 1] - mb) * inv);
        hv[2 * i] = bfr(bfr(n0 * bfr(1.f + lo_f(sv[i]))) + lo_f(tv[i]));
        hv[2 * i + 1] = bfr(bfr(n1 * bfr(1.f + hi_f(sv[i]))) + hi_f(tv[i]));
    }
}
__device__ __forceinline__ uint32_t ld_rlx(const uint32_t* f) { uint32_t v; asm volatile("ld.relaxed.gpu.global.u32 %0, [%1];" : "=r"(v) : "l"(f) : "memory"); return v; }
__device__ __forceinline__ void bump(uint32_t* f) { asm volatile("red.relaxed.gpu.global.add.u32 [%0], 1;" :: "l"(f) : "memory"); }
__device__ __forceinline__ void flag_wait(const uint32_t* f, uint32_t target) {
    for (int n = 0;; n++) {
        uint32_t v; asm volatile("ld.relaxed.gpu.global.u32 %0, [%1];" : "=r"(v) : "l"(f) : "memory");
        if (v >= target) break;
        if (n > (1 << 23)) __trap();
    }
}
__device__ __forceinline__ void flag_add(uint32_t* f, uint32_t v = 1) { asm volatile("red.release.gpu.global.add.u32 [%0], %1;" :: "l"(f), "r"(v) : "memory"); }
constexpr int N_SIDE = 36;
__device__ __forceinline__ void flags_release(int lane) {
    uint32_t old = 0;
    if (lane == 0) asm volatile("atom.relaxed.gpu.global.add.u32 %0, [%1], 1;" : "=r"(old) : "l"(&g_flags.done) : "memory");
    if (__shfl_sync(0xffffffffu, old, 0) == 96 + N_SIDE - 1)
        for (int i = lane; i < (int)(sizeof(Flags) / 16); i += 32) ((uint4*)&g_flags)[i] = make_uint4(0, 0, 0, 0);
}

struct ChainMaps { CUtensorMap wq, wk, wv, wo, h2, wmod; };
struct ChainArgs { const bf16 *x, *mem0, *c, *wv, *wo; bf16* out; int D1, D2, DG; };
constexpr uint32_t SM_BASE = 1024;
#define NRING 11
#define FILL_AT 1
#define VF 6
#define VPRE 2
#define XORD 0
#define B5AT 41
#define QCUT 0x7f
#define NCH 2
#define ALA 1
#define VPOS 0
#define NPRE 9
#define REG_P 208
#define REG_L (504 - 2 * REG_P)
constexpr int WO_BLK = 7 * 4096;
constexpr int C_WV = 0, C_WO = 81920, C_XR = 167936, C_VP = C_XR + 7 * 4096, C_VX = C_XR + 8 * 4096, C_QX = C_VX + 4096, C_KX = C_QX + 4096,
              C_MEM = C_KX + 4096, C_OX = C_MEM + 9216, C_VM = C_OX + 3072, C_QM = C_VM + 1024, C_KM = C_QM + 1024, C_SC = C_KM + 1024, C_BAR = C_SC + 3840;
constexpr int CB_W = C_BAR, CB_W2 = C_BAR + 8, CB_SC = C_BAR + 16, CB_XD = C_BAR + 24, CB_VX = C_BAR + 32, CB_PRE = C_BAR + 40, CB_XM = C_BAR + 48, CB_OX = C_BAR + 56,
              CB_XF = C_BAR + 64, C_LAG = C_BAR + 96;
constexpr int C_SMEM = C_BAR + 128;
#define PROF(i)
#define PROFG(i)
#define PROFV(i, v)
static_assert(C_SMEM <= 232448, "chain shared memory");
__device__ __forceinline__ uint32_t umax3(uint32_t a, uint32_t b, uint32_t c) { return max(max(a, b), c); }
__device__ __forceinline__ void wait_until(uint32_t t) {
    asm volatile("{ .reg .pred p; .reg .s32 c;\nU_%=: mov.u32 c, %%clock; sub.s32 c, c, %0; setp.lt.s32 p, c, 0; @p bra.uni U_%=; }" :: "r"(t) : "memory");
}
__device__ __forceinline__ uint32_t gtime() { uint32_t c; asm volatile("mov.u32 %0, %%globaltimer_lo;" : "=r"(c)); return c; }
__device__ __forceinline__ uint32_t opaque(uint32_t v) { uint32_t r; asm volatile("shfl.sync.bfly.b32 %0, %1, 0, 31, -1;" : "=r"(r) : "r"(v)); return r; }
__device__ __forceinline__ uint32_t lds32(uint32_t a) { uint32_t v; asm volatile("ld.shared.u32 %0, [%1];" : "=r"(v) : "r"(a) : "memory"); return v; }
__device__ __forceinline__ float2 lds64f(uint32_t a) { float2 v; asm volatile("ld.shared.v2.f32 {%0,%1}, [%2];" : "=f"(v.x), "=f"(v.y) : "r"(a) : "memory"); return v; }
__device__ __forceinline__ float4 lds128f(uint32_t a) { float4 v; asm volatile("ld.shared.v4.f32 {%0,%1,%2,%3}, [%4];" : "=f"(v.x), "=f"(v.y), "=f"(v.z), "=f"(v.w) : "r"(a) : "memory"); return v; }
__device__ __forceinline__ void sts128f(uint32_t a, float x, float y, float z, float w) { asm volatile("st.shared.v4.f32 [%0], {%1,%2,%3,%4};" :: "r"(a), "f"(x), "f"(y), "f"(z), "f"(w) : "memory"); }
__device__ __forceinline__ void lds64(uint32_t (&v)[2], uint32_t a) { asm volatile("ld.shared.v2.u32 {%0,%1}, [%2];" : "=r"(v[0]), "=r"(v[1]) : "r"(a) : "memory"); }
__device__ __forceinline__ void mma16q(float (&d)[4], const uint32_t (&a)[4], uint32_t b0, uint32_t b1) { mma16(d, a[0], a[1], a[2], a[3], b0, b1); }
__device__ __forceinline__ uint32_t f16_to_bf16(uint32_t v) {
    float lo, hi; asm("{ .reg .f16 l, h; mov.b32 {l, h}, %2; cvt.f32.f16 %0, l; cvt.f32.f16 %1, h; }" : "=f"(lo), "=f"(hi) : "r"(v));
    return pack2(lo, hi);
}
__device__ __forceinline__ uint32_t pack2h(float lo, float hi) { uint32_t r; asm("cvt.rn.f16x2.f32 %0, %1, %2;" : "=r"(r) : "f"(hi), "f"(lo)); return r; }
#define SPLIT 1
__device__ __forceinline__ void cut(uint32_t never, int n) {
    asm volatile("{ .reg .pred p; setp.ne.u32 p, %0, %1; @p bra.uni C_%=; trap; C_%=: }" :: "r"(never), "r"(n) : "memory");
}
__device__ __forceinline__ void pin(uint32_t never, uint32_t a, uint32_t b, uint32_t c, uint32_t d) {
    asm volatile("{ .reg .pred p; setp.eq.u32 p, %0, 0; @p st.shared.v4.u32 [%0], {%1,%2,%3,%4}; }" :: "r"(never), "r"(a), "r"(b), "r"(c), "r"(d) : "memory");
}
__device__ __forceinline__ void pin0(uint32_t never) {
    asm volatile("{ .reg .pred p; setp.eq.u32 p, %0, 0; @p st.shared.u32 [%0], 0; }" :: "r"(never) : "memory");
}
#define ELECTED(txt) "{ .reg .pred e; elect.sync _|e, -1; @e " txt " }"
__device__ __forceinline__ void w_bulk_s2g(void* dst, uint32_t src, int bytes) {
    asm volatile(ELECTED("cp.async.bulk.global.shared::cta.bulk_group [%0], [%1], %2;") :: "l"(dst), "r"(src), "r"(bytes) : "memory");
}
__device__ __forceinline__ void w_bump(uint32_t* f) { asm volatile(ELECTED("red.relaxed.gpu.global.add.u32 [%0], 1;") :: "l"(f) : "memory"); }
__device__ __forceinline__ void w_expect(uint32_t bar, int bytes) { asm volatile(ELECTED("mbarrier.arrive.expect_tx.shared::cta.b64 _, [%0], %1;") :: "r"(bar), "r"(bytes) : "memory"); }
__device__ __forceinline__ void w_flag_wait(const uint32_t* f, uint32_t target) {
    asm volatile("{ .reg .pred p; .reg .u32 n, v; mov.u32 n, 0;\n"
                 "F_%=: ld.relaxed.gpu.global.u32 v, [%0]; setp.ge.u32 p, v, %1; vote.sync.all.pred p, p, -1; @p bra.uni G_%=;\n"
                 "add.u32 n, n, 1; setp.lt.u32 p, n, 0x800000; @p bra.uni F_%=;\ntrap;\nG_%=: }" :: "l"(f), "r"(target) : "memory");
}
#define BULK_COMMIT()    asm volatile("cp.async.bulk.commit_group;" ::: "memory")
#define BULK_WAIT()      asm volatile("cp.async.bulk.wait_group 0;" ::: "memory")
#define BULK_WAIT_READ() asm volatile("cp.async.bulk.wait_group.read 0;" ::: "memory")
#define PROXY_FENCE()    asm volatile("fence.proxy.async.shared::cta;" ::: "memory")
__device__ __forceinline__ void score_tile(const uint32_t (&qa)[2][4], const uint32_t (&kb)[2][4], bool odd, float (&x)[4]) {
    float sc[2][4] = {{0, 0, 0, 0}, {0, 0, 0, 0}};
#pragma unroll
    for (int k = 0; k < 4; k++) mma16q(sc[k & 1], qa[k >> 1], kb[k >> 1][2 * (k & 1)], kb[k >> 1][2 * (k & 1) + 1]);
    float a = sc[0][0] + sc[1][2], b = sc[0][1] + sc[1][3];
    float c = __shfl_xor_sync(0xffffffffu, a, 1), d = __shfl_xor_sync(0xffffffffu, b, 1);
    x[0] = odd ? c : a; x[1] = odd ? d : b; x[2] = odd ? a : c; x[3] = odd ? b : d;
}
__device__ __forceinline__ void send_piece(const float (&x)[4], uint32_t rdst, uint32_t rbar, uint32_t ldst) {
    asm volatile("st.async.shared::cluster.mbarrier::complete_tx::bytes.v4.f32 [%0], {%1,%2,%3,%4}, [%5];"
        :: "r"(rdst), "f"(x[0]), "f"(x[1]), "f"(x[2]), "f"(x[3]), "r"(rbar) : "memory");
    sts128f(ldst, x[0], x[1], x[2], x[3]);
}

__device__ __forceinline__ void seg_done(int n, int head) {
    w_bump(&g_flags.seg[n * 32 + head]);
    if ((n & 3) == 3) w_bump(&g_flags.qk[n >> 2]);
}
__device__ __forceinline__ void x_part(const uint32_t (&wa)[40][4], uint32_t sm, int n, int wg, int w, uint32_t ln, int head) {
    const int s = n - 1; (void)s;
    float acc[16]; uint32_t giv[8];
#pragma unroll
    for (int i = 0; i < 16; i++) acc[i] = 0.f;
    const uint32_t x0 = (uint32_t)mkdesc(SM_BASE + C_XR + wg * 4096, 16, 1024) + ln, xl[2] = {__shfl_sync(0xffffffffu, x0, 0), __shfl_sync(0xffffffffu, x0, 1)};
    auto chunk = [&](int a0, int i, int first) {
#pragma unroll
        for (int ks = 0; ks < 4; ks++)
            wgmma_rs_n32(acc, wa[a0 + 4 * i + ks], (mkdesc(0, 0, 1024) | (uint32_t)(xl[!a0] + ((((i ? (i - 1) * 8192 : C_MEM - C_XR) + ks * 32) >> 4) - !a0))), !(first && ks == 0));
    };
    mbar_wait(sm + CB_XF, n & 1);
    if (n) bar_sync(5, 384);
    if (wg == 0 && w == 0) PROF(12);
    WG_FENCE();
    chunk(20, 1, 1); chunk(20, 2, 0); chunk(20, 3, 0);
    mbar_wait(sm + CB_XM, n & 1);
    if (wg == 0 && w == 0) PROF(13);
    WG_FENCE();
    chunk(20, 0, 0);
    mbar_wait(sm + CB_XF + 8, n & 1);
    if (wg == 0 && w == 0) PROF(17);
    WG_FENCE();
    chunk(20, 4, 0);
    WG_COMMIT();
    if (n) {
        if (wg == 1 && w == 1) { BULK_WAIT(); seg_done(n - 1, head); }
        bar_sync(8, 256);
    }
    if (wg == 0 && w == 0) PROF(18);
    const uint32_t xb = sm + w * 512 + ln * 16, xw = xb + C_KX - wg * 4096, xr = xb + C_QX + wg * 4096;
    WG_WAIT(0);
#pragma unroll
    for (int i = 0; i < 8; i++) asm volatile("cvt.rn.bf16x2.f32 %0, %1, %2;" : "=r"(giv[i]) : "f"(acc[2 * i + 1]), "f"(acc[2 * i]));
#pragma unroll
    for (int p = 0; p < 2; p++) asm volatile("st.shared.v4.u32 [%0], {%1,%2,%3,%4};" :: "r"(xw + p * 2048), "r"(giv[4 * p]), "r"(giv[4 * p + 1]), "r"(giv[4 * p + 2]), "r"(giv[4 * p + 3]) : "memory");
    bar_arrive(12 + wg, 256);
    WG_FENCE();
    chunk(0, 0, 1);
    WG_COMMIT();
    chunk(0, 1, 0);
    if (XORD) chunk(0, 2, 0);
    bar_sync(13 - wg, 256);
#pragma unroll
    for (int p = 0; p < 2; p++) asm volatile("ld.shared.v4.u32 {%0,%1,%2,%3}, [%4];" : "=r"(giv[4 * p]), "=r"(giv[4 * p + 1]), "=r"(giv[4 * p + 2]), "=r"(giv[4 * p + 3]) : "r"(xr + p * 2048) : "memory");
    WG_COMMIT(); WG_WAIT(1); bar_arrive(9, 384);
    WG_FENCE();
    if (!XORD) chunk(0, 2, 0);
    chunk(0, 3, 0); chunk(0, 4, 0);
    WG_COMMIT();
    const uint32_t r = ln & 7, mi = ln >> 3, dst = sm + (wg == 0 ? C_QX : C_KX) + ((mi >> 1) * 8 + r) * 128 + (((2 * w + (mi & 1)) ^ r) << 4);
    pin(xb, giv[0], giv[4], dst, 0);
    bar_sync(10 + wg, 128);
    WG_WAIT(0);
    if (wg == 0 && w == 0) PROF(30);
    if (w == 0 && ln < 3) mbar_arrive_remote(mapa(sm + CB_XD, ln));
#pragma unroll
    for (int i = 0; i < 8; i++) { acc[2 * i] += lo_f(giv[i]); acc[2 * i + 1] += hi_f(giv[i]); }
#pragma unroll
    for (int p = 0; p < 2; p++)
        stsm4t(dst + p * 2048, pack2(acc[8 * p], acc[8 * p + 1]), pack2(acc[8 * p + 2], acc[8 * p + 3]), pack2(acc[8 * p + 4], acc[8 * p + 5]), pack2(acc[8 * p + 6], acc[8 * p + 7]));
}
__device__ __forceinline__ void x_fill(const ChainMaps& mp, uint32_t sm, int n, int j, int g) {
    mbar_expect(sm + CB_XF + 8 * g, g ? 8192 : 24576);
    const int c = g ? 6 : 2 * j;
    if (!g || j == 2)
        asm volatile("cp.async.bulk.tensor.3d.shared::cluster.global.mbarrier::complete_tx::bytes.multicast::cluster [%0], [%1, {0, %3, %4}], [%2], %5;"
            :: "r"(sm + C_XR + c * 4096), "l"((uint64_t)&mp.h2), "r"(sm + CB_XF + 8 * g), "r"(n * SEG), "r"(2 + c), "h"((uint16_t)7) : "memory");
}

__global__ void __cluster_dims__(3, 1, 1) __launch_bounds__(384, 1) k_chain(const __grid_constant__ ChainMaps mp, const __grid_constant__ ChainArgs ar) {
    const int D1 = ar.D1, DG = ar.DG;
    extern __shared__ __align__(1024) uint8_t smraw[];
    const uint32_t sm = SM_BASE + ((blockIdx.x % 3) << 24);
    if (smem_u32(smraw) != sm) __trap();
    uint32_t tid; asm volatile("mov.u32 %0, %%tid.x;" : "=r"(tid));
    const int warp = __shfl_sync(0xffffffffu, tid >> 5, 0), lane = tid & 31, wg = warp >> 2, w = warp & 3;
    const int blk = blockIdx.x, head = blk / 3, j = blk % 3;
    const int col0 = head * DH + j * 64;
    asm volatile("griddepcontrol.launch_dependents;");
#define PPROF(i)
    {
        const int mc0 = (blk >> 1) * 80 + (blk & 1) * 32, mcn = (blk & 1) ? 24 : 16;
        const int nrow = blk < 74 ? 2 : blk == 74 ? (warp < 8 ? 2 : 1) : 1;
        if (tid == 0) {
            mbar_init(sm + CB_PRE, 1);
            asm volatile("fence.mbarrier_init.release.cluster;" ::: "memory");
            const int n1 = blk < 74 ? 15360 : blk == 74 ? 10240 : 0;
            mbar_expect(sm + CB_PRE, 61440 + 1280 + 15360 + n1);
            bulk_g2s(sm + C_QM, ar.c, 1280, sm + CB_PRE);
#pragma unroll 1
            for (int c = 0; c < 4; c++) tma2d(sm + C_WO + 24576 + c * 15360, &mp.wmod, mc0, c * 160, sm + CB_PRE);
            bulk_g2s(sm + C_XR, ar.x + blk * 12 * DM, 15360, sm + CB_PRE);
            if (n1) bulk_g2s(sm + C_XR + 15360, ar.x + (1152 + blk * 12) * DM, n1, sm + CB_PRE);
        }
        if (tid == 32) {
#pragma unroll 1
            for (int c = 0; c < 11; c++) if (c != 5) mbar_init(sm + C_BAR + 8 * c, c == 2 ? 5 : c == 3 ? 6 : 1);
            asm volatile("fence.mbarrier_init.release.cluster;" ::: "memory");
            mbar_expect(sm + CB_SC, 2560); mbar_expect(sm + CB_OX, 2048);
        }
        if (warp == 2) {
            ((uint4*)g_acc)[blk * 32 + lane] = make_uint4(0, 0, 0, 0);
            if (blk < 12) ((uint4*)g_stamp)[blk * 32 + lane] = make_uint4(0, 0, 0, 0);
            __threadfence();
        }
        PPROF(8);
        asm volatile("barrier.cluster.arrive.release.aligned; barrier.cluster.wait.acquire.aligned;" ::: "memory");
        PPROF(9);
        mbar_wait(sm + CB_PRE, 0);
        PPROF(10);
        if (tid == 352) {
            const uint64_t ef = policy_stream();
            mbar_expect(sm + CB_W, 2 * 81920);
#pragma unroll 1
            for (int c = 0; c < 10; c++) tma2d_ef(sm + C_WV + c * 8192, &mp.wq, col0, c * 64, sm + CB_W, ef);
        }
        if (tid < 320) {
            const uint32_t cv = lds32(sm + C_QM + tid * 4);
            asm volatile("st.shared.v2.f32 [%0], {%1,%2};" :: "r"(sm + C_QX + tid * 8), "f"(bfr(__fdividef(lo_f(cv), 1.f + __expf(-lo_f(cv))))),
                         "f"(bfr(__fdividef(hi_f(cv), 1.f + __expf(-hi_f(cv))))) : "memory");
        }
        __syncthreads();
        {
            float a0 = 0, a1 = 0;
            const uint32_t k0 = (tid / 24) * 40, wa0 = sm + C_WO + 24576 + k0 * 96 + (tid % 24) * 4;
#pragma unroll 4
            for (int i = 0; i < 40; i++) {
                const float sc = __uint_as_float(lds32(sm + C_QX + (k0 + i) * 4));
                const uint32_t wv = lds32(wa0 + i * 96);
                a0 += sc * lo_f(wv); a1 += sc * hi_f(wv);
            }
            asm volatile("st.shared.v2.f32 [%0], {%1,%2};" :: "r"(sm + C_MEM + tid * 8), "f"(a0), "f"(a1) : "memory");
        }
        __syncthreads();
        PPROF(11);
        if (warp == 0) {
            float a0 = 0, a1 = 0;
            const int cp = lane < mcn ? lane : 0;
#pragma unroll 4
            for (int i = 0; i < 16; i++) { const float2 v = lds64f(sm + C_MEM + (i * 24 + cp) * 8); a0 += v.x; a1 += v.y; }
            uint32_t* dst = (uint32_t*)(g_mod + mc0) + cp;
            *dst = pack2(a0, a1);
            const uint32_t rb = ld_rlx(dst);
            PPROF(1);
            if (__all_sync(0xffffffffu, rb == pack2(a0, a1)) && tid == 0) bump(blk < 32 ? &g_flags.mod : &g_flags.h);
            if (tid == 0) flag_wait(&g_flags.mod, 32);
            PPROF(2);
        }
        __syncthreads();
        uint32_t sv[10], tv[10], bad = 0;
#pragma unroll
        for (int i = 0; i < 10; i++) { sv[i] = __ldcg((const uint32_t*)g_mod + DM / 2 + lane + 32 * i); tv[i] = __ldcg((const uint32_t*)g_mod + lane + 32 * i); }
#pragma unroll 1
        for (int q = 0; q < nrow; q++) {
            float xv[20], hv[20];
#pragma unroll
            for (int i = 0; i < 10; i++) { const uint32_t v = lds32(sm + C_XR + q * 15360 + warp * 1280 + lane * 4 + i * 128); xv[2 * i] = lo_f(v); xv[2 * i + 1] = hi_f(v); }
            ln_mod(xv, sv, tv, hv);
            uint32_t* dst = (uint32_t*)g_h + (q * 1152 + blk * 12 + warp) * (DM / 2) + lane;
#pragma unroll
            for (int i = 0; i < 10; i++) dst[32 * i] = pack2(hv[2 * i], hv[2 * i + 1]);
#pragma unroll
            for (int i = 0; i < 10; i++) bad |= ld_rlx(dst + 32 * i) ^ pack2(hv[2 * i], hv[2 * i + 1]);
        }
        if (__syncthreads_or(bad)) __trap();
        PPROF(3);
        if (tid == 0) {
            bump(&g_flags.h);
            flag_wait(&g_flags.h, 160);
            mbar_expect(sm + CB_XM, 8192); tma3d(sm + C_MEM, &mp.h2, 0, 0, sm + CB_XM);
            x_fill(mp, sm, 0, j, 0); x_fill(mp, sm, 0, j, 1);
            const uint64_t ef = policy_stream();
#pragma unroll 1
            for (int c = 0; c < 10; c++) tma2d_ef(sm + C_WO + c * 8192, &mp.wk, col0, c * 64, sm + CB_W, ef);
        }
        PPROF(4);
        __syncthreads();
        if (tid >= 64) {
#pragma unroll 1
            for (int i = tid - 64; i < 640 + 192 * 4; i += 320)
                asm volatile("prefetch.global.L2 [%0];" :: "l"(i < 640 ? ar.wv + (size_t)i * HD + col0 : ar.wo + (size_t)(head * DH + ((i - 640) >> 2)) * DM + j * 224 + min((i & 3) * 64, 639 - j * 224)));
        }
    }
    const int r = lane & 7, mi = lane >> 3;
    const uint32_t memrd = opaque(sm + C_MEM + lane * 16);
    constexpr float S_ACC = 64.f;
    if (wg < 2) {
        asm volatile("setmaxnreg.inc.sync.aligned.u32 %0;" :: "n"(REG_P));
        uint32_t wa[40][4];
        mbar_wait(sm + CB_W, 0);
#pragma unroll
        for (int ks = 0; ks < 40; ks++)
            ldsm4t(wa[ks], sm + ((wg == 0) == (ks < 20) ? C_WV : C_WO) + ((mi >> 1) * 8 + r) * 128 + (((2 * w + (mi & 1)) ^ r) << 4) + (ks % 20 / 4 * 8 + 4 * wg + (ks & 3)) * 2048);
        PPROF(5);
        bar_sync(1, 384);
        x_part(wa, sm, 0, wg, w, lane, head);
        PPROF(6);
        mbar_wait(sm + CB_W2, 0);
        PPROF(7);
        const uint32_t qst = opaque(sm + (wg == 0 ? C_QM : C_KM) + (2 * w + (mi & 1)) * 128 + r * 16);
        const uint32_t vrd = opaque(sm + C_WV + ((mi >> 1) * 8 + r) * 128 + (((2 * w + (mi & 1)) ^ r) << 4) + 4 * wg * 2048);
        const uint32_t mrd = opaque(memrd + wg * 1024);
        for (int s = 0; s < NSEG; s++) {
            const float un = s ? 1.f / S_ACC : 1.f;
            cut(s + ar.D2, 0);
            bar_sync(1, 384);
            if (warp == 0) { PROF(0); PROFG(24); }
            uint32_t b[3][4], a[5][4];
            float dv[2][4] = {{0, 0, 0, 0}, {0, 0, 0, 0}};
            auto fb = [&](int n) { return mrd + (n >> 1) * 2048 + (n & 1) * 512; };
            auto fa = [&](int k) { return vrd + (k >> 2) * 16384 + (k & 3) * 2048; };
            {
                float d[2][4] = {{0, 0, 0, 0}, {0, 0, 0, 0}}, g[2][4] = {{0, 0, 0, 0}, {0, 0, 0, 0}};
                ldsm4t(b[0], fb(0)); pin0(mrd); ldsm4t(b[1], fb(1)); pin0(mrd);
#pragma unroll
                for (int n = 0; n < 10; n++) {
                    const int c1 = (NCH == 2 || n >= 8);
                    if (n < 8) ldsm4t(b[(n + 2) % 3], fb(n + 2));
                    if (n + ALA >= 2 && n + ALA < 2 + VF) ldsm4t(a[2 + (n + ALA) % 3], fa(2 * (n + ALA)));
                    if (!VPOS && n >= 9 - VPRE && n < 9) ldsm4t(a[n - 9 + VPRE], fa(16 + n - 9 + VPRE));
                    mma16q(g[0], wa[20 + 2 * n], b[n % 3][0], b[n % 3][1]); mma16q(d[0], wa[2 * n], b[n % 3][0], b[n % 3][1]);
                    if (n >= 2 && n < 2 + VF) mma16q(dv[0], a[2 + n % 3], b[n % 3][0], b[n % 3][1]);
                    mma16q(g[c1], wa[21 + 2 * n], b[n % 3][2], b[n % 3][3]); mma16q(d[c1], wa[2 * n + 1], b[n % 3][2], b[n % 3][3]);
                    if (QCUT >> n & 1) cut(s + ar.D2, 1 + n);
                }
                const uint32_t xb = mrd - wg * 1024 - (C_MEM - C_VP) + w * 512;
                sts128f(xb + wg * 2048, g[0][0] + g[1][0], g[0][1] + g[1][1], g[0][2] + g[1][2], g[0][3] + g[1][3]);
                bar_sync(8, 256);
                const float4 z = lds128f(xb + (wg ^ 1) * 2048);
                if (VPOS) {
                    pin0(mrd);
#pragma unroll
                    for (int i = 0; i < VPRE; i++) ldsm4t(a[i], fa(16 + i));
                }
                stsm2t(qst, pack2((d[0][0] + d[1][0] + z.x) * un, (d[0][1] + d[1][1] + z.y) * un), pack2((d[0][2] + d[1][2] + z.z) * un, (d[0][3] + d[1][3] + z.w) * un));
            }
            bar_arrive(2, 384);
            if (w == 0) PROF(1 + wg);
            {
                if (warp == 3)
                    asm volatile(ELECTED("st.relaxed.gpu.global.u32 [%0], %1;") :: "l"(g_stamp + (s & 3) * 384 + (blk >> 3) * 32 + (blk & 7)), "r"((gtime() & ~31u) | ((s >> 2) + 1)) : "memory");
                PROXY_FENCE();
                bar_sync(7, 384);
                constexpr int NR = 16 - VF, NB = 4 + 12 - 2 * VF;
                auto kst = [&](int i) { return i < 4 ? 16 + i : i < NB ? i + 2 * VF : 5 + 2 * (i - NB); };
                const uint32_t mo = mrd + 256 + (mrd & 256);
                auto fc = [&](int p) { return 2 * p < NB ? fb(p + VF) : mo + (1 + (2 * p - NB) / 2) * 2048; };
#pragma unroll
                for (int i = VPRE; i < 4; i++) ldsm4t(a[i], fa(kst(i)));
#pragma unroll
                for (int i = 0; i < NR; i++) {
                    if (i + 4 < NR) ldsm4t(a[(i + 4) % 5], fa(kst(i + 4)));
                    if (!(i & 1) && i + 4 < NR) ldsm4t(b[(i / 2 + 1) % 3], fc(i / 2 + 2));
                    mma16q(dv[~i & 1], a[i % 5], b[(i / 2 + 2) % 3][2 * (i & 1)], b[(i / 2 + 2) % 3][2 * (i & 1) + 1]);
                }
                sts128f(mrd - (C_MEM - C_VP) + wg * 1024 + w * 512, dv[0][0] + dv[1][0], dv[0][1] + dv[1][1], dv[0][2] + dv[1][2], dv[0][3] + dv[1][3]);
            }
            if (warp == 0) bar_sync(4, 384);
            else bar_arrive(4, 384);
            if (warp == 0) {
                PROF(7);
                if (s + 1 < NSEG && elect()) {
                    mbar_expect(sm + CB_XM, 8192); tma3d(sm + C_MEM, &mp.h2, (s + 1) * SEG, 0, sm + CB_XM);
                }
            } else {
                if (wg == 1) {
                    if (w == 1) {
                        uint8_t* rec = g_att + (s * NH + head) * AT_REC;
                        w_bulk_s2g(rec + j * 8192, sm + C_QX, 8192); w_bulk_s2g(rec + AT_KM + j * 1024, sm + C_KM, 1024);
                        BULK_COMMIT();
                        if (s + 1 == NSEG) { BULK_WAIT(); seg_done(s, head); }
                    }
                    if (w == 2 && blk < 10 && s + 3 < NSEG)
                        asm volatile(ELECTED("cp.async.bulk.prefetch.L2.global [%0], 4096;") :: "l"((const uint8_t*)g_h + (s + 3) * (SEG * DM * 2) + blk * 4096) : "memory");
                } else if (w == 3) {
                    const uint32_t l = opaque(mrd) >> 4 & 31, tag = (s >> 2) + 1, now = gtime();
                    const uint32_t* sp = g_stamp + (s & 3) * 384 + (l >> 3) * 32 + (l & 7);
                    uint32_t t[3];
                    for (int n = 0;; n++) {
#pragma unroll
                        for (int i = 0; i < 3; i++) t[i] = ld_rlx(sp + i * 128);
                        if (!__any_sync(0xffffffffu, ((t[0] ^ tag) | (t[1] ^ tag) | (t[2] ^ tag)) & 31) || n > SPIN_LIMIT) break;
                    }
                    int all = -(1 << 30), own = all;
#pragma unroll
                    for (int i = 0; i < 3; i++) { const int d = t[i] - now; all = max(all, d); if ((i * 32 + l) / 3 == head) own = d; }
                    const int lag = min(__reduce_max_sync(0xffffffffu, all) - __reduce_max_sync(0xffffffffu, own), 8000);
                    PROFV(15, lag);
                    asm volatile("st.shared.u32 [%0], %1;" :: "r"(sm + C_LAG), "r"(D1 + ((lag * DG) >> 4)) : "memory");
                    if (s + 1 < NSEG) bar_arrive(6, 160);
                } else if (w == 2) {
                    if (s + 1 < NSEG) {
                        if ((s & 3) == 3) w_flag_wait(&g_flags.v[((s + 1) >> 2) * 32 + head], 2);
                        if (elect()) { mbar_expect(sm + CB_VX, 4096); bulk_g2s(sm + C_VX, g_att + ((s + 1) * NH + head) * AT_REC + AT_V + j * 4096, 4096, sm + CB_VX); }
                    }
                    if ((s & 3) == 1 && s + 3 < NSEG) asm volatile("prefetch.global.L2 [%0];" :: "l"(&g_flags.v[((s + 3) >> 2) * 32]));
                    if (s + 2 < NSEG && ((s & 3) != 2 || __all_sync(0xffffffffu, ld_rlx(&g_flags.v[((s + 2) >> 2) * 32 + head]) >= 2)))
                        asm volatile("prefetch.global.L2 [%0];" :: "l"(g_att + ((s + 2) * NH + head) * AT_REC + AT_V + j * 4096 + (opaque(mrd) << 3 & 0xf80)));
                } else if (s + 1 < NSEG) {
                    mbar_wait(sm + CB_OX, s & 1);
                    if (elect()) x_fill(mp, sm, s + 1, j, 1);
                }
            }
            if (s + 1 == NSEG) break;
            x_part(wa, sm, s + 1, wg, w, opaque(mrd) >> 4 & 31, head);
            if (warp == 0) PROF(11);
        }
    } else {
        asm volatile("setmaxnreg.dec.sync.aligned.u32 %0;" :: "n"(REG_L));
        bar_sync(1, 384);
        if (tid == 256) {
            mbar_expect(sm + CB_W2, 81920 + 3 * WO_BLK);
#pragma unroll 1
            for (int c = 0; c < 10; c++) tma2d(sm + C_WV + c * 8192, &mp.wv, col0, c * 64, sm + CB_W2);
#pragma unroll 1
            for (int c = 0; c < 3; c++) tma3d(sm + C_WO + c * WO_BLK, &mp.wo, head * DH + (j + c) % 3 * 64, 7 * j, sm + CB_W2);
        }
        bar_sync(9, 384);
#pragma unroll 1
        for (int c = tid - 256; c < DM; c += 128) {
            uint32_t u[8];
#pragma unroll
            for (int i = 0; i < 8; i++) u[i] = __ldg((const unsigned short*)ar.mem0 + i * DM + c);
            asm volatile("st.shared.v4.u32 [%0], {%1,%2,%3,%4};" :: "r"(sm + C_MEM + c * 16), "r"(u[0] | u[1] << 16), "r"(u[2] | u[3] << 16), "r"(u[4] | u[5] << 16), "r"(u[6] | u[7] << 16) : "memory");
        }
        __syncwarp();
        if (w == 1) {
            w_flag_wait(&g_flags.v[head], 2);
            if (elect()) { mbar_expect(sm + CB_VX, 4096); bulk_g2s(sm + C_VX, g_att + head * AT_REC + AT_V + j * 4096, 4096, sm + CB_VX); }
        }
        mbar_wait(sm + CB_W2, 0);
        const float scale = 0.07216878364870322f;
        uint32_t va[8][4], mr = memrd;
#pragma unroll
        for (int i = 0; i < 8; i++) ldsm4t(va[i], sm + C_WV + ((mi >> 1) * 8 + r) * 128 + (((2 * w + (mi & 1)) ^ r) << 4) + i * 2048);
        for (int s = 0; s < NSEG; s++) {
            const float un = s ? 1.f / S_ACC : 1.f;
            bar_sync(1, 384);
            if (w == 0) {
                mbar_wait(sm + CB_XD, s & 1);
                if (s + 1 < NSEG && elect()) x_fill(mp, sm, s + 1, j, 0);
            } else if (w == 1 && s > 0) { BULK_WAIT(); seg_done(s - 1, head); }
            const uint32_t l0 = mr >> 4 & 31, r0 = l0 & 7, m0 = l0 >> 3;
            uint32_t kb[2][4];
            {
                const uint32_t k7 = (4 * (w & 1) + (r0 >> 2) * 2 + (r0 & 1)) ^ (r0 << 1 & 4);
                const uint32_t kxrd = sm + C_KX + (16 * (w >> 1) + (r0 << 2 & 8) + k7) * 128 + ((m0 ^ k7) << 4);
                ldsm4(kb[0], kxrd); ldsm4(kb[1], kxrd ^ 64);
            }
            float vd[4];
            {
                uint32_t c[4][4];
#pragma unroll
                for (int i = 0; i < 4; i++) ldsm4t(c[i], mr + i * 512);
                float d[2][4] = {{0, 0, 0, 0}, {0, 0, 0, 0}};
#pragma unroll
                for (int i = 0; i < 8; i++) mma16q(d[i & 1], va[i], c[i >> 1][2 * (i & 1)], c[i >> 1][2 * (i & 1) + 1]);
#pragma unroll
                for (int i = 0; i < 4; i++) vd[i] = d[0][i] + d[1][i];
            }
            uint32_t zr = 0;
            if (w == 2)
                asm volatile("atom.relaxed.gpu.global.exch.b32 %0, [%1], 0;" : "=r"(zr)
                    : "l"(g_acc + ((s & 2) ^ 2) * (ACC_PAIR / 2) + (s & 1) * 512 + (blk >> 2) * 1024 + (blk & 3) * 128 + l0 * 4) : "memory");
            __syncwarp();
            const uint32_t sco = (w >> 1) * 512 + (l0 >> 2) * 64 + (w & 1) * 32 + ((l0 >> 1) & 1) * 16;
            const uint32_t qrd = sm + C_QM + ((m0 & 1) * 2 + (m0 >> 1)) * 128 + r0 * 16;
            const uint32_t scdst = sm + C_SC + j * 1280 + sco;
            const uint32_t rbase = mapa(sm, (j + 1 + (l0 & 1)) % 3) - sm;
            const uint32_t scm = 1024 + (l0 >> 1) * 16 - sco;
            const uint32_t v7 = r0 ^ (m0 << 2 & 4), vxrd = sm + C_VX + (8 * m0 + v7) * 128 + (((2 * w) ^ v7) << 4);
            mbar_wait(sm + CB_VX, s & 1);
            uint32_t vb[2][4];
            ldsm4t(vb[0], vxrd); ldsm4t(vb[1], vxrd ^ 16);
            const uint32_t word = sm + C_WO + (m0 & 1) * 4096 + ((m0 >> 1) * 8 + r0) * 64 + ((w ^ (r0 >> 1)) << 4);
            const uint32_t word6 = word + 6 * 4096 - (m0 & 1) * 3072;
            const uint32_t oxrd = sm + C_OX + l0 * 8;
            const uint32_t ord = sm + C_OX + (l0 >> 1) * 16 + w * 256 + (2 - (l0 & 1)) * 1024 + rbase;
            pin(mr, qrd, scdst, rbase, scm); pin(mr, scdst + scm + rbase, scdst + rbase, sm + CB_SC + rbase, scdst + scm); pin(mr, word, word6, oxrd, ord);
            pin(mr, __float_as_uint(vd[0]), __float_as_uint(vd[1]), __float_as_uint(vd[2]), __float_as_uint(vd[3]));
            bar_sync(2, 384);
            const bool odd = mr & 16;
            {
                uint32_t qa[2][4];
                ldsm4(qa[0], qrd); ldsm4(qa[1], qrd + 512);
                float x[4];
                if (w == 3) {
                    uint32_t km[2][4]; float y[4];
                    ldsm4(km[0], mr + (C_KM - C_MEM)); ldsm4(km[1], mr + (C_KM - C_MEM) + 512);
                    score_tile(qa, kb, odd, x); score_tile(qa, km, odd, y);
                    send_piece(x, scdst + rbase, sm + CB_SC + rbase, scdst); send_piece(y, scdst + scm + rbase, sm + CB_SC + rbase, scdst + scm);
                } else {
                    score_tile(qa, kb, odd, x);
                    send_piece(x, scdst + rbase, sm + CB_SC + rbase, scdst);
                }
            }
            bar_arrive(7, 384);
            if (elect()) mbar_arrive(sm + CB_SC);
            if (w == 0) PROF(4);
            const uint32_t vp = mr - (C_MEM - C_VP) + w * 512, vmst = mr + (C_VM - C_MEM) + w * 256;
            if (s + 1 == NSEG) {
                mbar_wait(sm + CB_SC, s & 1);
                bar_sync(4, 384);
                const float4 y0 = lds128f(vp), y1 = lds128f(vp + 2048);
                stsm2t(vmst, pack2((vd[0] + y0.x + y1.x) * un, (vd[1] + y0.y + y1.y) * un), pack2((vd[2] + y0.z + y1.z) * un, (vd[3] + y0.w + y1.w) * un));
                PROXY_FENCE();
                bar_sync(3, 128);
                if (w == 1) {
                    w_bulk_s2g(g_att + (s * NH + head) * AT_REC + AT_VM + j * 1024, sm + C_VM, 1024);
                    BULK_COMMIT(); BULK_WAIT(); seg_done(s, head);
                }
                __syncwarp();
                break;
            }
            pin(mr, vp, vmst, oxrd + w * 256, sm + CB_OX + rbase);
            cut(s + ar.D2, 0);
            mbar_wait(sm + CB_SC, s & 1);
            if (w == 0) PROF(8);
            float sv[10];
            {
                const uint32_t scrd = mr + (C_SC - C_MEM);
                float4 x[3], y[3]; float2 z[3];
#pragma unroll
                for (int p = 0; p < 3; p++) { x[p] = lds128f(scrd + p * 1280); y[p] = lds128f(scrd + p * 1280 + 512); z[p] = lds64f(oxrd + (C_SC - C_OX) + p * 1280 + 1024); }
                sv[0] = (x[0].x + x[1].x) + x[2].x; sv[1] = (x[0].y + x[1].y) + x[2].y; sv[2] = (x[0].z + x[1].z) + x[2].z; sv[3] = (x[0].w + x[1].w) + x[2].w;
                sv[4] = (y[0].x + y[1].x) + y[2].x; sv[5] = (y[0].y + y[1].y) + y[2].y; sv[6] = (y[0].z + y[1].z) + y[2].z; sv[7] = (y[0].w + y[1].w) + y[2].w;
                sv[8] = (z[0].x + z[1].x) + z[2].x; sv[9] = (z[0].y + z[1].y) + z[2].y;
            }
            float mx = fmaxf(fmaxf(fmaxf(sv[0], sv[1]), fmaxf(sv[2], sv[3])), fmaxf(fmaxf(fmaxf(sv[4], sv[5]), fmaxf(sv[6], sv[7])), fmaxf(sv[8], sv[9])));
            uint32_t a[NRING][4];
            auto frag = [&](int i) { const int p = i / 7, u = i % 7, o = (p >> 1) * WO_BLK + (p & 1) * 2048;
                                     return u == 3 ? word6 + o : word + o + (u > 3 ? 1024 + (u - 4) * 8192 : u * 8192); };
            mx = fmaxf(fmaxf(mx, __shfl_xor_sync(0xffffffffu, mx, 1)), fmaxf(__shfl_xor_sync(0xffffffffu, mx, 2), __shfl_xor_sync(0xffffffffu, mx, 3)));
            pin(mr, __float_as_uint(mx), 0, 0, 0);
            bar_sync(4, 384);
            {
                const float4 y0 = lds128f(vp), y1 = lds128f(vp + 2048);
                pin0(mr);
#pragma unroll
                for (int i = 0; i < NPRE; i++) ldsm4t(a[i], frag(i));
                pin0(mr);
                const float sl2e = scale * 1.4426950408889634f, mxl = mx * sl2e;
#pragma unroll
                for (int i = 9; i >= 0; i--) asm volatile("ex2.approx.ftz.f32 %0, %1;" : "=f"(sv[i]) : "f"(fmaf(sv[i], sl2e, -mxl)));
                const uint32_t pq[4] = {pack2(sv[0], sv[1]), pack2(sv[4], sv[5]), pack2(sv[2], sv[3]), pack2(sv[6], sv[7])}, pm = pack2(sv[8], sv[9]);
                if (w == 0) PROF(6);
                float o[2][4] = {{0, 0, 0, 0}, {0, 0, 0, 0}}, o2[2][4] = {{0, 0, 0, 0}, {0, 0, 0, 0}}, sx[4] = {0, 0, 0, 0};
                const uint32_t vm0 = pack2((vd[0] + y0.x + y1.x) * un, (vd[1] + y0.y + y1.y) * un), vm1 = pack2((vd[2] + y0.z + y1.z) * un, (vd[3] + y0.w + y1.w) * un);
                mma8(sx, pm, 0, 0x3f803f80u); mma8(o[0], pm, 0, vm0); mma8(o[1], pm, 0, vm1);
                mma16q(sx, pq, 0x3f803f80u, 0x3f803f80u);
#pragma unroll
                for (int u = 0; u < 2; u++) { mma16q(o[u], pq, vb[u][0], vb[u][1]); mma16q(o2[u], pq, vb[u][2], vb[u][3]); }
                float inv; asm("rcp.approx.ftz.f32 %0, %1;" : "=f"(inv) : "f"((sx[0] + sx[2]) * (1.f / S_ACC)));
                const uint32_t f0 = pack2((o[0][0] + o2[0][2]) * inv, (o[0][1] + o2[0][3]) * inv), f1 = pack2((o[1][0] + o2[1][2]) * inv, (o[1][1] + o2[1][3]) * inv);
                const uint32_t c = __shfl_xor_sync(0xffffffffu, f0, 1), d = __shfl_xor_sync(0xffffffffu, f1, 1);
                asm volatile("st.shared.v2.u32 [%0], {%1,%2};" :: "r"(oxrd + w * 256), "r"(f0), "r"(f1) : "memory");
                asm volatile("st.async.shared::cluster.mbarrier::complete_tx::bytes.v4.b32 [%0], {%1,%2,%3,%4}, [%5];"
                    :: "r"(ord), "r"(odd ? c : f0), "r"(odd ? d : f1), "r"(odd ? f0 : c), "r"(odd ? f1 : d), "r"(sm + CB_OX + rbase) : "memory");
                stsm2t(vmst, vm0, vm1);
            }
            if (w == 0) PROF(10);
#pragma unroll
            for (int i = NPRE; i < NRING; i++) ldsm4t(a[i], frag(i));
            bar_sync(3, 128);
            float e[5][4];
#pragma unroll
            for (int q = 0; q < 5; q++) e[q][0] = e[q][1] = e[q][2] = e[q][3] = 0.f;
            constexpr int LAG = 2;
            uint8_t* pdst = g_acc + ((s & 2) * (ACC_PAIR / 2) + (s & 1) * 512 + w * 2048 + j * 8192 - C_MEM - sm + mr);
#pragma unroll
            for (int h = 0; h < 3; h++) {
                uint32_t ob[4][2];
                if (h == 1) {
#pragma unroll
                    for (int i = 14 - LAG; i < 14; i++) ldsm4t(a[i % NRING], frag(i + NRING));
                    pin(mr, zr, (uint32_t)(uint64_t)pdst, (uint32_t)((uint64_t)pdst >> 32), 0);
                    mbar_wait(sm + CB_OX, s & 1);
                    if (w == 0) PROF(9);
                }
#pragma unroll
                for (int k = 0; k < 4; k++) lds64(ob[k], oxrd + h * 1024 + k * 256);
#pragma unroll
                for (int i = 14 * h; i < 14 * h + 14; i++) {
                    const int u = i % 7, k = 2 * (i / 7 & 1);
                    if (u == 3) { mma16q(e[3], a[i % NRING], ob[k][0], ob[k][1]); mma16q(e[4], a[i % NRING], ob[k + 1][0], ob[k + 1][1]); }
                    else mma16q(e[u & 3], a[i % NRING], ob[k + (u >> 2)][0], ob[k + (u >> 2)][1]);
                    if (i == B5AT) { pin(mr, a[i % NRING][0], a[i % NRING][1], a[i % NRING][2], a[i % NRING][3]); bar_arrive(5, 384); }
                    if (i >= LAG && !(i >= 14 && i < 14 + LAG) && i - LAG + NRING < 42) ldsm4t(a[(i - LAG) % NRING], frag(i - LAG + NRING));
                }
            }
            {
                const uint32_t w6 = pack2h(e[3][0] + e[4][2], e[3][1] + e[4][3]), one = 0x3c003c00u;
                asm volatile("red.relaxed.gpu.global.add.noftz.v4.f16x2 [%0], {%1,%2,%3,%4};"
                    :: "l"(pdst), "r"(pack2h(e[0][0], e[0][1])), "r"(pack2h(e[0][2], e[0][3])), "r"(pack2h(e[1][0], e[1][1])), "r"(odd ? w6 : one) : "memory");
                asm volatile("red.relaxed.gpu.global.add.noftz.v4.f16x2 [%0], {%1,%2,%3,%4};"
                    :: "l"(pdst + 1024), "r"(pack2h(e[1][2], e[1][3])), "r"(pack2h(e[2][0], e[2][1])), "r"(pack2h(e[2][2], e[2][3])), "r"(odd ? one : w6) : "memory");
            }
            const uint32_t tw = clock();
            if (w == 0) { PROF(14); PROFG(25); }
            PROXY_FENCE();
            bar_sync(6, 160);
            mr = opaque(mr);
            const uint32_t ln = mr >> 4 & 31, due = tw + lds32(sm + C_LAG);
            const uint32_t vr = sm + C_WV + ((ln >> 4) * 8 + (ln & 7)) * 128 + (((2 * w + (ln >> 3 & 1)) ^ (ln & 7)) << 4);
            const uint32_t ms0 = sm + C_MEM + w * 128 + (ln & 7) * 16 + (ln >> 3) * 512, ms1 = ms0 + (ln < 24 ? 2048 : 1536);
            if (w == 2) { w_expect(sm + CB_SC, 2560); w_expect(sm + CB_OX, 2048); }
            if (w == 1) { w_bulk_s2g(g_att + (s * NH + head) * AT_REC + AT_VM + j * 1024, sm + C_VM, 1024); BULK_COMMIT(); }
            const uint8_t* src = pdst - j * 8192;
            pin(mr, ms0, ms1, (uint32_t)(uint64_t)src, (uint32_t)((uint64_t)src >> 32));
            pin(mr, vr, due, 0, 0);
            cut(s + ar.D2, 1);
#pragma unroll
            for (int i = 0; i < 8; i++) ldsm4t(va[i], vr + i * 2048);
            wait_until(due);
            if (w == 0) { PROF(5); PROFG(26); }
            uint4 v[6];
            auto fetch = [&]() {
#pragma unroll
                for (int k = 0; k < 6; k++)
                    asm volatile("ld.relaxed.gpu.global.v4.u32 {%0,%1,%2,%3}, [%4];" : "=r"(v[k].x), "=r"(v[k].y), "=r"(v[k].z), "=r"(v[k].w) : "l"(src + (k >> 1) * 8192 + (k & 1) * 1024) : "memory");
            };
            fetch();
            bar_sync(9, 384);
#pragma unroll 1
            for (int n = 0;; n++) {
                uint32_t all = 0x50005000u;
#pragma unroll
                for (int k = 0; k < 3; k++) {
                    const uint4 x = v[2 * k], y = v[2 * k + 1];
                    all &= odd ? y.w : x.w;
                    stsm4(ms0 + k * 3584, f16_to_bf16(x.x), f16_to_bf16(x.y), f16_to_bf16(x.z), f16_to_bf16(y.x));
                    if (k < 2) { const uint32_t w6 = f16_to_bf16(odd ? x.w : y.w); stsm4(ms1 + k * 3584, f16_to_bf16(y.y), f16_to_bf16(y.z), w6, w6); }
                    else asm volatile("stmatrix.sync.aligned.m8n8.x2.shared.b16 [%0], {%1,%2};" :: "r"(ms1 + k * 3584), "r"(f16_to_bf16(y.y)), "r"(f16_to_bf16(y.z)) : "memory");
                }
                if (!__any_sync(0xffffffffu, all != 0x50005000u)) { PROFV(20 + w, n); break; }
                cut(n, SPIN_LIMIT);
                fetch();
            }
            if (w == 0) PROF(16);
        }
    }
}

struct SideMaps { CUtensorMap h, wv, ost, o, wo, slab3, slab2, lnp[3], wgate, wup, wdown; };
constexpr int SD_ST = 43008, SD_NST = 4, SD_EPI = SD_NST * SD_ST, SD_PAR = SD_EPI + 2 * 24576, SD_BAR = SD_PAR + 6400, SD_SMEM = SD_BAR + 256;
#define VLEAD 16
#define SEG_LAST 60
#define B_LATE 14
#define N_LIGHT 6
#define B_HELP 13
#define AUNR_ 2
constexpr int AUNR = AUNR_;
#define KSO 6
#define KSA 3
#define B_8 10
#define B_16 13
__device__ __forceinline__ int o_shift(int b) { return b >= B_16 ? 4 : b >= B_8 ? 3 : 2; }
__device__ __forceinline__ int o_split(int b) { return 1 << o_shift(b); }
__device__ __forceinline__ int next_item(int lane, bool late) {
    const int b0 = lane & 15, hi = lane >> 4;
    for (int n = 0;; n++) {
        const uint32_t w0 = ld_rlx(g_flags.qk + lane), w1 = ld_rlx(g_flags.at + lane), w2 = ld_rlx(&g_flags.c[0][0] + lane), w3 = ld_rlx(&g_flags.c[2][0] + lane), w4 = ld_rlx(&g_flags.seg[SEG_LAST * 32]);
        const uint32_t o01 = __ballot_sync(0xffffffffu, w2 < 32), o23 = __ballot_sync(0xffffffffu, b0 < B_LATE && w3 < 2u * o_split(b0));
        const uint32_t ra = __ballot_sync(0xffffffffu, w0 >= (hi ? 64u : 192u)), rb = __ballot_sync(0xffffffffu, w1 >= (hi ? 4u * o_split(b0) : 256u));
        const int bv = __ffs(o01 | 0x10000) - 1, ba = __ffs(o01 >> 16 | 0x10000) - 1, bo = __ffs(o23 | 0x10000) - 1, bl = __ffs(o23 >> 16 | 0x10000) - 1;
        if (bl == 16 && (late || ba == 16)) return -1;
        const int bc = __ffs(~ra | 0x10000) - 1;
        const bool last = ba == 15 && w4 >= 6;
        const bool r1 = (ra & ra >> 16) >> ba & 1, r2 = (rb & 0xffff) >> bo & 1, r3 = rb >> 16 >> bl & 1;
        const int kind = late || ba == 16 ? (bo < ba ? 2 : bl < bo ? 3 : -1) : last ? 1 :
                         blockIdx.x < N_LIGHT ? (r1 ? 1 : r3 ? 3 : bv < 16 ? 0 : -1) :
                         bv < 16 && (bv <= bc + VLEAD || !r2) ? 0 : r1 && ba >= B_HELP ? 1 : r2 ? 2 : r1 ? 1 : r3 ? 3 : bo < ba ? 2 : -1;
        if (kind < 0) { if (n > (1 << 20)) __trap(); __nanosleep(300); continue; }
        const int b = kind == 3 ? bl : kind == 2 ? bo : kind == 1 ? ba : bv;
        uint32_t i = 0;
        if (lane == 0) asm volatile("atom.relaxed.gpu.global.add.u32 %0, [%1], 1;" : "=r"(i) : "l"(&g_flags.c[kind][b]) : "memory");
        i = __shfl_sync(0xffffffffu, i, 0);
        if (i < (kind < 2 ? 32u : 2u * o_split(b))) return kind << 16 | b << 8 | i | ((kind == 1 ? r1 : kind == 2 ? r2 : r3) ? 128 : 0);
    }
}

template <int NP, int CH>
__device__ __forceinline__ void tile_out(const float (&acc)[8 * NP], uint32_t eb, uint32_t efull, uint32_t eempty, int& eph, int lane) {
    const int r = lane & 7, mi = lane >> 3, row = (mi & 1) * 8 + r;
    mbar_wait(eempty, eph); eph ^= 1;
#pragma unroll
    for (int p = 0; p < NP; p++) {
        const int oc = 2 * p + (mi >> 1);
        stsm4(eb + (oc >> 3) * CH + row * 128 + (((oc & 7) ^ r) << 4), pack2(acc[8 * p], acc[8 * p + 1]), pack2(acc[8 * p + 2], acc[8 * p + 3]),
              pack2(acc[8 * p + 4], acc[8 * p + 5]), pack2(acc[8 * p + 6], acc[8 * p + 7]));
    }
    asm volatile("fence.proxy.async.shared::cta;" ::: "memory");
    __syncwarp();
    if (lane == 0) mbar_arrive(efull);
}

template <int MT>
__device__ __forceinline__ void attn_tile(uint32_t base, uint32_t dst, uint32_t eempty, int eph, int lane) {
    constexpr int NK = MT ? 5 : 3;
    const int r = lane & 7, mi = lane >> 3, g = lane >> 2, t = lane & 3;
    float sc[NK][4];
#pragma unroll
    for (int n = 0; n < NK; n++) sc[n][0] = sc[n][1] = sc[n][2] = sc[n][3] = 0.f;
#pragma unroll AUNR
    for (int k2 = 0; k2 < 6; k2++) {
        const uint32_t cb = (k2 >> 1) * 8192, c0 = (k2 & 1) * 4;
        uint32_t a0[4], a1[4], bb[NK][4];
        ldsm4(a0, base + cb + (16 * MT + (mi & 1) * 8 + r) * 128 + (((c0 + (mi >> 1)) ^ r) << 4));
        ldsm4(a1, base + cb + (16 * MT + (mi & 1) * 8 + r) * 128 + (((c0 + 2 + (mi >> 1)) ^ r) << 4));
#pragma unroll
        for (int n = 0; n < NK; n++)
            ldsm4(bb[n], n < NK - 1 ? base + 4096 + cb + (8 * n + r) * 128 + (((c0 + mi) ^ r) << 4) : base + 36864 + k2 * 512 + lane * 16);
#pragma unroll
        for (int n = 0; n < NK; n++) mma16(sc[n], a0[0], a0[1], a0[2], a0[3], bb[n][0], bb[n][1]);
#pragma unroll
        for (int n = 0; n < NK; n++) mma16(sc[n], a1[0], a1[1], a1[2], a1[3], bb[n][2], bb[n][3]);
    }
    const float scale = 0.07216878364870322f, l2e = 1.4426950408889634f;
    float v[2][2 * NK], mx[2], sum[2];
#pragma unroll
    for (int hf = 0; hf < 2; hf++) {
        mx[hf] = -INFINITY;
#pragma unroll
        for (int n = 0; n < NK; n++) {
            uint32_t u = pack2(sc[n][2 * hf], sc[n][2 * hf + 1]);
            u = pack2(lo_f(u) * scale, hi_f(u) * scale);
            const int lim = 16 * MT + 8 * hf + g - 8 * n - 2 * t;
            v[hf][2 * n] = (n < NK - 1 && lim < 0) ? -1e9f : lo_f(u);
            v[hf][2 * n + 1] = (n < NK - 1 && lim < 1) ? -1e9f : hi_f(u);
            mx[hf] = fmaxf(mx[hf], fmaxf(v[hf][2 * n], v[hf][2 * n + 1]));
        }
    }
#pragma unroll
    for (int o = 1; o < 4; o <<= 1)
#pragma unroll
        for (int hf = 0; hf < 2; hf++) mx[hf] = fmaxf(mx[hf], __shfl_xor_sync(0xffffffffu, mx[hf], o));
#pragma unroll
    for (int hf = 0; hf < 2; hf++) {
        sum[hf] = 0;
#pragma unroll
        for (int q = 0; q < 2 * NK; q++) { asm("ex2.approx.ftz.f32 %0, %1;" : "=f"(v[hf][q]) : "f"((v[hf][q] - mx[hf]) * l2e)); sum[hf] += v[hf][q]; }
    }
#pragma unroll
    for (int o = 1; o < 4; o <<= 1)
#pragma unroll
        for (int hf = 0; hf < 2; hf++) sum[hf] += __shfl_xor_sync(0xffffffffu, sum[hf], o);
    uint32_t pa[NK][2];
#pragma unroll
    for (int hf = 0; hf < 2; hf++) {
        const float inv = __fdividef(1.f, sum[hf]);
#pragma unroll
        for (int n = 0; n < NK; n++) pa[n][hf] = pack2(v[hf][2 * n] * inv, v[hf][2 * n + 1] * inv);
    }
    mbar_wait(eempty, eph);
#pragma unroll AUNR
    for (int n4 = 0; n4 < 6; n4++) {
        const uint32_t cb = (n4 >> 1) * 4096, c0 = (n4 & 1) * 4;
        uint32_t bm[4], bb[2 + 2 * MT][4];
        ldsm4t(bm, base + AT_VM + n4 * 512 + lane * 16);
#pragma unroll
        for (int u = 0; u < 2 + 2 * MT; u++) ldsm4t(bb[u], base + AT_V + cb + (16 * (u >> 1) + 8 * (mi & 1) + r) * 128 + (((c0 + 2 * (u & 1) + (mi >> 1)) ^ r) << 4));
        float o[4][4];
#pragma unroll
        for (int u = 0; u < 4; u++) { o[u][0] = o[u][1] = o[u][2] = o[u][3] = 0.f; mma8(o[u], pa[NK - 1][0], pa[NK - 1][1], bm[u]); }
#pragma unroll
        for (int u = 0; u < 4 + 4 * MT; u++) mma16(o[u & 3], pa[u >> 2 << 1][0], pa[u >> 2 << 1][1], pa[(u >> 2 << 1) + 1][0], pa[(u >> 2 << 1) + 1][1], bb[u >> 1][2 * (u & 1)], bb[u >> 1][2 * (u & 1) + 1]);
#pragma unroll
        for (int p = 0; p < 2; p++)
            stsm4(dst + (n4 >> 1) * 2048 + ((mi & 1) * 8 + r) * 128 + (((c0 + 2 * p + (mi >> 1)) ^ r) << 4), pack2(o[2 * p][0], o[2 * p][1]), pack2(o[2 * p][2], o[2 * p][3]),
                  pack2(o[2 * p + 1][0], o[2 * p + 1][1]), pack2(o[2 * p + 1][2], o[2 * p + 1][3]));
    }
}

__device__ __forceinline__ void mod_tail(const SideMaps& mp, bf16* out, const uint32_t sm, const uint32_t bar, const int blk, const int tid) {
#define TPROF(i)
    const int warp = __shfl_sync(0xffffffffu, tid >> 5, 0), lane = tid & 31, r = lane & 7, mi = lane >> 3;
    constexpr int T_WG = 0, T_WU = 20480, T_WD = 40960, T_X = 65536, T_GU = 81920, T_RED = 106496, T_KEY = 122880;
    bar_sync(1, 256);
    if (tid == 32) {
        mbar_expect(bar, 40960 + (blk < 80 ? 24576 : 0));
#pragma unroll 1
        for (int c = 0; c < 8; c++) tma2d(sm + T_WG + c * 5120, c < 4 ? &mp.wgate : &mp.wup, blk * 16, (c & 3) * 160, bar);
#pragma unroll 1
        for (int c = 0; c < 6 && blk < 80; c++) tma2d(sm + T_WD + c * 4096, &mp.wdown, blk * 8, c * 256, bar);
    }
    if (warp == 0) w_flag_wait(&g_flags.ln[lane & 15], 128);
    bar_sync(1, 256);
    TPROF(1);
    {
        const uint4 u = __ldcg((const uint4*)g_r + tid);
        const uint32_t uu[4] = {u.x, u.y, u.z, u.w};
        uint32_t k[8];
#pragma unroll
        for (int i = 0; i < 8; i++) { const uint32_t v = i & 1 ? uu[i >> 1] & 0xffff0000u : uu[i >> 1] << 16; k[i] = (((int)v < 0 ? ~v : v | 0x80000000u) & 0xffff0000u) | (uint32_t)(S_TOK - 1 - (tid * 8 + i)); }
#pragma unroll 1
        for (int pass = 0; pass < 2; pass++) {
#pragma unroll 1
            for (int it = 0; it < 8; it++) {
                const uint32_t m = __reduce_max_sync(0xffffffffu, max(umax3(k[0], k[1], k[2]), max(umax3(k[3], k[4], k[5]), max(k[6], k[7]))));
#pragma unroll
                for (int i = 0; i < 8; i++) if (k[i] == m) k[i] = 0;
                asm volatile("st.shared.u32 [%0], %1;" :: "r"(sm + T_KEY + pass * 256 + (warp * 8 + it) * 4), "r"(m) : "memory");
            }
            if (pass) break;
            bar_sync(1, 256);
#pragma unroll
            for (int i = 2; i < 8; i++) k[i] = 0;
            k[0] = lds32(sm + T_KEY + lane * 4); k[1] = lds32(sm + T_KEY + 128 + lane * 4);
        }
        __syncwarp();
    }
    auto sel = [&](int i) { return S_TOK - 1 - (int)(lds32(sm + T_KEY + 256 + (warp * 8 + i) * 4) & 0xffffu); };
    TPROF(2);
    {
        const bf16* src = g_h2 + sel(r) * DM + warp * 80 + mi * 8;
        uint4 v[3];
#pragma unroll
        for (int i = 0; i < 3; i++) v[i] = __ldcg((const uint4*)(src + (i < 2 || mi < 2 ? i * 32 : 0)));
#pragma unroll
        for (int i = 0; i < 3; i++) asm volatile("st.shared.v4.u32 [%0], {%1,%2,%3,%4};" :: "r"(sm + T_X + warp * 1536 + i * 512 + lane * 16), "r"(v[i].x), "r"(v[i].y), "r"(v[i].z), "r"(v[i].w) : "memory");
    }
    const int trow = sel(lane >> 2), tcol = (blk < 80 ? blk : 0) * 8 + (lane & 3) * 2;
    const uint32_t fx1 = __ldcg((const uint32_t*)(g_x1 + trow * DM + tcol)), fh2 = __ldcg((const uint32_t*)(g_h2 + trow * DM + tcol)),
                   fgb = __ldcg((const uint32_t*)(g_mod + 5 * DM + tcol));
    const float fr = __uint_as_float((uint32_t)__ldcg((const unsigned short*)g_r + trow) << 16);
    mbar_wait(bar, 0);
    __syncwarp();
    TPROF(3);
    {
        float dg[4] = {0, 0, 0, 0}, du[4] = {0, 0, 0, 0};
        uint32_t b[3][4];
#pragma unroll
        for (int i = 0; i < 3; i++) ldsm4(b[i], sm + T_X + warp * 1536 + i * 512 + lane * 16);
#pragma unroll
        for (int h = 0; h < 5; h++) {
            uint32_t ag[4], au[4];
            const uint32_t o = ((warp * 5 + h) * 16 + (mi >> 1) * 8 + r) * 32 + (mi & 1) * 16;
            ldsm4t(ag, sm + T_WG + o); ldsm4t(au, sm + T_WU + o);
            mma16q(dg, ag, b[h >> 1][2 * (h & 1)], b[h >> 1][2 * (h & 1) + 1]); mma16q(du, au, b[h >> 1][2 * (h & 1)], b[h >> 1][2 * (h & 1) + 1]);
        }
        sts128f(sm + T_RED + warp * 1024 + lane * 16, dg[0], dg[1], dg[2], dg[3]); sts128f(sm + T_RED + warp * 1024 + 512 + lane * 16, du[0], du[1], du[2], du[3]);
    }
    bar_sync(1, 256);
    if (warp == 0) {
        float g4[4] = {0, 0, 0, 0}, u4[4] = {0, 0, 0, 0};
#pragma unroll
        for (int i = 0; i < 8; i++) {
            const float4 a = lds128f(sm + T_RED + i * 1024 + lane * 16), b = lds128f(sm + T_RED + i * 1024 + 512 + lane * 16);
            g4[0] += a.x; g4[1] += a.y; g4[2] += a.z; g4[3] += a.w; u4[0] += b.x; u4[1] += b.y; u4[2] += b.z; u4[3] += b.w;
        }
        float y[4];
#pragma unroll
        for (int i = 0; i < 4; i++) { const float gq = bfr(g4[i]); y[i] = bfr(__fdividef(gq, 1.f + __expf(-gq))) * bfr(u4[i]); }
        g_gu[blk * 64 + lane] = movm_t(pack2(y[0], y[1])); g_gu[blk * 64 + 32 + lane] = movm_t(pack2(y[2], y[3]));
        __syncwarp();
        TPROF(4);
        if (lane == 0) {
            flag_add(&g_flags.gu);
            if (blk < 80) {
                flag_wait(&g_flags.gu, 96);
                mbar_expect(bar + 8, 24576); bulk_g2s(sm + T_GU, g_gu, 24576, bar + 8);
            }
        }
        __syncwarp();
    }
    if (warp == 0 && blk >= 80) flags_release(lane);
    if (blk < 80) {
        mbar_wait(bar + 8, 0);
        TPROF(5);
        float d[2][4] = {{0, 0, 0, 0}, {0, 0, 0, 0}};
#pragma unroll
        for (int k2 = 0; k2 < 6; k2++) {
            uint32_t a[4], b[4];
            ldsm4t(b, sm + T_WD + (warp * 6 + k2) * 512 + lane * 16);
            ldsm4(a, sm + T_GU + ((warp * 6 + k2) * 4 + (mi & 1) * 2 + (mi >> 1)) * 128 + r * 16);
            mma16q(d[0], a, b[0], b[1]); mma16q(d[1], a, b[2], b[3]);
        }
        asm volatile("st.shared.v2.f32 [%0], {%1,%2};" :: "r"(sm + T_RED + warp * 256 + lane * 8), "f"(d[0][0] + d[1][2]), "f"(d[0][1] + d[1][3]) : "memory");
        bar_sync(1, 256);
        if (warp == 0) {
            float y0 = 0, y1 = 0;
#pragma unroll
            for (int i = 0; i < 8; i++) { const float2 a = lds64f(sm + T_RED + i * 256 + lane * 8); y0 += a.x; y1 += a.y; }
            const float sg = bfr(__fdividef(1.f, 1.f + __expf(-fr)));
            const float b0 = bfr(lo_f(fh2) + bfr(bfr(y0) * sg)), b1 = bfr(hi_f(fh2) + bfr(bfr(y1) * sg));
            *(uint32_t*)(out + trow * DM + tcol) = pack2(lo_f(fx1) + bfr(lo_f(fgb) * b0), hi_f(fx1) + bfr(hi_f(fgb) * b1));
        }
    }
    TPROF(6);
}

__global__ void __launch_bounds__(384, 1) k_side(const __grid_constant__ SideMaps mp, const bf16* __restrict__ x, const bf16* __restrict__ wr,
                                                 bf16* __restrict__ out) {
    extern __shared__ __align__(1024) uint8_t smraw[];
    const uint32_t sm = smem_u32(smraw);
    if (sm & 1023) __trap();
    const uint32_t FULL = sm + SD_BAR, EMPTY = FULL + 32, EFULL = FULL + 64, EEMPTY = FULL + 80, IFULL = FULL + 96, IEMPTY = FULL + 128, IQ = FULL + 160, SCHED = FULL + 176, PARAM = FULL + 184, TAILB = FULL + 192;
    const int tid = threadIdx.x, warp = __shfl_sync(0xffffffffu, tid >> 5, 0), lane = tid & 31;
    const uint64_t ef = policy_stream();
    if (tid == 0) {
        for (int i = 0; i < SD_NST; i++) { mbar_init(FULL + 8 * i, 1); mbar_init(EMPTY + 8 * i, 2); }
        for (int i = 0; i < 2; i++) { mbar_init(EFULL + 8 * i, 4); mbar_init(EEMPTY + 8 * i, 1); }
        for (int i = 0; i < 4; i++) { mbar_init(IFULL + 8 * i, 1); mbar_init(IEMPTY + 8 * i, 11); }
        mbar_init(SCHED, 1); mbar_init(PARAM, 1); mbar_init(TAILB, 1); mbar_init(TAILB + 8, 1);
        asm volatile("fence.mbarrier_init.release.cluster;" ::: "memory");
    }
    __syncthreads();
    if (warp >= 8) {
      asm volatile("setmaxnreg.dec.sync.aligned.u32 40;");
      if (warp == 8) {
        int st = 0, ph = 1;
        for (int q = 0;; q++) {
            mbar_wait(IFULL + 8 * (q & 3), (q >> 2) & 1);
            const int it = __shfl_sync(0xffffffffu, lds32(IQ + 4 * (q & 3)), 0);
            if (elect()) mbar_arrive(IEMPTY + 8 * (q & 3));
            if (it < 0) break;
            const int kind = it >> 16, b = (it >> 8) & 255, i = it & 127;
            const int nst = kind == 0 ? 10 : kind == 1 ? 4 : kind == 2 ? 192 >> o_shift(b) : 2;
            const int ksched = kind == 0 ? 4 : kind == 2 ? nst - KSO : kind == 1 && !(it & 128) ? KSA : 0;
            const bool look = !(it & 128);
            if (look && kind == 1) flag_wait(&g_flags.v[b * 32 + i], 2);
            if (look && kind == 3) flag_wait(&g_flags.o[b], 4 << o_shift(b));
            for (int kb = 0; kb < nst; kb++) {
                mbar_wait(EMPTY + 8 * st, ph);
                const uint32_t base = sm + st * SD_ST, fb = FULL + 8 * st;
                if (look && kind == 1) flag_wait(&g_flags.seg[(b * 4 + kb) * 32 + i], 6);
                if (kb == ksched && elect()) mbar_arrive(SCHED);
                if (kind == 0) {
                    if (q == 0 && kb == 0) {
                        if (elect()) {
#pragma unroll 1
                            for (int c = 0; c < SD_NST; c++) tma3d(sm + c * SD_ST + 16384, &mp.wv, c * 64, i * 3, FULL + 8 * c);
#pragma unroll 1
                            for (int c = SD_NST; c < 10; c++)
                                asm volatile("cp.async.bulk.prefetch.tensor.3d.L2.global [%0, {0, %1, %2}];" :: "l"((uint64_t)&mp.wv), "r"(c * 64), "r"(i * 3) : "memory");
                        }
                        flag_wait(&g_flags.h, 160);
                    }
                    if (elect()) {
                        mbar_expect(fb, 40960);
                        tma2d(base, &mp.h, kb * 64, b * 128, fb);
                        if (q || kb >= SD_NST) tma3d(base + 16384, &mp.wv, kb * 64, i * 3, fb);
                    }
                } else if (kind == 1) {
                    if (elect()) {
                        mbar_expect(fb, 43008);
                        asm volatile("cp.async.bulk.shared::cluster.global.mbarrier::complete_tx::bytes.L2::cache_hint [%0], [%1], %2, [%3], %4;"
                            :: "r"(base), "l"(g_att + ((b * 4 + kb) * NH + i) * AT_REC), "r"(AT_REC), "r"(fb), "l"(ef) : "memory");
                    }
                } else if (kind == 3) {
                    if (elect()) { mbar_expect(fb, 40960); tma3d_ef(base, &mp.lnp[o_shift(b) - 2], i * (160 >> o_shift(b)), b * KSPLIT + (kb << o_shift(b) >> 1), fb, ef); }
                } else {
                    const int k0 = ((i >> 1) * nst + kb) * 32;
                    if (elect()) { mbar_expect(fb, 28672); tma3d(base + 8192, &mp.wo, k0, (i & 1) * 5, fb); }
                    if (look && kb % 12 == 0) flag_wait(&g_flags.pair[b * 16 + k0 / 384], 16);
                    if (elect()) tma2d_ef(base, &mp.o, k0, b * 128, fb, ef);
                }
                __syncwarp();
                if (++st == SD_NST) { st = 0; ph ^= 1; }
            }
        }
      } else if (warp == 11) {
        const int lt = (int)blockIdx.x - N_SIDE;
        int own = lt >= 0 && lt < 32 * (16 - B_LATE) ? (15 - (lt >> 5)) << 8 | (lt & 31) : -1;
        for (int q = 0;; q++) {
            if (q) mbar_wait(SCHED, (q - 1) & 1);
            int it = own >= 0 && q == 0 ? 2 << 16 | own : own == -2 ? -1 : next_item(lane, lt >= 0);
            if (it < 0 && own >= 0) { it = 3 << 16 | own; own = -2; }

            if (lane == 0) {
                if (it >> 16 == 3) {
                    const int b = (it >> 8) & 255, nr = 64 >> o_shift(b);
                    asm volatile("cp.async.bulk.prefetch.L2.global [%0], %1;" :: "l"(x + (b * 128 + (it & 127) * nr) * DM), "r"(nr * DM * 2) : "memory");
                }
                mbar_wait(IEMPTY + 8 * (q & 3), ((q >> 2) & 1) ^ 1);
                asm volatile("st.shared.u32 [%0], %1;" :: "r"(IQ + 4 * (q & 3)), "r"(it) : "memory");
                mbar_arrive(IFULL + 8 * (q & 3));
            }
            if (q == 0) {
                flag_wait(&g_flags.h, 160);
                if (lane == 0) { mbar_expect(PARAM, 6400); bulk_g2s(sm + SD_PAR, g_mod + 2 * DM, 5120, PARAM); bulk_g2s(sm + SD_PAR + 5120, wr, 1280, PARAM); mbar_wait(PARAM, 0); }
            }
            __syncwarp();
            if (it < 0) break;
        }
        if (blockIdx.x >= N_SIDE && blockIdx.x < N_SIDE + 80) mbar_wait(TAILB + 8, 0);
        if (blockIdx.x < N_SIDE + 80) flags_release(lane);
      } else {
        if (lane == 0) {
            const int wg = warp - 9; int ph = 0;
            for (int q = 0;; q++) {
                mbar_wait(IFULL + 8 * (q & 3), (q >> 2) & 1);
                const int it = lds32(IQ + 4 * (q & 3));
                mbar_arrive(IEMPTY + 8 * (q & 3));
                if (it < 0) break;
                const int kind = it >> 16, b = (it >> 8) & 255, i = it & 127;
                if (kind == 1) continue;
                if (kind > 2) {
                    if (wg == 0) { mbar_wait(EFULL, ph); ph ^= 1; mbar_arrive(EEMPTY); flag_add(&g_flags.ln[b], 64 >> o_shift(b)); }
                    continue;
                }
                for (int rd = 0; rd < (kind == 2 ? 2 : 1); rd++) {
                    mbar_wait(EFULL + 8 * wg, ph); ph ^= 1;
                    const uint32_t src = sm + SD_EPI + wg * 24576;
                    if (kind == 2) tma3d_store(rd ? &mp.slab2 : &mp.slab3, (b * KSPLIT + (i >> 1)) * 128 + wg * 64, (i & 1) * 5 + rd * 3, src, ef, false);
                    else for (int c = 0; c < 2; c++) {
                        uint8_t* dst = g_att + ((b * 4 + wg * 2 + c) * NH + i) * AT_REC + AT_V;
                        if (b > 1) asm volatile("cp.async.bulk.global.shared::cta.bulk_group.L2::cache_hint [%0], [%1], 12288, %2;" :: "l"(dst), "r"(src + c * 12288), "l"(ef) : "memory");
                        else asm volatile("cp.async.bulk.global.shared::cta.bulk_group [%0], [%1], 12288;" :: "l"(dst), "r"(src + c * 12288) : "memory");
                    }
                    asm volatile("cp.async.bulk.commit_group;" ::: "memory");
                    asm volatile("cp.async.bulk.wait_group.read 0;" ::: "memory");
                    mbar_arrive(EEMPTY + 8 * wg);
                }
                asm volatile("cp.async.bulk.wait_group 0;" ::: "memory");
                bump(kind == 0 ? &g_flags.v[b * 32 + i] : &g_flags.o[b]);
                if (kind == 0) bump(&g_flags.vb[b]);
            }
        }
      }
    } else {
        asm volatile("setmaxnreg.inc.sync.aligned.u32 232;");
        const int wg = warp >> 2, w = warp & 3;
        int st = 0, ph = 0, eph = 1;
        bool att = false;
        const uint32_t eb = sm + SD_EPI + wg * 24576;
        for (int q = 0;; q++) {
            mbar_wait(IFULL + 8 * (q & 3), (q >> 2) & 1);
            const int itc = lds32(IQ + 4 * (q & 3));
            __syncwarp();
            if (lane == 0) mbar_arrive(IEMPTY + 8 * (q & 3));
            if (itc < 0) break;
            const int kind = itc >> 16, b = (itc >> 8) & 255, i = itc & 127;
            if (att && kind != 1) { bar_sync(2 + wg, 128); att = false; }
            if (kind == 0) {
                float acc[96];
#pragma unroll
                for (int n = 0; n < 96; n++) acc[n] = 0.f;
                int prev = -1;
                for (int kb = 0; kb < 10; kb++) {
                    mbar_wait(FULL + 8 * st, ph);
                    const uint32_t base = sm + st * SD_ST;
                    WG_FENCE();
#pragma unroll
                    for (int ks = 0; ks < 4; ks++)
                        wgmma_ss_n192_tb(acc, mkdesc(base + wg * 8192 + ks * 32, 16, 1024), mkdesc(base + 16384 + ks * 2048, 8192, 1024), (kb | ks) != 0);
                    WG_COMMIT();
                    if (prev >= 0) { WG_WAIT(1); if ((tid & 127) == 0) mbar_arrive(EMPTY + 8 * prev); }
                    prev = st;
                    if (++st == SD_NST) { st = 0; ph ^= 1; }
                }
                WG_WAIT(0);
                if ((tid & 127) == 0) mbar_arrive(EMPTY + 8 * prev);
                tile_out<12, 4096>(acc, eb + (w >> 1) * 12288 + (w & 1) * 2048, EFULL + 8 * wg, EEMPTY + 8 * wg, eph, lane);
            } else if (kind == 1) {
                const int seg = warp >> 1, mt = warp & 1;
                int sst = st + seg, sph = ph; if (sst >= SD_NST) { sst -= SD_NST; sph ^= 1; }
                ph ^= 1;
                mbar_wait(FULL + 8 * sst, sph);
                const uint32_t base = sm + sst * SD_ST;
                if (mt) attn_tile<1>(base, eb + w * 6144, EEMPTY + 8 * wg, eph, lane);
                else attn_tile<0>(base, eb + w * 6144, EEMPTY + 8 * wg, eph, lane);
                asm volatile("fence.proxy.async.shared::cta;" ::: "memory");
                __syncwarp();
                if (lane == 0) {
                    mbar_arrive(EMPTY + 8 * sst);
                    tma3d_store(&mp.ost, b * 128 + warp * 16, i * 3, eb + w * 6144, ef, false);
                    BULK_COMMIT(); BULK_WAIT();
                    bump(&g_flags.pair[b * 16 + (i >> 1)]); bump(&g_flags.at[b]);
                }
                __syncwarp();
                att = true;
            } else if (kind == 2) {
                float acc[96], acc2[64];
#pragma unroll
                for (int n = 0; n < 96; n++) acc[n] = 0.f;
#pragma unroll
                for (int n = 0; n < 64; n++) acc2[n] = 0.f;
                int prev = -1;
                for (int kb = 192 >> o_shift(b); kb > 0; kb--) {
                    const uint32_t base = sm + st * SD_ST;
                    mbar_wait(FULL + 8 * st, ph);
                    WG_FENCE();
#pragma unroll
                    for (int ks = 0; ks < 2; ks++) {
                        const uint64_t da = (mkdesc(base + wg * 4096 + ks * 32, 16, 512) & ~(3ull << 62)) | (2ull << 62);
                        wgmma_ss_n192_tb(acc, da, mkdesc(base + 8192 + ks * 2048, 4096, 1024), 1);
                        wgmma_ss_n128_tb(acc2, da, mkdesc(base + 8192 + 3 * 4096 + ks * 2048, 4096, 1024), 1);
                    }
                    WG_COMMIT();
                    if (prev >= 0) { WG_WAIT(1); if ((tid & 127) == 0) mbar_arrive(EMPTY + 8 * prev); }
                    prev = st;
                    if (++st == SD_NST) { st = 0; ph ^= 1; }
                }
                WG_WAIT(0);
                if ((tid & 127) == 0) mbar_arrive(EMPTY + 8 * prev);
                tile_out<12, 8192>(acc, eb + w * 2048, EFULL + 8 * wg, EEMPTY + 8 * wg, eph, lane);
                tile_out<8, 8192>(acc2, eb + w * 2048, EFULL + 8 * wg, EEMPTY + 8 * wg, eph, lane);
            } else {
                const int sh = o_shift(b), nr = 64 >> sh;
                int st1 = st + 1, ph1 = ph; if (st1 == SD_NST) { st1 = 0; ph1 ^= 1; }
                uint2 xin[2][5];
                uint32_t as[2][10];
#pragma unroll
                for (int q2 = 0; q2 < 10; q2++) xin[q2 & 1][q2 >> 1] = ld_ef(x + (b * 128 + i * nr + ((warp + 8 * (q2 & 1)) & (nr - 1))) * DM + lane * 4 + (q2 >> 1) * 128, ef);
                mbar_wait(PARAM, 0); mbar_wait(FULL + 8 * st, ph); mbar_wait(FULL + 8 * st1, ph1);
#pragma unroll
                for (int u2 = 0; u2 < 2; u2++) {
                    float a[20];
#pragma unroll
                    for (int q2 = 0; q2 < 20; q2++) a[q2] = 0.f;
                    if (warp + 8 * u2 < nr) {
#pragma unroll 2
                        for (int k = 0; k < (1 << sh); k++) {
                            const uint32_t ad = sm + ((k >> (sh - 1)) ? st1 : st) * SD_ST + (((k & ((1 << sh >> 1) - 1)) << (6 - sh)) + warp + 8 * u2) * 1280 + lane * 8;
                            uint32_t z[5][2];
#pragma unroll
                            for (int q2 = 0; q2 < 5; q2++) lds64(z[q2], ad + q2 * 256);
#pragma unroll
                            for (int q2 = 0; q2 < 5; q2++) { a[4 * q2] += lo_f(z[q2][0]); a[4 * q2 + 1] += hi_f(z[q2][0]); a[4 * q2 + 2] += lo_f(z[q2][1]); a[4 * q2 + 3] += hi_f(z[q2][1]); }
                        }
                    }
#pragma unroll
                    for (int q2 = 0; q2 < 10; q2++) as[u2][q2] = pack2(a[2 * q2], a[2 * q2 + 1]);
                }
                bar_sync(2 + wg, 128);
                if ((tid & 127) == 0) { mbar_arrive(EMPTY + 8 * st); mbar_arrive(EMPTY + 8 * st1); }
#pragma unroll 1
                for (int lrow = warp; lrow < nr; lrow += 8) {
                    const int row = b * 128 + i * nr + lrow;
                    const uint32_t pa = sm + SD_PAR + lane * 8;
                    float xv[20], hv[20];
                    uint32_t sv[10], tv[10];
#pragma unroll
                    for (int q2 = 0; q2 < 5; q2++) {
                        uint32_t ga[2], t[2], u[2];
                        lds64(ga, pa + q2 * 256); lds64(t, pa + 1280 + q2 * 256); lds64(u, pa + 2560 + q2 * 256);
#pragma unroll
                        for (int e = 0; e < 2; e++) {
                            const uint32_t xi = e ? xin[0][q2].y : xin[0][q2].x, ai = as[0][2 * q2 + e];
                            xv[4 * q2 + 2 * e] = bfr(lo_f(xi) + bfr(lo_f(ga[e]) * lo_f(ai))); xv[4 * q2 + 2 * e + 1] = bfr(hi_f(xi) + bfr(hi_f(ga[e]) * hi_f(ai)));
                            tv[2 * q2 + e] = t[e]; sv[2 * q2 + e] = u[e]; as[0][2 * q2 + e] = as[1][2 * q2 + e];
                        }
                        xin[0][q2] = xin[1][q2];
                    }
                    ln_mod(xv, sv, tv, hv);
                    float rs = 0;
#pragma unroll
                    for (int q2 = 0; q2 < 5; q2++) {
                        const int c = row * DM + lane * 4 + q2 * 128;
                        const float* xx = xv + 4 * q2; const float* hh = hv + 4 * q2;
                        uint32_t gb[2], wv[2];
                        lds64(gb, pa + 3840 + q2 * 256); lds64(wv, pa + 5120 + q2 * 256);
                        rs += (hh[0] * lo_f(wv[0]) + hh[1] * hi_f(wv[0])) + (hh[2] * lo_f(wv[1]) + hh[3] * hi_f(wv[1]));
                        st_ef(g_x1 + c, make_uint2(pack2(xx[0], xx[1]), pack2(xx[2], xx[3])), ef);
                        st_ef(g_h2 + c, make_uint2(pack2(hh[0], hh[1]), pack2(hh[2], hh[3])), ef);
                        st_ef(out + c, make_uint2(pack2(xx[0] + bfr(lo_f(gb[0]) * hh[0]), xx[1] + bfr(hi_f(gb[0]) * hh[1])),
                                                  pack2(xx[2] + bfr(lo_f(gb[1]) * hh[2]), xx[3] + bfr(hi_f(gb[1]) * hh[3]))), ef);
                    }
                    rs = warp_sum(rs);
                    if (lane == 0) g_r[row] = __float2bfloat16_rn(rs);
                }
                bar_sync(1, 256);
                if (wg == 0) { mbar_wait(EEMPTY, eph); eph ^= 1; if (lane == 0) mbar_arrive(EFULL); }
                st = st1 + 1; ph = ph1; if (st == SD_NST) { st = 0; ph ^= 1; }
            }
        }
        if (blockIdx.x >= N_SIDE) mod_tail(mp, out, sm, TAILB, blockIdx.x - N_SIDE, tid);
    }
    __syncwarp();
    asm volatile("griddepcontrol.wait;" ::: "memory");
}

#define P_D1 650
#define P_DL 700
#define P_DG 29
typedef CUresult (*EncodeFn)(CUtensorMap*, CUtensorMapDataType, cuuint32_t, void*, const cuuint64_t*, const cuuint64_t*, const cuuint32_t*, const cuuint32_t*,
                             CUtensorMapInterleave, CUtensorMapSwizzle, CUtensorMapL2promotion, CUtensorMapFloatOOBfill);
static EncodeFn s_encode = nullptr;
static void make_map(CUtensorMap* m, const void* p, int rows, int cols, int box_rows, int box_cols = 64) {
    cuuint64_t dims[2] = {(cuuint64_t)cols, (cuuint64_t)rows}, strides[1] = {(cuuint64_t)cols * 2};
    cuuint32_t box[2] = {(cuuint32_t)box_cols, (cuuint32_t)box_rows}, es[2] = {1, 1};
    s_encode(m, CU_TENSOR_MAP_DATA_TYPE_BFLOAT16, 2, (void*)p, dims, strides, box, es, CU_TENSOR_MAP_INTERLEAVE_NONE,
             box_cols == 64 ? CU_TENSOR_MAP_SWIZZLE_128B : box_cols == 32 ? CU_TENSOR_MAP_SWIZZLE_64B : CU_TENSOR_MAP_SWIZZLE_NONE, CU_TENSOR_MAP_L2_PROMOTION_L2_256B, CU_TENSOR_MAP_FLOAT_OOB_FILL_NONE);
}
static void make_map3(CUtensorMap* m, const void* p, int rows, int cols, int box_rows, int box_chunks, int cw = 64) {
    cuuint64_t dims[3] = {(cuuint64_t)cw, (cuuint64_t)rows, (cuuint64_t)(cols / cw)}, strides[2] = {(cuuint64_t)cols * 2, (cuuint64_t)cw * 2};
    cuuint32_t box[3] = {(cuuint32_t)cw, (cuuint32_t)box_rows, (cuuint32_t)box_chunks}, es[3] = {1, 1, 1};
    s_encode(m, CU_TENSOR_MAP_DATA_TYPE_BFLOAT16, 3, (void*)p, dims, strides, box, es, CU_TENSOR_MAP_INTERLEAVE_NONE,
             cw == 64 ? CU_TENSOR_MAP_SWIZZLE_128B : CU_TENSOR_MAP_SWIZZLE_64B, CU_TENSOR_MAP_L2_PROMOTION_L2_256B, CU_TENSOR_MAP_FLOAT_OOB_FILL_NONE);
}
template <typename T> static void* sym(T& s) { void* p = nullptr; cudaGetSymbolAddress(&p, s); return p; }

extern "C" void kernel_launch(void* const* d_in, const int* in_sizes, int n_in, void* d_out, int out_size) {
    const bf16 *x = (const bf16*)d_in[0], *mem0 = (const bf16*)d_in[1], *Wq = (const bf16*)d_in[2], *Wk = (const bf16*)d_in[3],
               *Wv = (const bf16*)d_in[4], *Wo = (const bf16*)d_in[5], *wr = (const bf16*)d_in[8], *wgate = (const bf16*)d_in[9],
               *wup = (const bf16*)d_in[10], *wdown = (const bf16*)d_in[11], *c = (const bf16*)d_in[12], *wmod = (const bf16*)d_in[13];
    bf16* out = (bf16*)d_out;
    if (!s_encode) {
        cudaDriverEntryPointQueryResult qr;
        cudaGetDriverEntryPoint("cuTensorMapEncodeTiled", (void**)&s_encode, cudaEnableDefault, &qr);
        cudaFuncSetAttribute(k_side, cudaFuncAttributeMaxDynamicSharedMemorySize, SD_SMEM);
        cudaFuncSetAttribute(k_chain, cudaFuncAttributeMaxDynamicSharedMemorySize, C_SMEM);
    }
    ChainMaps cm; SideMaps sd;
    make_map(&sd.h, sym(g_h), S_TOK, DM, 128); make_map3(&sd.wv, Wv, DM, HD, 64, 3);
    make_map3(&sd.ost, sym(g_o), S_TOK, HD, 16, 3); make_map(&sd.o, sym(g_o), S_TOK, HD, 128, 32); make_map3(&sd.wo, Wo, HD, DM, 32, 5);
    make_map3(&sd.slab3, sym(g_slab), 16 * KSPLIT * 128, DM, 64, 3); make_map3(&sd.slab2, sym(g_slab), 16 * KSPLIT * 128, DM, 64, 2);
    for (int i = 0; i < 3; i++) {
        cuuint64_t dims[3] = {256, 320, 16 * KSPLIT}, strides[2] = {512, 128 * DM * 2};
        cuuint32_t box[3] = {256, 40u >> i, 2u << i}, es[3] = {1, 1, 1};
        s_encode(&sd.lnp[i], CU_TENSOR_MAP_DATA_TYPE_BFLOAT16, 3, sym(g_slab), dims, strides, box, es, CU_TENSOR_MAP_INTERLEAVE_NONE,
                 CU_TENSOR_MAP_SWIZZLE_NONE, CU_TENSOR_MAP_L2_PROMOTION_L2_256B, CU_TENSOR_MAP_FLOAT_OOB_FILL_NONE);
    }
    make_map(&cm.wq, Wq, DM, HD, 64); make_map(&cm.wk, Wk, DM, HD, 64); make_map(&cm.wv, Wv, DM, HD, 64); make_map3(&cm.wo, Wo, HD, DM, 64, 7, 32);
    make_map3(&cm.h2, sym(g_h), S_TOK, DM, 32, 2);
    make_map(&sd.wgate, wgate, DM, FF, 160, 16); make_map(&sd.wup, wup, DM, FF, 160, 16); make_map(&sd.wdown, wdown, FF, DM, 256, 8);
    make_map(&cm.wmod, wmod, DM, 6 * DM, 160, 48);
    ChainArgs ar = {x, mem0, c, Wv, Wo, out, P_D1, P_DL, P_DG};
    k_chain<<<96, 384, C_SMEM>>>(cm, ar);
    cudaLaunchConfig_t cfg = {};
    cfg.gridDim = dim3(N_SIDE + 96); cfg.blockDim = dim3(384); cfg.dynamicSmemBytes = SD_SMEM; cfg.stream = cudaStreamPerThread;
    cudaLaunchAttribute at[1]; at[0].id = cudaLaunchAttributeProgrammaticStreamSerialization; at[0].val.programmaticStreamSerializationAllowed = 1;
    cfg.attrs = at; cfg.numAttrs = 1;
    cudaLaunchKernelEx(&cfg, k_side, sd, x, wr, out);
}
```

```cpp
#include <cuda_runtime.h>
#include <cuda_bf16.h>
#include <cuda.h>
#include <stdint.h>
#include <stdio.h>
#include <string.h>
#include <stdlib.h>

typedef __nv_bfloat16 bf16;
constexpr int S_TOK = 2048, DM = 640, NH = 32, DH = 192, HD = NH * DH, NSEG = 64, SEG = 32, FF = 1536;

__device__ bf16 g_mod[6 * DM];
__device__ bf16 g_h[S_TOK * DM];
constexpr int AT_REC = 43008, AT_V = 24576, AT_KM = 36864, AT_VM = 39936;
__device__ __align__(1024) uint8_t g_att[NSEG * NH * AT_REC];
__device__ bf16 g_o[S_TOK * HD];
__device__ bf16 g_A[S_TOK * DM];
__device__ bf16 g_x1[S_TOK * DM];
__device__ bf16 g_h2[S_TOK * DM];
__device__ __align__(128) uint32_t g_key[S_TOK];
__device__ int g_idx[8];
__device__ __align__(128) uint32_t g_gu[FF / 8 * 32];
constexpr int ACC_PAIR = 24 * 1024;
__device__ __align__(1024) uint8_t g_acc[2 * ACC_PAIR];
__device__ __align__(1024) uint32_t g_stamp[4 * 12 * 32];
constexpr int KSPLIT = 16;
__device__ bf16 g_slab[16 * KSPLIT * 128 * DM];
struct __align__(128) Flags {
    uint32_t qk[16], vb[16];
    uint32_t at[16], o[16];
    uint32_t c[4][16];
    uint32_t ln[16], pad0[16];
    uint32_t v[16 * 32];
    uint32_t seg[64 * 32];
    uint32_t pair[16 * 16];
    uint32_t mod, h, pad1[30], gu, pad2[31], done, pad3[31];
};
__device__ Flags g_flags;

__device__ __forceinline__ uint32_t smem_u32(const void* p) { return (uint32_t)__cvta_generic_to_shared(p); }
__device__ __forceinline__ uint32_t pack2(float lo, float hi) {
    uint32_t r; asm("cvt.rn.bf16x2.f32 %0, %1, %2;" : "=r"(r) : "f"(hi), "f"(lo)); return r;
}
__device__ __forceinline__ float bfr(float x) { return __uint_as_float(pack2(0.f, x)); }
__device__ __forceinline__ float inv_std(float var) {
    float s, r; asm("sqrt.approx.f32 %0, %1;" : "=f"(s) : "f"(bfr(bfr(var) + 1e-5f))); asm("rcp.approx.f32 %0, %1;" : "=f"(r) : "f"(bfr(s))); return r;
}
__device__ __forceinline__ float lo_f(uint32_t v) { return __uint_as_float(v << 16); }
__device__ __forceinline__ float hi_f(uint32_t v) { return __uint_as_float(v & 0xffff0000u); }
__device__ __forceinline__ void mbar_init(uint32_t bar, int cnt) { asm volatile("mbarrier.init.shared::cta.b64 [%0], %1;" :: "r"(bar), "r"(cnt) : "memory"); }
__device__ __forceinline__ void mbar_expect(uint32_t bar, int bytes) { asm volatile("mbarrier.arrive.expect_tx.shared::cta.b64 _, [%0], %1;" :: "r"(bar), "r"(bytes) : "memory"); }
__device__ __forceinline__ void mbar_arrive(uint32_t bar) { asm volatile("mbarrier.arrive.shared::cta.b64 _, [%0];" :: "r"(bar) : "memory"); }
__device__ __forceinline__ bool mbar_try(uint32_t bar, int par) {
    uint32_t ok; asm volatile("{ .reg .pred p; mbarrier.try_wait.parity.shared::cta.b64 p, [%1], %2; selp.u32 %0, 1, 0, p; }" : "=r"(ok) : "r"(bar), "r"(par) : "memory"); return ok;
}
__device__ __forceinline__ bool mbar_try_cluster(uint32_t bar, int par) {
    uint32_t ok; asm volatile("{ .reg .pred p; mbarrier.try_wait.parity.acquire.cluster.shared::cta.b64 p, [%1], %2; selp.u32 %0, 1, 0, p; }" : "=r"(ok) : "r"(bar), "r"(par) : "memory"); return ok;
}
__device__ __forceinline__ bool mbar_test(uint32_t bar, uint32_t par) {
    uint32_t ok; asm volatile("{ .reg .pred p; mbarrier.test_wait.parity.shared::cta.b64 p, [%1], %2; selp.u32 %0, 1, 0, p; }" : "=r"(ok) : "r"(bar), "r"(par) : "memory"); return ok;
}
constexpr int SPIN_LIMIT = 1 << 18;
__device__ __forceinline__ void mbar_wait(uint32_t bar, uint32_t par) {
    asm volatile("{ .reg .pred p, q; .reg .u32 n; mov.u32 n, 0;\n"
                 "W_%=: mbarrier.try_wait.parity.shared::cta.b64 p, [%0], %1;\n"
                 "@p bra.uni D_%=;\n"
                 "add.u32 n, n, 1; setp.lt.u32 q, n, 0x200000; @q bra.uni W_%=;\n"
                 "trap;\n"
                 "D_%=: }" :: "r"(bar), "r"(par) : "memory");
}
__device__ __forceinline__ void tma2d(uint32_t dst, const CUtensorMap* m, int c0, int c1, uint32_t bar) {
    asm volatile("cp.async.bulk.tensor.2d.shared::cluster.global.mbarrier::complete_tx::bytes [%0], [%1, {%3, %4}], [%2];"
        :: "r"(dst), "l"((uint64_t)m), "r"(bar), "r"(c0), "r"(c1) : "memory");
}
__device__ __forceinline__ void tma2d_mc(uint32_t dst, const CUtensorMap* m, int c0, int c1, uint32_t bar, uint16_t mask) {
    asm volatile("cp.async.bulk.tensor.2d.shared::cluster.global.mbarrier::complete_tx::bytes.multicast::cluster [%0], [%1, {%3, %4}], [%2], %5;"
        :: "r"(dst), "l"((uint64_t)m), "r"(bar), "r"(c0), "r"(c1), "h"(mask) : "memory");
}
__device__ __forceinline__ uint64_t policy_stream() { uint64_t p; asm("createpolicy.fractional.L2::evict_first.b64 %0, 1.0;" : "=l"(p)); return p; }
__device__ __forceinline__ void tma2d_ef(uint32_t dst, const CUtensorMap* m, int c0, int c1, uint32_t bar, uint64_t pol) {
    asm volatile("cp.async.bulk.tensor.2d.shared::cluster.global.mbarrier::complete_tx::bytes.L2::cache_hint [%0], [%1, {%3, %4}], [%2], %5;"
        :: "r"(dst), "l"((uint64_t)m), "r"(bar), "r"(c0), "r"(c1), "l"(pol) : "memory");
}
__device__ __forceinline__ void tma3d(uint32_t dst, const CUtensorMap* m, int row, int chunk, uint32_t bar) {
    asm volatile("cp.async.bulk.tensor.3d.shared::cluster.global.mbarrier::complete_tx::bytes [%0], [%1, {0, %3, %4}], [%2];"
        :: "r"(dst), "l"((uint64_t)m), "r"(bar), "r"(row), "r"(chunk) : "memory");
}
__device__ __forceinline__ void tma3d_ef(uint32_t dst, const CUtensorMap* m, int row, int chunk, uint32_t bar, uint64_t pol) {
    asm volatile("cp.async.bulk.tensor.3d.shared::cluster.global.mbarrier::complete_tx::bytes.L2::cache_hint [%0], [%1, {0, %3, %4}], [%2], %5;"
        :: "r"(dst), "l"((uint64_t)m), "r"(bar), "r"(row), "r"(chunk), "l"(pol) : "memory");
}
__device__ __forceinline__ void tma3d_store(const CUtensorMap* m, int row, int chunk, uint32_t src, uint64_t pol, bool hint) {
    if (hint) asm volatile("cp.async.bulk.tensor.3d.global.shared::cta.bulk_group.L2::cache_hint [%0, {0, %2, %3}], [%1], %4;"
        :: "l"((uint64_t)m), "r"(src), "r"(row), "r"(chunk), "l"(pol) : "memory");
    else asm volatile("cp.async.bulk.tensor.3d.global.shared::cta.bulk_group [%0, {0, %2, %3}], [%1];"
        :: "l"((uint64_t)m), "r"(src), "r"(row), "r"(chunk) : "memory");
}
__device__ __forceinline__ bool elect() { uint32_t p; asm volatile("{ .reg .pred e; elect.sync _|e, -1; selp.u32 %0, 1, 0, e; }" : "=r"(p)); return p; }
__device__ __forceinline__ uint2 ld_ef(const void* p, uint64_t pol) {
    uint2 v; asm volatile("ld.relaxed.gpu.global.L2::cache_hint.v2.u32 {%0,%1}, [%2], %3;" : "=r"(v.x), "=r"(v.y) : "l"(p), "l"(pol)); return v;
}
__device__ __forceinline__ void st_ef(void* p, uint2 v, uint64_t pol) {
    asm volatile("st.global.L2::cache_hint.v2.u32 [%0], {%1,%2}, %3;" :: "l"(p), "r"(v.x), "r"(v.y), "l"(pol) : "memory");
}
__device__ __forceinline__ void tma2d_prefetch(const CUtensorMap* m, int c0, int c1) {
    asm volatile("cp.async.bulk.prefetch.tensor.2d.L2.global [%0, {%1, %2}];" :: "l"((uint64_t)m), "r"(c0), "r"(c1) : "memory");
}
__device__ __forceinline__ void mbar_arrive_remote(uint32_t bar) { asm volatile("mbarrier.arrive.relaxed.cluster.shared::cluster.b64 _, [%0];" :: "r"(bar) : "memory"); }
__device__ __forceinline__ void tma2d_store(const CUtensorMap* m, int c0, int c1, uint32_t src) {
    asm volatile("cp.async.bulk.tensor.2d.global.shared::cta.bulk_group [%0, {%2, %3}], [%1];"
        :: "l"((uint64_t)m), "r"(src), "r"(c0), "r"(c1) : "memory");
}
__device__ __forceinline__ void bulk_g2s(uint32_t dst, const void* src, int bytes, uint32_t bar) {
    asm volatile("cp.async.bulk.shared::cluster.global.mbarrier::complete_tx::bytes [%0], [%1], %2, [%3];" :: "r"(dst), "l"(src), "r"(bytes), "r"(bar) : "memory");
}
__device__ __forceinline__ void ldsm4(uint32_t (&r)[4], uint32_t a) {
    asm volatile("ldmatrix.sync.aligned.m8n8.x4.shared.b16 {%0,%1,%2,%3}, [%4];" : "=r"(r[0]), "=r"(r[1]), "=r"(r[2]), "=r"(r[3]) : "r"(a) : "memory");
}
__device__ __forceinline__ void ldsm4t(uint32_t (&r)[4], uint32_t a) {
    asm volatile("ldmatrix.sync.aligned.m8n8.x4.trans.shared.b16 {%0,%1,%2,%3}, [%4];" : "=r"(r[0]), "=r"(r[1]), "=r"(r[2]), "=r"(r[3]) : "r"(a) : "memory");
}
__device__ __forceinline__ void stsm4(uint32_t a, uint32_t r0, uint32_t r1, uint32_t r2, uint32_t r3) {
    asm volatile("stmatrix.sync.aligned.m8n8.x4.shared.b16 [%0], {%1,%2,%3,%4};" :: "r"(a), "r"(r0), "r"(r1), "r"(r2), "r"(r3) : "memory");
}
__device__ __forceinline__ void stsm4t(uint32_t a, uint32_t r0, uint32_t r1, uint32_t r2, uint32_t r3) {
    asm volatile("stmatrix.sync.aligned.m8n8.x4.trans.shared.b16 [%0], {%1,%2,%3,%4};" :: "r"(a), "r"(r0), "r"(r1), "r"(r2), "r"(r3) : "memory");
}
__device__ __forceinline__ void stsm2t(uint32_t a, uint32_t r0, uint32_t r1) {
    asm volatile("stmatrix.sync.aligned.m8n8.x2.trans.shared.b16 [%0], {%1,%2};" :: "r"(a), "r"(r0), "r"(r1) : "memory");
}
__device__ __forceinline__ uint32_t movm_t(uint32_t v) { uint32_t r; asm volatile("movmatrix.sync.aligned.m8n8.trans.b16 %0, %1;" : "=r"(r) : "r"(v)); return r; }
__device__ __forceinline__ void mma16(float (&d)[4], uint32_t a0, uint32_t a1, uint32_t a2, uint32_t a3, uint32_t b0, uint32_t b1) {
    asm volatile("mma.sync.aligned.m16n8k16.row.col.f32.bf16.bf16.f32 {%0,%1,%2,%3}, {%4,%5,%6,%7}, {%8,%9}, {%0,%1,%2,%3};"
        : "+f"(d[0]), "+f"(d[1]), "+f"(d[2]), "+f"(d[3]) : "r"(a0), "r"(a1), "r"(a2), "r"(a3), "r"(b0), "r"(b1));
}
__device__ __forceinline__ void mma8(float (&d)[4], uint32_t a0, uint32_t a1, uint32_t b0) {
    asm volatile("mma.sync.aligned.m16n8k8.row.col.f32.bf16.bf16.f32 {%0,%1,%2,%3}, {%4,%5}, {%6}, {%0,%1,%2,%3};"
        : "+f"(d[0]), "+f"(d[1]), "+f"(d[2]), "+f"(d[3]) : "r"(a0), "r"(a1), "r"(b0));
}
__device__ __forceinline__ uint32_t mapa(uint32_t a, uint32_t r) { uint32_t o; asm volatile("mapa.shared::cluster.u32 %0, %1, %2;" : "=r"(o) : "r"(a), "r"(r)); return o; }
__device__ __forceinline__ void bar_sync(int id, int n) { asm volatile("bar.sync %0, %1;" :: "r"(id), "r"(n) : "memory"); }
__device__ __forceinline__ void bar_arrive(int id, int n) { asm volatile("bar.arrive %0, %1;" :: "r"(id), "r"(n) : "memory"); }
__device__ __forceinline__ uint64_t mkdesc(uint32_t addr, uint32_t lbo, uint32_t sbo) {
    return (uint64_t)((addr & 0x3FFFF) >> 4) | ((uint64_t)(lbo >> 4) << 16) | ((uint64_t)(sbo >> 4) << 32) | (1ull << 62);
}
#define WG_FENCE()  asm volatile("wgmma.fence.sync.aligned;" ::: "memory")
#define WG_COMMIT() asm volatile("wgmma.commit_group.sync.aligned;" ::: "memory")
#define WG_WAIT(n)  asm volatile("wgmma.wait_group.sync.aligned %0;" :: "n"(n) : "memory")

__device__ __forceinline__ void wgmma_ss_n192_tb(float (&d)[96], uint64_t a, uint64_t b, int acc) {
    asm volatile("{ .reg .pred p; setp.ne.b32 p, %98, 0;\n"
        "wgmma.mma_async.sync.aligned.m64n192k16.f32.bf16.bf16 {%0,%1,%2,%3,%4,%5,%6,%7,%8,%9,%10,%11,%12,%13,%14,%15,%16,%17,%18,%19,%20,%21,%22,%23,%24,%25,%26,%27,%28,%29,%30,%31,%32,%33,%34,%35,%36,%37,%38,%39,%40,%41,%42,%43,%44,%45,%46,%47,%48,%49,%50,%51,%52,%53,%54,%55,%56,%57,%58,%59,%60,%61,%62,%63,%64,%65,%66,%67,%68,%69,%70,%71,%72,%73,%74,%75,%76,%77,%78,%79,%80,%81,%82,%83,%84,%85,%86,%87,%88,%89,%90,%91,%92,%93,%94,%95}, %96, %97, p, 1, 1, 0, 1; }"
        : "+f"(d[0]), "+f"(d[1]), "+f"(d[2]), "+f"(d[3]), "+f"(d[4]), "+f"(d[5]), "+f"(d[6]), "+f"(d[7]), "+f"(d[8]), "+f"(d[9]), "+f"(d[10]), "+f"(d[11]), "+f"(d[12]), "+f"(d[13]), "+f"(d[14]), "+f"(d[15]), "+f"(d[16]), "+f"(d[17]), "+f"(d[18]), "+f"(d[19]), "+f"(d[20]), "+f"(d[21]), "+f"(d[22]), "+f"(d[23]), "+f"(d[24]), "+f"(d[25]), "+f"(d[26]), "+f"(d[27]), "+f"(d[28]), "+f"(d[29]), "+f"(d[30]), "+f"(d[31]), "+f"(d[32]), "+f"(d[33]), "+f"(d[34]), "+f"(d[35]), "+f"(d[36]), "+f"(d[37]), "+f"(d[38]), "+f"(d[39]), "+f"(d[40]), "+f"(d[41]), "+f"(d[42]), "+f"(d[43]), "+f"(d[44]), "+f"(d[45]), "+f"(d[46]), "+f"(d[47]), "+f"(d[48]), "+f"(d[49]), "+f"(d[50]), "+f"(d[51]), "+f"(d[52]), "+f"(d[53]), "+f"(d[54]), "+f"(d[55]), "+f"(d[56]), "+f"(d[57]), "+f"(d[58]), "+f"(d[59]), "+f"(d[60]), "+f"(d[61]), "+f"(d[62]), "+f"(d[63]), "+f"(d[64]), "+f"(d[65]), "+f"(d[66]), "+f"(d[67]), "+f"(d[68]), "+f"(d[69]), "+f"(d[70]), "+f"(d[71]), "+f"(d[72]), "+f"(d[73]), "+f"(d[74]), "+f"(d[75]), "+f"(d[76]), "+f"(d[77]), "+f"(d[78]), "+f"(d[79]), "+f"(d[80]), "+f"(d[81]), "+f"(d[82]), "+f"(d[83]), "+f"(d[84]), "+f"(d[85]), "+f"(d[86]), "+f"(d[87]), "+f"(d[88]), "+f"(d[89]), "+f"(d[90]), "+f"(d[91]), "+f"(d[92]), "+f"(d[93]), "+f"(d[94]), "+f"(d[95])
        : "l"(a), "l"(b), "r"(acc));
}

__device__ __forceinline__ void wgmma_ss_n128_tb(float (&d)[64], uint64_t a, uint64_t b, int acc) {
    asm volatile("{ .reg .pred p; setp.ne.b32 p, %66, 0;\n"
        "wgmma.mma_async.sync.aligned.m64n128k16.f32.bf16.bf16 {%0,%1,%2,%3,%4,%5,%6,%7,%8,%9,%10,%11,%12,%13,%14,%15,%16,%17,%18,%19,%20,%21,%22,%23,%24,%25,%26,%27,%28,%29,%30,%31,%32,%33,%34,%35,%36,%37,%38,%39,%40,%41,%42,%43,%44,%45,%46,%47,%48,%49,%50,%51,%52,%53,%54,%55,%56,%57,%58,%59,%60,%61,%62,%63}, %64, %65, p, 1, 1, 0, 1; }"
        : "+f"(d[0]), "+f"(d[1]), "+f"(d[2]), "+f"(d[3]), "+f"(d[4]), "+f"(d[5]), "+f"(d[6]), "+f"(d[7]), "+f"(d[8]), "+f"(d[9]), "+f"(d[10]), "+f"(d[11]), "+f"(d[12]), "+f"(d[13]), "+f"(d[14]), "+f"(d[15]), "+f"(d[16]), "+f"(d[17]), "+f"(d[18]), "+f"(d[19]), "+f"(d[20]), "+f"(d[21]), "+f"(d[22]), "+f"(d[23]), "+f"(d[24]), "+f"(d[25]), "+f"(d[26]), "+f"(d[27]), "+f"(d[28]), "+f"(d[29]), "+f"(d[30]), "+f"(d[31]), "+f"(d[32]), "+f"(d[33]), "+f"(d[34]), "+f"(d[35]), "+f"(d[36]), "+f"(d[37]), "+f"(d[38]), "+f"(d[39]), "+f"(d[40]), "+f"(d[41]), "+f"(d[42]), "+f"(d[43]), "+f"(d[44]), "+f"(d[45]), "+f"(d[46]), "+f"(d[47]), "+f"(d[48]), "+f"(d[49]), "+f"(d[50]), "+f"(d[51]), "+f"(d[52]), "+f"(d[53]), "+f"(d[54]), "+f"(d[55]), "+f"(d[56]), "+f"(d[57]), "+f"(d[58]), "+f"(d[59]), "+f"(d[60]), "+f"(d[61]), "+f"(d[62]), "+f"(d[63])
        : "l"(a), "l"(b), "r"(acc));
}

__device__ __forceinline__ void wgmma_rs_n32(float (&d)[16], const uint32_t (&a)[4], uint64_t b, int acc) {
    asm volatile("{ .reg .pred p; setp.ne.b32 p, %21, 0;\n"
        "wgmma.mma_async.sync.aligned.m64n32k16.f32.bf16.bf16 {%0,%1,%2,%3,%4,%5,%6,%7,%8,%9,%10,%11,%12,%13,%14,%15}, {%16,%17,%18,%19}, %20, p, 1, 1, 0; }"
        : "+f"(d[0]), "+f"(d[1]), "+f"(d[2]), "+f"(d[3]), "+f"(d[4]), "+f"(d[5]), "+f"(d[6]), "+f"(d[7]), "+f"(d[8]), "+f"(d[9]), "+f"(d[10]), "+f"(d[11]), "+f"(d[12]), "+f"(d[13]), "+f"(d[14]), "+f"(d[15])
        : "r"(a[0]), "r"(a[1]), "r"(a[2]), "r"(a[3]), "l"(b), "r"(acc));
}

__device__ __forceinline__ float warp_sum(float v) {
#pragma unroll
    for (int o = 16; o; o >>= 1) v += __shfl_xor_sync(0xffffffffu, v, o);
    return v;
}
__device__ __forceinline__ uint32_t add2(uint32_t a, uint32_t b) { uint32_t r; asm("add.rn.bf16x2 %0, %1, %2;" : "=r"(r) : "r"(a), "r"(b)); return r; }
__device__ __forceinline__ uint32_t mul2(uint32_t a, uint32_t b) { uint32_t r; asm("mul.rn.bf16x2 %0, %1, %2;" : "=r"(r) : "r"(a), "r"(b)); return r; }
__device__ __forceinline__ void ln_mod(const uint32_t (&xv)[10], const uint32_t (&sv)[10], const uint32_t (&tv)[10], uint32_t (&hv)[10]) {
    float s0 = 0, s1 = 0;
#pragma unroll
    for (int i = 0; i < 10; i++) { s0 += lo_f(xv[i]); s1 += hi_f(xv[i]); }
    const float mean = warp_sum(s0 + s1) * (1.f / DM);
    float q0 = 0, q1 = 0;
#pragma unroll
    for (int i = 0; i < 10; i++) { const float d0 = lo_f(xv[i]) - mean, d1 = hi_f(xv[i]) - mean; q0 += d0 * d0; q1 += d1 * d1; }
    const float inv = inv_std(warp_sum(q0 + q1) * (1.f / DM));
    const uint32_t mb = pack2(-mean, -mean);
#pragma unroll
    for (int i = 0; i < 10; i++) {
        const uint32_t d = add2(xv[i], mb);
        hv[i] = add2(mul2(pack2(lo_f(d) * inv, hi_f(d) * inv), add2(sv[i], 0x3f803f80u)), tv[i]);
    }
}
__device__ __forceinline__ uint32_t ld_rlx(const uint32_t* f) { uint32_t v; asm volatile("ld.relaxed.gpu.global.u32 %0, [%1];" : "=r"(v) : "l"(f) : "memory"); return v; }
__device__ __forceinline__ void bump(uint32_t* f) { asm volatile("red.relaxed.gpu.global.add.u32 [%0], 1;" :: "l"(f) : "memory"); }
__device__ __forceinline__ void flag_wait(const uint32_t* f, uint32_t target) {
    for (int n = 0;; n++) {
        uint32_t v; asm volatile("ld.relaxed.gpu.global.u32 %0, [%1];" : "=r"(v) : "l"(f) : "memory");
        if (v >= target) break;
        if (n > (1 << 23)) __trap();
    }
}
__device__ __forceinline__ void flag_add(uint32_t* f, uint32_t v = 1) { asm volatile("red.release.gpu.global.add.u32 [%0], %1;" :: "l"(f), "r"(v) : "memory"); }
constexpr int N_SIDE = 36;
__device__ __forceinline__ void flags_release(int lane) {
    uint32_t old = 0;
    if (lane == 0) asm volatile("atom.relaxed.gpu.global.add.u32 %0, [%1], 1;" : "=r"(old) : "l"(&g_flags.done) : "memory");
    if (__shfl_sync(0xffffffffu, old, 0) == 96 + N_SIDE - 1)
        for (int i = lane; i < (int)(sizeof(Flags) / 16); i += 32) ((uint4*)&g_flags)[i] = make_uint4(0, 0, 0, 0);
}

struct ChainMaps { CUtensorMap wq, wk, wv, wo, h2, wmod; };
struct ChainArgs { const bf16 *x, *mem0, *c, *wv, *wo; bf16* out; int D1, D2, DG; };
constexpr uint32_t SM_BASE = 1024;
#define NRING 11
#define FILL_AT 1
#define VF 6
#define VPRE 2
#define XORD 0
#define B5AT 41
#define QCUT 0x7f
#define NCH 2
#define ALA 1
#define VPOS 0
#define NPRE 9
#define REG_P 208
#define REG_L (504 - 2 * REG_P)
constexpr int WO_BLK = 7 * 4096;
constexpr int C_WV = 0, C_WO = 81920, C_XR = 167936, C_VP = C_XR + 7 * 4096, C_VX = C_XR + 8 * 4096, C_QX = C_VX + 4096, C_KX = C_QX + 4096,
              C_MEM = C_KX + 4096, C_OX = C_MEM + 9216, C_VM = C_OX + 3072, C_QM = C_VM + 1024, C_KM = C_QM + 1024, C_SC = C_KM + 1024, C_BAR = C_SC + 3840;
constexpr int CB_W = C_BAR, CB_W2 = C_BAR + 8, CB_SC = C_BAR + 16, CB_XD = C_BAR + 24, CB_VX = C_BAR + 32, CB_PRE = C_BAR + 40, CB_XM = C_BAR + 48, CB_OX = C_BAR + 56,
              CB_XF = C_BAR + 64, C_LAG = C_BAR + 96;
constexpr int C_SMEM = C_BAR + 128;
#define PROF(i)
#define PROFG(i)
#define PROFV(i, v)
static_assert(C_SMEM <= 232448, "chain shared memory");
__device__ __forceinline__ uint32_t umax3(uint32_t a, uint32_t b, uint32_t c) { return max(max(a, b), c); }
__device__ __forceinline__ void wait_until(uint32_t t) {
    asm volatile("{ .reg .pred p; .reg .s32 c;\nU_%=: mov.u32 c, %%clock; sub.s32 c, c, %0; setp.lt.s32 p, c, 0; @p bra.uni U_%=; }" :: "r"(t) : "memory");
}
__device__ __forceinline__ uint32_t gtime() { uint32_t c; asm volatile("mov.u32 %0, %%globaltimer_lo;" : "=r"(c)); return c; }
__device__ __forceinline__ uint32_t opaque(uint32_t v) { uint32_t r; asm volatile("shfl.sync.bfly.b32 %0, %1, 0, 31, -1;" : "=r"(r) : "r"(v)); return r; }
__device__ __forceinline__ uint32_t lds32(uint32_t a) { uint32_t v; asm volatile("ld.shared.u32 %0, [%1];" : "=r"(v) : "r"(a) : "memory"); return v; }
__device__ __forceinline__ float2 lds64f(uint32_t a) { float2 v; asm volatile("ld.shared.v2.f32 {%0,%1}, [%2];" : "=f"(v.x), "=f"(v.y) : "r"(a) : "memory"); return v; }
__device__ __forceinline__ float4 lds128f(uint32_t a) { float4 v; asm volatile("ld.shared.v4.f32 {%0,%1,%2,%3}, [%4];" : "=f"(v.x), "=f"(v.y), "=f"(v.z), "=f"(v.w) : "r"(a) : "memory"); return v; }
__device__ __forceinline__ void sts128f(uint32_t a, float x, float y, float z, float w) { asm volatile("st.shared.v4.f32 [%0], {%1,%2,%3,%4};" :: "r"(a), "f"(x), "f"(y), "f"(z), "f"(w) : "memory"); }
__device__ __forceinline__ void lds64(uint32_t (&v)[2], uint32_t a) { asm volatile("ld.shared.v2.u32 {%0,%1}, [%2];" : "=r"(v[0]), "=r"(v[1]) : "r"(a) : "memory"); }
__device__ __forceinline__ void mma16q(float (&d)[4], const uint32_t (&a)[4], uint32_t b0, uint32_t b1) { mma16(d, a[0], a[1], a[2], a[3], b0, b1); }
__device__ __forceinline__ uint32_t f16_to_bf16(uint32_t v) {
    float lo, hi; asm("{ .reg .f16 l, h; mov.b32 {l, h}, %2; cvt.f32.f16 %0, l; cvt.f32.f16 %1, h; }" : "=f"(lo), "=f"(hi) : "r"(v));
    return pack2(lo, hi);
}
__device__ __forceinline__ uint32_t pack2h(float lo, float hi) { uint32_t r; asm("cvt.rn.f16x2.f32 %0, %1, %2;" : "=r"(r) : "f"(hi), "f"(lo)); return r; }
#define SPLIT 1
__device__ __forceinline__ void cut(uint32_t never, int n) {
    asm volatile("{ .reg .pred p; setp.ne.u32 p, %0, %1; @p bra.uni C_%=; trap; C_%=: }" :: "r"(never), "r"(n) : "memory");
}
__device__ __forceinline__ void pin(uint32_t never, uint32_t a, uint32_t b, uint32_t c, uint32_t d) {
    asm volatile("{ .reg .pred p; setp.eq.u32 p, %0, 0; @p st.shared.v4.u32 [%0], {%1,%2,%3,%4}; }" :: "r"(never), "r"(a), "r"(b), "r"(c), "r"(d) : "memory");
}
__device__ __forceinline__ void pin0(uint32_t never) {
    asm volatile("{ .reg .pred p; setp.eq.u32 p, %0, 0; @p st.shared.u32 [%0], 0; }" :: "r"(never) : "memory");
}
#define ELECTED(txt) "{ .reg .pred e; elect.sync _|e, -1; @e " txt " }"
__device__ __forceinline__ void w_bulk_s2g(void* dst, uint32_t src, int bytes) {
    asm volatile(ELECTED("cp.async.bulk.global.shared::cta.bulk_group [%0], [%1], %2;") :: "l"(dst), "r"(src), "r"(bytes) : "memory");
}
__device__ __forceinline__ void w_bump(uint32_t* f) { asm volatile(ELECTED("red.relaxed.gpu.global.add.u32 [%0], 1;") :: "l"(f) : "memory"); }
__device__ __forceinline__ void w_expect(uint32_t bar, int bytes) { asm volatile(ELECTED("mbarrier.arrive.expect_tx.shared::cta.b64 _, [%0], %1;") :: "r"(bar), "r"(bytes) : "memory"); }
__device__ __forceinline__ void w_flag_wait(const uint32_t* f, uint32_t target) {
    asm volatile("{ .reg .pred p; .reg .u32 n, v; mov.u32 n, 0;\n"
                 "F_%=: ld.relaxed.gpu.global.u32 v, [%0]; setp.ge.u32 p, v, %1; vote.sync.all.pred p, p, -1; @p bra.uni G_%=;\n"
                 "add.u32 n, n, 1; setp.lt.u32 p, n, 0x800000; @p bra.uni F_%=;\ntrap;\nG_%=: }" :: "l"(f), "r"(target) : "memory");
}
#define BULK_COMMIT()    asm volatile("cp.async.bulk.commit_group;" ::: "memory")
#define BULK_WAIT()      asm volatile("cp.async.bulk.wait_group 0;" ::: "memory")
#define BULK_WAIT_READ() asm volatile("cp.async.bulk.wait_group.read 0;" ::: "memory")
#define PROXY_FENCE()    asm volatile("fence.proxy.async.shared::cta;" ::: "memory")
__device__ __forceinline__ void score_tile(const uint32_t (&qa)[2][4], const uint32_t (&kb)[2][4], bool odd, float (&x)[4]) {
    float sc[2][4] = {{0, 0, 0, 0}, {0, 0, 0, 0}};
#pragma unroll
    for (int k = 0; k < 4; k++) mma16q(sc[k & 1], qa[k >> 1], kb[k >> 1][2 * (k & 1)], kb[k >> 1][2 * (k & 1) + 1]);
    float a = sc[0][0] + sc[1][2], b = sc[0][1] + sc[1][3];
    float c = __shfl_xor_sync(0xffffffffu, a, 1), d = __shfl_xor_sync(0xffffffffu, b, 1);
    x[0] = odd ? c : a; x[1] = odd ? d : b; x[2] = odd ? a : c; x[3] = odd ? b : d;
}
__device__ __forceinline__ void send_piece(const float (&x)[4], uint32_t rdst, uint32_t rbar, uint32_t ldst) {
    asm volatile("st.async.shared::cluster.mbarrier::complete_tx::bytes.v4.f32 [%0], {%1,%2,%3,%4}, [%5];"
        :: "r"(rdst), "f"(x[0]), "f"(x[1]), "f"(x[2]), "f"(x[3]), "r"(rbar) : "memory");
    sts128f(ldst, x[0], x[1], x[2], x[3]);
}

__device__ __forceinline__ void seg_done(int n, int head) {
    w_bump(&g_flags.seg[n * 32 + head]);
    if ((n & 3) == 3) w_bump(&g_flags.qk[n >> 2]);
}
__device__ __forceinline__ void x_part(const uint32_t (&wa)[40][4], uint32_t sm, int n, int wg, int w, uint32_t ln, int head) {
    const int s = n - 1; (void)s;
    float acc[16]; uint32_t giv[8];
#pragma unroll
    for (int i = 0; i < 16; i++) acc[i] = 0.f;
    const uint32_t x0 = (uint32_t)mkdesc(SM_BASE + C_XR + wg * 4096, 16, 1024) + ln, xl[2] = {__shfl_sync(0xffffffffu, x0, 0), __shfl_sync(0xffffffffu, x0, 1)};
    auto chunk = [&](int a0, int i, int first) {
#pragma unroll
        for (int ks = 0; ks < 4; ks++)
            wgmma_rs_n32(acc, wa[a0 + 4 * i + ks], (mkdesc(0, 0, 1024) | (uint32_t)(xl[!a0] + ((((i ? (i - 1) * 8192 : C_MEM - C_XR) + ks * 32) >> 4) - !a0))), !(first && ks == 0));
    };
    mbar_wait(sm + CB_XF, n & 1);
    if (n) bar_sync(5, 384);
    if (wg == 0 && w == 0) PROF(12);
    WG_FENCE();
    chunk(20, 1, 1); chunk(20, 2, 0); chunk(20, 3, 0);
    mbar_wait(sm + CB_XM, n & 1);
    if (wg == 0 && w == 0) PROF(13);
    WG_FENCE();
    chunk(20, 0, 0);
    mbar_wait(sm + CB_XF + 8, n & 1);
    if (wg == 0 && w == 0) PROF(17);
    WG_FENCE();
    chunk(20, 4, 0);
    WG_COMMIT();
    if (n) {
        if (wg == 1 && w == 1) { BULK_WAIT(); seg_done(n - 1, head); }
        bar_sync(8, 256);
    }
    if (wg == 0 && w == 0) PROF(18);
    const uint32_t xb = sm + w * 512 + ln * 16, xw = xb + C_KX - wg * 4096, xr = xb + C_QX + wg * 4096;
    WG_WAIT(0);
#pragma unroll
    for (int i = 0; i < 8; i++) asm volatile("cvt.rn.bf16x2.f32 %0, %1, %2;" : "=r"(giv[i]) : "f"(acc[2 * i + 1]), "f"(acc[2 * i]));
#pragma unroll
    for (int p = 0; p < 2; p++) asm volatile("st.shared.v4.u32 [%0], {%1,%2,%3,%4};" :: "r"(xw + p * 2048), "r"(giv[4 * p]), "r"(giv[4 * p + 1]), "r"(giv[4 * p + 2]), "r"(giv[4 * p + 3]) : "memory");
    bar_arrive(12 + wg, 256);
    WG_FENCE();
    chunk(0, 0, 1);
    WG_COMMIT();
    chunk(0, 1, 0);
    if (XORD) chunk(0, 2, 0);
    bar_sync(13 - wg, 256);
#pragma unroll
    for (int p = 0; p < 2; p++) asm volatile("ld.shared.v4.u32 {%0,%1,%2,%3}, [%4];" : "=r"(giv[4 * p]), "=r"(giv[4 * p + 1]), "=r"(giv[4 * p + 2]), "=r"(giv[4 * p + 3]) : "r"(xr + p * 2048) : "memory");
    WG_COMMIT(); WG_WAIT(1); bar_arrive(9, 384);
    WG_FENCE();
    if (!XORD) chunk(0, 2, 0);
    chunk(0, 3, 0); chunk(0, 4, 0);
    WG_COMMIT();
    const uint32_t r = ln & 7, mi = ln >> 3, dst = sm + (wg == 0 ? C_QX : C_KX) + ((mi >> 1) * 8 + r) * 128 + (((2 * w + (mi & 1)) ^ r) << 4);
    pin(xb, giv[0], giv[4], dst, 0);
    bar_sync(10 + wg, 128);
    WG_WAIT(0);
    if (wg == 0 && w == 0) PROF(30);
    if (w == 0 && ln < 3) mbar_arrive_remote(mapa(sm + CB_XD, ln));
#pragma unroll
    for (int i = 0; i < 8; i++) { acc[2 * i] += lo_f(giv[i]); acc[2 * i + 1] += hi_f(giv[i]); }
#pragma unroll
    for (int p = 0; p < 2; p++)
        stsm4t(dst + p * 2048, pack2(acc[8 * p], acc[8 * p + 1]), pack2(acc[8 * p + 2], acc[8 * p + 3]), pack2(acc[8 * p + 4], acc[8 * p + 5]), pack2(acc[8 * p + 6], acc[8 * p + 7]));
}
__device__ __forceinline__ void x_fill(const ChainMaps& mp, uint32_t sm, int n, int j, int g) {
    mbar_expect(sm + CB_XF + 8 * g, g ? 8192 : 24576);
    const int c = g ? 6 : 2 * j;
    if (!g || j == 2)
        asm volatile("cp.async.bulk.tensor.3d.shared::cluster.global.mbarrier::complete_tx::bytes.multicast::cluster [%0], [%1, {0, %3, %4}], [%2], %5;"
            :: "r"(sm + C_XR + c * 4096), "l"((uint64_t)&mp.h2), "r"(sm + CB_XF + 8 * g), "r"(n * SEG), "r"(2 + c), "h"((uint16_t)7) : "memory");
}

__global__ void __cluster_dims__(3, 1, 1) __launch_bounds__(384, 1) k_chain(const __grid_constant__ ChainMaps mp, const __grid_constant__ ChainArgs ar) {
    const int D1 = ar.D1, DG = ar.DG;
    extern __shared__ __align__(1024) uint8_t smraw[];
    const uint32_t sm = SM_BASE + ((blockIdx.x % 3) << 24);
    if (smem_u32(smraw) != sm) __trap();
    uint32_t tid; asm volatile("mov.u32 %0, %%tid.x;" : "=r"(tid));
    const int warp = __shfl_sync(0xffffffffu, tid >> 5, 0), lane = tid & 31, wg = warp >> 2, w = warp & 3;
    const int blk = blockIdx.x, head = blk / 3, j = blk % 3;
    const int col0 = head * DH + j * 64;
    asm volatile("griddepcontrol.launch_dependents;");
#define PPROF(i)
    {
        const int mc0 = (blk >> 1) * 80 + (blk & 1) * 32, mcn = (blk & 1) ? 24 : 16;
        const int nrow = blk < 74 ? 2 : blk == 74 ? (warp < 8 ? 2 : 1) : 1;
        if (tid == 0) {
            mbar_init(sm + CB_PRE, 1);
            asm volatile("fence.mbarrier_init.release.cluster;" ::: "memory");
            const int n1 = blk < 74 ? 15360 : blk == 74 ? 10240 : 0;
            mbar_expect(sm + CB_PRE, 61440 + 1280 + 15360 + n1);
            bulk_g2s(sm + C_QM, ar.c, 1280, sm + CB_PRE);
#pragma unroll 1
            for (int c = 0; c < 4; c++) tma2d(sm + C_WO + 24576 + c * 15360, &mp.wmod, mc0, c * 160, sm + CB_PRE);
            bulk_g2s(sm + C_XR, ar.x + blk * 12 * DM, 15360, sm + CB_PRE);
            if (n1) bulk_g2s(sm + C_XR + 15360, ar.x + (1152 + blk * 12) * DM, n1, sm + CB_PRE);
        }
        if (tid == 32) {
#pragma unroll 1
            for (int c = 0; c < 11; c++) if (c != 5) mbar_init(sm + C_BAR + 8 * c, c == 2 ? 5 : c == 3 ? 6 : 1);
            asm volatile("fence.mbarrier_init.release.cluster;" ::: "memory");
            mbar_expect(sm + CB_SC, 2560); mbar_expect(sm + CB_OX, 2048);
        }
        if (warp == 2) {
            ((uint4*)g_acc)[blk * 32 + lane] = make_uint4(0, 0, 0, 0);
            if (blk < 12) ((uint4*)g_stamp)[blk * 32 + lane] = make_uint4(0, 0, 0, 0);
            else if (blk < 28) ((uint4*)g_key)[(blk - 12) * 32 + lane] = make_uint4(0, 0, 0, 0);
            else if (blk < 76) ((uint4*)g_gu)[(blk - 28) * 32 + lane] = make_uint4(~0u, ~0u, ~0u, ~0u);
            __threadfence();
        }
        PPROF(8);
        asm volatile("barrier.cluster.arrive.release.aligned; barrier.cluster.wait.acquire.aligned;" ::: "memory");
        PPROF(9);
        mbar_wait(sm + CB_PRE, 0);
        PPROF(10);
        if (tid == 352) {
            const uint64_t ef = policy_stream();
            mbar_expect(sm + CB_W, 2 * 81920);
#pragma unroll 1
            for (int c = 0; c < 10; c++) tma2d_ef(sm + C_WV + c * 8192, &mp.wq, col0, c * 64, sm + CB_W, ef);
        }
        if (tid < 320) {
            const uint32_t cv = lds32(sm + C_QM + tid * 4);
            asm volatile("st.shared.v2.f32 [%0], {%1,%2};" :: "r"(sm + C_QX + tid * 8), "f"(bfr(__fdividef(lo_f(cv), 1.f + __expf(-lo_f(cv))))),
                         "f"(bfr(__fdividef(hi_f(cv), 1.f + __expf(-hi_f(cv))))) : "memory");
        }
        __syncthreads();
        {
            float a0 = 0, a1 = 0;
            const uint32_t k0 = (tid / 24) * 40, wa0 = sm + C_WO + 24576 + k0 * 96 + (tid % 24) * 4;
#pragma unroll 4
            for (int i = 0; i < 40; i++) {
                const float sc = __uint_as_float(lds32(sm + C_QX + (k0 + i) * 4));
                const uint32_t wv = lds32(wa0 + i * 96);
                a0 += sc * lo_f(wv); a1 += sc * hi_f(wv);
            }
            asm volatile("st.shared.v2.f32 [%0], {%1,%2};" :: "r"(sm + C_MEM + tid * 8), "f"(a0), "f"(a1) : "memory");
        }
        __syncthreads();
        PPROF(11);
        if (warp == 0) {
            float a0 = 0, a1 = 0;
            const int cp = lane < mcn ? lane : 0;
#pragma unroll 4
            for (int i = 0; i < 16; i++) { const float2 v = lds64f(sm + C_MEM + (i * 24 + cp) * 8); a0 += v.x; a1 += v.y; }
            uint32_t* dst = (uint32_t*)(g_mod + mc0) + cp;
            *dst = pack2(a0, a1);
            const uint32_t rb = ld_rlx(dst);
            PPROF(1);
            if (__all_sync(0xffffffffu, rb == pack2(a0, a1)) && tid == 0) bump(blk < 32 ? &g_flags.mod : &g_flags.h);
            if (tid == 0) flag_wait(&g_flags.mod, 32);
            PPROF(2);
        }
        __syncthreads();
        uint32_t sv[10], tv[10], bad = 0;
#pragma unroll
        for (int i = 0; i < 10; i++) { sv[i] = __ldcg((const uint32_t*)g_mod + DM / 2 + lane + 32 * i); tv[i] = __ldcg((const uint32_t*)g_mod + lane + 32 * i); }
#pragma unroll 1
        for (int q = 0; q < nrow; q++) {
            uint32_t xv[10], hv[10];
#pragma unroll
            for (int i = 0; i < 10; i++) xv[i] = lds32(sm + C_XR + q * 15360 + warp * 1280 + lane * 4 + i * 128);
            ln_mod(xv, sv, tv, hv);
            uint32_t* dst = (uint32_t*)g_h + (q * 1152 + blk * 12 + warp) * (DM / 2) + lane;
#pragma unroll
            for (int i = 0; i < 10; i++) dst[32 * i] = hv[i];
#pragma unroll
            for (int i = 0; i < 10; i++) bad |= ld_rlx(dst + 32 * i) ^ hv[i];
        }
        if (__syncthreads_or(bad)) __trap();
        PPROF(3);
        if (tid == 0) {
            bump(&g_flags.h);
            flag_wait(&g_flags.h, 160);
            mbar_expect(sm + CB_XM, 8192); tma3d(sm + C_MEM, &mp.h2, 0, 0, sm + CB_XM);
            x_fill(mp, sm, 0, j, 0); x_fill(mp, sm, 0, j, 1);
            const uint64_t ef = policy_stream();
#pragma unroll 1
            for (int c = 0; c < 10; c++) tma2d_ef(sm + C_WO + c * 8192, &mp.wk, col0, c * 64, sm + CB_W, ef);
        }
        PPROF(4);
        __syncthreads();
        if (tid >= 64) {
#pragma unroll 1
            for (int i = tid - 64; i < 640 + 192 * 4; i += 320)
                asm volatile("prefetch.global.L2 [%0];" :: "l"(i < 640 ? ar.wv + (size_t)i * HD + col0 : ar.wo + (size_t)(head * DH + ((i - 640) >> 2)) * DM + j * 224 + min((i & 3) * 64, 639 - j * 224)));
        }
    }
    const int r = lane & 7, mi = lane >> 3;
    const uint32_t memrd = opaque(sm + C_MEM + lane * 16);
    constexpr float S_ACC = 64.f;
    if (wg < 2) {
        asm volatile("setmaxnreg.inc.sync.aligned.u32 %0;" :: "n"(REG_P));
        uint32_t wa[40][4];
        mbar_wait(sm + CB_W, 0);
#pragma unroll
        for (int ks = 0; ks < 40; ks++)
            ldsm4t(wa[ks], sm + ((wg == 0) == (ks < 20) ? C_WV : C_WO) + ((mi >> 1) * 8 + r) * 128 + (((2 * w + (mi & 1)) ^ r) << 4) + (ks % 20 / 4 * 8 + 4 * wg + (ks & 3)) * 2048);
        PPROF(5);
        bar_sync(1, 384);
        x_part(wa, sm, 0, wg, w, lane, head);
        PPROF(6);
        mbar_wait(sm + CB_W2, 0);
        PPROF(7);
        const uint32_t qst = opaque(sm + (wg == 0 ? C_QM : C_KM) + (2 * w + (mi & 1)) * 128 + r * 16);
        const uint32_t vrd = opaque(sm + C_WV + ((mi >> 1) * 8 + r) * 128 + (((2 * w + (mi & 1)) ^ r) << 4) + 4 * wg * 2048);
        const uint32_t mrd = opaque(memrd + wg * 1024);
        for (int s = 0; s < NSEG; s++) {
            const float un = s ? 1.f / S_ACC : 1.f;
            cut(s + ar.D2, 0);
            bar_sync(1, 384);
            if (warp == 0) { PROF(0); PROFG(24); }
            uint32_t b[3][4], a[5][4];
            float dv[2][4] = {{0, 0, 0, 0}, {0, 0, 0, 0}};
            auto fb = [&](int n) { return mrd + (n >> 1) * 2048 + (n & 1) * 512; };
            auto fa = [&](int k) { return vrd + (k >> 2) * 16384 + (k & 3) * 2048; };
            {
                float d[2][4] = {{0, 0, 0, 0}, {0, 0, 0, 0}}, g[2][4] = {{0, 0, 0, 0}, {0, 0, 0, 0}};
                ldsm4t(b[0], fb(0)); pin0(mrd); ldsm4t(b[1], fb(1)); pin0(mrd);
#pragma unroll
                for (int n = 0; n < 10; n++) {
                    const int c1 = (NCH == 2 || n >= 8);
                    if (n < 8) ldsm4t(b[(n + 2) % 3], fb(n + 2));
                    if (n + ALA >= 2 && n + ALA < 2 + VF) ldsm4t(a[2 + (n + ALA) % 3], fa(2 * (n + ALA)));
                    if (!VPOS && n >= 9 - VPRE && n < 9) ldsm4t(a[n - 9 + VPRE], fa(16 + n - 9 + VPRE));
                    mma16q(g[0], wa[20 + 2 * n], b[n % 3][0], b[n % 3][1]); mma16q(d[0], wa[2 * n], b[n % 3][0], b[n % 3][1]);
                    if (n >= 2 && n < 2 + VF) mma16q(dv[0], a[2 + n % 3], b[n % 3][0], b[n % 3][1]);
                    mma16q(g[c1], wa[21 + 2 * n], b[n % 3][2], b[n % 3][3]); mma16q(d[c1], wa[2 * n + 1], b[n % 3][2], b[n % 3][3]);
                    if (QCUT >> n & 1) cut(s + ar.D2, 1 + n);
                }
                const uint32_t xb = mrd - wg * 1024 - (C_MEM - C_VP) + w * 512;
                sts128f(xb + wg * 2048, g[0][0] + g[1][0], g[0][1] + g[1][1], g[0][2] + g[1][2], g[0][3] + g[1][3]);
                bar_sync(8, 256);
                const float4 z = lds128f(xb + (wg ^ 1) * 2048);
                if (VPOS) {
                    pin0(mrd);
#pragma unroll
                    for (int i = 0; i < VPRE; i++) ldsm4t(a[i], fa(16 + i));
                }
                stsm2t(qst, pack2((d[0][0] + d[1][0] + z.x) * un, (d[0][1] + d[1][1] + z.y) * un), pack2((d[0][2] + d[1][2] + z.z) * un, (d[0][3] + d[1][3] + z.w) * un));
            }
            bar_arrive(2, 384);
            if (w == 0) PROF(1 + wg);
            {
                if (warp == 3)
                    asm volatile(ELECTED("st.relaxed.gpu.global.u32 [%0], %1;") :: "l"(g_stamp + (s & 3) * 384 + (blk >> 3) * 32 + (blk & 7)), "r"((gtime() & ~31u) | ((s >> 2) + 1)) : "memory");
                PROXY_FENCE();
                bar_sync(7, 384);
                constexpr int NR = 16 - VF, NB = 4 + 12 - 2 * VF;
                auto kst = [&](int i) { return i < 4 ? 16 + i : i < NB ? i + 2 * VF : 5 + 2 * (i - NB); };
                const uint32_t mo = mrd + 256 + (mrd & 256);
                auto fc = [&](int p) { return 2 * p < NB ? fb(p + VF) : mo + (1 + (2 * p - NB) / 2) * 2048; };
#pragma unroll
                for (int i = VPRE; i < 4; i++) ldsm4t(a[i], fa(kst(i)));
#pragma unroll
                for (int i = 0; i < NR; i++) {
                    if (i + 4 < NR) ldsm4t(a[(i + 4) % 5], fa(kst(i + 4)));
                    if (!(i & 1) && i + 4 < NR) ldsm4t(b[(i / 2 + 1) % 3], fc(i / 2 + 2));
                    mma16q(dv[~i & 1], a[i % 5], b[(i / 2 + 2) % 3][2 * (i & 1)], b[(i / 2 + 2) % 3][2 * (i & 1) + 1]);
                }
                sts128f(mrd - (C_MEM - C_VP) + wg * 1024 + w * 512, dv[0][0] + dv[1][0], dv[0][1] + dv[1][1], dv[0][2] + dv[1][2], dv[0][3] + dv[1][3]);
            }
            if (warp == 0) bar_sync(4, 384);
            else bar_arrive(4, 384);
            if (warp == 0) {
                PROF(7);
                if (s + 1 < NSEG && elect()) {
                    mbar_expect(sm + CB_XM, 8192); tma3d(sm + C_MEM, &mp.h2, (s + 1) * SEG, 0, sm + CB_XM);
                }
            } else {
                if (wg == 1) {
                    if (w == 1) {
                        uint8_t* rec = g_att + (s * NH + head) * AT_REC;
                        w_bulk_s2g(rec + j * 8192, sm + C_QX, 8192); w_bulk_s2g(rec + AT_KM + j * 1024, sm + C_KM, 1024);
                        BULK_COMMIT();
                        if (s + 1 == NSEG) { BULK_WAIT(); seg_done(s, head); }
                    }
                    if (w == 2 && blk < 10 && s + 3 < NSEG)
                        asm volatile(ELECTED("cp.async.bulk.prefetch.L2.global [%0], 4096;") :: "l"((const uint8_t*)g_h + (s + 3) * (SEG * DM * 2) + blk * 4096) : "memory");
                } else if (w == 3) {
                    const uint32_t l = opaque(mrd) >> 4 & 31, tag = (s >> 2) + 1, now = gtime();
                    const uint32_t* sp = g_stamp + (s & 3) * 384 + (l >> 3) * 32 + (l & 7);
                    uint32_t t[3];
                    for (int n = 0;; n++) {
#pragma unroll
                        for (int i = 0; i < 3; i++) t[i] = ld_rlx(sp + i * 128);
                        if (!__any_sync(0xffffffffu, ((t[0] ^ tag) | (t[1] ^ tag) | (t[2] ^ tag)) & 31) || n > SPIN_LIMIT) break;
                    }
                    int all = -(1 << 30), own = all;
#pragma unroll
                    for (int i = 0; i < 3; i++) { const int d = t[i] - now; all = max(all, d); if ((i * 32 + l) / 3 == head) own = d; }
                    const int lag = min(__reduce_max_sync(0xffffffffu, all) - __reduce_max_sync(0xffffffffu, own), 8000);
                    PROFV(15, lag);
                    asm volatile("st.shared.u32 [%0], %1;" :: "r"(sm + C_LAG), "r"(D1 + ((lag * DG) >> 4)) : "memory");
                    if (s + 1 < NSEG) bar_arrive(6, 160);
                } else if (w == 2) {
                    if (s + 1 < NSEG) {
                        if ((s & 3) == 3) w_flag_wait(&g_flags.v[((s + 1) >> 2) * 32 + head], 2);
                        if (elect()) { mbar_expect(sm + CB_VX, 4096); bulk_g2s(sm + C_VX, g_att + ((s + 1) * NH + head) * AT_REC + AT_V + j * 4096, 4096, sm + CB_VX); }
                    }
                    if ((s & 3) == 1 && s + 3 < NSEG) asm volatile("prefetch.global.L2 [%0];" :: "l"(&g_flags.v[((s + 3) >> 2) * 32]));
                    if (s + 2 < NSEG && ((s & 3) != 2 || __all_sync(0xffffffffu, ld_rlx(&g_flags.v[((s + 2) >> 2) * 32 + head]) >= 2)))
                        asm volatile("prefetch.global.L2 [%0];" :: "l"(g_att + ((s + 2) * NH + head) * AT_REC + AT_V + j * 4096 + (opaque(mrd) << 3 & 0xf80)));
                } else if (s + 1 < NSEG) {
                    mbar_wait(sm + CB_OX, s & 1);
                    if (elect()) x_fill(mp, sm, s + 1, j, 1);
                }
            }
            if (s + 1 == NSEG) break;
            x_part(wa, sm, s + 1, wg, w, opaque(mrd) >> 4 & 31, head);
            if (warp == 0) PROF(11);
        }
    } else {
        asm volatile("setmaxnreg.dec.sync.aligned.u32 %0;" :: "n"(REG_L));
        bar_sync(1, 384);
        if (tid == 256) {
            mbar_expect(sm + CB_W2, 81920 + 3 * WO_BLK);
#pragma unroll 1
            for (int c = 0; c < 10; c++) tma2d(sm + C_WV + c * 8192, &mp.wv, col0, c * 64, sm + CB_W2);
#pragma unroll 1
            for (int c = 0; c < 3; c++) tma3d(sm + C_WO + c * WO_BLK, &mp.wo, head * DH + (j + c) % 3 * 64, 7 * j, sm + CB_W2);
        }
        bar_sync(9, 384);
#pragma unroll 1
        for (int c = tid - 256; c < DM; c += 128) {
            uint32_t u[8];
#pragma unroll
            for (int i = 0; i < 8; i++) u[i] = __ldg((const unsigned short*)ar.mem0 + i * DM + c);
            asm volatile("st.shared.v4.u32 [%0], {%1,%2,%3,%4};" :: "r"(sm + C_MEM + c * 16), "r"(u[0] | u[1] << 16), "r"(u[2] | u[3] << 16), "r"(u[4] | u[5] << 16), "r"(u[6] | u[7] << 16) : "memory");
        }
        __syncwarp();
        if (w == 1) {
            w_flag_wait(&g_flags.v[head], 2);
            if (elect()) { mbar_expect(sm + CB_VX, 4096); bulk_g2s(sm + C_VX, g_att + head * AT_REC + AT_V + j * 4096, 4096, sm + CB_VX); }
        }
        mbar_wait(sm + CB_W2, 0);
        const float scale = 0.07216878364870322f;
        uint32_t va[8][4], mr = memrd;
#pragma unroll
        for (int i = 0; i < 8; i++) ldsm4t(va[i], sm + C_WV + ((mi >> 1) * 8 + r) * 128 + (((2 * w + (mi & 1)) ^ r) << 4) + i * 2048);
        for (int s = 0; s < NSEG; s++) {
            const float un = s ? 1.f / S_ACC : 1.f;
            bar_sync(1, 384);
            if (w == 0) {
                mbar_wait(sm + CB_XD, s & 1);
                if (s + 1 < NSEG && elect()) x_fill(mp, sm, s + 1, j, 0);
            } else if (w == 1 && s > 0) { BULK_WAIT(); seg_done(s - 1, head); }
            const uint32_t l0 = mr >> 4 & 31, r0 = l0 & 7, m0 = l0 >> 3;
            uint32_t kb[2][4];
            {
                const uint32_t k7 = (4 * (w & 1) + (r0 >> 2) * 2 + (r0 & 1)) ^ (r0 << 1 & 4);
                const uint32_t kxrd = sm + C_KX + (16 * (w >> 1) + (r0 << 2 & 8) + k7) * 128 + ((m0 ^ k7) << 4);
                ldsm4(kb[0], kxrd); ldsm4(kb[1], kxrd ^ 64);
            }
            float vd[4];
            {
                uint32_t c[4][4];
#pragma unroll
                for (int i = 0; i < 4; i++) ldsm4t(c[i], mr + i * 512);
                float d[2][4] = {{0, 0, 0, 0}, {0, 0, 0, 0}};
#pragma unroll
                for (int i = 0; i < 8; i++) mma16q(d[i & 1], va[i], c[i >> 1][2 * (i & 1)], c[i >> 1][2 * (i & 1) + 1]);
#pragma unroll
                for (int i = 0; i < 4; i++) vd[i] = d[0][i] + d[1][i];
            }
            uint32_t zr = 0;
            if (w == 2)
                asm volatile("atom.relaxed.gpu.global.exch.b32 %0, [%1], 0;" : "=r"(zr)
                    : "l"(g_acc + ((s & 2) ^ 2) * (ACC_PAIR / 2) + (s & 1) * 512 + (blk >> 2) * 1024 + (blk & 3) * 128 + l0 * 4) : "memory");
            __syncwarp();
            const uint32_t sco = (w >> 1) * 512 + (l0 >> 2) * 64 + (w & 1) * 32 + ((l0 >> 1) & 1) * 16;
            const uint32_t qrd = sm + C_QM + ((m0 & 1) * 2 + (m0 >> 1)) * 128 + r0 * 16;
            const uint32_t scdst = sm + C_SC + j * 1280 + sco;
            const uint32_t rbase = mapa(sm, (j + 1 + (l0 & 1)) % 3) - sm;
            const uint32_t scm = 1024 + (l0 >> 1) * 16 - sco;
            const uint32_t v7 = r0 ^ (m0 << 2 & 4), vxrd = sm + C_VX + (8 * m0 + v7) * 128 + (((2 * w) ^ v7) << 4);
            mbar_wait(sm + CB_VX, s & 1);
            uint32_t vb[2][4];
            ldsm4t(vb[0], vxrd); ldsm4t(vb[1], vxrd ^ 16);
            const uint32_t word = sm + C_WO + (m0 & 1) * 4096 + ((m0 >> 1) * 8 + r0) * 64 + ((w ^ (r0 >> 1)) << 4);
            const uint32_t word6 = word + 6 * 4096 - (m0 & 1) * 3072;
            const uint32_t oxrd = sm + C_OX + l0 * 8;
            const uint32_t ord = sm + C_OX + (l0 >> 1) * 16 + w * 256 + (2 - (l0 & 1)) * 1024 + rbase;
            pin(mr, qrd, scdst, rbase, scm); pin(mr, scdst + scm + rbase, scdst + rbase, sm + CB_SC + rbase, scdst + scm); pin(mr, word, word6, oxrd, ord);
            pin(mr, __float_as_uint(vd[0]), __float_as_uint(vd[1]), __float_as_uint(vd[2]), __float_as_uint(vd[3]));
            bar_sync(2, 384);
            const bool odd = mr & 16;
            {
                uint32_t qa[2][4];
                ldsm4(qa[0], qrd); ldsm4(qa[1], qrd + 512);
                float x[4];
                if (w == 3) {
                    uint32_t km[2][4]; float y[4];
                    ldsm4(km[0], mr + (C_KM - C_MEM)); ldsm4(km[1], mr + (C_KM - C_MEM) + 512);
                    score_tile(qa, kb, odd, x); score_tile(qa, km, odd, y);
                    send_piece(x, scdst + rbase, sm + CB_SC + rbase, scdst); send_piece(y, scdst + scm + rbase, sm + CB_SC + rbase, scdst + scm);
                } else {
                    score_tile(qa, kb, odd, x);
                    send_piece(x, scdst + rbase, sm + CB_SC + rbase, scdst);
                }
            }
            bar_arrive(7, 384);
            if (elect()) mbar_arrive(sm + CB_SC);
            if (w == 0) PROF(4);
            const uint32_t vp = mr - (C_MEM - C_VP) + w * 512, vmst = mr + (C_VM - C_MEM) + w * 256;
            if (s + 1 == NSEG) {
                mbar_wait(sm + CB_SC, s & 1);
                bar_sync(4, 384);
                const float4 y0 = lds128f(vp), y1 = lds128f(vp + 2048);
                stsm2t(vmst, pack2((vd[0] + y0.x + y1.x) * un, (vd[1] + y0.y + y1.y) * un), pack2((vd[2] + y0.z + y1.z) * un, (vd[3] + y0.w + y1.w) * un));
                PROXY_FENCE();
                bar_sync(3, 128);
                if (w == 1) {
                    w_bulk_s2g(g_att + (s * NH + head) * AT_REC + AT_VM + j * 1024, sm + C_VM, 1024);
                    BULK_COMMIT(); BULK_WAIT(); seg_done(s, head);
                }
                __syncwarp();
                break;
            }
            pin(mr, vp, vmst, oxrd + w * 256, sm + CB_OX + rbase);
            cut(s + ar.D2, 0);
            mbar_wait(sm + CB_SC, s & 1);
            if (w == 0) PROF(8);
            float sv[10];
            {
                const uint32_t scrd = mr + (C_SC - C_MEM);
                float4 x[3], y[3]; float2 z[3];
#pragma unroll
                for (int p = 0; p < 3; p++) { x[p] = lds128f(scrd + p * 1280); y[p] = lds128f(scrd + p * 1280 + 512); z[p] = lds64f(oxrd + (C_SC - C_OX) + p * 1280 + 1024); }
                sv[0] = (x[0].x + x[1].x) + x[2].x; sv[1] = (x[0].y + x[1].y) + x[2].y; sv[2] = (x[0].z + x[1].z) + x[2].z; sv[3] = (x[0].w + x[1].w) + x[2].w;
                sv[4] = (y[0].x + y[1].x) + y[2].x; sv[5] = (y[0].y + y[1].y) + y[2].y; sv[6] = (y[0].z + y[1].z) + y[2].z; sv[7] = (y[0].w + y[1].w) + y[2].w;
                sv[8] = (z[0].x + z[1].x) + z[2].x; sv[9] = (z[0].y + z[1].y) + z[2].y;
            }
            float mx = fmaxf(fmaxf(fmaxf(sv[0], sv[1]), fmaxf(sv[2], sv[3])), fmaxf(fmaxf(fmaxf(sv[4], sv[5]), fmaxf(sv[6], sv[7])), fmaxf(sv[8], sv[9])));
            uint32_t a[NRING][4];
            auto frag = [&](int i) { const int p = i / 7, u = i % 7, o = (p >> 1) * WO_BLK + (p & 1) * 2048;
                                     return u == 3 ? word6 + o : word + o + (u > 3 ? 1024 + (u - 4) * 8192 : u * 8192); };
            mx = fmaxf(fmaxf(mx, __shfl_xor_sync(0xffffffffu, mx, 1)), fmaxf(__shfl_xor_sync(0xffffffffu, mx, 2), __shfl_xor_sync(0xffffffffu, mx, 3)));
            pin(mr, __float_as_uint(mx), 0, 0, 0);
            bar_sync(4, 384);
            {
                const float4 y0 = lds128f(vp), y1 = lds128f(vp + 2048);
                pin0(mr);
#pragma unroll
                for (int i = 0; i < NPRE; i++) ldsm4t(a[i], frag(i));
                pin0(mr);
                const float sl2e = scale * 1.4426950408889634f, mxl = mx * sl2e;
#pragma unroll
                for (int i = 9; i >= 0; i--) asm volatile("ex2.approx.ftz.f32 %0, %1;" : "=f"(sv[i]) : "f"(fmaf(sv[i], sl2e, -mxl)));
                const uint32_t pq[4] = {pack2(sv[0], sv[1]), pack2(sv[4], sv[5]), pack2(sv[2], sv[3]), pack2(sv[6], sv[7])}, pm = pack2(sv[8], sv[9]);
                if (w == 0) PROF(6);
                float o[2][4] = {{0, 0, 0, 0}, {0, 0, 0, 0}}, o2[2][4] = {{0, 0, 0, 0}, {0, 0, 0, 0}}, sx[4] = {0, 0, 0, 0};
                const uint32_t vm0 = pack2((vd[0] + y0.x + y1.x) * un, (vd[1] + y0.y + y1.y) * un), vm1 = pack2((vd[2] + y0.z + y1.z) * un, (vd[3] + y0.w + y1.w) * un);
                mma8(sx, pm, 0, 0x3f803f80u); mma8(o[0], pm, 0, vm0); mma8(o[1], pm, 0, vm1);
                mma16q(sx, pq, 0x3f803f80u, 0x3f803f80u);
#pragma unroll
                for (int u = 0; u < 2; u++) { mma16q(o[u], pq, vb[u][0], vb[u][1]); mma16q(o2[u], pq, vb[u][2], vb[u][3]); }
                float inv; asm("rcp.approx.ftz.f32 %0, %1;" : "=f"(inv) : "f"((sx[0] + sx[2]) * (1.f / S_ACC)));
                const uint32_t f0 = pack2((o[0][0] + o2[0][2]) * inv, (o[0][1] + o2[0][3]) * inv), f1 = pack2((o[1][0] + o2[1][2]) * inv, (o[1][1] + o2[1][3]) * inv);
                const uint32_t c = __shfl_xor_sync(0xffffffffu, f0, 1), d = __shfl_xor_sync(0xffffffffu, f1, 1);
                asm volatile("st.shared.v2.u32 [%0], {%1,%2};" :: "r"(oxrd + w * 256), "r"(f0), "r"(f1) : "memory");
                asm volatile("st.async.shared::cluster.mbarrier::complete_tx::bytes.v4.b32 [%0], {%1,%2,%3,%4}, [%5];"
                    :: "r"(ord), "r"(odd ? c : f0), "r"(odd ? d : f1), "r"(odd ? f0 : c), "r"(odd ? f1 : d), "r"(sm + CB_OX + rbase) : "memory");
                stsm2t(vmst, vm0, vm1);
            }
            if (w == 0) PROF(10);
#pragma unroll
            for (int i = NPRE; i < NRING; i++) ldsm4t(a[i], frag(i));
            bar_sync(3, 128);
            float e[5][4];
#pragma unroll
            for (int q = 0; q < 5; q++) e[q][0] = e[q][1] = e[q][2] = e[q][3] = 0.f;
            constexpr int LAG = 2;
            uint8_t* pdst = g_acc + ((s & 2) * (ACC_PAIR / 2) + (s & 1) * 512 + w * 2048 + j * 8192 - C_MEM - sm + mr);
#pragma unroll
            for (int h = 0; h < 3; h++) {
                uint32_t ob[4][2];
                if (h == 1) {
#pragma unroll
                    for (int i = 14 - LAG; i < 14; i++) ldsm4t(a[i % NRING], frag(i + NRING));
                    pin(mr, zr, (uint32_t)(uint64_t)pdst, (uint32_t)((uint64_t)pdst >> 32), 0);
                    mbar_wait(sm + CB_OX, s & 1);
                    if (w == 0) PROF(9);
                }
#pragma unroll
                for (int k = 0; k < 4; k++) lds64(ob[k], oxrd + h * 1024 + k * 256);
#pragma unroll
                for (int i = 14 * h; i < 14 * h + 14; i++) {
                    const int u = i % 7, k = 2 * (i / 7 & 1);
                    if (u == 3) { mma16q(e[3], a[i % NRING], ob[k][0], ob[k][1]); mma16q(e[4], a[i % NRING], ob[k + 1][0], ob[k + 1][1]); }
                    else mma16q(e[u & 3], a[i % NRING], ob[k + (u >> 2)][0], ob[k + (u >> 2)][1]);
                    if (i == B5AT) { pin(mr, a[i % NRING][0], a[i % NRING][1], a[i % NRING][2], a[i % NRING][3]); bar_arrive(5, 384); }
                    if (i >= LAG && !(i >= 14 && i < 14 + LAG) && i - LAG + NRING < 42) ldsm4t(a[(i - LAG) % NRING], frag(i - LAG + NRING));
                }
            }
            {
                const uint32_t w6 = pack2h(e[3][0] + e[4][2], e[3][1] + e[4][3]), one = 0x3c003c00u;
                asm volatile("red.relaxed.gpu.global.add.noftz.v4.f16x2 [%0], {%1,%2,%3,%4};"
                    :: "l"(pdst), "r"(pack2h(e[0][0], e[0][1])), "r"(pack2h(e[0][2], e[0][3])), "r"(pack2h(e[1][0], e[1][1])), "r"(odd ? w6 : one) : "memory");
                asm volatile("red.relaxed.gpu.global.add.noftz.v4.f16x2 [%0], {%1,%2,%3,%4};"
                    :: "l"(pdst + 1024), "r"(pack2h(e[1][2], e[1][3])), "r"(pack2h(e[2][0], e[2][1])), "r"(pack2h(e[2][2], e[2][3])), "r"(odd ? one : w6) : "memory");
            }
            const uint32_t tw = clock();
            if (w == 0) { PROF(14); PROFG(25); }
            PROXY_FENCE();
            bar_sync(6, 160);
            mr = opaque(mr);
            const uint32_t ln = mr >> 4 & 31, due = tw + lds32(sm + C_LAG);
            const uint32_t vr = sm + C_WV + ((ln >> 4) * 8 + (ln & 7)) * 128 + (((2 * w + (ln >> 3 & 1)) ^ (ln & 7)) << 4);
            const uint32_t ms0 = sm + C_MEM + w * 128 + (ln & 7) * 16 + (ln >> 3) * 512, ms1 = ms0 + (ln < 24 ? 2048 : 1536);
            if (w == 2) { w_expect(sm + CB_SC, 2560); w_expect(sm + CB_OX, 2048); }
            if (w == 1) { w_bulk_s2g(g_att + (s * NH + head) * AT_REC + AT_VM + j * 1024, sm + C_VM, 1024); BULK_COMMIT(); }
            const uint8_t* src = pdst - j * 8192;
            pin(mr, ms0, ms1, (uint32_t)(uint64_t)src, (uint32_t)((uint64_t)src >> 32));
            pin(mr, vr, due, 0, 0);
            cut(s + ar.D2, 1);
#pragma unroll
            for (int i = 0; i < 8; i++) ldsm4t(va[i], vr + i * 2048);
            wait_until(due);
            if (w == 0) { PROF(5); PROFG(26); }
            uint4 v[6];
            auto fetch = [&]() {
#pragma unroll
                for (int k = 0; k < 6; k++)
                    asm volatile("ld.relaxed.gpu.global.v4.u32 {%0,%1,%2,%3}, [%4];" : "=r"(v[k].x), "=r"(v[k].y), "=r"(v[k].z), "=r"(v[k].w) : "l"(src + (k >> 1) * 8192 + (k & 1) * 1024) : "memory");
            };
            fetch();
            bar_sync(9, 384);
#pragma unroll 1
            for (int n = 0;; n++) {
                uint32_t all = 0x50005000u;
#pragma unroll
                for (int k = 0; k < 3; k++) {
                    const uint4 x = v[2 * k], y = v[2 * k + 1];
                    all &= odd ? y.w : x.w;
                    stsm4(ms0 + k * 3584, f16_to_bf16(x.x), f16_to_bf16(x.y), f16_to_bf16(x.z), f16_to_bf16(y.x));
                    if (k < 2) { const uint32_t w6 = f16_to_bf16(odd ? x.w : y.w); stsm4(ms1 + k * 3584, f16_to_bf16(y.y), f16_to_bf16(y.z), w6, w6); }
                    else asm volatile("stmatrix.sync.aligned.m8n8.x2.shared.b16 [%0], {%1,%2};" :: "r"(ms1 + k * 3584), "r"(f16_to_bf16(y.y)), "r"(f16_to_bf16(y.z)) : "memory");
                }
                if (!__any_sync(0xffffffffu, all != 0x50005000u)) { PROFV(20 + w, n); break; }
                cut(n, SPIN_LIMIT);
                fetch();
            }
            if (w == 0) PROF(16);
        }
    }
}

struct SideMaps { CUtensorMap h, wv, ost, o, wo, slab3, slab2, lnp[3]; };
constexpr int SD_ST = 43008, SD_NST = 4, SD_EPI = SD_NST * SD_ST, SD_PAR = SD_EPI + 2 * 24576, SD_BAR = SD_PAR + 6400, SD_SMEM = SD_BAR + 256;
#define VLEAD 16
#define SEG_LAST 60
#define B_LATE 14
#define N_LIGHT 6
#define B_HELP 13
#define AUNR_ 6
constexpr int AUNR = AUNR_;
#define KSO 6
#define KSA 3
#define B_8 10
#define B_16 13
__device__ __forceinline__ int o_shift(int b) { return b >= B_16 ? 4 : b >= B_8 ? 3 : 2; }
__device__ __forceinline__ int o_split(int b) { return 1 << o_shift(b); }
__device__ __forceinline__ int next_item(int lane, bool late) {
    const int b0 = lane & 15, hi = lane >> 4;
    for (int n = 0;; n++) {
        const uint32_t w0 = ld_rlx(g_flags.qk + lane), w1 = ld_rlx(g_flags.at + lane), w2 = ld_rlx(&g_flags.c[0][0] + lane), w3 = ld_rlx(&g_flags.c[2][0] + lane), w4 = ld_rlx(&g_flags.seg[SEG_LAST * 32]);
        const uint32_t o01 = __ballot_sync(0xffffffffu, w2 < 32), o23 = __ballot_sync(0xffffffffu, b0 < B_LATE && w3 < 2u * o_split(b0));
        const uint32_t ra = __ballot_sync(0xffffffffu, w0 >= (hi ? 64u : 192u)), rb = __ballot_sync(0xffffffffu, w1 >= (hi ? 4u * o_split(b0) : 256u));
        const int bv = __ffs(o01 | 0x10000) - 1, ba = __ffs(o01 >> 16 | 0x10000) - 1, bo = __ffs(o23 | 0x10000) - 1, bl = __ffs(o23 >> 16 | 0x10000) - 1;
        if (bl == 16 && (late || ba == 16)) return -1;
        const int bc = __ffs(~ra | 0x10000) - 1;
        const bool last = ba == 15 && w4 >= 6;
        const bool r1 = (ra & ra >> 16) >> ba & 1, r2 = (rb & 0xffff) >> bo & 1, r3 = rb >> 16 >> bl & 1;
        const int kind = late || ba == 16 ? (bo < ba ? 2 : bl < bo ? 3 : -1) : last ? 1 :
                         blockIdx.x < N_LIGHT ? (r1 ? 1 : r3 ? 3 : bv < 16 ? 0 : -1) :
                         bv < 16 && (bv <= bc + VLEAD || !r2) ? 0 : r1 && ba >= B_HELP ? 1 : r2 ? 2 : r1 ? 1 : r3 ? 3 : bo < ba ? 2 : -1;
        if (kind < 0) { if (n > (1 << 20)) __trap(); __nanosleep(300); continue; }
        const int b = kind == 3 ? bl : kind == 2 ? bo : kind == 1 ? ba : bv;
        uint32_t i = 0;
        if (lane == 0) asm volatile("atom.relaxed.gpu.global.add.u32 %0, [%1], 1;" : "=r"(i) : "l"(&g_flags.c[kind][b]) : "memory");
        i = __shfl_sync(0xffffffffu, i, 0);
        if (i < (kind < 2 ? 32u : 2u * o_split(b))) return kind << 16 | b << 8 | i | ((kind == 1 ? r1 : kind == 2 ? r2 : r3) ? 128 : 0);
    }
}

template <int NP, int CH>
__device__ __forceinline__ void tile_out(const float (&acc)[8 * NP], uint32_t eb, uint32_t efull, uint32_t eempty, int& eph, int lane) {
    const int r = lane & 7, mi = lane >> 3, row = (mi & 1) * 8 + r;
    mbar_wait(eempty, eph); eph ^= 1;
#pragma unroll
    for (int p = 0; p < NP; p++) {
        const int oc = 2 * p + (mi >> 1);
        stsm4(eb + (oc >> 3) * CH + row * 128 + (((oc & 7) ^ r) << 4), pack2(acc[8 * p], acc[8 * p + 1]), pack2(acc[8 * p + 2], acc[8 * p + 3]),
              pack2(acc[8 * p + 4], acc[8 * p + 5]), pack2(acc[8 * p + 6], acc[8 * p + 7]));
    }
    asm volatile("fence.proxy.async.shared::cta;" ::: "memory");
    __syncwarp();
    if (lane == 0) mbar_arrive(efull);
}

template <int MT>
__device__ __forceinline__ void attn_tile(uint32_t base, uint32_t dst, uint32_t eempty, int eph, int lane) {
    constexpr int NK = MT ? 5 : 3;
    const int r = lane & 7, mi = lane >> 3, g = lane >> 2, t = lane & 3;
    float sc[NK][4];
#pragma unroll
    for (int n = 0; n < NK; n++) sc[n][0] = sc[n][1] = sc[n][2] = sc[n][3] = 0.f;
#pragma unroll AUNR
    for (int k2 = 0; k2 < 6; k2++) {
        const uint32_t cb = (k2 >> 1) * 8192, c0 = (k2 & 1) * 4;
        uint32_t a0[4], a1[4], bb[NK][4];
        ldsm4(a0, base + cb + (16 * MT + (mi & 1) * 8 + r) * 128 + (((c0 + (mi >> 1)) ^ r) << 4));
        ldsm4(a1, base + cb + (16 * MT + (mi & 1) * 8 + r) * 128 + (((c0 + 2 + (mi >> 1)) ^ r) << 4));
#pragma unroll
        for (int n = 0; n < NK; n++)
            ldsm4(bb[n], n < NK - 1 ? base + 4096 + cb + (8 * n + r) * 128 + (((c0 + mi) ^ r) << 4) : base + 36864 + k2 * 512 + lane * 16);
#pragma unroll
        for (int n = 0; n < NK; n++) mma16(sc[n], a0[0], a0[1], a0[2], a0[3], bb[n][0], bb[n][1]);
#pragma unroll
        for (int n = 0; n < NK; n++) mma16(sc[n], a1[0], a1[1], a1[2], a1[3], bb[n][2], bb[n][3]);
    }
    const float scale = 0.07216878364870322f, l2e = 1.4426950408889634f;
    float v[2][2 * NK], mx[2], sum[2];
#pragma unroll
    for (int hf = 0; hf < 2; hf++) {
        mx[hf] = -INFINITY;
#pragma unroll
        for (int n = 0; n < NK; n++) {
            uint32_t u = pack2(sc[n][2 * hf], sc[n][2 * hf + 1]);
            u = pack2(lo_f(u) * scale, hi_f(u) * scale);
            const int lim = 16 * MT + 8 * hf + g - 8 * n - 2 * t;
            v[hf][2 * n] = (n < NK - 1 && lim < 0) ? -1e9f : lo_f(u);
            v[hf][2 * n + 1] = (n < NK - 1 && lim < 1) ? -1e9f : hi_f(u);
            mx[hf] = fmaxf(mx[hf], fmaxf(v[hf][2 * n], v[hf][2 * n + 1]));
        }
    }
#pragma unroll
    for (int o = 1; o < 4; o <<= 1)
#pragma unroll
        for (int hf = 0; hf < 2; hf++) mx[hf] = fmaxf(mx[hf], __shfl_xor_sync(0xffffffffu, mx[hf], o));
#pragma unroll
    for (int hf = 0; hf < 2; hf++) {
        sum[hf] = 0;
#pragma unroll
        for (int q = 0; q < 2 * NK; q++) { asm("ex2.approx.ftz.f32 %0, %1;" : "=f"(v[hf][q]) : "f"((v[hf][q] - mx[hf]) * l2e)); sum[hf] += v[hf][q]; }
    }
#pragma unroll
    for (int o = 1; o < 4; o <<= 1)
#pragma unroll
        for (int hf = 0; hf < 2; hf++) sum[hf] += __shfl_xor_sync(0xffffffffu, sum[hf], o);
    uint32_t pa[NK][2];
#pragma unroll
    for (int hf = 0; hf < 2; hf++) {
        const float inv = __fdividef(1.f, sum[hf]);
#pragma unroll
        for (int n = 0; n < NK; n++) pa[n][hf] = pack2(v[hf][2 * n] * inv, v[hf][2 * n + 1] * inv);
    }
    mbar_wait(eempty, eph);
#pragma unroll AUNR
    for (int n4 = 0; n4 < 6; n4++) {
        const uint32_t cb = (n4 >> 1) * 4096, c0 = (n4 & 1) * 4;
        uint32_t bm[4], bb[2 + 2 * MT][4];
        ldsm4t(bm, base + AT_VM + n4 * 512 + lane * 16);
#pragma unroll
        for (int u = 0; u < 2 + 2 * MT; u++) ldsm4t(bb[u], base + AT_V + cb + (16 * (u >> 1) + 8 * (mi & 1) + r) * 128 + (((c0 + 2 * (u & 1) + (mi >> 1)) ^ r) << 4));
        float o[4][4];
#pragma unroll
        for (int u = 0; u < 4; u++) { o[u][0] = o[u][1] = o[u][2] = o[u][3] = 0.f; mma8(o[u], pa[NK - 1][0], pa[NK - 1][1], bm[u]); }
#pragma unroll
        for (int u = 0; u < 4 + 4 * MT; u++) mma16(o[u & 3], pa[u >> 2 << 1][0], pa[u >> 2 << 1][1], pa[(u >> 2 << 1) + 1][0], pa[(u >> 2 << 1) + 1][1], bb[u >> 1][2 * (u & 1)], bb[u >> 1][2 * (u & 1) + 1]);
#pragma unroll
        for (int p = 0; p < 2; p++)
            stsm4(dst + (n4 >> 1) * 2048 + ((mi & 1) * 8 + r) * 128 + (((c0 + 2 * p + (mi >> 1)) ^ r) << 4), pack2(o[2 * p][0], o[2 * p][1]), pack2(o[2 * p][2], o[2 * p][3]),
                  pack2(o[2 * p + 1][0], o[2 * p + 1][1]), pack2(o[2 * p + 1][2], o[2 * p + 1][3]));
    }
}

struct SideArgs { const bf16 *x, *wr, *wgate, *wup, *wdown; bf16* out; };
constexpr int T_WG = 0, T_WU = 20480, T_WD = 40960, T_X = 65536, T_RED = 77824;
__device__ __forceinline__ void tail_load(const SideArgs& ar, uint32_t tb, int blk, int tid) {
    bar_sync(1, 256);
#pragma unroll 1
    for (int c = tid; c < 1280; c += 256) {
        const int o = (c >> 1) * FF + blk * 16 + (c & 1) * 8;
        asm volatile("cp.async.cg.shared.global [%0], [%1], 16; cp.async.cg.shared.global [%0 + 20480], [%2], 16;" :: "r"(tb + T_WG + c * 16), "l"(ar.wgate + o), "l"(ar.wup + o) : "memory");
    }
#pragma unroll 1
    for (int c = tid; c < FF && blk < 80; c += 256) asm volatile("cp.async.cg.shared.global [%0], [%1], 16;" :: "r"(tb + T_WD + c * 16), "l"(ar.wdown + c * DM + blk * 8) : "memory");
}
__device__ __forceinline__ void mod_tail(const SideArgs& ar, const uint32_t tb, const uint32_t kb, const uint32_t bar, const int blk, const int tid) {
#define TPROF(i)
    const int warp = __shfl_sync(0xffffffffu, tid >> 5, 0), lane = tid & 31, r = lane & 7, mi = lane >> 3;
    {
        uint32_t k[8];
        for (int n = 0;; n++) {
#pragma unroll
            for (int i = 0; i < 2; i++) asm volatile("ld.relaxed.gpu.global.v4.u32 {%0,%1,%2,%3}, [%4];" : "=r"(k[4 * i]), "=r"(k[4 * i + 1]), "=r"(k[4 * i + 2]), "=r"(k[4 * i + 3]) : "l"(g_key + warp * 256 + i * 128 + lane * 4) : "memory");
            if (__all_sync(0xffffffffu, (k[0] & k[1] & k[2] & k[3] & k[4] & k[5] & k[6] & k[7] & S_TOK) != 0)) break;
            if (n > (1 << 22)) __trap();
        }
        const uint32_t m = __reduce_max_sync(0xffffffffu, max(umax3(k[0], k[1], k[2]), max(umax3(k[3], k[4], k[5]), max(k[6], k[7]))));
        asm volatile("st.shared.u32 [%0], %1; st.shared.u32 [%2], 0;" :: "r"(kb + warp * 4), "r"(m), "r"(kb + 32) : "memory");
        asm volatile("cp.async.wait_all;" ::: "memory");
        bar_sync(1, 256);
        TPROF(1);
        const uint32_t low = __reduce_min_sync(0xffffffffu, lds32(kb + r * 4));
#pragma unroll
        for (int i = 0; i < 8; i++)
            asm volatile("{ .reg .pred p; .reg .u32 a; setp.ge.u32 p, %0, %1; @p atom.shared.add.u32 a, [%2], 4; @p add.u32 a, a, %2; @p st.shared.u32 [a + 480], %0; }" :: "r"(k[i]), "r"(low), "r"(kb + 32) : "memory");
        if (warp == 7) { w_flag_wait(&g_flags.ln[lane & 15], 128); if (lane == 0) mbar_arrive(bar); }
        bar_sync(1, 256);
        const int nc = lds32(kb + 32);
#pragma unroll 1
        for (int c = lane * 4; c < nc; c += 128) {
            const uint32_t me = lds32(kb + 512 + c);
            int rank = 0;
#pragma unroll 4
            for (int e = 0; e < nc; e += 4) rank += lds32(kb + 512 + e) > me;
            if (rank < 8) asm volatile("st.shared.u32 [%0], %1;" :: "r"(kb + 64 + (warp * 8 + rank) * 4), "r"(me) : "memory");
        }
        __syncwarp();
    }
    const uint32_t k0 = lds32(kb + 64 + (warp * 8 + r) * 4), k1 = lds32(kb + 64 + (warp * 8 + (lane >> 2)) * 4);
    TPROF(2);
    const int trow = ~k1 & (S_TOK - 1), tcol = (blk < 80 ? blk : 0) * 8 + (lane & 3) * 2;
    uint2 xb[5];
#pragma unroll
    for (int h = 0; h < 5; h++) xb[h] = __ldcg((const uint2*)(g_h2 + trow * DM + (warp * 5 + h) * 16 + (lane & 3) * 4));
    const uint32_t fx1 = __ldcg((const uint32_t*)(g_x1 + trow * DM + tcol)), fh2 = __ldcg((const uint32_t*)(g_h2 + trow * DM + tcol)),
                   fgb = __ldcg((const uint32_t*)(g_mod + 5 * DM + tcol));
    const float fr = __uint_as_float(((int)k1 < 0 ? k1 ^ 0x80000000u : ~k1) & 0xffff0000u);
    {
        float dg[4] = {0, 0, 0, 0}, du[4] = {0, 0, 0, 0};
        uint32_t ag[5][4], au[5][4];
#pragma unroll
        for (int h = 0; h < 5; h++) {
            const uint32_t o = tb + ((warp * 5 + h) * 16 + (r >> 1) * 4 + (mi >> 1) * 2 + (r & 1)) * 32 + (mi & 1) * 16;
            ldsm4t(ag[h], o + T_WG); ldsm4t(au[h], o + T_WU);
        }
#pragma unroll
        for (int h = 0; h < 5; h++) { mma16q(dg, ag[h], xb[h].x, xb[h].y); mma16q(du, au[h], xb[h].x, xb[h].y); }
        TPROF(3);
        sts128f(tb + T_RED + warp * 1024 + lane * 16, dg[0], dg[1], dg[2], dg[3]); sts128f(tb + T_RED + warp * 1024 + 512 + lane * 16, du[0], du[1], du[2], du[3]);
    }
    bar_sync(1, 256);
    if (warp < 2) {
        float g2[2] = {0, 0}, u2[2] = {0, 0};
#pragma unroll
        for (int i = 0; i < 8; i++) {
            const float2 a = lds64f(tb + T_RED + i * 1024 + lane * 16 + warp * 8), b = lds64f(tb + T_RED + i * 1024 + 512 + lane * 16 + warp * 8);
            g2[0] += a.x; g2[1] += a.y; u2[0] += b.x; u2[1] += b.y;
        }
        float y[2];
#pragma unroll
        for (int i = 0; i < 2; i++) { const float gq = bfr(g2[i]); y[i] = bfr(__fdividef(gq, 1.f + __expf(-gq))) * bfr(u2[i]); }
        asm volatile("st.relaxed.gpu.global.u32 [%0], %1;" :: "l"(g_gu + (blk >> 1) * 128 + lane * 4 + warp * 2 + (blk & 1)), "r"(movm_t(pack2(y[0], y[1]))) : "memory");
    }
    TPROF(4);
    if (blk < 80) {
        uint32_t a[6][4], b[6][4];
#pragma unroll
        for (int k2 = 0; k2 < 6; k2++) ldsm4t(b[k2], tb + T_WD + (warp * 6 + k2) * 512 + lane * 16);
        for (int n = 0;; n++) {
            uint32_t m = 0;
#pragma unroll
            for (int k2 = 0; k2 < 6; k2++) asm volatile("ld.relaxed.gpu.global.v4.u32 {%0,%1,%2,%3}, [%4];" : "=r"(a[k2][0]), "=r"(a[k2][1]), "=r"(a[k2][2]), "=r"(a[k2][3]) : "l"(g_gu + (warp * 6 + k2) * 128 + lane * 4) : "memory");
#pragma unroll
            for (int k2 = 0; k2 < 6; k2++) m = umax3(umax3(m, a[k2][0], a[k2][1]), a[k2][2], a[k2][3]);
            if (!__any_sync(0xffffffffu, m == ~0u)) break;
            if (n > (1 << 22)) __trap();
        }
        TPROF(5);
        float d[2][4] = {{0, 0, 0, 0}, {0, 0, 0, 0}};
#pragma unroll
        for (int k2 = 0; k2 < 6; k2++) { mma16q(d[0], a[k2], b[k2][0], b[k2][1]); mma16q(d[1], a[k2], b[k2][2], b[k2][3]); }
        asm volatile("st.shared.v2.f32 [%0], {%1,%2};" :: "r"(tb + T_X + warp * 256 + lane * 8), "f"(d[0][0] + d[1][2]), "f"(d[0][1] + d[1][3]) : "memory");
        bar_sync(1, 256);
        if (warp == 0) {
            float y0 = 0, y1 = 0;
#pragma unroll
            for (int i = 0; i < 8; i++) { const float2 z = lds64f(tb + T_X + i * 256 + lane * 8); y0 += z.x; y1 += z.y; }
            const float sg = __fdividef(1.f, 1.f + __expf(-fr));
            *(uint32_t*)(ar.out + trow * DM + tcol) = add2(fx1, mul2(fgb, add2(fh2, mul2(pack2(y0, y1), pack2(sg, sg)))));
        }
    }
    TPROF(6);
}

__global__ void __launch_bounds__(384, 1) k_side(const __grid_constant__ SideMaps mp, const __grid_constant__ SideArgs ar) {
    const bf16* __restrict__ x = ar.x; const bf16* __restrict__ wr = ar.wr; bf16* __restrict__ out = ar.out;
    extern __shared__ __align__(1024) uint8_t smraw[];
    const uint32_t sm = smem_u32(smraw);
    if (sm & 1023) __trap();
    const uint32_t FULL = sm + SD_BAR, EMPTY = FULL + 32, EFULL = FULL + 64, EEMPTY = FULL + 80, IFULL = FULL + 96, IEMPTY = FULL + 128, IQ = FULL + 160, SCHED = FULL + 176, PARAM = FULL + 184, TAILB = FULL + 192;
    const int tid = threadIdx.x, warp = __shfl_sync(0xffffffffu, tid >> 5, 0), lane = tid & 31;
    const uint64_t ef = policy_stream();
    if (tid == 0) {
        for (int i = 0; i < SD_NST; i++) { mbar_init(FULL + 8 * i, 1); mbar_init(EMPTY + 8 * i, 2); }
        for (int i = 0; i < 2; i++) { mbar_init(EFULL + 8 * i, 4); mbar_init(EEMPTY + 8 * i, 1); }
        for (int i = 0; i < 4; i++) { mbar_init(IFULL + 8 * i, 1); mbar_init(IEMPTY + 8 * i, 11); }
        mbar_init(SCHED, 1); mbar_init(PARAM, 1); mbar_init(TAILB, 1);
        asm volatile("fence.mbarrier_init.release.cluster;" ::: "memory");
    }
    __syncthreads();
    if (warp >= 8) {
      asm volatile("setmaxnreg.dec.sync.aligned.u32 40;");
      if (warp == 8) {
        int st = 0, ph = 1;
        for (int q = 0;; q++) {
            mbar_wait(IFULL + 8 * (q & 3), (q >> 2) & 1);
            const int it = __shfl_sync(0xffffffffu, lds32(IQ + 4 * (q & 3)), 0);
            if (elect()) mbar_arrive(IEMPTY + 8 * (q & 3));
            if (it < 0) break;
            const int kind = it >> 16, b = (it >> 8) & 255, i = it & 63;
            const int nst = kind == 0 ? 10 : kind == 1 ? 4 : kind == 2 ? 192 >> o_shift(b) : 2;
            const int ksched = kind == 0 ? 4 : kind == 2 ? nst - KSO : (it & 128) ? -1 : kind == 1 ? KSA : 0;
            if (ksched < 0 && elect()) mbar_arrive(SCHED);
            const bool look = !(it & 128);
            if (look && kind == 1) flag_wait(&g_flags.v[b * 32 + i], 2);
            if (look && kind == 3) flag_wait(&g_flags.o[b], 4 << o_shift(b));
            for (int kb = 0; kb < nst; kb++) {
                mbar_wait(EMPTY + 8 * st, ph);
                const uint32_t base = sm + st * SD_ST, fb = FULL + 8 * st;
                if (look && kind == 1) flag_wait(&g_flags.seg[(b * 4 + kb) * 32 + i], 6);
                if (kb == ksched && elect()) mbar_arrive(SCHED);
                if (kind == 0) {
                    if (q == 0 && kb == 0) {
                        if (elect()) {
#pragma unroll 1
                            for (int c = 0; c < SD_NST; c++) tma3d(sm + c * SD_ST + 16384, &mp.wv, c * 64, i * 3, FULL + 8 * c);
#pragma unroll 1
                            for (int c = SD_NST; c < 10; c++)
                                asm volatile("cp.async.bulk.prefetch.tensor.3d.L2.global [%0, {0, %1, %2}];" :: "l"((uint64_t)&mp.wv), "r"(c * 64), "r"(i * 3) : "memory");
                        }
                        flag_wait(&g_flags.h, 160);
                    }
                    if (elect()) {
                        mbar_expect(fb, 40960);
                        tma2d(base, &mp.h, kb * 64, b * 128, fb);
                        if (q || kb >= SD_NST) tma3d(base + 16384, &mp.wv, kb * 64, i * 3, fb);
                    }
                } else if (kind == 1) {
                    if (elect()) {
                        mbar_expect(fb, 43008);
                        asm volatile("cp.async.bulk.shared::cluster.global.mbarrier::complete_tx::bytes.L2::cache_hint [%0], [%1], %2, [%3], %4;"
                            :: "r"(base), "l"(g_att + ((b * 4 + kb) * NH + i) * AT_REC), "r"(AT_REC), "r"(fb), "l"(ef) : "memory");
                    }
                } else if (kind == 3) {
                    if (elect()) { mbar_expect(fb, 40960); tma3d_ef(base, &mp.lnp[o_shift(b) - 2], i * (160 >> o_shift(b)), b * KSPLIT + (kb << o_shift(b) >> 1), fb, ef); }
                } else {
                    const int k0 = ((i >> 1) * nst + kb) * 32;
                    if (elect()) { mbar_expect(fb, 28672); tma3d(base + 8192, &mp.wo, k0, (i & 1) * 5, fb); }
                    if (look && kb % 12 == 0) flag_wait(&g_flags.pair[b * 16 + k0 / 384], 16);
                    if (elect()) tma2d_ef(base, &mp.o, k0, b * 128, fb, ef);
                }
                __syncwarp();
                if (++st == SD_NST) { st = 0; ph ^= 1; }
            }
        }
      } else if (warp == 11) {
        const int lt = (int)blockIdx.x - N_SIDE;
        int own = lt >= 0 && lt < 32 * (16 - B_LATE) ? (15 - (lt >> 5)) << 8 | (lt & 31) : -1;
        for (int q = 0;; q++) {
            if (q) mbar_wait(SCHED, (q - 1) & 1);
            int it = own >= 0 && q == 0 ? 2 << 16 | own : own == -2 ? -1 : next_item(lane, lt >= 0);
            if (it < 0 && own >= 0) { it = 3 << 16 | 64 | own; own = -2; }

            if (lane == 0) {
                if (it >> 16 == 3) {
                    const int b = (it >> 8) & 255, nr = 64 >> o_shift(b);
                    asm volatile("cp.async.bulk.prefetch.L2.global [%0], %1;" :: "l"(x + (b * 128 + (it & 63) * nr) * DM), "r"(nr * DM * 2) : "memory");
                }
                mbar_wait(IEMPTY + 8 * (q & 3), ((q >> 2) & 1) ^ 1);
                asm volatile("st.shared.u32 [%0], %1;" :: "r"(IQ + 4 * (q & 3)), "r"(it) : "memory");
                mbar_arrive(IFULL + 8 * (q & 3));
            }
            if (q == 0) {
                flag_wait(&g_flags.h, 160);
                if (lane == 0) { mbar_expect(PARAM, 6400); bulk_g2s(sm + SD_PAR, g_mod + 2 * DM, 5120, PARAM); bulk_g2s(sm + SD_PAR + 5120, wr, 1280, PARAM); mbar_wait(PARAM, 0); }
            }
            __syncwarp();
            if (it < 0) break;
        }
        if (lt >= 0) mbar_wait(TAILB, 0);
        flags_release(lane);
      } else {
        if (lane == 0) {
            const int wg = warp - 9; int ph = 0;
            for (int q = 0;; q++) {
                mbar_wait(IFULL + 8 * (q & 3), (q >> 2) & 1);
                const int it = lds32(IQ + 4 * (q & 3));
                mbar_arrive(IEMPTY + 8 * (q & 3));
                if (it < 0) break;
                const int kind = it >> 16, b = (it >> 8) & 255, i = it & 63;
                if (kind == 1) continue;
                if (kind > 2) {
                    if (wg == 0) { mbar_wait(EFULL, ph); ph ^= 1; mbar_arrive(EEMPTY); flag_add(&g_flags.ln[b], 64 >> o_shift(b)); }
                    continue;
                }
                for (int rd = 0; rd < (kind == 2 ? 2 : 1); rd++) {
                    mbar_wait(EFULL + 8 * wg, ph); ph ^= 1;
                    const uint32_t src = sm + SD_EPI + wg * 24576;
                    if (kind == 2) tma3d_store(rd ? &mp.slab2 : &mp.slab3, (b * KSPLIT + (i >> 1)) * 128 + wg * 64, (i & 1) * 5 + rd * 3, src, ef, false);
                    else for (int c = 0; c < 2; c++) {
                        uint8_t* dst = g_att + ((b * 4 + wg * 2 + c) * NH + i) * AT_REC + AT_V;
                        if (b > 1) asm volatile("cp.async.bulk.global.shared::cta.bulk_group.L2::cache_hint [%0], [%1], 12288, %2;" :: "l"(dst), "r"(src + c * 12288), "l"(ef) : "memory");
                        else asm volatile("cp.async.bulk.global.shared::cta.bulk_group [%0], [%1], 12288;" :: "l"(dst), "r"(src + c * 12288) : "memory");
                    }
                    asm volatile("cp.async.bulk.commit_group;" ::: "memory");
                    asm volatile("cp.async.bulk.wait_group.read 0;" ::: "memory");
                    mbar_arrive(EEMPTY + 8 * wg);
                }
                asm volatile("cp.async.bulk.wait_group 0;" ::: "memory");
                bump(kind == 0 ? &g_flags.v[b * 32 + i] : &g_flags.o[b]);
                if (kind == 0) bump(&g_flags.vb[b]);
            }
        }
      }
    } else {
        asm volatile("setmaxnreg.inc.sync.aligned.u32 232;");
        const int wg = warp >> 2, w = warp & 3;
        int st = 0, ph = 0, eph = 1;
        bool att = false, tl = false;
        const uint32_t eb = sm + SD_EPI + wg * 24576;
        for (int q = 0;; q++) {
            mbar_wait(IFULL + 8 * (q & 3), (q >> 2) & 1);
            const int itc = lds32(IQ + 4 * (q & 3));
            __syncwarp();
            if (lane == 0) mbar_arrive(IEMPTY + 8 * (q & 3));
            if (itc < 0) break;
            const int kind = itc >> 16, b = (itc >> 8) & 255, i = itc & 63;
            if (att && kind != 1) { bar_sync(2 + wg, 128); att = false; }
            if (kind == 0) {
                float acc[96];
#pragma unroll
                for (int n = 0; n < 96; n++) acc[n] = 0.f;
                int prev = -1;
                for (int kb = 0; kb < 10; kb++) {
                    mbar_wait(FULL + 8 * st, ph);
                    const uint32_t base = sm + st * SD_ST;
                    WG_FENCE();
#pragma unroll
                    for (int ks = 0; ks < 4; ks++)
                        wgmma_ss_n192_tb(acc, mkdesc(base + wg * 8192 + ks * 32, 16, 1024), mkdesc(base + 16384 + ks * 2048, 8192, 1024), (kb | ks) != 0);
                    WG_COMMIT();
                    if (prev >= 0) { WG_WAIT(1); if ((tid & 127) == 0) mbar_arrive(EMPTY + 8 * prev); }
                    prev = st;
                    if (++st == SD_NST) { st = 0; ph ^= 1; }
                }
                WG_WAIT(0);
                if ((tid & 127) == 0) mbar_arrive(EMPTY + 8 * prev);
                tile_out<12, 4096>(acc, eb + (w >> 1) * 12288 + (w & 1) * 2048, EFULL + 8 * wg, EEMPTY + 8 * wg, eph, lane);
            } else if (kind == 1) {
                const int seg = warp >> 1, mt = warp & 1;
                int sst = st + seg, sph = ph; if (sst >= SD_NST) { sst -= SD_NST; sph ^= 1; }
                ph ^= 1;
                mbar_wait(FULL + 8 * sst, sph);
                const uint32_t base = sm + sst * SD_ST;
                if (mt) attn_tile<1>(base, eb + w * 6144, EEMPTY + 8 * wg, eph, lane);
                else attn_tile<0>(base, eb + w * 6144, EEMPTY + 8 * wg, eph, lane);
                asm volatile("fence.proxy.async.shared::cta;" ::: "memory");
                __syncwarp();
                if (lane == 0) {
                    mbar_arrive(EMPTY + 8 * sst);
                    tma3d_store(&mp.ost, b * 128 + warp * 16, i * 3, eb + w * 6144, ef, false);
                    BULK_COMMIT(); BULK_WAIT();
                    bump(&g_flags.pair[b * 16 + (i >> 1)]); bump(&g_flags.at[b]);
                }
                __syncwarp();
                att = true;
            } else if (kind == 2) {
                float acc[96], acc2[64];
#pragma unroll
                for (int n = 0; n < 96; n++) acc[n] = 0.f;
#pragma unroll
                for (int n = 0; n < 64; n++) acc2[n] = 0.f;
                int prev = -1;
                for (int kb = 192 >> o_shift(b); kb > 0; kb--) {
                    const uint32_t base = sm + st * SD_ST;
                    mbar_wait(FULL + 8 * st, ph);
                    WG_FENCE();
#pragma unroll
                    for (int ks = 0; ks < 2; ks++) {
                        const uint64_t da = (mkdesc(base + wg * 4096 + ks * 32, 16, 512) & ~(3ull << 62)) | (2ull << 62);
                        wgmma_ss_n192_tb(acc, da, mkdesc(base + 8192 + ks * 2048, 4096, 1024), 1);
                        wgmma_ss_n128_tb(acc2, da, mkdesc(base + 8192 + 3 * 4096 + ks * 2048, 4096, 1024), 1);
                    }
                    WG_COMMIT();
                    if (prev >= 0) { WG_WAIT(1); if ((tid & 127) == 0) mbar_arrive(EMPTY + 8 * prev); }
                    prev = st;
                    if (++st == SD_NST) { st = 0; ph ^= 1; }
                }
                WG_WAIT(0);
                if ((tid & 127) == 0) mbar_arrive(EMPTY + 8 * prev);
                tile_out<12, 8192>(acc, eb + w * 2048, EFULL + 8 * wg, EEMPTY + 8 * wg, eph, lane);
                tile_out<8, 8192>(acc2, eb + w * 2048, EFULL + 8 * wg, EEMPTY + 8 * wg, eph, lane);
            } else {
                const int sh = o_shift(b), nr = 64 >> sh;
                int st1 = st + 1, ph1 = ph; if (st1 == SD_NST) { st1 = 0; ph1 ^= 1; }
                uint2 xin[2][5];
                uint32_t as[2][10];
#pragma unroll
                for (int q2 = 0; q2 < 10; q2++) xin[q2 & 1][q2 >> 1] = ld_ef(x + (b * 128 + i * nr + ((warp + 8 * (q2 & 1)) & (nr - 1))) * DM + lane * 4 + (q2 >> 1) * 128, ef);
                if (itc & 64) { tail_load(ar, sm + (st ^ 2) * SD_ST, blockIdx.x - N_SIDE, tid); tl = true; }
                mbar_wait(PARAM, 0); mbar_wait(FULL + 8 * st, ph); mbar_wait(FULL + 8 * st1, ph1);
#pragma unroll
                for (int u2 = 0; u2 < 2; u2++) {
                    float a[20];
#pragma unroll
                    for (int q2 = 0; q2 < 20; q2++) a[q2] = 0.f;
                    if (warp + 8 * u2 < nr) {
#pragma unroll 2
                        for (int k = 0; k < (1 << sh); k++) {
                            const uint32_t ad = sm + ((k >> (sh - 1)) ? st1 : st) * SD_ST + (((k & ((1 << sh >> 1) - 1)) << (6 - sh)) + warp + 8 * u2) * 1280 + lane * 8;
                            uint32_t z[5][2];
#pragma unroll
                            for (int q2 = 0; q2 < 5; q2++) lds64(z[q2], ad + q2 * 256);
#pragma unroll
                            for (int q2 = 0; q2 < 5; q2++) { a[4 * q2] += lo_f(z[q2][0]); a[4 * q2 + 1] += hi_f(z[q2][0]); a[4 * q2 + 2] += lo_f(z[q2][1]); a[4 * q2 + 3] += hi_f(z[q2][1]); }
                        }
                    }
#pragma unroll
                    for (int q2 = 0; q2 < 10; q2++) as[u2][q2] = pack2(a[2 * q2], a[2 * q2 + 1]);
                }
                bar_sync(2 + wg, 128);
                if ((tid & 127) == 0) { mbar_arrive(EMPTY + 8 * st); mbar_arrive(EMPTY + 8 * st1); }
#pragma unroll 1
                for (int lrow = warp; lrow < nr; lrow += 8) {
                    const int row = b * 128 + i * nr + lrow;
                    const uint32_t pa = sm + SD_PAR + lane * 8;
                    uint32_t xv[10], hv[10], sv[10], tv[10];
#pragma unroll
                    for (int q2 = 0; q2 < 5; q2++) {
                        uint32_t ga[2], t[2], u[2];
                        lds64(ga, pa + q2 * 256); lds64(t, pa + 1280 + q2 * 256); lds64(u, pa + 2560 + q2 * 256);
#pragma unroll
                        for (int e = 0; e < 2; e++) {
                            xv[2 * q2 + e] = add2(e ? xin[0][q2].y : xin[0][q2].x, mul2(ga[e], as[0][2 * q2 + e]));
                            tv[2 * q2 + e] = t[e]; sv[2 * q2 + e] = u[e]; as[0][2 * q2 + e] = as[1][2 * q2 + e];
                        }
                        xin[0][q2] = xin[1][q2];
                        st_ef(g_x1 + row * DM + lane * 4 + q2 * 128, make_uint2(xv[2 * q2], xv[2 * q2 + 1]), ef);
                    }
                    ln_mod(xv, sv, tv, hv);
                    float rs = 0;
#pragma unroll
                    for (int q2 = 0; q2 < 5; q2++) {
                        const int c = row * DM + lane * 4 + q2 * 128;
                        const uint32_t h0 = hv[2 * q2], h1 = hv[2 * q2 + 1];
                        uint32_t gb[2], wv[2];
                        lds64(gb, pa + 3840 + q2 * 256); lds64(wv, pa + 5120 + q2 * 256);
                        rs += (lo_f(h0) * lo_f(wv[0]) + hi_f(h0) * hi_f(wv[0])) + (lo_f(h1) * lo_f(wv[1]) + hi_f(h1) * hi_f(wv[1]));
                        st_ef(g_h2 + c, make_uint2(h0, h1), ef);
                        st_ef(out + c, make_uint2(add2(xv[2 * q2], mul2(gb[0], h0)), add2(xv[2 * q2 + 1], mul2(gb[1], h1))), ef);
                    }
                    const uint32_t rb = pack2(0.f, warp_sum(rs));
                    if (lane == 0) asm volatile("st.relaxed.gpu.global.u32 [%0], %1;" :: "l"(g_key + row), "r"((((int)rb < 0 ? ~rb : rb | 0x80000000u) & 0xffff0000u) | (uint32_t)(2 * S_TOK - 1 - row)) : "memory");
                }
                bar_sync(1, 256);
                if (wg == 0) { mbar_wait(EEMPTY, eph); eph ^= 1; if (lane == 0) mbar_arrive(EFULL); }
                st = st1 + 1; ph = ph1; if (st == SD_NST) { st = 0; ph ^= 1; }
            }
        }
        if (blockIdx.x >= N_SIDE) {
            if (!tl) tail_load(ar, sm + st * SD_ST, blockIdx.x - N_SIDE, tid);
            mbar_wait(EEMPTY + 8 * wg, eph); bar_sync(1, 256);
            mod_tail(ar, sm + st * SD_ST, sm + SD_EPI, TAILB, blockIdx.x - N_SIDE, tid);
        }
    }
    __syncwarp();
    asm volatile("griddepcontrol.wait;" ::: "memory");
}

#define P_D1 650
#define P_DL 700
#define P_DG 29
typedef CUresult (*EncodeFn)(CUtensorMap*, CUtensorMapDataType, cuuint32_t, void*, const cuuint64_t*, const cuuint64_t*, const cuuint32_t*, const cuuint32_t*,
                             CUtensorMapInterleave, CUtensorMapSwizzle, CUtensorMapL2promotion, CUtensorMapFloatOOBfill);
static EncodeFn s_encode = nullptr;
static void make_map(CUtensorMap* m, const void* p, int rows, int cols, int box_rows, int box_cols = 64) {
    cuuint64_t dims[2] = {(cuuint64_t)cols, (cuuint64_t)rows}, strides[1] = {(cuuint64_t)cols * 2};
    cuuint32_t box[2] = {(cuuint32_t)box_cols, (cuuint32_t)box_rows}, es[2] = {1, 1};
    s_encode(m, CU_TENSOR_MAP_DATA_TYPE_BFLOAT16, 2, (void*)p, dims, strides, box, es, CU_TENSOR_MAP_INTERLEAVE_NONE,
             box_cols == 64 ? CU_TENSOR_MAP_SWIZZLE_128B : box_cols == 32 ? CU_TENSOR_MAP_SWIZZLE_64B : CU_TENSOR_MAP_SWIZZLE_NONE, CU_TENSOR_MAP_L2_PROMOTION_L2_256B, CU_TENSOR_MAP_FLOAT_OOB_FILL_NONE);
}
static void make_map3(CUtensorMap* m, const void* p, int rows, int cols, int box_rows, int box_chunks, int cw = 64) {
    cuuint64_t dims[3] = {(cuuint64_t)cw, (cuuint64_t)rows, (cuuint64_t)(cols / cw)}, strides[2] = {(cuuint64_t)cols * 2, (cuuint64_t)cw * 2};
    cuuint32_t box[3] = {(cuuint32_t)cw, (cuuint32_t)box_rows, (cuuint32_t)box_chunks}, es[3] = {1, 1, 1};
    s_encode(m, CU_TENSOR_MAP_DATA_TYPE_BFLOAT16, 3, (void*)p, dims, strides, box, es, CU_TENSOR_MAP_INTERLEAVE_NONE,
             cw == 64 ? CU_TENSOR_MAP_SWIZZLE_128B : CU_TENSOR_MAP_SWIZZLE_64B, CU_TENSOR_MAP_L2_PROMOTION_L2_256B, CU_TENSOR_MAP_FLOAT_OOB_FILL_NONE);
}
template <typename T> static void* sym(T& s) { void* p = nullptr; cudaGetSymbolAddress(&p, s); return p; }

extern "C" void kernel_launch(void* const* d_in, const int* in_sizes, int n_in, void* d_out, int out_size) {
    const bf16 *x = (const bf16*)d_in[0], *mem0 = (const bf16*)d_in[1], *Wq = (const bf16*)d_in[2], *Wk = (const bf16*)d_in[3],
               *Wv = (const bf16*)d_in[4], *Wo = (const bf16*)d_in[5], *wr = (const bf16*)d_in[8], *wgate = (const bf16*)d_in[9],
               *wup = (const bf16*)d_in[10], *wdown = (const bf16*)d_in[11], *c = (const bf16*)d_in[12], *wmod = (const bf16*)d_in[13];
    bf16* out = (bf16*)d_out;
    if (!s_encode) {
        cudaDriverEntryPointQueryResult qr;
        cudaGetDriverEntryPoint("cuTensorMapEncodeTiled", (void**)&s_encode, cudaEnableDefault, &qr);
        cudaFuncSetAttribute(k_side, cudaFuncAttributeMaxDynamicSharedMemorySize, SD_SMEM);
        cudaFuncSetAttribute(k_chain, cudaFuncAttributeMaxDynamicSharedMemorySize, C_SMEM);
    }
    ChainMaps cm; SideMaps sd;
    make_map(&sd.h, sym(g_h), S_TOK, DM, 128); make_map3(&sd.wv, Wv, DM, HD, 64, 3);
    make_map3(&sd.ost, sym(g_o), S_TOK, HD, 16, 3); make_map(&sd.o, sym(g_o), S_TOK, HD, 128, 32); make_map3(&sd.wo, Wo, HD, DM, 32, 5);
    make_map3(&sd.slab3, sym(g_slab), 16 * KSPLIT * 128, DM, 64, 3); make_map3(&sd.slab2, sym(g_slab), 16 * KSPLIT * 128, DM, 64, 2);
    for (int i = 0; i < 3; i++) {
        cuuint64_t dims[3] = {256, 320, 16 * KSPLIT}, strides[2] = {512, 128 * DM * 2};
        cuuint32_t box[3] = {256, 40u >> i, 2u << i}, es[3] = {1, 1, 1};
        s_encode(&sd.lnp[i], CU_TENSOR_MAP_DATA_TYPE_BFLOAT16, 3, sym(g_slab), dims, strides, box, es, CU_TENSOR_MAP_INTERLEAVE_NONE,
                 CU_TENSOR_MAP_SWIZZLE_NONE, CU_TENSOR_MAP_L2_PROMOTION_L2_256B, CU_TENSOR_MAP_FLOAT_OOB_FILL_NONE);
    }
    make_map(&cm.wq, Wq, DM, HD, 64); make_map(&cm.wk, Wk, DM, HD, 64); make_map(&cm.wv, Wv, DM, HD, 64); make_map3(&cm.wo, Wo, HD, DM, 64, 7, 32);
    make_map3(&cm.h2, sym(g_h), S_TOK, DM, 32, 2);
    make_map(&cm.wmod, wmod, DM, 6 * DM, 160, 48);
    ChainArgs ar = {x, mem0, c, Wv, Wo, out, P_D1, P_DL, P_DG};
    k_chain<<<96, 384, C_SMEM>>>(cm, ar);
    cudaLaunchConfig_t cfg = {};
    cfg.gridDim = dim3(N_SIDE + 96); cfg.blockDim = dim3(384); cfg.dynamicSmemBytes = SD_SMEM; cfg.stream = cudaStreamPerThread;
    cudaLaunchAttribute at[1]; at[0].id = cudaLaunchAttributeProgrammaticStreamSerialization; at[0].val.programmaticStreamSerializationAllowed = 1;
    cfg.attrs = at; cfg.numAttrs = 1;
    cudaLaunchKernelEx(&cfg, k_side, sd, SideArgs{x, wr, wgate, wup, wdown, out});
}
```

```cpp
#include <cuda_runtime.h>
#include <cuda_bf16.h>
#include <cuda.h>
#include <stdint.h>
#include <stdio.h>
#include <string.h>
#include <stdlib.h>

typedef __nv_bfloat16 bf16;
constexpr int S_TOK = 2048, DM = 640, NH = 32, DH = 192, HD = NH * DH, NSEG = 64, SEG = 32, FF = 1536;

__device__ bf16 g_mod[6 * DM];
__device__ bf16 g_h[S_TOK * DM];
constexpr int AT_REC = 43008, AT_V = 24576, AT_KM = 36864, AT_VM = 39936;
__device__ __align__(1024) uint8_t g_att[NSEG * NH * AT_REC];
__device__ bf16 g_o[S_TOK * HD];
__device__ bf16 g_A[S_TOK * DM];
__device__ bf16 g_x1[S_TOK * DM];
__device__ bf16 g_h2[S_TOK * DM];
__device__ __align__(128) uint32_t g_key[S_TOK];
__device__ int g_idx[8];
__device__ __align__(128) uint32_t g_gu[FF / 8 * 32];
constexpr int ACC_PAIR = 24 * 1024;
__device__ __align__(1024) uint8_t g_acc[2 * ACC_PAIR];
__device__ __align__(1024) uint32_t g_stamp[4 * 12 * 32];
constexpr int KSPLIT = 16;
__device__ bf16 g_slab[16 * KSPLIT * 128 * DM];
struct __align__(128) Flags {
    uint32_t qk[16], vb[16];
    uint32_t at[16], o[16];
    uint32_t c[4][16];
    uint32_t half[32];
    uint32_t fin[4 * 32];
    uint32_t v[16 * 32];
    uint32_t seg[64 * 32];
    uint32_t pair[16 * 16];
    uint32_t mod, h, pad1[30], gu, pad2[31], done, pad3[31];
};
__device__ Flags g_flags;

__device__ __forceinline__ uint32_t smem_u32(const void* p) { return (uint32_t)__cvta_generic_to_shared(p); }
__device__ __forceinline__ uint32_t pack2(float lo, float hi) {
    uint32_t r; asm("cvt.rn.bf16x2.f32 %0, %1, %2;" : "=r"(r) : "f"(hi), "f"(lo)); return r;
}
__device__ __forceinline__ float bfr(float x) { return __uint_as_float(pack2(0.f, x)); }
__device__ __forceinline__ float inv_std(float var) {
    float s, r; asm("sqrt.approx.f32 %0, %1;" : "=f"(s) : "f"(bfr(bfr(var) + 1e-5f))); asm("rcp.approx.f32 %0, %1;" : "=f"(r) : "f"(bfr(s))); return r;
}
__device__ __forceinline__ float lo_f(uint32_t v) { return __uint_as_float(v << 16); }
__device__ __forceinline__ float hi_f(uint32_t v) { return __uint_as_float(v & 0xffff0000u); }
__device__ __forceinline__ void mbar_init(uint32_t bar, int cnt) { asm volatile("mbarrier.init.shared::cta.b64 [%0], %1;" :: "r"(bar), "r"(cnt) : "memory"); }
__device__ __forceinline__ void mbar_expect(uint32_t bar, int bytes) { asm volatile("mbarrier.arrive.expect_tx.shared::cta.b64 _, [%0], %1;" :: "r"(bar), "r"(bytes) : "memory"); }
__device__ __forceinline__ void mbar_arrive(uint32_t bar) { asm volatile("mbarrier.arrive.shared::cta.b64 _, [%0];" :: "r"(bar) : "memory"); }
__device__ __forceinline__ bool mbar_try(uint32_t bar, int par) {
    uint32_t ok; asm volatile("{ .reg .pred p; mbarrier.try_wait.parity.shared::cta.b64 p, [%1], %2; selp.u32 %0, 1, 0, p; }" : "=r"(ok) : "r"(bar), "r"(par) : "memory"); return ok;
}
__device__ __forceinline__ bool mbar_try_cluster(uint32_t bar, int par) {
    uint32_t ok; asm volatile("{ .reg .pred p; mbarrier.try_wait.parity.acquire.cluster.shared::cta.b64 p, [%1], %2; selp.u32 %0, 1, 0, p; }" : "=r"(ok) : "r"(bar), "r"(par) : "memory"); return ok;
}
__device__ __forceinline__ bool mbar_test(uint32_t bar, uint32_t par) {
    uint32_t ok; asm volatile("{ .reg .pred p; mbarrier.test_wait.parity.shared::cta.b64 p, [%1], %2; selp.u32 %0, 1, 0, p; }" : "=r"(ok) : "r"(bar), "r"(par) : "memory"); return ok;
}
constexpr int SPIN_LIMIT = 1 << 18;
__device__ __forceinline__ void mbar_wait(uint32_t bar, uint32_t par) {
    asm volatile("{ .reg .pred p, q; .reg .u32 n; mov.u32 n, 0;\n"
                 "W_%=: mbarrier.try_wait.parity.shared::cta.b64 p, [%0], %1;\n"
                 "@p bra.uni D_%=;\n"
                 "add.u32 n, n, 1; setp.lt.u32 q, n, 0x200000; @q bra.uni W_%=;\n"
                 "trap;\n"
                 "D_%=: }" :: "r"(bar), "r"(par) : "memory");
}
__device__ __forceinline__ void tma2d(uint32_t dst, const CUtensorMap* m, int c0, int c1, uint32_t bar) {
    asm volatile("cp.async.bulk.tensor.2d.shared::cluster.global.mbarrier::complete_tx::bytes [%0], [%1, {%3, %4}], [%2];"
        :: "r"(dst), "l"((uint64_t)m), "r"(bar), "r"(c0), "r"(c1) : "memory");
}
__device__ __forceinline__ void tma2d_mc(uint32_t dst, const CUtensorMap* m, int c0, int c1, uint32_t bar, uint16_t mask) {
    asm volatile("cp.async.bulk.tensor.2d.shared::cluster.global.mbarrier::complete_tx::bytes.multicast::cluster [%0], [%1, {%3, %4}], [%2], %5;"
        :: "r"(dst), "l"((uint64_t)m), "r"(bar), "r"(c0), "r"(c1), "h"(mask) : "memory");
}
__device__ __forceinline__ uint64_t policy_stream() { uint64_t p; asm("createpolicy.fractional.L2::evict_first.b64 %0, 1.0;" : "=l"(p)); return p; }
__device__ __forceinline__ void tma2d_ef(uint32_t dst, const CUtensorMap* m, int c0, int c1, uint32_t bar, uint64_t pol) {
    asm volatile("cp.async.bulk.tensor.2d.shared::cluster.global.mbarrier::complete_tx::bytes.L2::cache_hint [%0], [%1, {%3, %4}], [%2], %5;"
        :: "r"(dst), "l"((uint64_t)m), "r"(bar), "r"(c0), "r"(c1), "l"(pol) : "memory");
}
__device__ __forceinline__ void tma3d(uint32_t dst, const CUtensorMap* m, int row, int chunk, uint32_t bar) {
    asm volatile("cp.async.bulk.tensor.3d.shared::cluster.global.mbarrier::complete_tx::bytes [%0], [%1, {0, %3, %4}], [%2];"
        :: "r"(dst), "l"((uint64_t)m), "r"(bar), "r"(row), "r"(chunk) : "memory");
}
__device__ __forceinline__ void tma3d_ef(uint32_t dst, const CUtensorMap* m, int row, int chunk, uint32_t bar, uint64_t pol) {
    asm volatile("cp.async.bulk.tensor.3d.shared::cluster.global.mbarrier::complete_tx::bytes.L2::cache_hint [%0], [%1, {0, %3, %4}], [%2], %5;"
        :: "r"(dst), "l"((uint64_t)m), "r"(bar), "r"(row), "r"(chunk), "l"(pol) : "memory");
}
__device__ __forceinline__ void tma3d_store(const CUtensorMap* m, int row, int chunk, uint32_t src, uint64_t pol, bool hint) {
    if (hint) asm volatile("cp.async.bulk.tensor.3d.global.shared::cta.bulk_group.L2::cache_hint [%0, {0, %2, %3}], [%1], %4;"
        :: "l"((uint64_t)m), "r"(src), "r"(row), "r"(chunk), "l"(pol) : "memory");
    else asm volatile("cp.async.bulk.tensor.3d.global.shared::cta.bulk_group [%0, {0, %2, %3}], [%1];"
        :: "l"((uint64_t)m), "r"(src), "r"(row), "r"(chunk) : "memory");
}
__device__ __forceinline__ bool elect() { uint32_t p; asm volatile("{ .reg .pred e; elect.sync _|e, -1; selp.u32 %0, 1, 0, e; }" : "=r"(p)); return p; }
__device__ __forceinline__ uint2 ld_ef(const void* p, uint64_t pol) {
    uint2 v; asm volatile("ld.relaxed.gpu.global.L2::cache_hint.v2.u32 {%0,%1}, [%2], %3;" : "=r"(v.x), "=r"(v.y) : "l"(p), "l"(pol)); return v;
}
__device__ __forceinline__ void st_ef(void* p, uint2 v, uint64_t pol) {
    asm volatile("st.global.L2::cache_hint.v2.u32 [%0], {%1,%2}, %3;" :: "l"(p), "r"(v.x), "r"(v.y), "l"(pol) : "memory");
}
__device__ __forceinline__ void tma2d_prefetch(const CUtensorMap* m, int c0, int c1) {
    asm volatile("cp.async.bulk.prefetch.tensor.2d.L2.global [%0, {%1, %2}];" :: "l"((uint64_t)m), "r"(c0), "r"(c1) : "memory");
}
__device__ __forceinline__ void mbar_arrive_remote(uint32_t bar) { asm volatile("mbarrier.arrive.relaxed.cluster.shared::cluster.b64 _, [%0];" :: "r"(bar) : "memory"); }
__device__ __forceinline__ void tma2d_store(const CUtensorMap* m, int c0, int c1, uint32_t src) {
    asm volatile("cp.async.bulk.tensor.2d.global.shared::cta.bulk_group [%0, {%2, %3}], [%1];"
        :: "l"((uint64_t)m), "r"(src), "r"(c0), "r"(c1) : "memory");
}
__device__ __forceinline__ void bulk_g2s(uint32_t dst, const void* src, int bytes, uint32_t bar) {
    asm volatile("cp.async.bulk.shared::cluster.global.mbarrier::complete_tx::bytes [%0], [%1], %2, [%3];" :: "r"(dst), "l"(src), "r"(bytes), "r"(bar) : "memory");
}
__device__ __forceinline__ void ldsm4(uint32_t (&r)[4], uint32_t a) {
    asm volatile("ldmatrix.sync.aligned.m8n8.x4.shared.b16 {%0,%1,%2,%3}, [%4];" : "=r"(r[0]), "=r"(r[1]), "=r"(r[2]), "=r"(r[3]) : "r"(a) : "memory");
}
__device__ __forceinline__ void ldsm4t(uint32_t (&r)[4], uint32_t a) {
    asm volatile("ldmatrix.sync.aligned.m8n8.x4.trans.shared.b16 {%0,%1,%2,%3}, [%4];" : "=r"(r[0]), "=r"(r[1]), "=r"(r[2]), "=r"(r[3]) : "r"(a) : "memory");
}
__device__ __forceinline__ void stsm4(uint32_t a, uint32_t r0, uint32_t r1, uint32_t r2, uint32_t r3) {
    asm volatile("stmatrix.sync.aligned.m8n8.x4.shared.b16 [%0], {%1,%2,%3,%4};" :: "r"(a), "r"(r0), "r"(r1), "r"(r2), "r"(r3) : "memory");
}
__device__ __forceinline__ void stsm4t(uint32_t a, uint32_t r0, uint32_t r1, uint32_t r2, uint32_t r3) {
    asm volatile("stmatrix.sync.aligned.m8n8.x4.trans.shared.b16 [%0], {%1,%2,%3,%4};" :: "r"(a), "r"(r0), "r"(r1), "r"(r2), "r"(r3) : "memory");
}
__device__ __forceinline__ void stsm2t(uint32_t a, uint32_t r0, uint32_t r1) {
    asm volatile("stmatrix.sync.aligned.m8n8.x2.trans.shared.b16 [%0], {%1,%2};" :: "r"(a), "r"(r0), "r"(r1) : "memory");
}
__device__ __forceinline__ uint32_t movm_t(uint32_t v) { uint32_t r; asm volatile("movmatrix.sync.aligned.m8n8.trans.b16 %0, %1;" : "=r"(r) : "r"(v)); return r; }
__device__ __forceinline__ void mma16(float (&d)[4], uint32_t a0, uint32_t a1, uint32_t a2, uint32_t a3, uint32_t b0, uint32_t b1) {
    asm volatile("mma.sync.aligned.m16n8k16.row.col.f32.bf16.bf16.f32 {%0,%1,%2,%3}, {%4,%5,%6,%7}, {%8,%9}, {%0,%1,%2,%3};"
        : "+f"(d[0]), "+f"(d[1]), "+f"(d[2]), "+f"(d[3]) : "r"(a0), "r"(a1), "r"(a2), "r"(a3), "r"(b0), "r"(b1));
}
__device__ __forceinline__ void mma8(float (&d)[4], uint32_t a0, uint32_t a1, uint32_t b0) {
    asm volatile("mma.sync.aligned.m16n8k8.row.col.f32.bf16.bf16.f32 {%0,%1,%2,%3}, {%4,%5}, {%6}, {%0,%1,%2,%3};"
        : "+f"(d[0]), "+f"(d[1]), "+f"(d[2]), "+f"(d[3]) : "r"(a0), "r"(a1), "r"(b0));
}
__device__ __forceinline__ uint32_t mapa(uint32_t a, uint32_t r) { uint32_t o; asm volatile("mapa.shared::cluster.u32 %0, %1, %2;" : "=r"(o) : "r"(a), "r"(r)); return o; }
__device__ __forceinline__ void bar_sync(int id, int n) { asm volatile("bar.sync %0, %1;" :: "r"(id), "r"(n) : "memory"); }
__device__ __forceinline__ void bar_arrive(int id, int n) { asm volatile("bar.arrive %0, %1;" :: "r"(id), "r"(n) : "memory"); }
__device__ __forceinline__ uint64_t mkdesc(uint32_t addr, uint32_t lbo, uint32_t sbo) {
    return (uint64_t)((addr & 0x3FFFF) >> 4) | ((uint64_t)(lbo >> 4) << 16) | ((uint64_t)(sbo >> 4) << 32) | (1ull << 62);
}
#define WG_FENCE()  asm volatile("wgmma.fence.sync.aligned;" ::: "memory")
#define WG_COMMIT() asm volatile("wgmma.commit_group.sync.aligned;" ::: "memory")
#define WG_WAIT(n)  asm volatile("wgmma.wait_group.sync.aligned %0;" :: "n"(n) : "memory")

__device__ __forceinline__ void wgmma_ss_n192_tb(float (&d)[96], uint64_t a, uint64_t b, int acc) {
    asm volatile("{ .reg .pred p; setp.ne.b32 p, %98, 0;\n"
        "wgmma.mma_async.sync.aligned.m64n192k16.f32.bf16.bf16 {%0,%1,%2,%3,%4,%5,%6,%7,%8,%9,%10,%11,%12,%13,%14,%15,%16,%17,%18,%19,%20,%21,%22,%23,%24,%25,%26,%27,%28,%29,%30,%31,%32,%33,%34,%35,%36,%37,%38,%39,%40,%41,%42,%43,%44,%45,%46,%47,%48,%49,%50,%51,%52,%53,%54,%55,%56,%57,%58,%59,%60,%61,%62,%63,%64,%65,%66,%67,%68,%69,%70,%71,%72,%73,%74,%75,%76,%77,%78,%79,%80,%81,%82,%83,%84,%85,%86,%87,%88,%89,%90,%91,%92,%93,%94,%95}, %96, %97, p, 1, 1, 0, 1; }"
        : "+f"(d[0]), "+f"(d[1]), "+f"(d[2]), "+f"(d[3]), "+f"(d[4]), "+f"(d[5]), "+f"(d[6]), "+f"(d[7]), "+f"(d[8]), "+f"(d[9]), "+f"(d[10]), "+f"(d[11]), "+f"(d[12]), "+f"(d[13]), "+f"(d[14]), "+f"(d[15]), "+f"(d[16]), "+f"(d[17]), "+f"(d[18]), "+f"(d[19]), "+f"(d[20]), "+f"(d[21]), "+f"(d[22]), "+f"(d[23]), "+f"(d[24]), "+f"(d[25]), "+f"(d[26]), "+f"(d[27]), "+f"(d[28]), "+f"(d[29]), "+f"(d[30]), "+f"(d[31]), "+f"(d[32]), "+f"(d[33]), "+f"(d[34]), "+f"(d[35]), "+f"(d[36]), "+f"(d[37]), "+f"(d[38]), "+f"(d[39]), "+f"(d[40]), "+f"(d[41]), "+f"(d[42]), "+f"(d[43]), "+f"(d[44]), "+f"(d[45]), "+f"(d[46]), "+f"(d[47]), "+f"(d[48]), "+f"(d[49]), "+f"(d[50]), "+f"(d[51]), "+f"(d[52]), "+f"(d[53]), "+f"(d[54]), "+f"(d[55]), "+f"(d[56]), "+f"(d[57]), "+f"(d[58]), "+f"(d[59]), "+f"(d[60]), "+f"(d[61]), "+f"(d[62]), "+f"(d[63]), "+f"(d[64]), "+f"(d[65]), "+f"(d[66]), "+f"(d[67]), "+f"(d[68]), "+f"(d[69]), "+f"(d[70]), "+f"(d[71]), "+f"(d[72]), "+f"(d[73]), "+f"(d[74]), "+f"(d[75]), "+f"(d[76]), "+f"(d[77]), "+f"(d[78]), "+f"(d[79]), "+f"(d[80]), "+f"(d[81]), "+f"(d[82]), "+f"(d[83]), "+f"(d[84]), "+f"(d[85]), "+f"(d[86]), "+f"(d[87]), "+f"(d[88]), "+f"(d[89]), "+f"(d[90]), "+f"(d[91]), "+f"(d[92]), "+f"(d[93]), "+f"(d[94]), "+f"(d[95])
        : "l"(a), "l"(b), "r"(acc));
}

__device__ __forceinline__ void wgmma_ss_n128_tb(float (&d)[64], uint64_t a, uint64_t b, int acc) {
    asm volatile("{ .reg .pred p; setp.ne.b32 p, %66, 0;\n"
        "wgmma.mma_async.sync.aligned.m64n128k16.f32.bf16.bf16 {%0,%1,%2,%3,%4,%5,%6,%7,%8,%9,%10,%11,%12,%13,%14,%15,%16,%17,%18,%19,%20,%21,%22,%23,%24,%25,%26,%27,%28,%29,%30,%31,%32,%33,%34,%35,%36,%37,%38,%39,%40,%41,%42,%43,%44,%45,%46,%47,%48,%49,%50,%51,%52,%53,%54,%55,%56,%57,%58,%59,%60,%61,%62,%63}, %64, %65, p, 1, 1, 0, 1; }"
        : "+f"(d[0]), "+f"(d[1]), "+f"(d[2]), "+f"(d[3]), "+f"(d[4]), "+f"(d[5]), "+f"(d[6]), "+f"(d[7]), "+f"(d[8]), "+f"(d[9]), "+f"(d[10]), "+f"(d[11]), "+f"(d[12]), "+f"(d[13]), "+f"(d[14]), "+f"(d[15]), "+f"(d[16]), "+f"(d[17]), "+f"(d[18]), "+f"(d[19]), "+f"(d[20]), "+f"(d[21]), "+f"(d[22]), "+f"(d[23]), "+f"(d[24]), "+f"(d[25]), "+f"(d[26]), "+f"(d[27]), "+f"(d[28]), "+f"(d[29]), "+f"(d[30]), "+f"(d[31]), "+f"(d[32]), "+f"(d[33]), "+f"(d[34]), "+f"(d[35]), "+f"(d[36]), "+f"(d[37]), "+f"(d[38]), "+f"(d[39]), "+f"(d[40]), "+f"(d[41]), "+f"(d[42]), "+f"(d[43]), "+f"(d[44]), "+f"(d[45]), "+f"(d[46]), "+f"(d[47]), "+f"(d[48]), "+f"(d[49]), "+f"(d[50]), "+f"(d[51]), "+f"(d[52]), "+f"(d[53]), "+f"(d[54]), "+f"(d[55]), "+f"(d[56]), "+f"(d[57]), "+f"(d[58]), "+f"(d[59]), "+f"(d[60]), "+f"(d[61]), "+f"(d[62]), "+f"(d[63])
        : "l"(a), "l"(b), "r"(acc));
}

__device__ __forceinline__ void wgmma_rs_n32(float (&d)[16], const uint32_t (&a)[4], uint64_t b, int acc) {
    asm volatile("{ .reg .pred p; setp.ne.b32 p, %21, 0;\n"
        "wgmma.mma_async.sync.aligned.m64n32k16.f32.bf16.bf16 {%0,%1,%2,%3,%4,%5,%6,%7,%8,%9,%10,%11,%12,%13,%14,%15}, {%16,%17,%18,%19}, %20, p, 1, 1, 0; }"
        : "+f"(d[0]), "+f"(d[1]), "+f"(d[2]), "+f"(d[3]), "+f"(d[4]), "+f"(d[5]), "+f"(d[6]), "+f"(d[7]), "+f"(d[8]), "+f"(d[9]), "+f"(d[10]), "+f"(d[11]), "+f"(d[12]), "+f"(d[13]), "+f"(d[14]), "+f"(d[15])
        : "r"(a[0]), "r"(a[1]), "r"(a[2]), "r"(a[3]), "l"(b), "r"(acc));
}

__device__ __forceinline__ float warp_sum(float v) {
#pragma unroll
    for (int o = 16; o; o >>= 1) v += __shfl_xor_sync(0xffffffffu, v, o);
    return v;
}
__device__ __forceinline__ uint32_t add2(uint32_t a, uint32_t b) { uint32_t r; asm("add.rn.bf16x2 %0, %1, %2;" : "=r"(r) : "r"(a), "r"(b)); return r; }
__device__ __forceinline__ uint32_t mul2(uint32_t a, uint32_t b) { uint32_t r; asm("mul.rn.bf16x2 %0, %1, %2;" : "=r"(r) : "r"(a), "r"(b)); return r; }
__device__ __forceinline__ void ln_mod(const uint32_t (&xv)[10], const uint32_t (&sv)[10], const uint32_t (&tv)[10], uint32_t (&hv)[10]) {
    float s0 = 0, s1 = 0;
#pragma unroll
    for (int i = 0; i < 10; i++) { s0 += lo_f(xv[i]); s1 += hi_f(xv[i]); }
    const float mean = warp_sum(s0 + s1) * (1.f / DM);
    float q0 = 0, q1 = 0;
#pragma unroll
    for (int i = 0; i < 10; i++) { const float d0 = lo_f(xv[i]) - mean, d1 = hi_f(xv[i]) - mean; q0 += d0 * d0; q1 += d1 * d1; }
    const float inv = inv_std(warp_sum(q0 + q1) * (1.f / DM));
    const uint32_t mb = pack2(-mean, -mean);
#pragma unroll
    for (int i = 0; i < 10; i++) {
        const uint32_t d = add2(xv[i], mb);
        hv[i] = add2(mul2(pack2(lo_f(d) * inv, hi_f(d) * inv), add2(sv[i], 0x3f803f80u)), tv[i]);
    }
}
__device__ __forceinline__ uint32_t ld_rlx(const uint32_t* f) { uint32_t v; asm volatile("ld.relaxed.gpu.global.u32 %0, [%1];" : "=r"(v) : "l"(f) : "memory"); return v; }
__device__ __forceinline__ void bump(uint32_t* f) { asm volatile("red.relaxed.gpu.global.add.u32 [%0], 1;" :: "l"(f) : "memory"); }
#define NAP 100
__device__ __forceinline__ void flag_wait(const uint32_t* f, uint32_t target) {
    for (int n = 0;; n++) {
        uint32_t v; asm volatile("ld.relaxed.gpu.global.u32 %0, [%1];" : "=r"(v) : "l"(f) : "memory");
        if (v >= target) break;
        if (n > (1 << 22)) __trap();
        __nanosleep(NAP);
    }
}
__device__ __forceinline__ void flag_add(uint32_t* f, uint32_t v = 1) { asm volatile("red.release.gpu.global.add.u32 [%0], %1;" :: "l"(f), "r"(v) : "memory"); }
constexpr int N_SIDE = 36;
__device__ __forceinline__ void flags_release(int lane) {
    uint32_t old = 0;
    if (lane == 0) asm volatile("atom.relaxed.gpu.global.add.u32 %0, [%1], 1;" : "=r"(old) : "l"(&g_flags.done) : "memory");
    if (__shfl_sync(0xffffffffu, old, 0) == 96 + N_SIDE - 1)
#pragma unroll 1
        for (int i = lane; i < (int)(sizeof(Flags) / 16); i += 32) ((uint4*)&g_flags)[i] = make_uint4(0, 0, 0, 0);
}

struct ChainMaps { CUtensorMap wq, wk, wv, wmod, wo, h2, wo15, o15, slab16; };
struct ChainArgs { const bf16 *x, *mem0, *c, *wv, *wo, *wr, *wgate, *wup, *wdown; bf16* out; int D1, D2, DG; };
constexpr uint32_t SM_BASE = 1024;
#define NRING 11
#define FILL_AT 1
#define VF 6
#define VPRE 2
#define XORD 0
#define B5AT 41
#define QCUT 0x7f
#define NCH 2
#define ALA 1
#define VPOS 0
#define NPRE 9
#define REG_P 208
#define REG_L (504 - 2 * REG_P)
constexpr int WO_BLK = 7 * 4096;
constexpr int C_WV = 0, C_WO = 81920, C_XR = 167936, C_VP = C_XR + 7 * 4096, C_VX = C_XR + 8 * 4096, C_QX = C_VX + 4096, C_KX = C_QX + 4096,
              C_MEM = C_KX + 4096, C_OX = C_MEM + 9216, C_VM = C_OX + 3072, C_QM = C_VM + 1024, C_KM = C_QM + 1024, C_SC = C_KM + 1024, C_BAR = C_SC + 3840;
constexpr int CB_W = C_BAR, CB_W2 = C_BAR + 8, CB_SC = C_BAR + 16, CB_XD = C_BAR + 24, CB_VX = C_BAR + 32, CB_PRE = C_BAR + 40, CB_XM = C_BAR + 48, CB_OX = C_BAR + 56,
              CB_XF = C_BAR + 64, C_LAG = C_BAR + 96;
constexpr int C_SMEM = C_BAR + 128;
#define PROF(i)
#define PROFG(i)
#define PROFV(i, v)
static_assert(C_SMEM <= 232448, "chain shared memory");
__device__ __forceinline__ uint32_t umax3(uint32_t a, uint32_t b, uint32_t c) { return max(max(a, b), c); }
__device__ __forceinline__ void wait_until(uint32_t t) {
    asm volatile("{ .reg .pred p; .reg .s32 c;\nU_%=: mov.u32 c, %%clock; sub.s32 c, c, %0; setp.lt.s32 p, c, 0; @p bra.uni U_%=; }" :: "r"(t) : "memory");
}
__device__ __forceinline__ uint32_t gtime() { uint32_t c; asm volatile("mov.u32 %0, %%globaltimer_lo;" : "=r"(c)); return c; }
__device__ __forceinline__ uint32_t opaque(uint32_t v) { uint32_t r; asm volatile("shfl.sync.bfly.b32 %0, %1, 0, 31, -1;" : "=r"(r) : "r"(v)); return r; }
__device__ __forceinline__ uint32_t lds32(uint32_t a) { uint32_t v; asm volatile("ld.shared.u32 %0, [%1];" : "=r"(v) : "r"(a) : "memory"); return v; }
__device__ __forceinline__ float2 lds64f(uint32_t a) { float2 v; asm volatile("ld.shared.v2.f32 {%0,%1}, [%2];" : "=f"(v.x), "=f"(v.y) : "r"(a) : "memory"); return v; }
__device__ __forceinline__ float4 lds128f(uint32_t a) { float4 v; asm volatile("ld.shared.v4.f32 {%0,%1,%2,%3}, [%4];" : "=f"(v.x), "=f"(v.y), "=f"(v.z), "=f"(v.w) : "r"(a) : "memory"); return v; }
__device__ __forceinline__ void sts128f(uint32_t a, float x, float y, float z, float w) { asm volatile("st.shared.v4.f32 [%0], {%1,%2,%3,%4};" :: "r"(a), "f"(x), "f"(y), "f"(z), "f"(w) : "memory"); }
__device__ __forceinline__ void lds64(uint32_t (&v)[2], uint32_t a) { asm volatile("ld.shared.v2.u32 {%0,%1}, [%2];" : "=r"(v[0]), "=r"(v[1]) : "r"(a) : "memory"); }
__device__ __forceinline__ void mma16q(float (&d)[4], const uint32_t (&a)[4], uint32_t b0, uint32_t b1) { mma16(d, a[0], a[1], a[2], a[3], b0, b1); }
__device__ __forceinline__ uint32_t f16_to_bf16(uint32_t v) {
    float lo, hi; asm("{ .reg .f16 l, h; mov.b32 {l, h}, %2; cvt.f32.f16 %0, l; cvt.f32.f16 %1, h; }" : "=f"(lo), "=f"(hi) : "r"(v));
    return pack2(lo, hi);
}
__device__ __forceinline__ uint32_t pack2h(float lo, float hi) { uint32_t r; asm("cvt.rn.f16x2.f32 %0, %1, %2;" : "=r"(r) : "f"(hi), "f"(lo)); return r; }
#define SPLIT 1
__device__ __forceinline__ void cut(uint32_t never, int n) {
    asm volatile("{ .reg .pred p; setp.ne.u32 p, %0, %1; @p bra.uni C_%=; trap; C_%=: }" :: "r"(never), "r"(n) : "memory");
}
__device__ __forceinline__ void pin(uint32_t never, uint32_t a, uint32_t b, uint32_t c, uint32_t d) {
    asm volatile("{ .reg .pred p; setp.eq.u32 p, %0, 0; @p st.shared.v4.u32 [%0], {%1,%2,%3,%4}; }" :: "r"(never), "r"(a), "r"(b), "r"(c), "r"(d) : "memory");
}
__device__ __forceinline__ void pin0(uint32_t never) {
    asm volatile("{ .reg .pred p; setp.eq.u32 p, %0, 0; @p st.shared.u32 [%0], 0; }" :: "r"(never) : "memory");
}
#define ELECTED(txt) "{ .reg .pred e; elect.sync _|e, -1; @e " txt " }"
__device__ __forceinline__ void w_bulk_s2g(void* dst, uint32_t src, int bytes) {
    asm volatile(ELECTED("cp.async.bulk.global.shared::cta.bulk_group [%0], [%1], %2;") :: "l"(dst), "r"(src), "r"(bytes) : "memory");
}
__device__ __forceinline__ void w_bump(uint32_t* f) { asm volatile(ELECTED("red.relaxed.gpu.global.add.u32 [%0], 1;") :: "l"(f) : "memory"); }
__device__ __forceinline__ void w_expect(uint32_t bar, int bytes) { asm volatile(ELECTED("mbarrier.arrive.expect_tx.shared::cta.b64 _, [%0], %1;") :: "r"(bar), "r"(bytes) : "memory"); }
__device__ __forceinline__ void w_flag_wait(const uint32_t* f, uint32_t target) {
    asm volatile("{ .reg .pred p; .reg .u32 n, v; mov.u32 n, 0;\n"
                 "F_%=: ld.relaxed.gpu.global.u32 v, [%0]; setp.ge.u32 p, v, %1; vote.sync.all.pred p, p, -1; @p bra.uni G_%=;\n"
                 "nanosleep.u32 %2; add.u32 n, n, 1; setp.lt.u32 p, n, 0x400000; @p bra.uni F_%=;\ntrap;\nG_%=: }" :: "l"(f), "r"(target), "n"(NAP) : "memory");
}
#define BULK_COMMIT()    asm volatile("cp.async.bulk.commit_group;" ::: "memory")
#define BULK_WAIT()      asm volatile("cp.async.bulk.wait_group 0;" ::: "memory")
#define BULK_WAIT_READ() asm volatile("cp.async.bulk.wait_group.read 0;" ::: "memory")
#define PROXY_FENCE()    asm volatile("fence.proxy.async.shared::cta;" ::: "memory")
__device__ __forceinline__ void score_tile(const uint32_t (&qa)[2][4], const uint32_t (&kb)[2][4], bool odd, float (&x)[4]) {
    float sc[2][4] = {{0, 0, 0, 0}, {0, 0, 0, 0}};
#pragma unroll
    for (int k = 0; k < 4; k++) mma16q(sc[k & 1], qa[k >> 1], kb[k >> 1][2 * (k & 1)], kb[k >> 1][2 * (k & 1) + 1]);
    float a = sc[0][0] + sc[1][2], b = sc[0][1] + sc[1][3];
    float c = __shfl_xor_sync(0xffffffffu, a, 1), d = __shfl_xor_sync(0xffffffffu, b, 1);
    x[0] = odd ? c : a; x[1] = odd ? d : b; x[2] = odd ? a : c; x[3] = odd ? b : d;
}
__device__ __forceinline__ void send_piece(const float (&x)[4], uint32_t rdst, uint32_t rbar, uint32_t ldst) {
    asm volatile("st.async.shared::cluster.mbarrier::complete_tx::bytes.v4.f32 [%0], {%1,%2,%3,%4}, [%5];"
        :: "r"(rdst), "f"(x[0]), "f"(x[1]), "f"(x[2]), "f"(x[3]), "r"(rbar) : "memory");
    sts128f(ldst, x[0], x[1], x[2], x[3]);
}

__device__ __forceinline__ void seg_done(int n, int head) {
    w_bump(&g_flags.seg[n * 32 + head]);
    if ((n & 3) == 3) w_bump(&g_flags.qk[n >> 2]);
}
__device__ __forceinline__ void x_part(const uint32_t (&wa)[40][4], uint32_t sm, int n, int wg, int w, uint32_t ln, int head) {
    const int s = n - 1; (void)s;
    float acc[16]; uint32_t giv[8];
#pragma unroll
    for (int i = 0; i < 16; i++) acc[i] = 0.f;
    const uint32_t x0 = (uint32_t)mkdesc(SM_BASE + C_XR + wg * 4096, 16, 1024) + ln, xl[2] = {__shfl_sync(0xffffffffu, x0, 0), __shfl_sync(0xffffffffu, x0, 1)};
    auto chunk = [&](int a0, int i, int first) {
#pragma unroll
        for (int ks = 0; ks < 4; ks++)
            wgmma_rs_n32(acc, wa[a0 + 4 * i + ks], (mkdesc(0, 0, 1024) | (uint32_t)(xl[!a0] + ((((i ? (i - 1) * 8192 : C_MEM - C_XR) + ks * 32) >> 4) - !a0))), !(first && ks == 0));
    };
    mbar_wait(sm + CB_XF, n & 1);
    if (n) bar_sync(5, 384);
    if (wg == 0 && w == 0) PROF(12);
    WG_FENCE();
    chunk(20, 1, 1); chunk(20, 2, 0); chunk(20, 3, 0);
    mbar_wait(sm + CB_XM, n & 1);
    if (wg == 0 && w == 0) PROF(13);
    WG_FENCE();
    chunk(20, 0, 0);
    mbar_wait(sm + CB_XF + 8, n & 1);
    if (wg == 0 && w == 0) PROF(17);
    WG_FENCE();
    chunk(20, 4, 0);
    WG_COMMIT();
    if (n) {
        if (wg == 1 && w == 1) { BULK_WAIT(); seg_done(n - 1, head); }
        bar_sync(8, 256);
    }
    if (wg == 0 && w == 0) PROF(18);
    const uint32_t xb = sm + w * 512 + ln * 16, xw = xb + C_KX - wg * 4096, xr = xb + C_QX + wg * 4096;
    WG_WAIT(0);
#pragma unroll
    for (int i = 0; i < 8; i++) asm volatile("cvt.rn.bf16x2.f32 %0, %1, %2;" : "=r"(giv[i]) : "f"(acc[2 * i + 1]), "f"(acc[2 * i]));
#pragma unroll
    for (int p = 0; p < 2; p++) asm volatile("st.shared.v4.u32 [%0], {%1,%2,%3,%4};" :: "r"(xw + p * 2048), "r"(giv[4 * p]), "r"(giv[4 * p + 1]), "r"(giv[4 * p + 2]), "r"(giv[4 * p + 3]) : "memory");
    bar_arrive(12 + wg, 256);
    WG_FENCE();
    chunk(0, 0, 1);
    WG_COMMIT();
    chunk(0, 1, 0);
    if (XORD) chunk(0, 2, 0);
    bar_sync(13 - wg, 256);
#pragma unroll
    for (int p = 0; p < 2; p++) asm volatile("ld.shared.v4.u32 {%0,%1,%2,%3}, [%4];" : "=r"(giv[4 * p]), "=r"(giv[4 * p + 1]), "=r"(giv[4 * p + 2]), "=r"(giv[4 * p + 3]) : "r"(xr + p * 2048) : "memory");
    WG_COMMIT(); WG_WAIT(1); bar_arrive(9, 384);
    WG_FENCE();
    if (!XORD) chunk(0, 2, 0);
    chunk(0, 3, 0); chunk(0, 4, 0);
    WG_COMMIT();
    const uint32_t r = ln & 7, mi = ln >> 3, dst = sm + (wg == 0 ? C_QX : C_KX) + ((mi >> 1) * 8 + r) * 128 + (((2 * w + (mi & 1)) ^ r) << 4);
    pin(xb, giv[0], giv[4], dst, 0);
    bar_sync(10 + wg, 128);
    WG_WAIT(0);
    if (wg == 0 && w == 0) PROF(30);
    if (w == 0 && ln < 3) mbar_arrive_remote(mapa(sm + CB_XD, ln));
#pragma unroll
    for (int i = 0; i < 8; i++) { acc[2 * i] += lo_f(giv[i]); acc[2 * i + 1] += hi_f(giv[i]); }
#pragma unroll
    for (int p = 0; p < 2; p++)
        stsm4t(dst + p * 2048, pack2(acc[8 * p], acc[8 * p + 1]), pack2(acc[8 * p + 2], acc[8 * p + 3]), pack2(acc[8 * p + 4], acc[8 * p + 5]), pack2(acc[8 * p + 6], acc[8 * p + 7]));
    if (wg == 0 && w == 0) PROF(11);
}
__device__ __forceinline__ void x_fill(const ChainMaps& mp, uint32_t sm, int n, int j, int g) {
    mbar_expect(sm + CB_XF + 8 * g, g ? 8192 : 24576);
    const int c = g ? 6 : 2 * j;
    if (!g || j == 2)
        asm volatile("cp.async.bulk.tensor.3d.shared::cluster.global.mbarrier::complete_tx::bytes.multicast::cluster [%0], [%1, {0, %3, %4}], [%2], %5;"
            :: "r"(sm + C_XR + c * 4096), "l"((uint64_t)&mp.h2), "r"(sm + CB_XF + 8 * g), "r"(n * SEG), "r"(2 + c), "h"((uint16_t)7) : "memory");
}

#define BPOS 1
#define TPF 1
#define B_LATE 14
constexpr int E_B = C_WO, E_STG = 196608, EB_A = 229376, EB_B = C_BAR + 80, EB_REL = C_BAR + 104;
__device__ __forceinline__ uint32_t e_slot(int wg, int c) { return wg && c == 2 ? E_B + 98304 : wg * 49152 + c * 16384; }
constexpr int T_WG = 0, T_WU = 20480, T_WD = 40960, T_X = 65536, T_RED = 77824, T_KEY = 86016;
__device__ __forceinline__ void wo_half(const ChainMaps& mp, uint32_t sm, int blk, int c) {
    if (blk < 80 && elect()) { mbar_expect(sm + EB_B + 8 * c, 49152); tma3d(sm + E_B + c * 49152, &mp.wo15, blk / 5 * 384 + c * 192, blk % 5 * 2, sm + EB_B + 8 * c); }
}
__device__ __forceinline__ void end_loads(const ChainMaps& mp, const ChainArgs& ar, uint32_t sm, int blk, int wg) {
    const uint32_t bar = sm + EB_A + wg * 48;
    const int kp = blk / 5;
    if (elect()) {
#pragma unroll 1
        for (int c = 0; c < 6; c++) mbar_init(bar + 8 * c, c < 3 ? 1 : 4);
        PROXY_FENCE();
    }
    __syncwarp();
    bar_arrive(5, 384);
    if (blk >= 80) {
        if (TPF && elect()) {
#pragma unroll 1
            for (int c = 0; c < 3; c++) asm volatile("cp.async.bulk.prefetch.L2.global [%0], 61440;" :: "l"((c == 0 ? ar.wgate : c == 1 ? ar.wup : ar.wdown) + ((blk - 80) * 2 + wg) * 30720) : "memory");
        }
        return;
    }
    const uint64_t ef = policy_stream();
#pragma unroll 1
    for (int b = B_LATE; b < 16; b++) {
        w_flag_wait(b == 15 ? &g_flags.half[kp * 2 + wg] : &g_flags.pair[b * 16 + kp], b == 15 ? 8 : 16);
#pragma unroll 1
        for (int c = 0; c < 3; c++) {
            if (b > B_LATE) mbar_wait(bar + 24 + 8 * c, (b - B_LATE - 1) & 1);
            if (elect()) { mbar_expect(bar + 8 * c, 16384); tma3d_ef(sm + e_slot(wg, c), &mp.o15, b * 128 + wg * 64, kp * 6 + c * 2, bar + 8 * c, ef); }
            __syncwarp();
        }
    }
}
__device__ __forceinline__ void last_blocks(const ChainMaps& mp, const ChainArgs& ar, uint32_t sm, int blk, int tid) {
    const int warp = __shfl_sync(0xffffffffu, tid >> 5, 0), lane = tid & 31, wg = warp >> 2, w = warp & 3, kp = blk / 5, ct = blk % 5;
    const uint32_t bar = sm + EB_A + wg * 48, stg = sm + E_STG + warp * 4096;
    const uint64_t ef = policy_stream();
    bar_sync(5, 384);
    float acc[64];
#pragma unroll
    for (int n = 0; n < 64; n++) acc[n] = 0.f;
#pragma unroll 1
    for (int b = B_LATE; b < 16 && blk < 80; b++) {
#pragma unroll 1
        for (int c = 0; c < 6; c++) {
            mbar_wait(sm + EB_B + 8 * (c >= 3), 0); mbar_wait(bar + 8 * (c >> 1), (b - B_LATE) & 1);
            const uint64_t da = mkdesc(SM_BASE + e_slot(wg, c >> 1) + (c & 1) * 8192, 16, 1024), db = mkdesc(SM_BASE + E_B + (c >= 3 ? 24576 : 0) + c * 8192, 24576, 1024);
            WG_FENCE();
#pragma unroll
            for (int ks = 0; ks < 4; ks++) wgmma_ss_n128_tb(acc, da + ks * 2, db + ks * 128, c | ks);
            WG_COMMIT();
            WG_WAIT(1);
            if ((c & 1) == 0 && c && elect()) mbar_arrive(bar + 16 + 4 * c);
        }
        WG_WAIT(0);
        if (elect()) mbar_arrive(bar + 40);
        const int r = lane & 7, mi = lane >> 3;
#pragma unroll
        for (int p = 0; p < 8; p++) {
            const int oc = 2 * p + (mi >> 1);
            stsm4(stg + (oc >> 3) * 2048 + ((mi & 1) * 8 + r) * 128 + (((oc & 7) ^ r) << 4), pack2(acc[8 * p], acc[8 * p + 1]), pack2(acc[8 * p + 2], acc[8 * p + 3]),
                  pack2(acc[8 * p + 4], acc[8 * p + 5]), pack2(acc[8 * p + 6], acc[8 * p + 7]));
        }
        PROXY_FENCE();
        __syncwarp();
        if (elect()) tma3d_store(&mp.slab16, (b * KSPLIT + kp) * 128 + warp * 16, ct * 2, stg, ef, false);
        BULK_COMMIT(); BULK_WAIT();
        if (w) bar_arrive(12 + wg, 128); else { bar_sync(12 + wg, 128); w_bump(b < 14 ? &g_flags.o[b] : &g_flags.fin[((b - 14) * 2 + wg) * 32]); }
    }
    bar_sync(8, 256);
    const int o = (tid >> 1) * FF + blk * 16 + (tid & 1) * 8;
    const bf16 *pg = ar.wgate + o, *pu = ar.wup + o, *pd = ar.wdown + tid * DM + (blk < 80 ? blk : 0) * 8;
#pragma unroll
    for (int i = 0; i < 16; i++)
        asm volatile("cp.async.cg.shared.global [%0], [%1], 16;" :: "r"(sm + E_B + i * 4096 + tid * 16), "l"(i < 5 ? pg + i * 128 * FF : i < 10 ? pu + (i - 5) * 128 * FF : pd + (i - 10) * 256 * DM) : "memory");
}
__device__ __forceinline__ void mod_tail(const ChainArgs& ar, const uint32_t tb, const uint32_t bar, const int blk, const int tid) {
#define TPROF(i)
    const int warp = __shfl_sync(0xffffffffu, tid >> 5, 0), lane = tid & 31, r = lane & 7, mi = lane >> 3;
    const uint32_t kb = tb + T_KEY;
    {
        uint32_t k[8];
        for (int n = 0;; n++) {
#pragma unroll
            for (int i = 0; i < 2; i++) asm volatile("ld.relaxed.gpu.global.v4.u32 {%0,%1,%2,%3}, [%4];" : "=r"(k[4 * i]), "=r"(k[4 * i + 1]), "=r"(k[4 * i + 2]), "=r"(k[4 * i + 3]) : "l"(g_key + warp * 256 + i * 128 + lane * 4) : "memory");
            if (__all_sync(0xffffffffu, (k[0] & k[1] & k[2] & k[3] & k[4] & k[5] & k[6] & k[7] & S_TOK) != 0)) break;
            if (n > (1 << 22)) __trap();
            __nanosleep(NAP);
        }
        const uint32_t m = __reduce_max_sync(0xffffffffu, max(umax3(k[0], k[1], k[2]), max(umax3(k[3], k[4], k[5]), max(k[6], k[7]))));
        asm volatile("st.shared.u32 [%0], %1; st.shared.u32 [%2], 0;" :: "r"(kb + warp * 4), "r"(m), "r"(kb + 32) : "memory");
        asm volatile("cp.async.wait_all;" ::: "memory");
        bar_sync(1, 256);
        TPROF(1);
        const uint32_t low = __reduce_min_sync(0xffffffffu, lds32(kb + r * 4));
        uint32_t cnt = 0;
#pragma unroll
        for (int i = 0; i < 8; i++) cnt += k[i] >= low ? 4 : 0;
        if (cnt) {
            uint32_t a; asm volatile("atom.shared.add.u32 %0, [%1], %2;" : "=r"(a) : "r"(kb + 32), "r"(cnt) : "memory");
#pragma unroll
            for (int i = 0; i < 8; i++) if (k[i] >= low) { asm volatile("st.shared.u32 [%0], %1;" :: "r"(kb + 512 + a), "r"(k[i]) : "memory"); a += 4; }
        }
        if (tid == 0) mbar_arrive(bar);
        bar_sync(1, 256);
        const int nc = lds32(kb + 32);
#pragma unroll 1
        for (int c = lane * 4; c < nc; c += 128) {
            const uint32_t me = lds32(kb + 512 + c);
            int rank = 0;
#pragma unroll 2
            for (int e = 0; e < nc; e += 16) {
                const float4 z = lds128f(kb + 512 + e);
                rank += (__float_as_uint(z.x) > me) + (e + 4 < nc && __float_as_uint(z.y) > me) + (e + 8 < nc && __float_as_uint(z.z) > me) + (e + 12 < nc && __float_as_uint(z.w) > me);
            }
            if (rank < 8) asm volatile("st.shared.u32 [%0], %1;" :: "r"(kb + 64 + (warp * 8 + rank) * 4), "r"(me) : "memory");
        }
        __syncwarp();
    }
    const uint32_t k0 = lds32(kb + 64 + (warp * 8 + r) * 4), k1 = lds32(kb + 64 + (warp * 8 + (lane >> 2)) * 4);
    TPROF(2);
    const int trow = ~k1 & (S_TOK - 1), tcol = (blk < 80 ? blk : 0) * 8 + (lane & 3) * 2;
    uint2 xb[5];
#pragma unroll
    for (int h = 0; h < 5; h++) xb[h] = __ldcg((const uint2*)(g_h2 + trow * DM + (warp * 5 + h) * 16 + (lane & 3) * 4));
    const uint32_t fx1 = __ldcg((const uint32_t*)(g_x1 + trow * DM + tcol)), fh2 = __ldcg((const uint32_t*)(g_h2 + trow * DM + tcol)),
                   fgb = __ldcg((const uint32_t*)(g_mod + 5 * DM + tcol));
    const float fr = __uint_as_float(((int)k1 < 0 ? k1 ^ 0x80000000u : ~k1) & 0xffff0000u);
    {
        float dg[4] = {0, 0, 0, 0}, du[4] = {0, 0, 0, 0};
        uint32_t ag[5][4], au[5][4];
#pragma unroll
        for (int h = 0; h < 5; h++) {
            const uint32_t o = tb + ((warp * 5 + h) * 16 + (r >> 1) * 4 + (mi >> 1) * 2 + (r & 1)) * 32 + (mi & 1) * 16;
            ldsm4t(ag[h], o + T_WG); ldsm4t(au[h], o + T_WU);
        }
#pragma unroll
        for (int h = 0; h < 5; h++) { mma16q(dg, ag[h], xb[h].x, xb[h].y); mma16q(du, au[h], xb[h].x, xb[h].y); }
        TPROF(3);
        sts128f(tb + T_RED + warp * 1024 + lane * 16, dg[0], dg[1], dg[2], dg[3]); sts128f(tb + T_RED + warp * 1024 + 512 + lane * 16, du[0], du[1], du[2], du[3]);
    }
    bar_sync(1, 256);
    if (warp < 2) {
        float g2[2] = {0, 0}, u2[2] = {0, 0};
#pragma unroll
        for (int i = 0; i < 8; i++) {
            const float2 a = lds64f(tb + T_RED + i * 1024 + lane * 16 + warp * 8), b = lds64f(tb + T_RED + i * 1024 + 512 + lane * 16 + warp * 8);
            g2[0] += a.x; g2[1] += a.y; u2[0] += b.x; u2[1] += b.y;
        }
        float y[2];
#pragma unroll
        for (int i = 0; i < 2; i++) { const float gq = bfr(g2[i]); y[i] = bfr(__fdividef(gq, 1.f + __expf(-gq))) * bfr(u2[i]); }
        asm volatile("st.relaxed.gpu.global.u32 [%0], %1;" :: "l"(g_gu + (blk >> 1) * 128 + lane * 4 + warp * 2 + (blk & 1)), "r"(movm_t(pack2(y[0], y[1]))) : "memory");
    }
    TPROF(4);
    if (blk < 80) {
        uint32_t a[6][4], b[6][4];
#pragma unroll
        for (int k2 = 0; k2 < 6; k2++) ldsm4t(b[k2], tb + T_WD + (warp * 6 + k2) * 512 + lane * 16);
        for (int n = 0;; n++) {
            uint32_t m = 0;
#pragma unroll
            for (int k2 = 0; k2 < 6; k2++) asm volatile("ld.relaxed.gpu.global.v4.u32 {%0,%1,%2,%3}, [%4];" : "=r"(a[k2][0]), "=r"(a[k2][1]), "=r"(a[k2][2]), "=r"(a[k2][3]) : "l"(g_gu + (warp * 6 + k2) * 128 + lane * 4) : "memory");
#pragma unroll
            for (int k2 = 0; k2 < 6; k2++) m = umax3(umax3(m, a[k2][0], a[k2][1]), a[k2][2], a[k2][3]);
            if (!__any_sync(0xffffffffu, m == ~0u)) break;
            if (n > (1 << 22)) __trap();
        }
        TPROF(5);
        float d[2][4] = {{0, 0, 0, 0}, {0, 0, 0, 0}};
#pragma unroll
        for (int k2 = 0; k2 < 6; k2++) { mma16q(d[0], a[k2], b[k2][0], b[k2][1]); mma16q(d[1], a[k2], b[k2][2], b[k2][3]); }
        asm volatile("st.shared.v2.f32 [%0], {%1,%2};" :: "r"(tb + T_X + warp * 256 + lane * 8), "f"(d[0][0] + d[1][2]), "f"(d[0][1] + d[1][3]) : "memory");
        bar_sync(1, 256);
        if (warp == 0) {
            float y0 = 0, y1 = 0;
#pragma unroll
            for (int i = 0; i < 8; i++) { const float2 z = lds64f(tb + T_X + i * 256 + lane * 8); y0 += z.x; y1 += z.y; }
            const float sg = __fdividef(1.f, 1.f + __expf(-fr));
            *(uint32_t*)(ar.out + trow * DM + tcol) = add2(fx1, mul2(fgb, add2(fh2, mul2(pack2(y0, y1), pack2(sg, sg)))));
        }
    }
    TPROF(6);
}

__global__ void __cluster_dims__(3, 1, 1) __launch_bounds__(384, 1) k_chain(const __grid_constant__ ChainMaps mp, const __grid_constant__ ChainArgs ar) {
    const int D1 = ar.D1, DG = ar.DG;
    extern __shared__ __align__(1024) uint8_t smraw[];
    const uint32_t sm = SM_BASE + ((blockIdx.x % 3) << 24);
    if (smem_u32(smraw) != sm) __trap();
    uint32_t tid; asm volatile("mov.u32 %0, %%tid.x;" : "=r"(tid));
    const int warp = __shfl_sync(0xffffffffu, tid >> 5, 0), lane = tid & 31, wg = warp >> 2, w = warp & 3;
    const int blk = blockIdx.x, head = blk / 3, j = blk % 3;
    const int col0 = head * DH + j * 64;
    asm volatile("griddepcontrol.launch_dependents;");
#define PPROF(i)
    {
        const int mc0 = (blk >> 1) * 80 + (blk & 1) * 32, mcn = (blk & 1) ? 24 : 16;
        const int nrow = blk < 74 ? 2 : blk == 74 ? (warp < 8 ? 2 : 1) : 1;
        if (tid == 0) {
            mbar_init(sm + CB_PRE, 1);
            asm volatile("fence.mbarrier_init.release.cluster;" ::: "memory");
            const int n1 = blk < 74 ? 15360 : blk == 74 ? 10240 : 0;
            mbar_expect(sm + CB_PRE, 61440 + 1280 + 15360 + n1);
            bulk_g2s(sm + C_QM, ar.c, 1280, sm + CB_PRE);
#pragma unroll 1
            for (int c = 0; c < 4; c++) tma2d(sm + C_WO + 24576 + c * 15360, &mp.wmod, mc0, c * 160, sm + CB_PRE);
            bulk_g2s(sm + C_XR, ar.x + blk * 12 * DM, 15360, sm + CB_PRE);
            if (n1) bulk_g2s(sm + C_XR + 15360, ar.x + (1152 + blk * 12) * DM, n1, sm + CB_PRE);
        }
        if (tid == 32) {
#pragma unroll 1
            for (int c = 0; c < 14; c++) if (c != 5 && c != 12) mbar_init(sm + C_BAR + 8 * c, c == 2 ? 5 : c == 3 ? 6 : 1);
            asm volatile("fence.mbarrier_init.release.cluster;" ::: "memory");
            mbar_expect(sm + CB_SC, 2560); mbar_expect(sm + CB_OX, 2048);
        }
        if (warp == 2) {
            ((uint4*)g_acc)[blk * 32 + lane] = make_uint4(0, 0, 0, 0);
            if (blk < 12) ((uint4*)g_stamp)[blk * 32 + lane] = make_uint4(0, 0, 0, 0);
            else if (blk < 28) ((uint4*)g_key)[(blk - 12) * 32 + lane] = make_uint4(0, 0, 0, 0);
            else if (blk < 76) ((uint4*)g_gu)[(blk - 28) * 32 + lane] = make_uint4(~0u, ~0u, ~0u, ~0u);
            __threadfence();
        }
        PPROF(8);
        asm volatile("barrier.cluster.arrive.release.aligned; barrier.cluster.wait.acquire.aligned;" ::: "memory");
        PPROF(9);
        mbar_wait(sm + CB_PRE, 0);
        PPROF(10);
        if (tid == 352) {
            const uint64_t ef = policy_stream();
            mbar_expect(sm + CB_W, 2 * 81920);
#pragma unroll 1
            for (int c = 0; c < 10; c++) tma2d_ef(sm + C_WV + c * 8192, &mp.wq, col0, c * 64, sm + CB_W, ef);
        }
        if (tid < 320) {
            const uint32_t cv = lds32(sm + C_QM + tid * 4);
            asm volatile("st.shared.v2.f32 [%0], {%1,%2};" :: "r"(sm + C_QX + tid * 8), "f"(bfr(__fdividef(lo_f(cv), 1.f + __expf(-lo_f(cv))))),
                         "f"(bfr(__fdividef(hi_f(cv), 1.f + __expf(-hi_f(cv))))) : "memory");
        }
        __syncthreads();
        {
            float a0 = 0, a1 = 0;
            const uint32_t k0 = (tid / 24) * 40, wa0 = sm + C_WO + 24576 + k0 * 96 + (tid % 24) * 4;
#pragma unroll 4
            for (int i = 0; i < 40; i++) {
                const float sc = __uint_as_float(lds32(sm + C_QX + (k0 + i) * 4));
                const uint32_t wv = lds32(wa0 + i * 96);
                a0 += sc * lo_f(wv); a1 += sc * hi_f(wv);
            }
            asm volatile("st.shared.v2.f32 [%0], {%1,%2};" :: "r"(sm + C_MEM + tid * 8), "f"(a0), "f"(a1) : "memory");
        }
        __syncthreads();
        PPROF(11);
        if (warp == 0) {
            float a0 = 0, a1 = 0;
            const int cp = lane < mcn ? lane : 0;
#pragma unroll 4
            for (int i = 0; i < 16; i++) { const float2 v = lds64f(sm + C_MEM + (i * 24 + cp) * 8); a0 += v.x; a1 += v.y; }
            uint32_t* dst = (uint32_t*)(g_mod + mc0) + cp;
            *dst = pack2(a0, a1);
            const uint32_t rb = ld_rlx(dst);
            PPROF(1);
            if (__all_sync(0xffffffffu, rb == pack2(a0, a1)) && tid == 0) bump(blk < 32 ? &g_flags.mod : &g_flags.h);
            if (tid == 0) flag_wait(&g_flags.mod, 32);
            PPROF(2);
        }
        __syncthreads();
        uint32_t sv[10], tv[10], bad = 0;
#pragma unroll
        for (int i = 0; i < 10; i++) { sv[i] = __ldcg((const uint32_t*)g_mod + DM / 2 + lane + 32 * i); tv[i] = __ldcg((const uint32_t*)g_mod + lane + 32 * i); }
#pragma unroll 1
        for (int q = 0; q < nrow; q++) {
            uint32_t xv[10], hv[10];
#pragma unroll
            for (int i = 0; i < 10; i++) xv[i] = lds32(sm + C_XR + q * 15360 + warp * 1280 + lane * 4 + i * 128);
            ln_mod(xv, sv, tv, hv);
            uint32_t* dst = (uint32_t*)g_h + (q * 1152 + blk * 12 + warp) * (DM / 2) + lane;
#pragma unroll
            for (int i = 0; i < 10; i++) dst[32 * i] = hv[i];
#pragma unroll
            for (int i = 0; i < 10; i++) bad |= ld_rlx(dst + 32 * i) ^ hv[i];
        }
        if (__syncthreads_or(bad)) __trap();
        PPROF(3);
        if (tid == 0) {
            bump(&g_flags.h);
            flag_wait(&g_flags.h, 160);
            mbar_expect(sm + CB_XM, 8192); tma3d(sm + C_MEM, &mp.h2, 0, 0, sm + CB_XM);
            x_fill(mp, sm, 0, j, 0); x_fill(mp, sm, 0, j, 1);
            const uint64_t ef = policy_stream();
#pragma unroll 1
            for (int c = 0; c < 10; c++) tma2d_ef(sm + C_WO + c * 8192, &mp.wk, col0, c * 64, sm + CB_W, ef);
        }
        PPROF(4);
        __syncthreads();
        if (tid >= 64) {
#pragma unroll 1
            for (int i = tid - 64; i < 640 + 192 * 4; i += 320)
                asm volatile("prefetch.global.L2 [%0];" :: "l"(i < 640 ? ar.wv + (size_t)i * HD + col0 : ar.wo + (size_t)(head * DH + ((i - 640) >> 2)) * DM + j * 224 + min((i & 3) * 64, 639 - j * 224)));
        }
    }
    const int r = lane & 7, mi = lane >> 3;
    const uint32_t memrd = opaque(sm + C_MEM + lane * 16);
    constexpr float S_ACC = 64.f;
    if (wg < 2) {
        asm volatile("setmaxnreg.inc.sync.aligned.u32 %0;" :: "n"(REG_P));
        uint32_t wa[40][4];
        mbar_wait(sm + CB_W, 0);
#pragma unroll
        for (int ks = 0; ks < 40; ks++)
            ldsm4t(wa[ks], sm + ((wg == 0) == (ks < 20) ? C_WV : C_WO) + ((mi >> 1) * 8 + r) * 128 + (((2 * w + (mi & 1)) ^ r) << 4) + (ks % 20 / 4 * 8 + 4 * wg + (ks & 3)) * 2048);
        PPROF(5);
        bar_sync(1, 384);
        const uint32_t qst = opaque(sm + (wg == 0 ? C_QM : C_KM) + (2 * w + (mi & 1)) * 128 + r * 16);
        const uint32_t vrd = opaque(sm + C_WV + ((mi >> 1) * 8 + r) * 128 + (((2 * w + (mi & 1)) ^ r) << 4) + 4 * wg * 2048);
        const uint32_t mrd = opaque(memrd + wg * 1024);
        for (int s = 0; s < NSEG; s++) {
            const float un = s ? 1.f / S_ACC : 1.f;
            x_part(wa, sm, s, wg, w, opaque(mrd) >> 4 & 31, head);
            cut(s + ar.D2, 0);
            bar_sync(1, 384);
            if (warp == 0) { PROF(0); PROFG(24); }
            uint32_t b[3][4], a[5][4];
            float dv[2][4] = {{0, 0, 0, 0}, {0, 0, 0, 0}};
            auto fb = [&](int n) { return mrd + (n >> 1) * 2048 + (n & 1) * 512; };
            auto fa = [&](int k) { return vrd + (k >> 2) * 16384 + (k & 3) * 2048; };
            {
                float d[2][4] = {{0, 0, 0, 0}, {0, 0, 0, 0}}, g[2][4] = {{0, 0, 0, 0}, {0, 0, 0, 0}};
                ldsm4t(b[0], fb(0)); pin0(mrd); ldsm4t(b[1], fb(1)); pin0(mrd);
#pragma unroll
                for (int n = 0; n < 10; n++) {
                    const int c1 = (NCH == 2 || n >= 8);
                    if (n < 8) ldsm4t(b[(n + 2) % 3], fb(n + 2));
                    if (n + ALA >= 2 && n + ALA < 2 + VF) ldsm4t(a[2 + (n + ALA) % 3], fa(2 * (n + ALA)));
                    if (!VPOS && n >= 9 - VPRE && n < 9) ldsm4t(a[n - 9 + VPRE], fa(16 + n - 9 + VPRE));
                    mma16q(g[0], wa[20 + 2 * n], b[n % 3][0], b[n % 3][1]); mma16q(d[0], wa[2 * n], b[n % 3][0], b[n % 3][1]);
                    if (n >= 2 && n < 2 + VF) mma16q(dv[0], a[2 + n % 3], b[n % 3][0], b[n % 3][1]);
                    mma16q(g[c1], wa[21 + 2 * n], b[n % 3][2], b[n % 3][3]); mma16q(d[c1], wa[2 * n + 1], b[n % 3][2], b[n % 3][3]);
                    if (QCUT >> n & 1) cut(s + ar.D2, 1 + n);
                }
                const uint32_t xb = mrd - wg * 1024 - (C_MEM - C_VP) + w * 512;
                sts128f(xb + wg * 2048, g[0][0] + g[1][0], g[0][1] + g[1][1], g[0][2] + g[1][2], g[0][3] + g[1][3]);
                bar_sync(8, 256);
                const float4 z = lds128f(xb + (wg ^ 1) * 2048);
                if (VPOS) {
                    pin0(mrd);
#pragma unroll
                    for (int i = 0; i < VPRE; i++) ldsm4t(a[i], fa(16 + i));
                }
                stsm2t(qst, pack2((d[0][0] + d[1][0] + z.x) * un, (d[0][1] + d[1][1] + z.y) * un), pack2((d[0][2] + d[1][2] + z.z) * un, (d[0][3] + d[1][3] + z.w) * un));
            }
            bar_arrive(2, 384);
            if (w == 0) PROF(1 + wg);
            {
                if (warp == 3)
                    asm volatile(ELECTED("st.relaxed.gpu.global.u32 [%0], %1;") :: "l"(g_stamp + (s & 3) * 384 + (blk >> 3) * 32 + (blk & 7)), "r"((gtime() & ~31u) | ((s >> 2) + 1)) : "memory");
                PROXY_FENCE();
                bar_sync(7, 384);
                constexpr int NR = 16 - VF, NB = 4 + 12 - 2 * VF;
                auto kst = [&](int i) { return i < 4 ? 16 + i : i < NB ? i + 2 * VF : 5 + 2 * (i - NB); };
                const uint32_t mo = mrd + 256 + (mrd & 256);
                auto fc = [&](int p) { return 2 * p < NB ? fb(p + VF) : mo + (1 + (2 * p - NB) / 2) * 2048; };
#pragma unroll
                for (int i = VPRE; i < 4; i++) ldsm4t(a[i], fa(kst(i)));
#pragma unroll
                for (int i = 0; i < NR; i++) {
                    if (i + 4 < NR) ldsm4t(a[(i + 4) % 5], fa(kst(i + 4)));
                    if (!(i & 1) && i + 4 < NR) ldsm4t(b[(i / 2 + 1) % 3], fc(i / 2 + 2));
                    mma16q(dv[~i & 1], a[i % 5], b[(i / 2 + 2) % 3][2 * (i & 1)], b[(i / 2 + 2) % 3][2 * (i & 1) + 1]);
                }
                sts128f(mrd - (C_MEM - C_VP) + wg * 1024 + w * 512, dv[0][0] + dv[1][0], dv[0][1] + dv[1][1], dv[0][2] + dv[1][2], dv[0][3] + dv[1][3]);
            }
            if (warp == 0) bar_sync(4, 384);
            else bar_arrive(4, 384);
            if (warp == 0) {
                PROF(7);
                if (s + 1 < NSEG && elect()) {
                    mbar_expect(sm + CB_XM, 8192); tma3d(sm + C_MEM, &mp.h2, (s + 1) * SEG, 0, sm + CB_XM);
                }
            } else {
                if (wg == 1) {
                    if (w == 1) {
                        uint8_t* rec = g_att + (s * NH + head) * AT_REC;
                        w_bulk_s2g(rec + j * 8192, sm + C_QX, 8192); w_bulk_s2g(rec + AT_KM + j * 1024, sm + C_KM, 1024);
                        BULK_COMMIT();
                        if (s + 1 == NSEG) { BULK_WAIT(); seg_done(s, head); }
                    }
                    if (w == 2 && blk < 10 && s + 3 < NSEG)
                        asm volatile(ELECTED("cp.async.bulk.prefetch.L2.global [%0], 4096;") :: "l"((const uint8_t*)g_h + (s + 3) * (SEG * DM * 2) + blk * 4096) : "memory");
                } else if (w == 3) { if (s + 1 < NSEG) {
                    const uint32_t l = opaque(mrd) >> 4 & 31, tag = (s >> 2) + 1, now = gtime();
                    const uint32_t* sp = g_stamp + (s & 3) * 384 + (l >> 3) * 32 + (l & 7);
                    uint32_t t[3];
                    for (int n = 0;; n++) {
#pragma unroll
                        for (int i = 0; i < 3; i++) t[i] = ld_rlx(sp + i * 128);
                        if (!__any_sync(0xffffffffu, ((t[0] ^ tag) | (t[1] ^ tag) | (t[2] ^ tag)) & 31) || n > SPIN_LIMIT) break;
                    }
                    int all = -(1 << 30), own = all;
#pragma unroll
                    for (int i = 0; i < 3; i++) { const int d = t[i] - now; all = max(all, d); if ((i * 32 + l) / 3 == head) own = d; }
                    const int lag = min(__reduce_max_sync(0xffffffffu, all) - __reduce_max_sync(0xffffffffu, own), 8000);
                    PROFV(15, lag);
                    asm volatile("st.shared.u32 [%0], %1;" :: "r"(sm + C_LAG), "r"(D1 + ((lag * DG) >> 4)) : "memory");
                    bar_arrive(6, 160); }
                } else if (w == 2) {
                    if (s + 1 < NSEG) {
                        if ((s & 3) == 3) w_flag_wait(&g_flags.v[((s + 1) >> 2) * 32 + head], 2);
                        if (elect()) { mbar_expect(sm + CB_VX, 4096); bulk_g2s(sm + C_VX, g_att + ((s + 1) * NH + head) * AT_REC + AT_V + j * 4096, 4096, sm + CB_VX); }
                    }
                    if ((s & 3) == 1 && s + 3 < NSEG) asm volatile("prefetch.global.L2 [%0];" :: "l"(&g_flags.v[((s + 3) >> 2) * 32]));
                    if (s + 2 < NSEG && ((s & 3) != 2 || __all_sync(0xffffffffu, ld_rlx(&g_flags.v[((s + 2) >> 2) * 32 + head]) >= 2)))
                        asm volatile("prefetch.global.L2 [%0];" :: "l"(g_att + ((s + 2) * NH + head) * AT_REC + AT_V + j * 4096 + (opaque(mrd) << 3 & 0xf80)));
                } else if (s + 1 < NSEG) {
                    mbar_wait(sm + CB_OX, s & 1);
                    if (elect()) x_fill(mp, sm, s + 1, j, 1);
                }
            }
        }
        const int t2 = (opaque(mrd) >> 4 & 31) + warp * 32;
        last_blocks(mp, ar, sm, blk, t2);
        mod_tail(ar, sm + E_B, sm + EB_REL, blk, t2);
    } else {
        asm volatile("setmaxnreg.dec.sync.aligned.u32 %0;" :: "n"(REG_L));
        bar_sync(1, 384);
        if (tid == 256) {
            mbar_expect(sm + CB_W2, 81920 + 3 * WO_BLK);
#pragma unroll 1
            for (int c = 0; c < 10; c++) tma2d(sm + C_WV + c * 8192, &mp.wv, col0, c * 64, sm + CB_W2);
#pragma unroll 1
            for (int c = 0; c < 3; c++) tma3d(sm + C_WO + c * WO_BLK, &mp.wo, head * DH + (j + c) % 3 * 64, 7 * j, sm + CB_W2);
        }
        bar_sync(9, 384);
#pragma unroll 1
        for (int c = tid - 256; c < DM; c += 128) {
            uint32_t u[8];
#pragma unroll
            for (int i = 0; i < 8; i++) u[i] = __ldg((const unsigned short*)ar.mem0 + i * DM + c);
            asm volatile("st.shared.v4.u32 [%0], {%1,%2,%3,%4};" :: "r"(sm + C_MEM + c * 16), "r"(u[0] | u[1] << 16), "r"(u[2] | u[3] << 16), "r"(u[4] | u[5] << 16), "r"(u[6] | u[7] << 16) : "memory");
        }
        __syncwarp();
        if (w == 1) {
            w_flag_wait(&g_flags.v[head], 2);
            if (elect()) { mbar_expect(sm + CB_VX, 4096); bulk_g2s(sm + C_VX, g_att + head * AT_REC + AT_V + j * 4096, 4096, sm + CB_VX); }
        }
        mbar_wait(sm + CB_W2, 0);
        const float scale = 0.07216878364870322f;
        uint32_t va[8][4], mr = memrd;
#pragma unroll
        for (int i = 0; i < 8; i++) ldsm4t(va[i], sm + C_WV + ((mi >> 1) * 8 + r) * 128 + (((2 * w + (mi & 1)) ^ r) << 4) + i * 2048);
        for (int s = 0; s < NSEG; s++) {
            const float un = s ? 1.f / S_ACC : 1.f;
            bar_sync(1, 384);
            if (w == 0) {
                mbar_wait(sm + CB_XD, s & 1);
                if (s + 1 < NSEG) { if (elect()) x_fill(mp, sm, s + 1, j, 0); }
                else { if (BPOS != 2) wo_half(mp, sm, blk, 0); if (BPOS != 0) wo_half(mp, sm, blk, 1); }
            } else if (w == 1 && s > 0) { BULK_WAIT(); seg_done(s - 1, head); }
            const uint32_t l0 = mr >> 4 & 31, r0 = l0 & 7, m0 = l0 >> 3;
            uint32_t kb[2][4];
            {
                const uint32_t k7 = (4 * (w & 1) + (r0 >> 2) * 2 + (r0 & 1)) ^ (r0 << 1 & 4);
                const uint32_t kxrd = sm + C_KX + (16 * (w >> 1) + (r0 << 2 & 8) + k7) * 128 + ((m0 ^ k7) << 4);
                ldsm4(kb[0], kxrd); ldsm4(kb[1], kxrd ^ 64);
            }
            float vd[4];
            {
                uint32_t c[4][4];
#pragma unroll
                for (int i = 0; i < 4; i++) ldsm4t(c[i], mr + i * 512);
                float d[2][4] = {{0, 0, 0, 0}, {0, 0, 0, 0}};
#pragma unroll
                for (int i = 0; i < 8; i++) mma16q(d[i & 1], va[i], c[i >> 1][2 * (i & 1)], c[i >> 1][2 * (i & 1) + 1]);
#pragma unroll
                for (int i = 0; i < 4; i++) vd[i] = d[0][i] + d[1][i];
            }
            uint32_t zr = 0;
            if (w == 2)
                asm volatile("atom.relaxed.gpu.global.exch.b32 %0, [%1], 0;" : "=r"(zr)
                    : "l"(g_acc + ((s & 2) ^ 2) * (ACC_PAIR / 2) + (s & 1) * 512 + (blk >> 2) * 1024 + (blk & 3) * 128 + l0 * 4) : "memory");
            __syncwarp();
            const uint32_t sco = (w >> 1) * 512 + (l0 >> 2) * 64 + (w & 1) * 32 + ((l0 >> 1) & 1) * 16;
            const uint32_t qrd = sm + C_QM + ((m0 & 1) * 2 + (m0 >> 1)) * 128 + r0 * 16;
            const uint32_t scdst = sm + C_SC + j * 1280 + sco;
            const uint32_t rbase = mapa(sm, (j + 1 + (l0 & 1)) % 3) - sm;
            const uint32_t scm = 1024 + (l0 >> 1) * 16 - sco;
            const uint32_t v7 = r0 ^ (m0 << 2 & 4), vxrd = sm + C_VX + (8 * m0 + v7) * 128 + (((2 * w) ^ v7) << 4);
            mbar_wait(sm + CB_VX, s & 1);
            uint32_t vb[2][4];
            ldsm4t(vb[0], vxrd); ldsm4t(vb[1], vxrd ^ 16);
            const uint32_t word = sm + C_WO + (m0 & 1) * 4096 + ((m0 >> 1) * 8 + r0) * 64 + ((w ^ (r0 >> 1)) << 4);
            const uint32_t word6 = word + 6 * 4096 - (m0 & 1) * 3072;
            const uint32_t oxrd = sm + C_OX + l0 * 8;
            const uint32_t ord = sm + C_OX + (l0 >> 1) * 16 + w * 256 + (2 - (l0 & 1)) * 1024 + rbase;
            pin(mr, qrd, scdst, rbase, scm); pin(mr, scdst + scm + rbase, scdst + rbase, sm + CB_SC + rbase, scdst + scm); pin(mr, word, word6, oxrd, ord);
            pin(mr, __float_as_uint(vd[0]), __float_as_uint(vd[1]), __float_as_uint(vd[2]), __float_as_uint(vd[3]));
            bar_sync(2, 384);
            const bool odd = mr & 16;
            {
                uint32_t qa[2][4];
                ldsm4(qa[0], qrd); ldsm4(qa[1], qrd + 512);
                float x[4];
                if (w == 3) {
                    uint32_t km[2][4]; float y[4];
                    ldsm4(km[0], mr + (C_KM - C_MEM)); ldsm4(km[1], mr + (C_KM - C_MEM) + 512);
                    score_tile(qa, kb, odd, x); score_tile(qa, km, odd, y);
                    send_piece(x, scdst + rbase, sm + CB_SC + rbase, scdst); send_piece(y, scdst + scm + rbase, sm + CB_SC + rbase, scdst + scm);
                } else {
                    score_tile(qa, kb, odd, x);
                    send_piece(x, scdst + rbase, sm + CB_SC + rbase, scdst);
                }
            }
            bar_arrive(7, 384);
            if (elect()) mbar_arrive(sm + CB_SC);
            if (w == 0) PROF(4);
            const uint32_t vp = mr - (C_MEM - C_VP) + w * 512, vmst = mr + (C_VM - C_MEM) + w * 256;
            if (s + 1 == NSEG) {
                mbar_wait(sm + CB_SC, s & 1);
                bar_sync(4, 384);
                const float4 y0 = lds128f(vp), y1 = lds128f(vp + 2048);
                stsm2t(vmst, pack2((vd[0] + y0.x + y1.x) * un, (vd[1] + y0.y + y1.y) * un), pack2((vd[2] + y0.z + y1.z) * un, (vd[3] + y0.w + y1.w) * un));
                PROXY_FENCE();
                bar_sync(3, 128);
                if (w == 1) {
                    w_bulk_s2g(g_att + (s * NH + head) * AT_REC + AT_VM + j * 1024, sm + C_VM, 1024);
                    BULK_COMMIT();
                    if (BPOS == 0) wo_half(mp, sm, blk, 1);
                    BULK_WAIT(); seg_done(s, head);
                }
                __syncwarp();
                break;
            }
            cut(s + ar.D2, 0);
            mbar_wait(sm + CB_SC, s & 1);
            if (w == 0) PROF(8);
            float sv[10];
            {
                const uint32_t scrd = mr + (C_SC - C_MEM);
                float4 x[3], y[3]; float2 z[3];
#pragma unroll
                for (int p = 0; p < 3; p++) { x[p] = lds128f(scrd + p * 1280); y[p] = lds128f(scrd + p * 1280 + 512); z[p] = lds64f(oxrd + (C_SC - C_OX) + p * 1280 + 1024); }
                sv[0] = (x[0].x + x[1].x) + x[2].x; sv[1] = (x[0].y + x[1].y) + x[2].y; sv[2] = (x[0].z + x[1].z) + x[2].z; sv[3] = (x[0].w + x[1].w) + x[2].w;
                sv[4] = (y[0].x + y[1].x) + y[2].x; sv[5] = (y[0].y + y[1].y) + y[2].y; sv[6] = (y[0].z + y[1].z) + y[2].z; sv[7] = (y[0].w + y[1].w) + y[2].w;
                sv[8] = (z[0].x + z[1].x) + z[2].x; sv[9] = (z[0].y + z[1].y) + z[2].y;
            }
            float mx = fmaxf(fmaxf(fmaxf(sv[0], sv[1]), fmaxf(sv[2], sv[3])), fmaxf(fmaxf(fmaxf(sv[4], sv[5]), fmaxf(sv[6], sv[7])), fmaxf(sv[8], sv[9])));
            uint32_t a[NRING][4];
            auto frag = [&](int i) { const int p = i / 7, u = i % 7, o = (p >> 1) * WO_BLK + (p & 1) * 2048;
                                     return u == 3 ? word6 + o : word + o + (u > 3 ? 1024 + (u - 4) * 8192 : u * 8192); };
            mx = fmaxf(fmaxf(mx, __shfl_xor_sync(0xffffffffu, mx, 1)), fmaxf(__shfl_xor_sync(0xffffffffu, mx, 2), __shfl_xor_sync(0xffffffffu, mx, 3)));
            pin(mr, __float_as_uint(mx), 0, 0, 0);
            bar_sync(4, 384);
            {
                const float4 y0 = lds128f(vp), y1 = lds128f(vp + 2048);
                pin0(mr);
#pragma unroll
                for (int i = 0; i < NPRE; i++) ldsm4t(a[i], frag(i));
                pin0(mr);
                const float sl2e = scale * 1.4426950408889634f, mxl = mx * sl2e;
#pragma unroll
                for (int i = 9; i >= 0; i--) asm volatile("ex2.approx.ftz.f32 %0, %1;" : "=f"(sv[i]) : "f"(fmaf(sv[i], sl2e, -mxl)));
                const uint32_t pq[4] = {pack2(sv[0], sv[1]), pack2(sv[4], sv[5]), pack2(sv[2], sv[3]), pack2(sv[6], sv[7])}, pm = pack2(sv[8], sv[9]);
                if (w == 0) PROF(6);
                float o[2][4] = {{0, 0, 0, 0}, {0, 0, 0, 0}}, o2[2][4] = {{0, 0, 0, 0}, {0, 0, 0, 0}}, sx[4] = {0, 0, 0, 0};
                const uint32_t vm0 = pack2((vd[0] + y0.x + y1.x) * un, (vd[1] + y0.y + y1.y) * un), vm1 = pack2((vd[2] + y0.z + y1.z) * un, (vd[3] + y0.w + y1.w) * un);
                mma8(sx, pm, 0, 0x3f803f80u); mma8(o[0], pm, 0, vm0); mma8(o[1], pm, 0, vm1);
                mma16q(sx, pq, 0x3f803f80u, 0x3f803f80u);
#pragma unroll
                for (int u = 0; u < 2; u++) { mma16q(o[u], pq, vb[u][0], vb[u][1]); mma16q(o2[u], pq, vb[u][2], vb[u][3]); }
                float inv; asm("rcp.approx.ftz.f32 %0, %1;" : "=f"(inv) : "f"((sx[0] + sx[2]) * (1.f / S_ACC)));
                const uint32_t f0 = pack2((o[0][0] + o2[0][2]) * inv, (o[0][1] + o2[0][3]) * inv), f1 = pack2((o[1][0] + o2[1][2]) * inv, (o[1][1] + o2[1][3]) * inv);
                const uint32_t c = __shfl_xor_sync(0xffffffffu, f0, 1), d = __shfl_xor_sync(0xffffffffu, f1, 1);
                asm volatile("st.shared.v2.u32 [%0], {%1,%2};" :: "r"(oxrd + w * 256), "r"(f0), "r"(f1) : "memory");
                asm volatile("st.async.shared::cluster.mbarrier::complete_tx::bytes.v4.b32 [%0], {%1,%2,%3,%4}, [%5];"
                    :: "r"(ord), "r"(odd ? c : f0), "r"(odd ? d : f1), "r"(odd ? f0 : c), "r"(odd ? f1 : d), "r"(sm + CB_OX + rbase) : "memory");
                stsm2t(vmst, vm0, vm1);
            }
            if (w == 0) PROF(10);
#pragma unroll
            for (int i = NPRE; i < NRING; i++) ldsm4t(a[i], frag(i));
            bar_sync(3, 128);
            float e[5][4];
#pragma unroll
            for (int q = 0; q < 5; q++) e[q][0] = e[q][1] = e[q][2] = e[q][3] = 0.f;
            constexpr int LAG = 2;
            uint8_t* pdst = g_acc + ((s & 2) * (ACC_PAIR / 2) + (s & 1) * 512 + w * 2048 + j * 8192 - C_MEM - sm + mr);
#pragma unroll
            for (int h = 0; h < 3; h++) {
                uint32_t ob[4][2];
                if (h == 1) {
#pragma unroll
                    for (int i = 14 - LAG; i < 14; i++) ldsm4t(a[i % NRING], frag(i + NRING));
                    pin(mr, zr, (uint32_t)(uint64_t)pdst, (uint32_t)((uint64_t)pdst >> 32), 0);
                    mbar_wait(sm + CB_OX, s & 1);
                    if (w == 0) PROF(9);
                }
#pragma unroll
                for (int k = 0; k < 4; k++) lds64(ob[k], oxrd + h * 1024 + k * 256);
#pragma unroll
                for (int i = 14 * h; i < 14 * h + 14; i++) {
                    const int u = i % 7, k = 2 * (i / 7 & 1);
                    if (u == 3) { mma16q(e[3], a[i % NRING], ob[k][0], ob[k][1]); mma16q(e[4], a[i % NRING], ob[k + 1][0], ob[k + 1][1]); }
                    else mma16q(e[u & 3], a[i % NRING], ob[k + (u >> 2)][0], ob[k + (u >> 2)][1]);
                    if (i == B5AT) { pin(mr, a[i % NRING][0], a[i % NRING][1], a[i % NRING][2], a[i % NRING][3]); bar_arrive(5, 384); }
                    if (i >= LAG && !(i >= 14 && i < 14 + LAG) && i - LAG + NRING < 42) ldsm4t(a[(i - LAG) % NRING], frag(i - LAG + NRING));
                }
            }
            {
                const uint32_t w6 = pack2h(e[3][0] + e[4][2], e[3][1] + e[4][3]), one = 0x3c003c00u;
                asm volatile("red.relaxed.gpu.global.add.noftz.v4.f16x2 [%0], {%1,%2,%3,%4};"
                    :: "l"(pdst), "r"(pack2h(e[0][0], e[0][1])), "r"(pack2h(e[0][2], e[0][3])), "r"(pack2h(e[1][0], e[1][1])), "r"(odd ? w6 : one) : "memory");
                asm volatile("red.relaxed.gpu.global.add.noftz.v4.f16x2 [%0], {%1,%2,%3,%4};"
                    :: "l"(pdst + 1024), "r"(pack2h(e[1][2], e[1][3])), "r"(pack2h(e[2][0], e[2][1])), "r"(pack2h(e[2][2], e[2][3])), "r"(odd ? one : w6) : "memory");
            }
            const uint32_t tw = clock();
            if (w == 0) { PROF(14); PROFG(25); }
            PROXY_FENCE();
            bar_sync(6, 160);
            mr = opaque(mr);
            const uint32_t ln = mr >> 4 & 31, due = tw + lds32(sm + C_LAG);
            const uint32_t vr = sm + C_WV + ((ln >> 4) * 8 + (ln & 7)) * 128 + (((2 * w + (ln >> 3 & 1)) ^ (ln & 7)) << 4);
            const uint32_t ms0 = sm + C_MEM + w * 128 + (ln & 7) * 16 + (ln >> 3) * 512, ms1 = ms0 + (ln < 24 ? 2048 : 1536);
            if (BPOS == 2 && w == 0 && s + 2 == NSEG) wo_half(mp, sm, blk, 0);
            if (w == 2) { w_expect(sm + CB_SC, 2560); w_expect(sm + CB_OX, 2048); }
            if (w == 1) { w_bulk_s2g(g_att + (s * NH + head) * AT_REC + AT_VM + j * 1024, sm + C_VM, 1024); BULK_COMMIT(); }
            const uint8_t* src = pdst - j * 8192;
            pin(mr, ms0, ms1, (uint32_t)(uint64_t)src, (uint32_t)((uint64_t)src >> 32));
            pin(mr, vr, due, 0, 0);
            cut(s + ar.D2, 1);
#pragma unroll
            for (int i = 0; i < 8; i++) ldsm4t(va[i], vr + i * 2048);
            wait_until(due);
            if (w == 0) { PROF(5); PROFG(26); }
            uint4 v[6];
            auto fetch = [&]() {
#pragma unroll
                for (int k = 0; k < 6; k++)
                    asm volatile("ld.relaxed.gpu.global.v4.u32 {%0,%1,%2,%3}, [%4];" : "=r"(v[k].x), "=r"(v[k].y), "=r"(v[k].z), "=r"(v[k].w) : "l"(src + (k >> 1) * 8192 + (k & 1) * 1024) : "memory");
            };
            fetch();
            PROFV(20 + w, 0);
            bar_sync(9, 384);
#pragma unroll 1
            for (int n = 0; __any_sync(0xffffffffu, ~((odd ? v[1].w & v[3].w & v[5].w : v[0].w & v[2].w & v[4].w)) & 0x50005000u); n++) {
                PROFV(20 + w, n + 1);
                cut(n, SPIN_LIMIT);
                fetch();
            }
#pragma unroll
            for (int k = 0; k < 3; k++) {
                const uint4 x = v[2 * k], y = v[2 * k + 1];
                stsm4(ms0 + k * 3584, f16_to_bf16(x.x), f16_to_bf16(x.y), f16_to_bf16(x.z), f16_to_bf16(y.x));
                if (k < 2) { const uint32_t w6 = f16_to_bf16(odd ? x.w : y.w); stsm4(ms1 + k * 3584, f16_to_bf16(y.y), f16_to_bf16(y.z), w6, w6); }
                else asm volatile("stmatrix.sync.aligned.m8n8.x2.shared.b16 [%0], {%1,%2};" :: "r"(ms1 + k * 3584), "r"(f16_to_bf16(y.y)), "r"(f16_to_bf16(y.z)) : "memory");
            }
            if (w == 0) PROF(16);
        }
        if (w >= 2) end_loads(mp, ar, sm, blk, w - 2);
        else bar_arrive(5, 384);
        if (w == 0) {
            const int l = mr >> 4 & 31;
            if (blk < 14) {
                uint4 k = __ldcg((const uint4*)g_key + blk * 32 + l);
#pragma unroll 1
                for (int it = 0; it < 3; it++) {
                    const uint32_t m = __reduce_max_sync(0xffffffffu, max(max(k.x, k.y), max(k.z, k.w)));
                    if (k.x == m) k.x = 0; if (k.y == m) k.y = 0; if (k.z == m) k.z = 0; if (k.w == m) k.w = 0;
                    if (m && l < 20) asm volatile("prefetch.global.L2 [%0];" :: "l"((l < 10 ? g_h2 : g_x1 - 640) + (~m & (S_TOK - 1)) * DM + l * 64));
                }
            }
            mbar_wait(sm + EB_REL, 0);
            flags_release(l);
        }
    }
}

struct SideMaps { CUtensorMap h, wv, ost, o, wo, slab3, slab2, lnp[3]; };
constexpr int SD_ST = 43008, SD_NST = 4, SD_EPI = SD_NST * SD_ST, SD_PAR = SD_EPI + 2 * 24576, SD_BAR = SD_PAR + 6400, SD_SMEM = SD_BAR + 256;
#define VLEAD 16
#define SEG_LAST 60
#define N_LIGHT 6
#define B_HELP 13
#define AUNR_ 2
constexpr int AUNR = AUNR_;
#define KSO 6
#define KSA 3
#define B_8 10
#define B_16 13
__device__ __forceinline__ int o_shift(int b) { return b >= B_16 ? 4 : b >= B_8 ? 3 : 2; }
__device__ __forceinline__ int o_split(int b) { return 1 << o_shift(b); }
__device__ __forceinline__ uint32_t o_done(int b) { return b >= B_LATE ? 160 : 4 << o_shift(b); }
__device__ __forceinline__ int next_item(int lane) {
    const int b0 = lane & 15, hi = lane >> 4;
    for (int n = 0;; n++) {
        const uint32_t w0 = ld_rlx(g_flags.qk + lane), w1 = ld_rlx(g_flags.at + lane), w2 = ld_rlx(&g_flags.c[0][0] + lane), w3 = ld_rlx(&g_flags.c[2][0] + lane), w4 = ld_rlx(&g_flags.seg[SEG_LAST * 32]);
        const uint32_t o01 = __ballot_sync(0xffffffffu, w2 < 32), o23 = __ballot_sync(0xffffffffu, b0 < (hi ? 14 : B_LATE) && w3 < 2u * o_split(b0));
        const uint32_t ra = __ballot_sync(0xffffffffu, w0 >= (hi ? 64u : 192u)), rb = __ballot_sync(0xffffffffu, w1 >= (hi ? o_done(b0) : 256u));
        const int bv = __ffs(o01 | 0x10000) - 1, ba = __ffs(o01 >> 16 | 0x10000) - 1, bo = __ffs(o23 | 0x10000) - 1, bl = __ffs(o23 >> 16 | 0x10000) - 1;
        if (bl == 16 && ba == 16) return -1;
        const int bc = __ffs(~ra | 0x10000) - 1;
        const bool last = ba == 15 && w4 >= 6;
        const bool r1 = (ra & ra >> 16) >> ba & 1, r2 = (rb & 0xffff) >> bo & 1, r3 = rb >> 16 >> bl & 1;
        const int kind = ba == 16 ? (bo < 16 ? 2 : 3) : last ? 1 :
                         blockIdx.x < N_LIGHT ? (r1 ? 1 : r3 ? 3 : bv < 16 ? 0 : -1) :
                         bv < 16 && (bv <= bc + VLEAD || !r2) ? 0 : r1 && ba >= B_HELP ? 1 : r2 ? 2 : r1 ? 1 : r3 ? 3 : bo < ba ? 2 : -1;
        if (kind < 0) { if (n > (1 << 20)) __trap(); __nanosleep(300); continue; }
        const int b = kind == 3 ? bl : kind == 2 ? bo : kind == 1 ? ba : bv;
        uint32_t i = 0;
        if (lane == 0) asm volatile("atom.relaxed.gpu.global.add.u32 %0, [%1], 1;" : "=r"(i) : "l"(&g_flags.c[kind][b]) : "memory");
        i = __shfl_sync(0xffffffffu, i, 0);
        if (i < (kind < 2 ? 32u : 2u * o_split(b))) return kind << 16 | b << 8 | i | ((kind == 1 ? r1 : kind == 2 ? r2 : r3) ? 128 : 0);
    }
}

template <int NP, int CH>
__device__ __forceinline__ void tile_out(const float (&acc)[8 * NP], uint32_t eb, uint32_t efull, uint32_t eempty, int& eph, int lane) {
    const int r = lane & 7, mi = lane >> 3, row = (mi & 1) * 8 + r;
    mbar_wait(eempty, eph); eph ^= 1;
#pragma unroll
    for (int p = 0; p < NP; p++) {
        const int oc = 2 * p + (mi >> 1);
        stsm4(eb + (oc >> 3) * CH + row * 128 + (((oc & 7) ^ r) << 4), pack2(acc[8 * p], acc[8 * p + 1]), pack2(acc[8 * p + 2], acc[8 * p + 3]),
              pack2(acc[8 * p + 4], acc[8 * p + 5]), pack2(acc[8 * p + 6], acc[8 * p + 7]));
    }
    asm volatile("fence.proxy.async.shared::cta;" ::: "memory");
    __syncwarp();
    if (lane == 0) mbar_arrive(efull);
}

template <int MT>
__device__ __forceinline__ void attn_tile(uint32_t base, uint32_t dst, uint32_t eempty, int eph, int lane) {
    constexpr int NK = MT ? 5 : 3;
    const int r = lane & 7, mi = lane >> 3, g = lane >> 2, t = lane & 3;
    float sc[NK][4];
#pragma unroll
    for (int n = 0; n < NK; n++) sc[n][0] = sc[n][1] = sc[n][2] = sc[n][3] = 0.f;
#pragma unroll AUNR
    for (int k2 = 0; k2 < 6; k2++) {
        const uint32_t cb = (k2 >> 1) * 8192, c0 = (k2 & 1) * 4;
        uint32_t a0[4], a1[4], bb[NK][4];
        ldsm4(a0, base + cb + (16 * MT + (mi & 1) * 8 + r) * 128 + (((c0 + (mi >> 1)) ^ r) << 4));
        ldsm4(a1, base + cb + (16 * MT + (mi & 1) * 8 + r) * 128 + (((c0 + 2 + (mi >> 1)) ^ r) << 4));
#pragma unroll
        for (int n = 0; n < NK; n++)
            ldsm4(bb[n], n < NK - 1 ? base + 4096 + cb + (8 * n + r) * 128 + (((c0 + mi) ^ r) << 4) : base + 36864 + k2 * 512 + lane * 16);
#pragma unroll
        for (int n = 0; n < NK; n++) mma16(sc[n], a0[0], a0[1], a0[2], a0[3], bb[n][0], bb[n][1]);
#pragma unroll
        for (int n = 0; n < NK; n++) mma16(sc[n], a1[0], a1[1], a1[2], a1[3], bb[n][2], bb[n][3]);
    }
    const float scale = 0.07216878364870322f, l2e = 1.4426950408889634f;
    float v[2][2 * NK], mx[2], sum[2];
#pragma unroll
    for (int hf = 0; hf < 2; hf++) {
        mx[hf] = -INFINITY;
#pragma unroll
        for (int n = 0; n < NK; n++) {
            uint32_t u = pack2(sc[n][2 * hf], sc[n][2 * hf + 1]);
            u = pack2(lo_f(u) * scale, hi_f(u) * scale);
            const int lim = 16 * MT + 8 * hf + g - 8 * n - 2 * t;
            v[hf][2 * n] = (n < NK - 1 && lim < 0) ? -1e9f : lo_f(u);
            v[hf][2 * n + 1] = (n < NK - 1 && lim < 1) ? -1e9f : hi_f(u);
            mx[hf] = fmaxf(mx[hf], fmaxf(v[hf][2 * n], v[hf][2 * n + 1]));
        }
    }
#pragma unroll
    for (int o = 1; o < 4; o <<= 1)
#pragma unroll
        for (int hf = 0; hf < 2; hf++) mx[hf] = fmaxf(mx[hf], __shfl_xor_sync(0xffffffffu, mx[hf], o));
#pragma unroll
    for (int hf = 0; hf < 2; hf++) {
        sum[hf] = 0;
#pragma unroll
        for (int q = 0; q < 2 * NK; q++) { asm("ex2.approx.ftz.f32 %0, %1;" : "=f"(v[hf][q]) : "f"((v[hf][q] - mx[hf]) * l2e)); sum[hf] += v[hf][q]; }
    }
#pragma unroll
    for (int o = 1; o < 4; o <<= 1)
#pragma unroll
        for (int hf = 0; hf < 2; hf++) sum[hf] += __shfl_xor_sync(0xffffffffu, sum[hf], o);
    uint32_t pa[NK][2];
#pragma unroll
    for (int hf = 0; hf < 2; hf++) {
        const float inv = __fdividef(1.f, sum[hf]);
#pragma unroll
        for (int n = 0; n < NK; n++) pa[n][hf] = pack2(v[hf][2 * n] * inv, v[hf][2 * n + 1] * inv);
    }
    mbar_wait(eempty, eph);
#pragma unroll AUNR
    for (int n4 = 0; n4 < 6; n4++) {
        const uint32_t cb = (n4 >> 1) * 4096, c0 = (n4 & 1) * 4;
        uint32_t bm[4], bb[2 + 2 * MT][4];
        ldsm4t(bm, base + AT_VM + n4 * 512 + lane * 16);
#pragma unroll
        for (int u = 0; u < 2 + 2 * MT; u++) ldsm4t(bb[u], base + AT_V + cb + (16 * (u >> 1) + 8 * (mi & 1) + r) * 128 + (((c0 + 2 * (u & 1) + (mi >> 1)) ^ r) << 4));
        float o[4][4];
#pragma unroll
        for (int u = 0; u < 4; u++) { o[u][0] = o[u][1] = o[u][2] = o[u][3] = 0.f; mma8(o[u], pa[NK - 1][0], pa[NK - 1][1], bm[u]); }
#pragma unroll
        for (int u = 0; u < 4 + 4 * MT; u++) mma16(o[u & 3], pa[u >> 2 << 1][0], pa[u >> 2 << 1][1], pa[(u >> 2 << 1) + 1][0], pa[(u >> 2 << 1) + 1][1], bb[u >> 1][2 * (u & 1)], bb[u >> 1][2 * (u & 1) + 1]);
#pragma unroll
        for (int p = 0; p < 2; p++)
            stsm4(dst + (n4 >> 1) * 2048 + ((mi & 1) * 8 + r) * 128 + (((c0 + 2 * p + (mi >> 1)) ^ r) << 4), pack2(o[2 * p][0], o[2 * p][1]), pack2(o[2 * p][2], o[2 * p][3]),
                  pack2(o[2 * p + 1][0], o[2 * p + 1][1]), pack2(o[2 * p + 1][2], o[2 * p + 1][3]));
    }
}

__device__ __forceinline__ uint32_t ln_row(const uint32_t (&as)[10], const uint2 (&xin)[5], int row, uint32_t par, bf16* out, uint64_t ef, int lane) {
    const uint32_t pa = par + lane * 8;
    uint32_t xv[10], hv[10], sv[10], tv[10];
#pragma unroll
    for (int q = 0; q < 5; q++) {
        uint32_t ga[2], t[2], u[2];
        lds64(ga, pa + q * 256); lds64(t, pa + 1280 + q * 256); lds64(u, pa + 2560 + q * 256);
#pragma unroll
        for (int e = 0; e < 2; e++) {
            xv[2 * q + e] = add2(e ? xin[q].y : xin[q].x, mul2(ga[e], as[2 * q + e]));
            tv[2 * q + e] = t[e]; sv[2 * q + e] = u[e];
        }
        st_ef(g_x1 + row * DM + lane * 4 + q * 128, make_uint2(xv[2 * q], xv[2 * q + 1]), ef);
    }
    ln_mod(xv, sv, tv, hv);
    float rs = 0;
#pragma unroll
    for (int q = 0; q < 5; q++) {
        const int c = row * DM + lane * 4 + q * 128;
        const uint32_t h0 = hv[2 * q], h1 = hv[2 * q + 1];
        uint32_t gb[2], wv[2];
        lds64(gb, pa + 3840 + q * 256); lds64(wv, pa + 5120 + q * 256);
        rs += (lo_f(h0) * lo_f(wv[0]) + hi_f(h0) * hi_f(wv[0])) + (lo_f(h1) * lo_f(wv[1]) + hi_f(h1) * hi_f(wv[1]));
        st_ef(g_h2 + c, make_uint2(h0, h1), ef);
        st_ef(out + c, make_uint2(add2(xv[2 * q], mul2(gb[0], h0)), add2(xv[2 * q + 1], mul2(gb[1], h1))), ef);
    }
    const uint32_t rb = pack2(0.f, warp_sum(rs));
    return (((int)rb < 0 ? ~rb : rb | 0x80000000u) & 0xffff0000u) | (uint32_t)(2 * S_TOK - 1 - row);
}
__device__ __forceinline__ void key_out(uint32_t key) {
    __syncwarp();
    if (key) asm volatile("st.release.gpu.global.u32 [%0], %1;" :: "l"(g_key + (~key & (S_TOK - 1))), "r"(key) : "memory");
}

__global__ void __launch_bounds__(384, 1) k_side(const __grid_constant__ SideMaps mp, const bf16* __restrict__ x, const bf16* __restrict__ wr, bf16* __restrict__ out) {
    extern __shared__ __align__(1024) uint8_t smraw[];
    const uint32_t sm = smem_u32(smraw);
    if (sm & 1023) __trap();
    const uint32_t FULL = sm + SD_BAR, EMPTY = FULL + 32, EFULL = FULL + 64, EEMPTY = FULL + 80, IFULL = FULL + 96, IEMPTY = FULL + 128, IQ = FULL + 160, SCHED = FULL + 176, PARAM = FULL + 184;
    const int tid = threadIdx.x, warp = __shfl_sync(0xffffffffu, tid >> 5, 0), lane = tid & 31;
    const uint64_t ef = policy_stream();
    if (tid == 0) {
        for (int i = 0; i < SD_NST; i++) { mbar_init(FULL + 8 * i, 1); mbar_init(EMPTY + 8 * i, 2); }
        for (int i = 0; i < 2; i++) { mbar_init(EFULL + 8 * i, 4); mbar_init(EEMPTY + 8 * i, 1); }
        for (int i = 0; i < 4; i++) { mbar_init(IFULL + 8 * i, 1); mbar_init(IEMPTY + 8 * i, 11); }
        mbar_init(SCHED, 1); mbar_init(PARAM, 1);
        asm volatile("fence.mbarrier_init.release.cluster;" ::: "memory");
    }
    __syncthreads();
    if (warp >= 8) {
      asm volatile("setmaxnreg.dec.sync.aligned.u32 40;");
      if (warp == 8) {
        int st = 0, ph = 1;
        for (int q = 0;; q++) {
            mbar_wait(IFULL + 8 * (q & 3), (q >> 2) & 1);
            const int it = __shfl_sync(0xffffffffu, lds32(IQ + 4 * (q & 3)), 0);
            if (elect()) mbar_arrive(IEMPTY + 8 * (q & 3));
            if (it < 0) break;
            const int kind = it >> 16, b = (it >> 8) & 255, i = it & 63;
            const int nst = kind == 0 ? 10 : kind == 1 ? 4 : kind == 2 ? 192 >> o_shift(b) : b == 14 ? 4 : 2;
            const int ksched = kind == 0 ? 4 : kind == 2 ? nst - KSO : (it & 128) ? -1 : kind == 1 ? KSA : 0;
            if (ksched < 0 && elect()) mbar_arrive(SCHED);
            const bool look = !(it & 128);
            if (look && kind == 1) flag_wait(&g_flags.v[b * 32 + i], 2);
            if (look && kind == 3 && b < 14) flag_wait(&g_flags.o[b], o_done(b));
            for (int kb = 0; kb < nst; kb++) {
                mbar_wait(EMPTY + 8 * st, ph);
                const uint32_t base = sm + st * SD_ST, fb = FULL + 8 * st;
                if (look && kind == 1) flag_wait(&g_flags.seg[(b * 4 + kb) * 32 + i], 6);
                if (kb == ksched && elect()) mbar_arrive(SCHED);
                if (kind == 0) {
                    if (q == 0 && kb == 0) {
                        if (elect()) {
#pragma unroll 1
                            for (int c = 0; c < SD_NST; c++) tma3d(sm + c * SD_ST + 16384, &mp.wv, c * 64, i * 3, FULL + 8 * c);
#pragma unroll 1
                            for (int c = SD_NST; c < 10; c++)
                                asm volatile("cp.async.bulk.prefetch.tensor.3d.L2.global [%0, {0, %1, %2}];" :: "l"((uint64_t)&mp.wv), "r"(c * 64), "r"(i * 3) : "memory");
                        }
                        flag_wait(&g_flags.h, 160);
                    }
                    if (elect()) {
                        mbar_expect(fb, 40960);
                        tma2d(base, &mp.h, kb * 64, b * 128, fb);
                        if (q || kb >= SD_NST) tma3d(base + 16384, &mp.wv, kb * 64, i * 3, fb);
                    }
                } else if (kind == 1) {
                    if (elect()) {
                        mbar_expect(fb, 43008);
                        asm volatile("cp.async.bulk.shared::cluster.global.mbarrier::complete_tx::bytes.L2::cache_hint [%0], [%1], %2, [%3], %4;"
                            :: "r"(base), "l"(g_att + ((b * 4 + kb) * NH + i) * AT_REC), "r"(AT_REC), "r"(fb), "l"(ef) : "memory");
                    }
                } else if (kind == 3) {
                    if (b == 14 && !(kb & 1)) flag_wait(&g_flags.fin[(kb + (i >> 4)) * 32], 80);
                    if (elect()) { mbar_expect(fb, 40960); tma3d_ef(base, &mp.lnp[o_shift(b) - 2], i * (160 >> o_shift(b)), b * KSPLIT + (kb << o_shift(b) >> 1), fb, ef); }
                } else {
                    const int k0 = ((i >> 1) * nst + kb) * 32;
                    if (elect()) { mbar_expect(fb, 28672); tma3d(base + 8192, &mp.wo, k0, (i & 1) * 5, fb); }
                    if (look && kb % 12 == 0) flag_wait(&g_flags.pair[b * 16 + k0 / 384], 16);
                    if (elect()) tma2d_ef(base, &mp.o, k0, b * 128, fb, ef);
                }
                __syncwarp();
                if (++st == SD_NST) { st = 0; ph ^= 1; }
            }
        }
      } else if (warp == 11) {
        bool fin = false;
        for (int q = 0;; q++) {
            if (q) mbar_wait(SCHED, (q - 1) & 1);
            int it = fin ? -1 : next_item(lane);
            if (it < 0 && !fin && blockIdx.x < 32) { it = 3 << 16 | 14 << 8 | blockIdx.x; fin = true; }
            if (lane == 0) {
                if (it >> 16 == 3) {
                    const int b = (it >> 8) & 255, nr = 64 >> o_shift(b);
                    asm volatile("cp.async.bulk.prefetch.L2.global [%0], %1;" :: "l"(x + (b * 128 + (it & 63) * nr) * DM), "r"(nr * DM * 2) : "memory");
                }
                mbar_wait(IEMPTY + 8 * (q & 3), ((q >> 2) & 1) ^ 1);
                asm volatile("st.shared.u32 [%0], %1;" :: "r"(IQ + 4 * (q & 3)), "r"(it) : "memory");
                mbar_arrive(IFULL + 8 * (q & 3));
            }
            if (q == 0 && it >= 0) {
                flag_wait(&g_flags.h, 160);
                if (lane == 0) { mbar_expect(PARAM, 6400); bulk_g2s(sm + SD_PAR, g_mod + 2 * DM, 5120, PARAM); bulk_g2s(sm + SD_PAR + 5120, wr, 1280, PARAM); mbar_wait(PARAM, 0); }
            }
            __syncwarp();
            if (it < 0) break;
        }
        flags_release(lane);
      } else {
        if (lane == 0) {
            const int wg = warp - 9; int ph = 0;
            for (int q = 0;; q++) {
                mbar_wait(IFULL + 8 * (q & 3), (q >> 2) & 1);
                const int it = lds32(IQ + 4 * (q & 3));
                mbar_arrive(IEMPTY + 8 * (q & 3));
                if (it < 0) break;
                const int kind = it >> 16, b = (it >> 8) & 255, i = it & 63;
                if (kind & 1) continue;
#pragma unroll 1
                for (int rd = 0; rd < (kind == 2 ? 2 : 1); rd++) {
                    mbar_wait(EFULL + 8 * wg, ph); ph ^= 1;
                    const uint32_t src = sm + SD_EPI + wg * 24576;
                    if (kind == 2) tma3d_store(rd ? &mp.slab2 : &mp.slab3, (b * KSPLIT + (i >> 1)) * 128 + wg * 64, (i & 1) * 5 + rd * 3, src, ef, false);
                    else {
                        uint8_t* dst = g_att + ((b * 4 + wg * 2) * NH + i) * AT_REC + AT_V;
                        asm volatile("cp.async.bulk.global.shared::cta.bulk_group.L2::cache_hint [%0], [%1], 12288, %2;" :: "l"(dst), "r"(src), "l"(ef) : "memory");
                        asm volatile("cp.async.bulk.global.shared::cta.bulk_group.L2::cache_hint [%0], [%1], 12288, %2;" :: "l"(dst + NH * AT_REC), "r"(src + 12288), "l"(ef) : "memory");
                    }
                    asm volatile("cp.async.bulk.commit_group;" ::: "memory");
                    asm volatile("cp.async.bulk.wait_group.read 0;" ::: "memory");
                    mbar_arrive(EEMPTY + 8 * wg);
                }
                asm volatile("cp.async.bulk.wait_group 0;" ::: "memory");
                bump(kind == 0 ? &g_flags.v[b * 32 + i] : &g_flags.o[b]);
                if (kind == 0) bump(&g_flags.vb[b]);
            }
        }
      }
    } else {
        asm volatile("setmaxnreg.inc.sync.aligned.u32 232;");
        const int wg = warp >> 2, w = warp & 3;
        int st = 0, ph = 0, eph = 1;
        bool att = false;
        const uint32_t eb = sm + SD_EPI + wg * 24576;
        for (int q = 0;; q++) {
            mbar_wait(IFULL + 8 * (q & 3), (q >> 2) & 1);
            const int itc = lds32(IQ + 4 * (q & 3));
            __syncwarp();
            if (lane == 0) mbar_arrive(IEMPTY + 8 * (q & 3));
            if (itc < 0) break;
            const int kind = itc >> 16, b = (itc >> 8) & 255, i = itc & 63;
            if (att && kind != 1) { bar_sync(2 + wg, 128); att = false; }
            if (kind == 0) {
                float acc[96];
#pragma unroll
                for (int n = 0; n < 96; n++) acc[n] = 0.f;
                int prev = -1;
#pragma unroll 1
                for (int kb = 0; kb < 10; kb++) {
                    mbar_wait(FULL + 8 * st, ph);
                    const uint32_t base = sm + st * SD_ST;
                    WG_FENCE();
#pragma unroll
                    for (int ks = 0; ks < 4; ks++)
                        wgmma_ss_n192_tb(acc, mkdesc(base + wg * 8192 + ks * 32, 16, 1024), mkdesc(base + 16384 + ks * 2048, 8192, 1024), (kb | ks) != 0);
                    WG_COMMIT();
                    WG_WAIT(1);
                    if (prev >= 0 && (tid & 127) == 0) mbar_arrive(EMPTY + 8 * prev);
                    prev = st;
                    if (++st == SD_NST) { st = 0; ph ^= 1; }
                }
                WG_WAIT(0);
                if ((tid & 127) == 0) mbar_arrive(EMPTY + 8 * prev);
                tile_out<12, 4096>(acc, eb + (w >> 1) * 12288 + (w & 1) * 2048, EFULL + 8 * wg, EEMPTY + 8 * wg, eph, lane);
            } else if (kind == 1) {
                const int seg = warp >> 1, mt = warp & 1;
                int sst = st + seg, sph = ph; if (sst >= SD_NST) { sst -= SD_NST; sph ^= 1; }
                ph ^= 1;
                mbar_wait(FULL + 8 * sst, sph);
                const uint32_t base = sm + sst * SD_ST;
                if (mt) attn_tile<1>(base, eb + w * 6144, EEMPTY + 8 * wg, eph, lane);
                else attn_tile<0>(base, eb + w * 6144, EEMPTY + 8 * wg, eph, lane);
                asm volatile("fence.proxy.async.shared::cta;" ::: "memory");
                __syncwarp();
                if (lane == 0) {
                    mbar_arrive(EMPTY + 8 * sst);
                    tma3d_store(&mp.ost, b * 128 + warp * 16, i * 3, eb + w * 6144, ef, false);
                    BULK_COMMIT(); BULK_WAIT();
                    bump(b == 15 ? &g_flags.half[(i & 30) + wg] : &g_flags.pair[b * 16 + (i >> 1)]); bump(&g_flags.at[b]);
                }
                __syncwarp();
                att = true;
            } else if (kind == 2) {
                float acc[96], acc2[64];
#pragma unroll
                for (int n = 0; n < 96; n++) acc[n] = 0.f;
#pragma unroll
                for (int n = 0; n < 64; n++) acc2[n] = 0.f;
                int prev = -1;
#pragma unroll 1
                for (int kb = 192 >> o_shift(b); kb > 0; kb--) {
                    const uint32_t base = sm + st * SD_ST;
                    mbar_wait(FULL + 8 * st, ph);
                    WG_FENCE();
#pragma unroll
                    for (int ks = 0; ks < 2; ks++) {
                        const uint64_t da = (mkdesc(base + wg * 4096 + ks * 32, 16, 512) & ~(3ull << 62)) | (2ull << 62);
                        wgmma_ss_n192_tb(acc, da, mkdesc(base + 8192 + ks * 2048, 4096, 1024), 1);
                        wgmma_ss_n128_tb(acc2, da, mkdesc(base + 8192 + 3 * 4096 + ks * 2048, 4096, 1024), 1);
                    }
                    WG_COMMIT();
                    WG_WAIT(1);
                    if (prev >= 0 && (tid & 127) == 0) mbar_arrive(EMPTY + 8 * prev);
                    prev = st;
                    if (++st == SD_NST) { st = 0; ph ^= 1; }
                }
                WG_WAIT(0);
                if ((tid & 127) == 0) mbar_arrive(EMPTY + 8 * prev);
                tile_out<12, 8192>(acc, eb + w * 2048, EFULL + 8 * wg, EEMPTY + 8 * wg, eph, lane);
                tile_out<8, 8192>(acc2, eb + w * 2048, EFULL + 8 * wg, EEMPTY + 8 * wg, eph, lane);
            } else {
                const int sh = o_shift(b), nr = 64 >> sh, fw = b == 14 ? wg : 0, row0 = (b + fw) * 128 + i * nr, lw = warp - 4 * fw;
                if (fw) { st += 2; if (st >= SD_NST) { st -= SD_NST; ph ^= 1; } }
                int st1 = st + 1, ph1 = ph; if (st1 == SD_NST) { st1 = 0; ph1 ^= 1; }
                uint2 xin[2][5];
                uint32_t as[2][10] = {};
#pragma unroll
                for (int q2 = 0; q2 < 10; q2++) xin[q2 & 1][q2 >> 1] = ld_ef(x + (row0 + ((warp + 8 * (q2 & 1)) & (nr - 1))) * DM + lane * 4 + (q2 >> 1) * 128, ef);
                mbar_wait(PARAM, 0); mbar_wait(FULL + 8 * st, ph); mbar_wait(FULL + 8 * st1, ph1);
#pragma unroll 1
                for (int lrow = lw + (nr & 16) / 2; lrow >= 0 && lrow < nr; lrow -= 8) {
                    float a[20];
#pragma unroll
                    for (int q2 = 0; q2 < 20; q2++) a[q2] = 0.f;
#pragma unroll 1
                    for (int k = 0; k < (1 << sh >> 1); k++) {
                        const uint32_t ad = sm + ((k << (6 - sh)) + lrow) * 1280 + lane * 8;
                        uint32_t z[10][2];
#pragma unroll
                        for (int q2 = 0; q2 < 10; q2++) lds64(z[q2], ad + (q2 < 5 ? st : st1) * SD_ST + q2 % 5 * 256);
#pragma unroll
                        for (int q2 = 0; q2 < 10; q2++) { float* p = a + q2 % 5 * 4; p[0] += lo_f(z[q2][0]); p[1] += hi_f(z[q2][0]); p[2] += lo_f(z[q2][1]); p[3] += hi_f(z[q2][1]); }
                    }
#pragma unroll
                    for (int q2 = 0; q2 < 10; q2++) { as[1][q2] = as[0][q2]; as[0][q2] = pack2(a[2 * q2], a[2 * q2 + 1]); }
                }
                bar_sync(2 + wg, 128);
                if ((tid & 127) == 0) { mbar_arrive(EMPTY + 8 * st); mbar_arrive(EMPTY + 8 * st1); }
                uint32_t key = 0;
#pragma unroll 1
                for (int lrow = lw; lrow < nr; lrow += 8) {
                    const int row = row0 + lrow;
                    const uint32_t k1 = ln_row(as[0], xin[0], row, sm + SD_PAR, out, ef, lane);
                    if (lane == lrow >> 3) key = k1;
#pragma unroll
                    for (int q2 = 0; q2 < 5; q2++) { as[0][2 * q2] = as[1][2 * q2]; as[0][2 * q2 + 1] = as[1][2 * q2 + 1]; xin[0][q2] = xin[1][q2]; }
                }
                key_out(key);
                st = st1 + 1; ph = ph1; if (st == SD_NST) { st = 0; ph ^= 1; }
            }
        }
    }
    __syncwarp();
    asm volatile("griddepcontrol.wait;" ::: "memory");
}

#define P_D1 650
#define P_DL 700
#define P_DG 29
typedef CUresult (*EncodeFn)(CUtensorMap*, CUtensorMapDataType, cuuint32_t, void*, const cuuint64_t*, const cuuint64_t*, const cuuint32_t*, const cuuint32_t*,
                             CUtensorMapInterleave, CUtensorMapSwizzle, CUtensorMapL2promotion, CUtensorMapFloatOOBfill);
static EncodeFn s_encode = nullptr;
static void make_map(CUtensorMap* m, const void* p, int rows, int cols, int box_rows, int box_cols = 64) {
    cuuint64_t dims[2] = {(cuuint64_t)cols, (cuuint64_t)rows}, strides[1] = {(cuuint64_t)cols * 2};
    cuuint32_t box[2] = {(cuuint32_t)box_cols, (cuuint32_t)box_rows}, es[2] = {1, 1};
    s_encode(m, CU_TENSOR_MAP_DATA_TYPE_BFLOAT16, 2, (void*)p, dims, strides, box, es, CU_TENSOR_MAP_INTERLEAVE_NONE,
             box_cols == 64 ? CU_TENSOR_MAP_SWIZZLE_128B : box_cols == 32 ? CU_TENSOR_MAP_SWIZZLE_64B : CU_TENSOR_MAP_SWIZZLE_NONE, CU_TENSOR_MAP_L2_PROMOTION_L2_256B, CU_TENSOR_MAP_FLOAT_OOB_FILL_NONE);
}
static void make_map3(CUtensorMap* m, const void* p, int rows, int cols, int box_rows, int box_chunks, int cw = 64) {
    cuuint64_t dims[3] = {(cuuint64_t)cw, (cuuint64_t)rows, (cuuint64_t)(cols / cw)}, strides[2] = {(cuuint64_t)cols * 2, (cuuint64_t)cw * 2};
    cuuint32_t box[3] = {(cuuint32_t)cw, (cuuint32_t)box_rows, (cuuint32_t)box_chunks}, es[3] = {1, 1, 1};
    s_encode(m, CU_TENSOR_MAP_DATA_TYPE_BFLOAT16, 3, (void*)p, dims, strides, box, es, CU_TENSOR_MAP_INTERLEAVE_NONE,
             cw == 64 ? CU_TENSOR_MAP_SWIZZLE_128B : CU_TENSOR_MAP_SWIZZLE_64B, CU_TENSOR_MAP_L2_PROMOTION_L2_256B, CU_TENSOR_MAP_FLOAT_OOB_FILL_NONE);
}
template <typename T> static void* sym(T& s) { void* p = nullptr; cudaGetSymbolAddress(&p, s); return p; }

extern "C" void kernel_launch(void* const* d_in, const int* in_sizes, int n_in, void* d_out, int out_size) {
    const bf16 *x = (const bf16*)d_in[0], *mem0 = (const bf16*)d_in[1], *Wq = (const bf16*)d_in[2], *Wk = (const bf16*)d_in[3],
               *Wv = (const bf16*)d_in[4], *Wo = (const bf16*)d_in[5], *wr = (const bf16*)d_in[8], *wgate = (const bf16*)d_in[9],
               *wup = (const bf16*)d_in[10], *wdown = (const bf16*)d_in[11], *c = (const bf16*)d_in[12], *wmod = (const bf16*)d_in[13];
    bf16* out = (bf16*)d_out;
    if (!s_encode) {
        cudaDriverEntryPointQueryResult qr;
        cudaGetDriverEntryPoint("cuTensorMapEncodeTiled", (void**)&s_encode, cudaEnableDefault, &qr);
        cudaFuncSetAttribute(k_side, cudaFuncAttributeMaxDynamicSharedMemorySize, SD_SMEM);
        cudaFuncSetAttribute(k_chain, cudaFuncAttributeMaxDynamicSharedMemorySize, C_SMEM);
    }
    ChainMaps cm; SideMaps sd;
    make_map(&sd.h, sym(g_h), S_TOK, DM, 128); make_map3(&sd.wv, Wv, DM, HD, 64, 3);
    make_map3(&sd.ost, sym(g_o), S_TOK, HD, 16, 3); make_map(&sd.o, sym(g_o), S_TOK, HD, 128, 32); make_map3(&sd.wo, Wo, HD, DM, 32, 5);
    make_map3(&sd.slab3, sym(g_slab), 16 * KSPLIT * 128, DM, 64, 3); make_map3(&sd.slab2, sym(g_slab), 16 * KSPLIT * 128, DM, 64, 2);
    make_map3(&cm.wo15, Wo, HD, DM, 192, 2); make_map3(&cm.o15, sym(g_o), S_TOK, HD, 64, 2); make_map3(&cm.slab16, sym(g_slab), 16 * KSPLIT * 128, DM, 16, 2);
    for (int i = 0; i < 3; i++) {
        cuuint64_t dims[3] = {256, 320, 16 * KSPLIT}, strides[2] = {512, 128 * DM * 2};
        cuuint32_t box[3] = {256, 40u >> i, 2u << i}, es[3] = {1, 1, 1};
        s_encode(&sd.lnp[i], CU_TENSOR_MAP_DATA_TYPE_BFLOAT16, 3, sym(g_slab), dims, strides, box, es, CU_TENSOR_MAP_INTERLEAVE_NONE,
                 CU_TENSOR_MAP_SWIZZLE_NONE, CU_TENSOR_MAP_L2_PROMOTION_L2_256B, CU_TENSOR_MAP_FLOAT_OOB_FILL_NONE);
    }
    make_map(&cm.wq, Wq, DM, HD, 64); make_map(&cm.wk, Wk, DM, HD, 64); make_map(&cm.wv, Wv, DM, HD, 64); make_map3(&cm.wo, Wo, HD, DM, 64, 7, 32);
    make_map3(&cm.h2, sym(g_h), S_TOK, DM, 32, 2);
    make_map(&cm.wmod, wmod, DM, 6 * DM, 160, 48);
    ChainArgs ar = {x, mem0, c, Wv, Wo, wr, wgate, wup, wdown, out, P_D1, P_DL, P_DG};
    k_chain<<<96, 384, C_SMEM>>>(cm, ar);
    cudaLaunchConfig_t cfg = {};
    cfg.gridDim = dim3(N_SIDE); cfg.blockDim = dim3(384); cfg.dynamicSmemBytes = SD_SMEM; cfg.stream = cudaStreamPerThread;
    cudaLaunchAttribute at[1]; at[0].id = cudaLaunchAttributeProgrammaticStreamSerialization; at[0].val.programmaticStreamSerializationAllowed = 1;
    cfg.attrs = at; cfg.numAttrs = 1;
    cudaLaunchKernelEx(&cfg, k_side, sd, x, wr, out);
}
```

```cpp
#include <cuda_runtime.h>
#include <cuda_bf16.h>
#include <cuda.h>
#include <stdint.h>
#include <stdio.h>
#include <string.h>
#include <stdlib.h>

typedef __nv_bfloat16 bf16;
constexpr int S_TOK = 2048, DM = 640, NH = 32, DH = 192, HD = NH * DH, NSEG = 64, SEG = 32, FF = 1536;

__device__ bf16 g_mod[6 * DM];
__device__ bf16 g_h[S_TOK * DM];
constexpr int AT_REC = 43008, AT_V = 24576, AT_KM = 36864, AT_VM = 39936;
__device__ __align__(1024) uint8_t g_att[NSEG * NH * AT_REC];
__device__ bf16 g_o[S_TOK * HD];
__device__ bf16 g_A[S_TOK * DM];
__device__ bf16 g_x1[S_TOK * DM];
__device__ bf16 g_h2[S_TOK * DM];
__device__ __align__(128) uint32_t g_key[S_TOK];
__device__ int g_idx[8];
__device__ __align__(128) uint32_t g_gu[FF / 8 * 32];
constexpr int ACC_PAIR = 24 * 1024;
__device__ __align__(1024) uint8_t g_acc[2 * ACC_PAIR];
__device__ __align__(1024) uint32_t g_stamp[4 * 12 * 32];
constexpr int KSPLIT = 16;
__device__ bf16 g_slab[16 * KSPLIT * 128 * DM];
struct __align__(128) Flags {
    uint32_t qk[16], vb[16];
    uint32_t at[16], o[16];
    uint32_t c[4][16];
    uint32_t half[32];
    uint32_t fin[4 * 32];
    uint32_t v[16 * 32];
    uint32_t seg[64 * 32];
    uint32_t pair[16 * 16];
    uint32_t h, pad2[31], done, mod, pad3[30];
    uint32_t mod1[DM];
    uint32_t wmax[96];
};
__device__ Flags g_flags;

__device__ __forceinline__ uint32_t smem_u32(const void* p) { return (uint32_t)__cvta_generic_to_shared(p); }
__device__ __forceinline__ uint32_t pack2(float lo, float hi) {
    uint32_t r; asm("cvt.rn.bf16x2.f32 %0, %1, %2;" : "=r"(r) : "f"(hi), "f"(lo)); return r;
}
__device__ __forceinline__ float bfr(float x) { return __uint_as_float(pack2(0.f, x)); }
__device__ __forceinline__ float inv_std(float var) {
    float s, r; asm("sqrt.approx.f32 %0, %1;" : "=f"(s) : "f"(bfr(bfr(var) + 1e-5f))); asm("rcp.approx.f32 %0, %1;" : "=f"(r) : "f"(bfr(s))); return r;
}
__device__ __forceinline__ float lo_f(uint32_t v) { return __uint_as_float(v << 16); }
__device__ __forceinline__ float hi_f(uint32_t v) { return __uint_as_float(v & 0xffff0000u); }
__device__ __forceinline__ void mbar_init(uint32_t bar, int cnt) { asm volatile("mbarrier.init.shared::cta.b64 [%0], %1;" :: "r"(bar), "r"(cnt) : "memory"); }
__device__ __forceinline__ void mbar_expect(uint32_t bar, int bytes) { asm volatile("mbarrier.arrive.expect_tx.shared::cta.b64 _, [%0], %1;" :: "r"(bar), "r"(bytes) : "memory"); }
__device__ __forceinline__ void mbar_arrive(uint32_t bar) { asm volatile("mbarrier.arrive.shared::cta.b64 _, [%0];" :: "r"(bar) : "memory"); }
__device__ __forceinline__ bool mbar_try(uint32_t bar, int par) {
    uint32_t ok; asm volatile("{ .reg .pred p; mbarrier.try_wait.parity.shared::cta.b64 p, [%1], %2; selp.u32 %0, 1, 0, p; }" : "=r"(ok) : "r"(bar), "r"(par) : "memory"); return ok;
}
__device__ __forceinline__ bool mbar_try_cluster(uint32_t bar, int par) {
    uint32_t ok; asm volatile("{ .reg .pred p; mbarrier.try_wait.parity.acquire.cluster.shared::cta.b64 p, [%1], %2; selp.u32 %0, 1, 0, p; }" : "=r"(ok) : "r"(bar), "r"(par) : "memory"); return ok;
}
__device__ __forceinline__ bool mbar_test(uint32_t bar, uint32_t par) {
    uint32_t ok; asm volatile("{ .reg .pred p; mbarrier.test_wait.parity.shared::cta.b64 p, [%1], %2; selp.u32 %0, 1, 0, p; }" : "=r"(ok) : "r"(bar), "r"(par) : "memory"); return ok;
}
constexpr int SPIN_LIMIT = 1 << 18;
__device__ __forceinline__ void mbar_wait(uint32_t bar, uint32_t par) {
    asm volatile("{ .reg .pred p, q; .reg .u32 n; mov.u32 n, 0;\n"
                 "W_%=: mbarrier.try_wait.parity.shared::cta.b64 p, [%0], %1;\n"
                 "@p bra.uni D_%=;\n"
                 "add.u32 n, n, 1; setp.lt.u32 q, n, 0x200000; @q bra.uni W_%=;\n"
                 "trap;\n"
                 "D_%=: }" :: "r"(bar), "r"(par) : "memory");
}
__device__ __forceinline__ void tma2d(uint32_t dst, const CUtensorMap* m, int c0, int c1, uint32_t bar) {
    asm volatile("cp.async.bulk.tensor.2d.shared::cluster.global.mbarrier::complete_tx::bytes [%0], [%1, {%3, %4}], [%2];"
        :: "r"(dst), "l"((uint64_t)m), "r"(bar), "r"(c0), "r"(c1) : "memory");
}
__device__ __forceinline__ void tma2d_mc(uint32_t dst, const CUtensorMap* m, int c0, int c1, uint32_t bar, uint16_t mask) {
    asm volatile("cp.async.bulk.tensor.2d.shared::cluster.global.mbarrier::complete_tx::bytes.multicast::cluster [%0], [%1, {%3, %4}], [%2], %5;"
        :: "r"(dst), "l"((uint64_t)m), "r"(bar), "r"(c0), "r"(c1), "h"(mask) : "memory");
}
__device__ __forceinline__ uint64_t policy_stream() { uint64_t p; asm("createpolicy.fractional.L2::evict_first.b64 %0, 1.0;" : "=l"(p)); return p; }
__device__ __forceinline__ void tma2d_ef(uint32_t dst, const CUtensorMap* m, int c0, int c1, uint32_t bar, uint64_t pol) {
    asm volatile("cp.async.bulk.tensor.2d.shared::cluster.global.mbarrier::complete_tx::bytes.L2::cache_hint [%0], [%1, {%3, %4}], [%2], %5;"
        :: "r"(dst), "l"((uint64_t)m), "r"(bar), "r"(c0), "r"(c1), "l"(pol) : "memory");
}
__device__ __forceinline__ void tma3d(uint32_t dst, const CUtensorMap* m, int row, int chunk, uint32_t bar) {
    asm volatile("cp.async.bulk.tensor.3d.shared::cluster.global.mbarrier::complete_tx::bytes [%0], [%1, {0, %3, %4}], [%2];"
        :: "r"(dst), "l"((uint64_t)m), "r"(bar), "r"(row), "r"(chunk) : "memory");
}
__device__ __forceinline__ void tma3d_ef(uint32_t dst, const CUtensorMap* m, int row, int chunk, uint32_t bar, uint64_t pol) {
    asm volatile("cp.async.bulk.tensor.3d.shared::cluster.global.mbarrier::complete_tx::bytes.L2::cache_hint [%0], [%1, {0, %3, %4}], [%2], %5;"
        :: "r"(dst), "l"((uint64_t)m), "r"(bar), "r"(row), "r"(chunk), "l"(pol) : "memory");
}
__device__ __forceinline__ void tma3d_store(const CUtensorMap* m, int row, int chunk, uint32_t src, uint64_t pol, bool hint) {
    if (hint) asm volatile("cp.async.bulk.tensor.3d.global.shared::cta.bulk_group.L2::cache_hint [%0, {0, %2, %3}], [%1], %4;"
        :: "l"((uint64_t)m), "r"(src), "r"(row), "r"(chunk), "l"(pol) : "memory");
    else asm volatile("cp.async.bulk.tensor.3d.global.shared::cta.bulk_group [%0, {0, %2, %3}], [%1];"
        :: "l"((uint64_t)m), "r"(src), "r"(row), "r"(chunk) : "memory");
}
__device__ __forceinline__ bool elect() { uint32_t p; asm volatile("{ .reg .pred e; elect.sync _|e, -1; selp.u32 %0, 1, 0, e; }" : "=r"(p)); return p; }
__device__ __forceinline__ uint2 ld_ef(const void* p, uint64_t pol) {
    uint2 v; asm volatile("ld.relaxed.gpu.global.L2::cache_hint.v2.u32 {%0,%1}, [%2], %3;" : "=r"(v.x), "=r"(v.y) : "l"(p), "l"(pol)); return v;
}
__device__ __forceinline__ void st_ef(void* p, uint2 v, uint64_t pol) {
    asm volatile("st.global.L2::cache_hint.v2.u32 [%0], {%1,%2}, %3;" :: "l"(p), "r"(v.x), "r"(v.y), "l"(pol) : "memory");
}
__device__ __forceinline__ void tma2d_prefetch(const CUtensorMap* m, int c0, int c1) {
    asm volatile("cp.async.bulk.prefetch.tensor.2d.L2.global [%0, {%1, %2}];" :: "l"((uint64_t)m), "r"(c0), "r"(c1) : "memory");
}
__device__ __forceinline__ void mbar_arrive_remote(uint32_t bar) { asm volatile("mbarrier.arrive.relaxed.cluster.shared::cluster.b64 _, [%0];" :: "r"(bar) : "memory"); }
__device__ __forceinline__ void tma2d_store(const CUtensorMap* m, int c0, int c1, uint32_t src) {
    asm volatile("cp.async.bulk.tensor.2d.global.shared::cta.bulk_group [%0, {%2, %3}], [%1];"
        :: "l"((uint64_t)m), "r"(src), "r"(c0), "r"(c1) : "memory");
}
__device__ __forceinline__ void bulk_g2s(uint32_t dst, const void* src, int bytes, uint32_t bar) {
    asm volatile("cp.async.bulk.shared::cluster.global.mbarrier::complete_tx::bytes [%0], [%1], %2, [%3];" :: "r"(dst), "l"(src), "r"(bytes), "r"(bar) : "memory");
}
__device__ __forceinline__ void ldsm4(uint32_t (&r)[4], uint32_t a) {
    asm volatile("ldmatrix.sync.aligned.m8n8.x4.shared.b16 {%0,%1,%2,%3}, [%4];" : "=r"(r[0]), "=r"(r[1]), "=r"(r[2]), "=r"(r[3]) : "r"(a) : "memory");
}
__device__ __forceinline__ void ldsm4t(uint32_t (&r)[4], uint32_t a) {
    asm volatile("ldmatrix.sync.aligned.m8n8.x4.trans.shared.b16 {%0,%1,%2,%3}, [%4];" : "=r"(r[0]), "=r"(r[1]), "=r"(r[2]), "=r"(r[3]) : "r"(a) : "memory");
}
__device__ __forceinline__ void stsm4(uint32_t a, uint32_t r0, uint32_t r1, uint32_t r2, uint32_t r3) {
    asm volatile("stmatrix.sync.aligned.m8n8.x4.shared.b16 [%0], {%1,%2,%3,%4};" :: "r"(a), "r"(r0), "r"(r1), "r"(r2), "r"(r3) : "memory");
}
__device__ __forceinline__ void stsm4t(uint32_t a, uint32_t r0, uint32_t r1, uint32_t r2, uint32_t r3) {
    asm volatile("stmatrix.sync.aligned.m8n8.x4.trans.shared.b16 [%0], {%1,%2,%3,%4};" :: "r"(a), "r"(r0), "r"(r1), "r"(r2), "r"(r3) : "memory");
}
__device__ __forceinline__ void stsm2t(uint32_t a, uint32_t r0, uint32_t r1) {
    asm volatile("stmatrix.sync.aligned.m8n8.x2.trans.shared.b16 [%0], {%1,%2};" :: "r"(a), "r"(r0), "r"(r1) : "memory");
}
__device__ __forceinline__ uint32_t movm_t(uint32_t v) { uint32_t r; asm volatile("movmatrix.sync.aligned.m8n8.trans.b16 %0, %1;" : "=r"(r) : "r"(v)); return r; }
__device__ __forceinline__ void mma16(float (&d)[4], uint32_t a0, uint32_t a1, uint32_t a2, uint32_t a3, uint32_t b0, uint32_t b1) {
    asm volatile("mma.sync.aligned.m16n8k16.row.col.f32.bf16.bf16.f32 {%0,%1,%2,%3}, {%4,%5,%6,%7}, {%8,%9}, {%0,%1,%2,%3};"
        : "+f"(d[0]), "+f"(d[1]), "+f"(d[2]), "+f"(d[3]) : "r"(a0), "r"(a1), "r"(a2), "r"(a3), "r"(b0), "r"(b1));
}
__device__ __forceinline__ void mma8(float (&d)[4], uint32_t a0, uint32_t a1, uint32_t b0) {
    asm volatile("mma.sync.aligned.m16n8k8.row.col.f32.bf16.bf16.f32 {%0,%1,%2,%3}, {%4,%5}, {%6}, {%0,%1,%2,%3};"
        : "+f"(d[0]), "+f"(d[1]), "+f"(d[2]), "+f"(d[3]) : "r"(a0), "r"(a1), "r"(b0));
}
__device__ __forceinline__ uint32_t mapa(uint32_t a, uint32_t r) { uint32_t o; asm volatile("mapa.shared::cluster.u32 %0, %1, %2;" : "=r"(o) : "r"(a), "r"(r)); return o; }
__device__ __forceinline__ void bar_sync(int id, int n) { asm volatile("bar.sync %0, %1;" :: "r"(id), "r"(n) : "memory"); }
__device__ __forceinline__ void bar_arrive(int id, int n) { asm volatile("bar.arrive %0, %1;" :: "r"(id), "r"(n) : "memory"); }
__device__ __forceinline__ uint64_t mkdesc(uint32_t addr, uint32_t lbo, uint32_t sbo) {
    return (uint64_t)((addr & 0x3FFFF) >> 4) | ((uint64_t)(lbo >> 4) << 16) | ((uint64_t)(sbo >> 4) << 32) | (1ull << 62);
}
#define WG_FENCE()  asm volatile("wgmma.fence.sync.aligned;" ::: "memory")
#define WG_COMMIT() asm volatile("wgmma.commit_group.sync.aligned;" ::: "memory")
#define WG_WAIT(n)  asm volatile("wgmma.wait_group.sync.aligned %0;" :: "n"(n) : "memory")

__device__ __forceinline__ void wgmma_ss_n192_tb(float (&d)[96], uint64_t a, uint64_t b, int acc) {
    asm volatile("{ .reg .pred p; setp.ne.b32 p, %98, 0;\n"
        "wgmma.mma_async.sync.aligned.m64n192k16.f32.bf16.bf16 {%0,%1,%2,%3,%4,%5,%6,%7,%8,%9,%10,%11,%12,%13,%14,%15,%16,%17,%18,%19,%20,%21,%22,%23,%24,%25,%26,%27,%28,%29,%30,%31,%32,%33,%34,%35,%36,%37,%38,%39,%40,%41,%42,%43,%44,%45,%46,%47,%48,%49,%50,%51,%52,%53,%54,%55,%56,%57,%58,%59,%60,%61,%62,%63,%64,%65,%66,%67,%68,%69,%70,%71,%72,%73,%74,%75,%76,%77,%78,%79,%80,%81,%82,%83,%84,%85,%86,%87,%88,%89,%90,%91,%92,%93,%94,%95}, %96, %97, p, 1, 1, 0, 1; }"
        : "+f"(d[0]), "+f"(d[1]), "+f"(d[2]), "+f"(d[3]), "+f"(d[4]), "+f"(d[5]), "+f"(d[6]), "+f"(d[7]), "+f"(d[8]), "+f"(d[9]), "+f"(d[10]), "+f"(d[11]), "+f"(d[12]), "+f"(d[13]), "+f"(d[14]), "+f"(d[15]), "+f"(d[16]), "+f"(d[17]), "+f"(d[18]), "+f"(d[19]), "+f"(d[20]), "+f"(d[21]), "+f"(d[22]), "+f"(d[23]), "+f"(d[24]), "+f"(d[25]), "+f"(d[26]), "+f"(d[27]), "+f"(d[28]), "+f"(d[29]), "+f"(d[30]), "+f"(d[31]), "+f"(d[32]), "+f"(d[33]), "+f"(d[34]), "+f"(d[35]), "+f"(d[36]), "+f"(d[37]), "+f"(d[38]), "+f"(d[39]), "+f"(d[40]), "+f"(d[41]), "+f"(d[42]), "+f"(d[43]), "+f"(d[44]), "+f"(d[45]), "+f"(d[46]), "+f"(d[47]), "+f"(d[48]), "+f"(d[49]), "+f"(d[50]), "+f"(d[51]), "+f"(d[52]), "+f"(d[53]), "+f"(d[54]), "+f"(d[55]), "+f"(d[56]), "+f"(d[57]), "+f"(d[58]), "+f"(d[59]), "+f"(d[60]), "+f"(d[61]), "+f"(d[62]), "+f"(d[63]), "+f"(d[64]), "+f"(d[65]), "+f"(d[66]), "+f"(d[67]), "+f"(d[68]), "+f"(d[69]), "+f"(d[70]), "+f"(d[71]), "+f"(d[72]), "+f"(d[73]), "+f"(d[74]), "+f"(d[75]), "+f"(d[76]), "+f"(d[77]), "+f"(d[78]), "+f"(d[79]), "+f"(d[80]), "+f"(d[81]), "+f"(d[82]), "+f"(d[83]), "+f"(d[84]), "+f"(d[85]), "+f"(d[86]), "+f"(d[87]), "+f"(d[88]), "+f"(d[89]), "+f"(d[90]), "+f"(d[91]), "+f"(d[92]), "+f"(d[93]), "+f"(d[94]), "+f"(d[95])
        : "l"(a), "l"(b), "r"(acc));
}

__device__ __forceinline__ void wgmma_ss_n128_tb(float (&d)[64], uint64_t a, uint64_t b, int acc) {
    asm volatile("{ .reg .pred p; setp.ne.b32 p, %66, 0;\n"
        "wgmma.mma_async.sync.aligned.m64n128k16.f32.bf16.bf16 {%0,%1,%2,%3,%4,%5,%6,%7,%8,%9,%10,%11,%12,%13,%14,%15,%16,%17,%18,%19,%20,%21,%22,%23,%24,%25,%26,%27,%28,%29,%30,%31,%32,%33,%34,%35,%36,%37,%38,%39,%40,%41,%42,%43,%44,%45,%46,%47,%48,%49,%50,%51,%52,%53,%54,%55,%56,%57,%58,%59,%60,%61,%62,%63}, %64, %65, p, 1, 1, 0, 1; }"
        : "+f"(d[0]), "+f"(d[1]), "+f"(d[2]), "+f"(d[3]), "+f"(d[4]), "+f"(d[5]), "+f"(d[6]), "+f"(d[7]), "+f"(d[8]), "+f"(d[9]), "+f"(d[10]), "+f"(d[11]), "+f"(d[12]), "+f"(d[13]), "+f"(d[14]), "+f"(d[15]), "+f"(d[16]), "+f"(d[17]), "+f"(d[18]), "+f"(d[19]), "+f"(d[20]), "+f"(d[21]), "+f"(d[22]), "+f"(d[23]), "+f"(d[24]), "+f"(d[25]), "+f"(d[26]), "+f"(d[27]), "+f"(d[28]), "+f"(d[29]), "+f"(d[30]), "+f"(d[31]), "+f"(d[32]), "+f"(d[33]), "+f"(d[34]), "+f"(d[35]), "+f"(d[36]), "+f"(d[37]), "+f"(d[38]), "+f"(d[39]), "+f"(d[40]), "+f"(d[41]), "+f"(d[42]), "+f"(d[43]), "+f"(d[44]), "+f"(d[45]), "+f"(d[46]), "+f"(d[47]), "+f"(d[48]), "+f"(d[49]), "+f"(d[50]), "+f"(d[51]), "+f"(d[52]), "+f"(d[53]), "+f"(d[54]), "+f"(d[55]), "+f"(d[56]), "+f"(d[57]), "+f"(d[58]), "+f"(d[59]), "+f"(d[60]), "+f"(d[61]), "+f"(d[62]), "+f"(d[63])
        : "l"(a), "l"(b), "r"(acc));
}

__device__ __forceinline__ void wgmma_rs_n32(float (&d)[16], const uint32_t (&a)[4], uint64_t b, int acc) {
    asm volatile("{ .reg .pred p; setp.ne.b32 p, %21, 0;\n"
        "wgmma.mma_async.sync.aligned.m64n32k16.f32.bf16.bf16 {%0,%1,%2,%3,%4,%5,%6,%7,%8,%9,%10,%11,%12,%13,%14,%15}, {%16,%17,%18,%19}, %20, p, 1, 1, 0; }"
        : "+f"(d[0]), "+f"(d[1]), "+f"(d[2]), "+f"(d[3]), "+f"(d[4]), "+f"(d[5]), "+f"(d[6]), "+f"(d[7]), "+f"(d[8]), "+f"(d[9]), "+f"(d[10]), "+f"(d[11]), "+f"(d[12]), "+f"(d[13]), "+f"(d[14]), "+f"(d[15])
        : "r"(a[0]), "r"(a[1]), "r"(a[2]), "r"(a[3]), "l"(b), "r"(acc));
}

__device__ __forceinline__ float warp_sum(float v) {
#pragma unroll
    for (int o = 16; o; o >>= 1) v += __shfl_xor_sync(0xffffffffu, v, o);
    return v;
}
__device__ __forceinline__ uint32_t add2(uint32_t a, uint32_t b) { uint32_t r; asm("add.rn.bf16x2 %0, %1, %2;" : "=r"(r) : "r"(a), "r"(b)); return r; }
__device__ __forceinline__ uint32_t mul2(uint32_t a, uint32_t b) { uint32_t r; asm("mul.rn.bf16x2 %0, %1, %2;" : "=r"(r) : "r"(a), "r"(b)); return r; }
__device__ __forceinline__ uint32_t amax2(uint32_t m, uint32_t v) { uint32_t r; asm("max.u16x2 %0, %1, %2;" : "=r"(r) : "r"(m), "r"(v & 0x7fff7fffu)); return r; }
__device__ __forceinline__ uint32_t amax_warp(uint32_t m) { return __reduce_max_sync(0xffffffffu, max(m & 0xffffu, m >> 16)); }
__device__ __forceinline__ void ln_norm(const uint32_t (&xv)[10], uint32_t (&nv)[10]) {
    float s0 = 0, s1 = 0;
#pragma unroll
    for (int i = 0; i < 10; i++) { s0 += lo_f(xv[i]); s1 += hi_f(xv[i]); }
    const float mean = warp_sum(s0 + s1) * (1.f / DM);
    float q0 = 0, q1 = 0;
#pragma unroll
    for (int i = 0; i < 10; i++) { const float d0 = lo_f(xv[i]) - mean, d1 = hi_f(xv[i]) - mean; q0 += d0 * d0; q1 += d1 * d1; }
    const float inv = inv_std(warp_sum(q0 + q1) * (1.f / DM));
    const uint32_t mb = pack2(-mean, -mean);
#pragma unroll
    for (int i = 0; i < 10; i++) { const uint32_t d = add2(xv[i], mb); nv[i] = pack2(lo_f(d) * inv, hi_f(d) * inv); }
}
__device__ __forceinline__ void ln_mod(const uint32_t (&xv)[10], const uint32_t (&sv)[10], const uint32_t (&tv)[10], uint32_t (&hv)[10]) {
    ln_norm(xv, hv);
#pragma unroll
    for (int i = 0; i < 10; i++) hv[i] = add2(mul2(hv[i], add2(sv[i], 0x3f803f80u)), tv[i]);
}
__device__ __forceinline__ uint32_t ld_rlx(const uint32_t* f) { uint32_t v; asm volatile("ld.relaxed.gpu.global.u32 %0, [%1];" : "=r"(v) : "l"(f) : "memory"); return v; }
__device__ __forceinline__ void bump(uint32_t* f) { asm volatile("red.relaxed.gpu.global.add.u32 [%0], 1;" :: "l"(f) : "memory"); }
#define NAP 100
__device__ __forceinline__ void flag_wait(const uint32_t* f, uint32_t target) {
    for (int n = 0;; n++) {
        uint32_t v; asm volatile("ld.relaxed.gpu.global.u32 %0, [%1];" : "=r"(v) : "l"(f) : "memory");
        if (v >= target) break;
        if (n > (1 << 22)) __trap();
        __nanosleep(NAP);
    }
}
__device__ __forceinline__ void flag_add(uint32_t* f, uint32_t v = 1) { asm volatile("red.release.gpu.global.add.u32 [%0], %1;" :: "l"(f), "r"(v) : "memory"); }
constexpr int N_SIDE = 36;
__device__ __forceinline__ void flags_release(int lane) {
    uint32_t old = 0;
    if (lane == 0) asm volatile("atom.relaxed.gpu.global.add.u32 %0, [%1], 1;" : "=r"(old) : "l"(&g_flags.done) : "memory");
    if (__shfl_sync(0xffffffffu, old, 0) == 96 + N_SIDE - 1)
#pragma unroll 1
        for (int i = lane; i < (int)(sizeof(Flags) / 16); i += 32) ((uint4*)&g_flags)[i] = make_uint4(0, 0, 0, 0);
}

template <int NT> struct ModSlice {
    static constexpr int R = 2 * DM / NT;
    float sc[R]; uint4 wv[R];
    __device__ __forceinline__ void load(const bf16* wmod, const bf16* c, int col, int tid) {
        const bf16* wm = wmod + (tid >> 1) * (6 * DM) + col + (tid & 1) * 8;
#pragma unroll
        for (int i = 0; i < R; i++) {
            asm volatile("ld.global.nc.L1::no_allocate.L2::128B.v4.u32 {%0,%1,%2,%3}, [%4];" : "=r"(wv[i].x), "=r"(wv[i].y), "=r"(wv[i].z), "=r"(wv[i].w) : "l"(wm + i * (NT / 2) * (6 * DM)));
            sc[i] = __uint_as_float((uint32_t)__ldg((const unsigned short*)c + (tid >> 1) + NT / 2 * i) << 16);
        }
    }
    __device__ __forceinline__ void partial(uint32_t buf, int tid) {
        const int lane = tid & 31;
        float a[8] = {0, 0, 0, 0, 0, 0, 0, 0};
#pragma unroll
        for (int i = 0; i < R; i++) {
            const float f = bfr(__fdividef(sc[i], 1.f + __expf(-sc[i])));
            const uint32_t u[4] = {wv[i].x, wv[i].y, wv[i].z, wv[i].w};
#pragma unroll
            for (int e = 0; e < 4; e++) { a[2 * e] += f * lo_f(u[e]); a[2 * e + 1] += f * hi_f(u[e]); }
        }
#pragma unroll
        for (int h = 4; h; h >>= 1)
#pragma unroll
            for (int e = 0; e < h; e++) { const bool up = lane & (4 * h); a[e] = (up ? a[e + h] : a[e]) + __shfl_xor_sync(0xffffffffu, up ? a[e] : a[e + h], 4 * h); }
        a[0] += __shfl_xor_sync(0xffffffffu, a[0], 2);
        asm volatile("st.shared.f32 [%0], %1;" :: "r"(buf + (tid >> 5) * 64 + (lane & 1) * 32 + (lane >> 2) * 4), "f"(a[0]) : "memory");
    }
    static __device__ __forceinline__ uint32_t total(uint32_t buf, int lane) {
        float a0 = 0, a1 = 0;
#pragma unroll
        for (int i = 0; i < NT / 32; i++) { float x, y; asm volatile("ld.shared.v2.f32 {%0,%1}, [%2];" : "=f"(x), "=f"(y) : "r"(buf + i * 64 + (lane & 7) * 8) : "memory"); a0 += x; a1 += y; }
        return pack2(a0, a1);
    }
};

struct ChainMaps { CUtensorMap wq, wk, wv, wo, h2, wo15, o15, slab16; };
struct ChainArgs { const bf16 *x, *mem0, *c, *wmod, *wv, *wo, *wgate, *wup, *wdown; bf16* out; int D1, D2, DG; };
constexpr uint32_t SM_BASE = 1024;
#define NRING 10
#define FILL_AT 1
#define VF 6
#define VPRE 2
#define XORD 0
#define B5AT 41
#define QCUT 0x7f
#define NCH 2
#define ALA 1
#define VPOS 0
#define NPRE 9
#define REG_P 208
#define REG_L (504 - 2 * REG_P)
constexpr int WO_BLK = 7 * 4096;
constexpr int C_WV = 0, C_WO = 81920, C_XR = 167936, C_VP = C_XR + 7 * 4096, C_VX = C_XR + 8 * 4096, C_QX = C_VX + 4096, C_KX = C_QX + 4096,
              C_MEM = C_KX + 4096, C_OX = C_MEM + 9216, C_VM = C_OX + 3072, C_QM = C_VM + 1024, C_KM = C_QM + 1024, C_SC = C_KM + 1024, C_BAR = C_SC + 3840;
constexpr int CB_W = C_BAR, CB_W2 = C_BAR + 8, CB_SC = C_BAR + 16, CB_XD = C_BAR + 24, CB_VX = C_BAR + 32, CB_W3 = C_BAR + 40, CB_XM = C_BAR + 48, CB_OX = C_BAR + 56,
              CB_XF = C_BAR + 64, C_LAG = C_BAR + 96, C_UN = C_BAR + 100, C_MX = C_BAR + 112;
constexpr int C_SMEM = C_BAR + 128;
#define PROF(i)
#define PROFG(i)
#define PROFV(i, v)
static_assert(C_SMEM <= 232448, "chain shared memory");
__device__ __forceinline__ uint32_t umax3(uint32_t a, uint32_t b, uint32_t c) { return max(max(a, b), c); }
__device__ __forceinline__ void wait_until(uint32_t t) {
    asm volatile("{ .reg .pred p; .reg .s32 c;\nU_%=: mov.u32 c, %%clock; sub.s32 c, c, %0; setp.lt.s32 p, c, 0; @p bra.uni U_%=; }" :: "r"(t) : "memory");
}
__device__ __forceinline__ uint32_t gtime() { uint32_t c; asm volatile("mov.u32 %0, %%globaltimer_lo;" : "=r"(c)); return c; }
__device__ __forceinline__ uint32_t opaque(uint32_t v) { uint32_t r; asm volatile("shfl.sync.bfly.b32 %0, %1, 0, 31, -1;" : "=r"(r) : "r"(v)); return r; }
__device__ __forceinline__ uint32_t lds32(uint32_t a) { uint32_t v; asm volatile("ld.shared.u32 %0, [%1];" : "=r"(v) : "r"(a) : "memory"); return v; }
__device__ __forceinline__ float2 lds64f(uint32_t a) { float2 v; asm volatile("ld.shared.v2.f32 {%0,%1}, [%2];" : "=f"(v.x), "=f"(v.y) : "r"(a) : "memory"); return v; }
__device__ __forceinline__ float4 lds128f(uint32_t a) { float4 v; asm volatile("ld.shared.v4.f32 {%0,%1,%2,%3}, [%4];" : "=f"(v.x), "=f"(v.y), "=f"(v.z), "=f"(v.w) : "r"(a) : "memory"); return v; }
__device__ __forceinline__ void sts128f(uint32_t a, float x, float y, float z, float w) { asm volatile("st.shared.v4.f32 [%0], {%1,%2,%3,%4};" :: "r"(a), "f"(x), "f"(y), "f"(z), "f"(w) : "memory"); }
__device__ __forceinline__ void lds64(uint32_t (&v)[2], uint32_t a) { asm volatile("ld.shared.v2.u32 {%0,%1}, [%2];" : "=r"(v[0]), "=r"(v[1]) : "r"(a) : "memory"); }
__device__ __forceinline__ void mma16q(float (&d)[4], const uint32_t (&a)[4], uint32_t b0, uint32_t b1) { mma16(d, a[0], a[1], a[2], a[3], b0, b1); }
__device__ __forceinline__ uint32_t f16_to_bf16(uint32_t v) {
    float lo, hi; asm("{ .reg .f16 l, h; mov.b32 {l, h}, %2; cvt.f32.f16 %0, l; cvt.f32.f16 %1, h; }" : "=f"(lo), "=f"(hi) : "r"(v));
    return pack2(lo, hi);
}
__device__ __forceinline__ uint32_t pack2h(float lo, float hi) { uint32_t r; asm("cvt.rn.f16x2.f32 %0, %1, %2;" : "=r"(r) : "f"(hi), "f"(lo)); return r; }
#define SPLIT 1
__device__ __forceinline__ void cut(uint32_t never, int n) {
    asm volatile("{ .reg .pred p; setp.ne.u32 p, %0, %1; @p bra.uni C_%=; trap; C_%=: }" :: "r"(never), "r"(n) : "memory");
}
__device__ __forceinline__ void pin(uint32_t never, uint32_t a, uint32_t b, uint32_t c, uint32_t d) {
    asm volatile("{ .reg .pred p; setp.eq.u32 p, %0, 0; @p st.shared.v4.u32 [%0], {%1,%2,%3,%4}; }" :: "r"(never), "r"(a), "r"(b), "r"(c), "r"(d) : "memory");
}
__device__ __forceinline__ void pin0(uint32_t never) {
    asm volatile("{ .reg .pred p; setp.eq.u32 p, %0, 0; @p st.shared.u32 [%0], 0; }" :: "r"(never) : "memory");
}
#define ELECTED(txt) "{ .reg .pred e; elect.sync _|e, -1; @e " txt " }"
__device__ __forceinline__ void w_bulk_s2g(void* dst, uint32_t src, int bytes) {
    asm volatile(ELECTED("cp.async.bulk.global.shared::cta.bulk_group [%0], [%1], %2;") :: "l"(dst), "r"(src), "r"(bytes) : "memory");
}
__device__ __forceinline__ void w_bump(uint32_t* f) { asm volatile(ELECTED("red.relaxed.gpu.global.add.u32 [%0], 1;") :: "l"(f) : "memory"); }
__device__ __forceinline__ void w_expect(uint32_t bar, int bytes) { asm volatile(ELECTED("mbarrier.arrive.expect_tx.shared::cta.b64 _, [%0], %1;") :: "r"(bar), "r"(bytes) : "memory"); }
__device__ __forceinline__ void w_flag_wait(const uint32_t* f, uint32_t target) {
    asm volatile("{ .reg .pred p; .reg .u32 n, v; mov.u32 n, 0;\n"
                 "F_%=: ld.relaxed.gpu.global.u32 v, [%0]; setp.ge.u32 p, v, %1; vote.sync.all.pred p, p, -1; @p bra.uni G_%=;\n"
                 "nanosleep.u32 %2; add.u32 n, n, 1; setp.lt.u32 p, n, 0x400000; @p bra.uni F_%=;\ntrap;\nG_%=: }" :: "l"(f), "r"(target), "n"(NAP) : "memory");
}
#define BULK_COMMIT()    asm volatile("cp.async.bulk.commit_group;" ::: "memory")
#define BULK_WAIT()      asm volatile("cp.async.bulk.wait_group 0;" ::: "memory")
#define BULK_WAIT_READ() asm volatile("cp.async.bulk.wait_group.read 0;" ::: "memory")
#define PROXY_FENCE()    asm volatile("fence.proxy.async.shared::cta;" ::: "memory")
__device__ __forceinline__ void score_tile(const uint32_t (&qa)[2][4], const uint32_t (&kb)[2][4], bool odd, float (&x)[4]) {
    float sc[2][4] = {{0, 0, 0, 0}, {0, 0, 0, 0}};
#pragma unroll
    for (int k = 0; k < 4; k++) mma16q(sc[k & 1], qa[k >> 1], kb[k >> 1][2 * (k & 1)], kb[k >> 1][2 * (k & 1) + 1]);
    float a = sc[0][0] + sc[1][2], b = sc[0][1] + sc[1][3];
    float c = __shfl_xor_sync(0xffffffffu, a, 1), d = __shfl_xor_sync(0xffffffffu, b, 1);
    x[0] = odd ? c : a; x[1] = odd ? d : b; x[2] = odd ? a : c; x[3] = odd ? b : d;
}
__device__ __forceinline__ void send_piece(const float (&x)[4], uint32_t rdst, uint32_t rbar, uint32_t ldst) {
    asm volatile("st.async.shared::cluster.mbarrier::complete_tx::bytes.v4.f32 [%0], {%1,%2,%3,%4}, [%5];"
        :: "r"(rdst), "f"(x[0]), "f"(x[1]), "f"(x[2]), "f"(x[3]), "r"(rbar) : "memory");
    sts128f(ldst, x[0], x[1], x[2], x[3]);
}

__device__ __forceinline__ void seg_done(int n, int head) {
    w_bump(&g_flags.seg[n * 32 + head]);
    if ((n & 3) == 3) w_bump(&g_flags.qk[n >> 2]);
}
__device__ __forceinline__ void x_part(const uint32_t (&wa)[40][4], uint32_t sm, int n, int wg, int w, uint32_t ln, int head) {
    const int s = n - 1; (void)s;
    float acc[16]; uint32_t giv[8];
#pragma unroll
    for (int i = 0; i < 16; i++) acc[i] = 0.f;
    const uint32_t x0 = (uint32_t)mkdesc(SM_BASE + C_XR + wg * 4096, 16, 1024) + ln, xl[2] = {__shfl_sync(0xffffffffu, x0, 0), __shfl_sync(0xffffffffu, x0, 1)};
    auto chunk = [&](int a0, int i, int first) {
#pragma unroll
        for (int ks = 0; ks < 4; ks++)
            wgmma_rs_n32(acc, wa[a0 + 4 * i + ks], (mkdesc(0, 0, 1024) | (uint32_t)(xl[!a0] + ((((i ? (i - 1) * 8192 : C_MEM - C_XR) + ks * 32) >> 4) - !a0))), !(first && ks == 0));
    };
    mbar_wait(sm + CB_XF, n & 1);
    if (n) bar_sync(5, 384);
    if (wg == 0 && w == 0) PROF(12);
    WG_FENCE();
    chunk(20, 1, 1); chunk(20, 2, 0); chunk(20, 3, 0);
    mbar_wait(sm + CB_XM, n & 1);
    if (wg == 0 && w == 0) PROF(13);
    WG_FENCE();
    chunk(20, 0, 0);
    mbar_wait(sm + CB_XF + 8, n & 1);
    if (wg == 0 && w == 0) PROF(17);
    WG_FENCE();
    chunk(20, 4, 0);
    WG_COMMIT();
    if (n) {
        if (wg == 1 && w == 1) { BULK_WAIT(); seg_done(n - 1, head); }
        bar_sync(8, 256);
    }
    if (wg == 0 && w == 0) PROF(18);
    const uint32_t xb = sm + w * 512 + ln * 16, xw = xb + C_KX - wg * 4096, xr = xb + C_QX + wg * 4096;
    WG_WAIT(0);
#pragma unroll
    for (int i = 0; i < 8; i++) asm volatile("cvt.rn.bf16x2.f32 %0, %1, %2;" : "=r"(giv[i]) : "f"(acc[2 * i + 1]), "f"(acc[2 * i]));
#pragma unroll
    for (int p = 0; p < 2; p++) asm volatile("st.shared.v4.u32 [%0], {%1,%2,%3,%4};" :: "r"(xw + p * 2048), "r"(giv[4 * p]), "r"(giv[4 * p + 1]), "r"(giv[4 * p + 2]), "r"(giv[4 * p + 3]) : "memory");
    bar_arrive(12 + wg, 256);
    WG_FENCE();
    chunk(0, 0, 1);
    WG_COMMIT();
    chunk(0, 1, 0);
    if (XORD) chunk(0, 2, 0);
    bar_sync(13 - wg, 256);
#pragma unroll
    for (int p = 0; p < 2; p++) asm volatile("ld.shared.v4.u32 {%0,%1,%2,%3}, [%4];" : "=r"(giv[4 * p]), "=r"(giv[4 * p + 1]), "=r"(giv[4 * p + 2]), "=r"(giv[4 * p + 3]) : "r"(xr + p * 2048) : "memory");
    WG_COMMIT(); WG_WAIT(1); bar_arrive(9, 384);
    WG_FENCE();
    if (!XORD) chunk(0, 2, 0);
    chunk(0, 3, 0); chunk(0, 4, 0);
    WG_COMMIT();
    const uint32_t r = ln & 7, mi = ln >> 3, dst = sm + (wg == 0 ? C_QX : C_KX) + ((mi >> 1) * 8 + r) * 128 + (((2 * w + (mi & 1)) ^ r) << 4);
    pin(xb, giv[0], giv[4], dst, 0);
    bar_sync(10 + wg, 128);
    WG_WAIT(0);
    if (wg == 0 && w == 0) PROF(30);
    if (w == 0 && ln < 3) mbar_arrive_remote(mapa(sm + CB_XD, ln));
#pragma unroll
    for (int i = 0; i < 8; i++) { acc[2 * i] += lo_f(giv[i]); acc[2 * i + 1] += hi_f(giv[i]); }
#pragma unroll
    for (int p = 0; p < 2; p++)
        stsm4t(dst + p * 2048, pack2(acc[8 * p], acc[8 * p + 1]), pack2(acc[8 * p + 2], acc[8 * p + 3]), pack2(acc[8 * p + 4], acc[8 * p + 5]), pack2(acc[8 * p + 6], acc[8 * p + 7]));
    if (wg == 0 && w == 0) PROF(11);
}
__device__ __forceinline__ void x_fill(const ChainMaps& mp, uint32_t sm, int n, int j, int g) {
    mbar_expect(sm + CB_XF + 8 * g, g ? 8192 : 24576);
    const int c = g ? 6 : 2 * j;
    if (!g || j == 2)
        asm volatile("cp.async.bulk.tensor.3d.shared::cluster.global.mbarrier::complete_tx::bytes.multicast::cluster [%0], [%1, {0, %3, %4}], [%2], %5;"
            :: "r"(sm + C_XR + c * 4096), "l"((uint64_t)&mp.h2), "r"(sm + CB_XF + 8 * g), "r"(n * SEG), "r"(2 + c), "h"((uint16_t)7) : "memory");
}

#define WPOS 0
#define BPOS 1
#define TPF 1
#define B_LATE 14
constexpr int E_B = C_WO, E_STG = 196608, EB_A = 229376, EB_B = C_BAR + 80, EB_REL = C_BAR + 104;
__device__ __forceinline__ uint32_t e_slot(int wg, int c) { return wg && c == 2 ? E_B + 98304 : wg * 49152 + c * 16384; }
constexpr int T_WG = 0, T_WU = 20480, T_WD = 40960, T_X = 65536, T_RED = 77824, T_KEY = 86016;
__device__ __forceinline__ void wo_half(const ChainMaps& mp, uint32_t sm, int blk, int c) {
    if (blk < 80 && elect()) { mbar_expect(sm + EB_B + 8 * c, 49152); tma3d(sm + E_B + c * 49152, &mp.wo15, blk / 5 * 384 + c * 192, blk % 5 * 2, sm + EB_B + 8 * c); }
}
__device__ __forceinline__ void end_loads(const ChainMaps& mp, const ChainArgs& ar, uint32_t sm, int blk, int wg) {
    const uint32_t bar = sm + EB_A + wg * 48;
    const int kp = blk / 5;
    if (elect()) {
#pragma unroll 1
        for (int c = 0; c < 6; c++) mbar_init(bar + 8 * c, c < 3 ? 1 : 4);
        PROXY_FENCE();
    }
    __syncwarp();
    bar_arrive(5, 384);
    if (blk >= 80) {
        if (TPF && elect()) {
#pragma unroll 1
            for (int c = 0; c < 3; c++) asm volatile("cp.async.bulk.prefetch.L2.global [%0], 61440;" :: "l"((c == 0 ? ar.wgate : c == 1 ? ar.wup : ar.wdown) + ((blk - 80) * 2 + wg) * 30720) : "memory");
        }
        return;
    }
    const uint64_t ef = policy_stream();
#pragma unroll 1
    for (int b = B_LATE; b < 16; b++) {
        w_flag_wait(b == 15 ? &g_flags.half[kp * 2 + wg] : &g_flags.pair[b * 16 + kp], b == 15 ? 8 : 16);
#pragma unroll 1
        for (int c = 0; c < 3; c++) {
            if (b > B_LATE) mbar_wait(bar + 24 + 8 * c, (b - B_LATE - 1) & 1);
            if (elect()) { mbar_expect(bar + 8 * c, 16384); tma3d_ef(sm + e_slot(wg, c), &mp.o15, b * 128 + wg * 64, kp * 6 + c * 2, bar + 8 * c, ef); }
            __syncwarp();
        }
    }
}
__device__ __forceinline__ void last_blocks(const ChainMaps& mp, const ChainArgs& ar, uint32_t sm, int blk, int tid) {
    const int warp = __shfl_sync(0xffffffffu, tid >> 5, 0), lane = tid & 31, wg = warp >> 2, w = warp & 3, kp = blk / 5, ct = blk % 5;
    const uint32_t bar = sm + EB_A + wg * 48, stg = sm + E_STG + warp * 4096;
    const uint64_t ef = policy_stream();
    bar_sync(5, 384);
    float acc[64];
#pragma unroll
    for (int n = 0; n < 64; n++) acc[n] = 0.f;
#pragma unroll 1
    for (int b = B_LATE; b < 16 && blk < 80; b++) {
#pragma unroll 1
        for (int c = 0; c < 6; c++) {
            mbar_wait(sm + EB_B + 8 * (c >= 3), 0); mbar_wait(bar + 8 * (c >> 1), (b - B_LATE) & 1);
            const uint64_t da = mkdesc(SM_BASE + e_slot(wg, c >> 1) + (c & 1) * 8192, 16, 1024), db = mkdesc(SM_BASE + E_B + (c >= 3 ? 24576 : 0) + c * 8192, 24576, 1024);
            WG_FENCE();
#pragma unroll
            for (int ks = 0; ks < 4; ks++) wgmma_ss_n128_tb(acc, da + ks * 2, db + ks * 128, c | ks);
            WG_COMMIT();
            WG_WAIT(1);
            if ((c & 1) == 0 && c && elect()) mbar_arrive(bar + 16 + 4 * c);
        }
        WG_WAIT(0);
        if (elect()) mbar_arrive(bar + 40);
        const int r = lane & 7, mi = lane >> 3;
#pragma unroll
        for (int p = 0; p < 8; p++) {
            const int oc = 2 * p + (mi >> 1);
            stsm4(stg + (oc >> 3) * 2048 + ((mi & 1) * 8 + r) * 128 + (((oc & 7) ^ r) << 4), pack2(acc[8 * p], acc[8 * p + 1]), pack2(acc[8 * p + 2], acc[8 * p + 3]),
                  pack2(acc[8 * p + 4], acc[8 * p + 5]), pack2(acc[8 * p + 6], acc[8 * p + 7]));
        }
        PROXY_FENCE();
        __syncwarp();
        if (elect()) tma3d_store(&mp.slab16, (b * KSPLIT + kp) * 128 + warp * 16, ct * 2, stg, ef, false);
        BULK_COMMIT(); BULK_WAIT();
        if (w) bar_arrive(12 + wg, 128); else { bar_sync(12 + wg, 128); w_bump(b < 14 ? &g_flags.o[b] : &g_flags.fin[((b - 14) * 2 + wg) * 32]); }
    }
    bar_sync(8, 256);
    const int o = (tid >> 1) * FF + blk * 16 + (tid & 1) * 8;
    const bf16 *pg = ar.wgate + o, *pu = ar.wup + o, *pd = ar.wdown + tid * DM + (blk < 80 ? blk : 0) * 8;
#pragma unroll
    for (int i = 0; i < 16; i++)
        asm volatile("cp.async.cg.shared.global [%0], [%1], 16;" :: "r"(sm + E_B + i * 4096 + tid * 16), "l"(i < 5 ? pg + i * 128 * FF : i < 10 ? pu + (i - 5) * 128 * FF : pd + (i - 10) * 256 * DM) : "memory");
}
__device__ __forceinline__ void mod_tail(const ChainArgs& ar, const uint32_t tb, const uint32_t bar, const int blk, const int tid) {
#define TPROF(i)
    const int warp = __shfl_sync(0xffffffffu, tid >> 5, 0), lane = tid & 31, r = lane & 7, mi = lane >> 3;
    const uint32_t kb = tb + T_KEY;
    {
        uint32_t k[8];
        for (int n = 0;; n++) {
#pragma unroll
            for (int i = 0; i < 2; i++) asm volatile("ld.relaxed.gpu.global.v4.u32 {%0,%1,%2,%3}, [%4];" : "=r"(k[4 * i]), "=r"(k[4 * i + 1]), "=r"(k[4 * i + 2]), "=r"(k[4 * i + 3]) : "l"(g_key + warp * 256 + i * 128 + lane * 4) : "memory");
            if (__all_sync(0xffffffffu, (k[0] & k[1] & k[2] & k[3] & k[4] & k[5] & k[6] & k[7] & S_TOK) != 0)) break;
            if (n > (1 << 22)) __trap();
            __nanosleep(NAP);
        }
        const uint32_t m = __reduce_max_sync(0xffffffffu, max(umax3(k[0], k[1], k[2]), max(umax3(k[3], k[4], k[5]), max(k[6], k[7]))));
        asm volatile("st.shared.u32 [%0], %1; st.shared.u32 [%2], 0;" :: "r"(kb + warp * 4), "r"(m), "r"(kb + 32) : "memory");
        asm volatile("cp.async.wait_all;" ::: "memory");
        bar_sync(1, 256);
        TPROF(1);
        const uint32_t low = __reduce_min_sync(0xffffffffu, lds32(kb + r * 4));
        uint32_t cnt = 0;
#pragma unroll
        for (int i = 0; i < 8; i++) cnt += k[i] >= low ? 4 : 0;
        if (cnt) {
            uint32_t a; asm volatile("atom.shared.add.u32 %0, [%1], %2;" : "=r"(a) : "r"(kb + 32), "r"(cnt) : "memory");
#pragma unroll
            for (int i = 0; i < 8; i++) if (k[i] >= low) { asm volatile("st.shared.u32 [%0], %1;" :: "r"(kb + 512 + a), "r"(k[i]) : "memory"); a += 4; }
        }
        if (tid == 0) mbar_arrive(bar);
        bar_sync(1, 256);
        const int nc = lds32(kb + 32);
#pragma unroll 1
        for (int c = lane * 4; c < nc; c += 128) {
            const uint32_t me = lds32(kb + 512 + c);
            int rank = 0;
#pragma unroll 2
            for (int e = 0; e < nc; e += 16) {
                const float4 z = lds128f(kb + 512 + e);
                rank += (__float_as_uint(z.x) > me) + (e + 4 < nc && __float_as_uint(z.y) > me) + (e + 8 < nc && __float_as_uint(z.z) > me) + (e + 12 < nc && __float_as_uint(z.w) > me);
            }
            if (rank < 8) asm volatile("st.shared.u32 [%0], %1;" :: "r"(kb + 64 + (warp * 8 + rank) * 4), "r"(me) : "memory");
        }
        __syncwarp();
    }
    const uint32_t k0 = lds32(kb + 64 + (warp * 8 + r) * 4), k1 = lds32(kb + 64 + (warp * 8 + (lane >> 2)) * 4);
    TPROF(2);
    const int trow = ~k1 & (S_TOK - 1), tcol = (blk < 80 ? blk : 0) * 8 + (lane & 3) * 2;
    uint2 xb[5];
#pragma unroll
    for (int h = 0; h < 5; h++) xb[h] = __ldcg((const uint2*)(g_h2 + trow * DM + (warp * 5 + h) * 16 + (lane & 3) * 4));
    const uint32_t fx1 = __ldcg((const uint32_t*)(g_x1 + trow * DM + tcol)), fh2 = __ldcg((const uint32_t*)(g_h2 + trow * DM + tcol)),
                   fgb = __ldcg((const uint32_t*)(g_mod + 5 * DM + tcol));
    const float fr = __uint_as_float(((int)k1 < 0 ? k1 ^ 0x80000000u : ~k1) & 0xffff0000u);
    {
        float dg[4] = {0, 0, 0, 0}, du[4] = {0, 0, 0, 0};
        uint32_t ag[5][4], au[5][4];
#pragma unroll
        for (int h = 0; h < 5; h++) {
            const uint32_t o = tb + ((warp * 5 + h) * 16 + (r >> 1) * 4 + (mi >> 1) * 2 + (r & 1)) * 32 + (mi & 1) * 16;
            ldsm4t(ag[h], o + T_WG); ldsm4t(au[h], o + T_WU);
        }
#pragma unroll
        for (int h = 0; h < 5; h++) { mma16q(dg, ag[h], xb[h].x, xb[h].y); mma16q(du, au[h], xb[h].x, xb[h].y); }
        TPROF(3);
        sts128f(tb + T_RED + warp * 1024 + lane * 16, dg[0], dg[1], dg[2], dg[3]); sts128f(tb + T_RED + warp * 1024 + 512 + lane * 16, du[0], du[1], du[2], du[3]);
    }
    bar_sync(1, 256);
    if (warp < 2) {
        float g2[2] = {0, 0}, u2[2] = {0, 0};
#pragma unroll
        for (int i = 0; i < 8; i++) {
            const float2 a = lds64f(tb + T_RED + i * 1024 + lane * 16 + warp * 8), b = lds64f(tb + T_RED + i * 1024 + 512 + lane * 16 + warp * 8);
            g2[0] += a.x; g2[1] += a.y; u2[0] += b.x; u2[1] += b.y;
        }
        float y[2];
#pragma unroll
        for (int i = 0; i < 2; i++) { const float gq = bfr(g2[i]); y[i] = bfr(__fdividef(gq, 1.f + __expf(-gq))) * bfr(u2[i]); }
        asm volatile("st.relaxed.gpu.global.u32 [%0], %1;" :: "l"(g_gu + (blk >> 1) * 128 + lane * 4 + warp * 2 + (blk & 1)), "r"(movm_t(pack2(y[0], y[1]))) : "memory");
    }
    TPROF(4);
    if (blk < 80) {
        uint32_t a[6][4], b[6][4];
#pragma unroll
        for (int k2 = 0; k2 < 6; k2++) ldsm4t(b[k2], tb + T_WD + (warp * 6 + k2) * 512 + lane * 16);
        for (int n = 0;; n++) {
            uint32_t m = 0;
#pragma unroll
            for (int k2 = 0; k2 < 6; k2++) asm volatile("ld.relaxed.gpu.global.v4.u32 {%0,%1,%2,%3}, [%4];" : "=r"(a[k2][0]), "=r"(a[k2][1]), "=r"(a[k2][2]), "=r"(a[k2][3]) : "l"(g_gu + (warp * 6 + k2) * 128 + lane * 4) : "memory");
#pragma unroll
            for (int k2 = 0; k2 < 6; k2++) m = umax3(umax3(m, a[k2][0], a[k2][1]), a[k2][2], a[k2][3]);
            if (!__any_sync(0xffffffffu, m == ~0u)) break;
            if (n > (1 << 22)) __trap();
        }
        TPROF(5);
        float d[2][4] = {{0, 0, 0, 0}, {0, 0, 0, 0}};
#pragma unroll
        for (int k2 = 0; k2 < 6; k2++) { mma16q(d[0], a[k2], b[k2][0], b[k2][1]); mma16q(d[1], a[k2], b[k2][2], b[k2][3]); }
        asm volatile("st.shared.v2.f32 [%0], {%1,%2};" :: "r"(tb + T_X + warp * 256 + lane * 8), "f"(d[0][0] + d[1][2]), "f"(d[0][1] + d[1][3]) : "memory");
        bar_sync(1, 256);
        if (warp == 0) {
            float y0 = 0, y1 = 0;
#pragma unroll
            for (int i = 0; i < 8; i++) { const float2 z = lds64f(tb + T_X + i * 256 + lane * 8); y0 += z.x; y1 += z.y; }
            const float sg = __fdividef(1.f, 1.f + __expf(-fr));
            *(uint32_t*)(ar.out + trow * DM + tcol) = add2(fx1, mul2(fgb, add2(fh2, mul2(pack2(y0, y1), pack2(sg, sg)))));
        }
    }
    TPROF(6);
}

__global__ void __cluster_dims__(3, 1, 1) __launch_bounds__(384, 1) k_chain(const __grid_constant__ ChainMaps mp, const __grid_constant__ ChainArgs ar) {
    const int D1 = ar.D1, DG = ar.DG;
    extern __shared__ __align__(1024) uint8_t smraw[];
    const uint32_t sm = SM_BASE + ((blockIdx.x % 3) << 24);
    if (smem_u32(smraw) != sm) __trap();
    uint32_t tid; asm volatile("mov.u32 %0, %%tid.x;" : "=r"(tid));
    const int warp = __shfl_sync(0xffffffffu, tid >> 5, 0), lane = tid & 31, wg = warp >> 2, w = warp & 3;
    const int blk = blockIdx.x, head = blk / 3, j = blk % 3;
    const int col0 = head * DH + j * 64;
    asm volatile("griddepcontrol.launch_dependents;");
#define PPROF(i)
    const int r = lane & 7, mi = lane >> 3;
    const uint32_t memrd = opaque(sm + C_MEM + lane * 16);
    if (wg < 2) {
        {
            uint32_t xv[3][10];
            const int row = blk * 8 + warp, nq = row < S_TOK - 1536 ? 3 : 2;
#pragma unroll
            for (int i = 0; i < 15; i++) {
                const uint2 v = __ldcs((const uint2*)(ar.x + (row + (i < 10 || nq == 3 ? i / 5 * 768 : 0)) * DM + lane * 4 + i % 5 * 128));
                xv[i / 5][i % 5 * 2] = v.x; xv[i / 5][i % 5 * 2 + 1] = v.y;
            }
            if (tid == 32) {
#pragma unroll 1
                for (int c = 0; c < 14; c++) if (c != 12) mbar_init(sm + C_BAR + 8 * c, c == 2 ? 5 : c == 3 ? 6 : 1);
                asm volatile("fence.mbarrier_init.release.cluster;" ::: "memory");
                mbar_expect(sm + CB_SC, 2560); mbar_expect(sm + CB_OX, 2048);
            }
            if (warp == 2) {
                const uint32_t f = blk >= 28 ? ~0u : 0u;
                ((uint4*)g_acc)[blk * 32 + lane] = make_uint4(0, 0, 0, 0);
                if (blk < 76) (blk < 12 ? (uint4*)g_stamp + blk * 32 : blk < 28 ? (uint4*)g_key + (blk - 12) * 32 : (uint4*)g_gu + (blk - 28) * 32)[lane] = make_uint4(f, f, f, f);
            }
            __syncwarp();
            asm volatile("barrier.cluster.arrive.relaxed.aligned;" ::: "memory");
            PPROF(8);
#pragma unroll 1
            for (int q = 0; q < 3; q++) {
                uint32_t nv[10];
                ln_norm(xv[0], nv);
#pragma unroll
                for (int i = 0; i < 10; i++) { xv[0][i] = xv[1][i]; xv[1][i] = xv[2][i]; xv[2][i] = nv[i]; }
            }
            PPROF(9);
            if (warp < 5) {
                uint4 u;
                for (int n = 0;; n++) {
                    asm volatile("ld.relaxed.gpu.global.v4.u32 {%0,%1,%2,%3}, [%4];" : "=r"(u.x), "=r"(u.y), "=r"(u.z), "=r"(u.w) : "l"(g_flags.mod1 + tid * 4) : "memory");
                    if (__all_sync(0xffffffffu, u.x && u.y && u.z && u.w)) break;
                    cut(n, 1 << 22);
                }
                asm volatile("st.shared.v4.u32 [%0], {%1,%2,%3,%4};" :: "r"(sm + C_KX + tid * 16), "r"(~u.x), "r"(~u.y), "r"(~u.z), "r"(~u.w) : "memory");
            }
            bar_sync(8, 256);
            PPROF(2);
            uint32_t m = 0;
#pragma unroll
            for (int i = 0; i < 5; i++) {
                uint32_t t[2], u[2];
                lds64(t, sm + C_KX + lane * 8 + i * 256); lds64(u, sm + C_KX + 1280 + lane * 8 + i * 256);
                u[0] = add2(u[0], 0x3f803f80u); u[1] = add2(u[1], 0x3f803f80u);
                m = amax2(amax2(amax2(amax2(m, t[0]), u[0]), t[1]), u[1]);
#pragma unroll
                for (int q = 0; q < 3; q++)
                    if (q < nq) *(uint2*)(g_h + (row + q * 768) * DM + lane * 4 + i * 128) = make_uint2(add2(mul2(xv[q][2 * i], u[0]), t[0]), add2(mul2(xv[q][2 * i + 1], u[1]), t[1]));
            }
            asm volatile("st.shared.u32 [%0], %1;" :: "r"(sm + C_LAG), "r"((amax_warp(m) >> 7) + 1) : "memory");
            bar_sync(8, 256);
            if (tid == 0) flag_add(&g_flags.h);
            __syncwarp();
            if (WPOS) bar_arrive(2, 288);
            PPROF(3);
            asm volatile("barrier.cluster.wait.aligned;" ::: "memory");
        }
        asm volatile("setmaxnreg.inc.sync.aligned.u32 %0;" :: "n"(REG_P));
        uint32_t wa[40][4];
        mbar_wait(sm + CB_W, 0);
#pragma unroll
        for (int ks = 0; ks < 40; ks++)
            ldsm4t(wa[ks], sm + ((wg == 0) == (ks < 20) ? C_WV : C_WO) + ((mi >> 1) * 8 + r) * 128 + (((2 * w + (mi & 1)) ^ r) << 4) + (ks % 20 / 4 * 8 + 4 * wg + (ks & 3)) * 2048);
        PPROF(5);
        bar_arrive(1, 288);
        const uint32_t qst = opaque(sm + (wg == 0 ? C_QM : C_KM) + (2 * w + (mi & 1)) * 128 + r * 16);
        const uint32_t vrd = opaque(sm + C_WV + ((mi >> 1) * 8 + r) * 128 + (((2 * w + (mi & 1)) ^ r) << 4) + 4 * wg * 2048);
        const uint32_t mrd = opaque(memrd + wg * 1024);
        for (int s = 0; s < NSEG; s++) {
            x_part(wa, sm, s, wg, w, opaque(mrd) >> 4 & 31, head);
            cut(s + ar.D2, 0);
            bar_sync(1, 384);
            if (warp == 0) { PROF(0); PROFG(24); }
            uint32_t b[3][4], a[5][4];
            float dv[2][4] = {{0, 0, 0, 0}, {0, 0, 0, 0}};
            auto fb = [&](int n) { return mrd + (n >> 1) * 2048 + (n & 1) * 512; };
            auto fa = [&](int k) { return vrd + (k >> 2) * 16384 + (k & 3) * 2048; };
            {
                float d[2][4] = {{0, 0, 0, 0}, {0, 0, 0, 0}}, g[2][4] = {{0, 0, 0, 0}, {0, 0, 0, 0}};
                ldsm4t(b[0], fb(0)); pin0(mrd); ldsm4t(b[1], fb(1)); pin0(mrd);
#pragma unroll
                for (int n = 0; n < 10; n++) {
                    const int c1 = (NCH == 2 || n >= 8);
                    if (n < 8) ldsm4t(b[(n + 2) % 3], fb(n + 2));
                    if (n + ALA >= 2 && n + ALA < 2 + VF) ldsm4t(a[2 + (n + ALA) % 3], fa(2 * (n + ALA)));
                    if (!VPOS && n >= 9 - VPRE && n < 9) ldsm4t(a[n - 9 + VPRE], fa(16 + n - 9 + VPRE));
                    mma16q(g[0], wa[20 + 2 * n], b[n % 3][0], b[n % 3][1]); mma16q(d[0], wa[2 * n], b[n % 3][0], b[n % 3][1]);
                    if (n >= 2 && n < 2 + VF) mma16q(dv[0], a[2 + n % 3], b[n % 3][0], b[n % 3][1]);
                    mma16q(g[c1], wa[21 + 2 * n], b[n % 3][2], b[n % 3][3]); mma16q(d[c1], wa[2 * n + 1], b[n % 3][2], b[n % 3][3]);
                    if (QCUT >> n & 1) cut(s + ar.D2, 1 + n);
                }
                const uint32_t xb = mrd - wg * 1024 - (C_MEM - C_VP) + w * 512;
                const float un = __uint_as_float(lds32(sm + C_UN));
                sts128f(xb + wg * 2048, g[0][0] + g[1][0], g[0][1] + g[1][1], g[0][2] + g[1][2], g[0][3] + g[1][3]);
                bar_sync(8, 256);
                const float4 z = lds128f(xb + (wg ^ 1) * 2048);
                if (VPOS) {
                    pin0(mrd);
#pragma unroll
                    for (int i = 0; i < VPRE; i++) ldsm4t(a[i], fa(16 + i));
                }
                stsm2t(qst, pack2((d[0][0] + d[1][0] + z.x) * un, (d[0][1] + d[1][1] + z.y) * un), pack2((d[0][2] + d[1][2] + z.z) * un, (d[0][3] + d[1][3] + z.w) * un));
            }
            bar_arrive(2, 384);
            if (w == 0) PROF(1 + wg);
            {
                if (warp == 3)
                    asm volatile(ELECTED("st.relaxed.gpu.global.u32 [%0], %1;") :: "l"(g_stamp + (s & 3) * 384 + (blk >> 3) * 32 + (blk & 7)), "r"((gtime() & ~31u) | ((s >> 2) + 1)) : "memory");
                PROXY_FENCE();
                bar_sync(7, 384);
                constexpr int NR = 16 - VF, NB = 4 + 12 - 2 * VF;
                auto kst = [&](int i) { return i < 4 ? 16 + i : i < NB ? i + 2 * VF : 5 + 2 * (i - NB); };
                const uint32_t mo = mrd + 256 + (mrd & 256);
                auto fc = [&](int p) { return 2 * p < NB ? fb(p + VF) : mo + (1 + (2 * p - NB) / 2) * 2048; };
#pragma unroll
                for (int i = VPRE; i < 4; i++) ldsm4t(a[i], fa(kst(i)));
#pragma unroll
                for (int i = 0; i < NR; i++) {
                    if (i + 4 < NR) ldsm4t(a[(i + 4) % 5], fa(kst(i + 4)));
                    if (!(i & 1) && i + 4 < NR) ldsm4t(b[(i / 2 + 1) % 3], fc(i / 2 + 2));
                    mma16q(dv[~i & 1], a[i % 5], b[(i / 2 + 2) % 3][2 * (i & 1)], b[(i / 2 + 2) % 3][2 * (i & 1) + 1]);
                }
                sts128f(mrd - (C_MEM - C_VP) + wg * 1024 + w * 512, dv[0][0] + dv[1][0], dv[0][1] + dv[1][1], dv[0][2] + dv[1][2], dv[0][3] + dv[1][3]);
            }
            if (warp == 0) bar_sync(4, 384);
            else bar_arrive(4, 384);
            if (warp == 0) {
                PROF(7);
                if (s + 1 < NSEG && elect()) {
                    mbar_expect(sm + CB_XM, 8192); tma3d(sm + C_MEM, &mp.h2, (s + 1) * SEG, 0, sm + CB_XM);
                }
            } else {
                if (wg == 1) {
                    if (w == 1) {
                        uint8_t* rec = g_att + (s * NH + head) * AT_REC;
                        w_bulk_s2g(rec + j * 8192, sm + C_QX, 8192); w_bulk_s2g(rec + AT_KM + j * 1024, sm + C_KM, 1024);
                        BULK_COMMIT();
                        if (s + 1 == NSEG) { BULK_WAIT(); seg_done(s, head); }
                    }
                    if (w == 2 && blk < 10 && s + 3 < NSEG)
                        asm volatile(ELECTED("cp.async.bulk.prefetch.L2.global [%0], 4096;") :: "l"((const uint8_t*)g_h + (s + 3) * (SEG * DM * 2) + blk * 4096) : "memory");
                } else if (w == 3) { if (s + 1 < NSEG) {
                    const uint32_t l = opaque(mrd) >> 4 & 31, tag = (s >> 2) + 1, now = gtime();
                    const uint32_t* sp = g_stamp + (s & 3) * 384 + (l >> 3) * 32 + (l & 7);
                    uint32_t t[3];
                    for (int n = 0;; n++) {
#pragma unroll
                        for (int i = 0; i < 3; i++) t[i] = ld_rlx(sp + i * 128);
                        if (!__any_sync(0xffffffffu, ((t[0] ^ tag) | (t[1] ^ tag) | (t[2] ^ tag)) & 31) || n > SPIN_LIMIT) break;
                    }
                    int all = -(1 << 30), own = all;
#pragma unroll
                    for (int i = 0; i < 3; i++) { const int d = t[i] - now; all = max(all, d); if ((i * 32 + l) / 3 == head) own = d; }
                    const int lag = min(__reduce_max_sync(0xffffffffu, all) - __reduce_max_sync(0xffffffffu, own), 8000);
                    PROFV(15, lag);
                    asm volatile("st.shared.u32 [%0], %1;" :: "r"(sm + C_LAG), "r"(D1 + ((lag * DG) >> 4)) : "memory");
                    bar_arrive(6, 160); }
                } else if (w == 2) {
                    if (s + 1 < NSEG) {
                        if ((s & 3) == 3) w_flag_wait(&g_flags.v[((s + 1) >> 2) * 32 + head], 2);
                        if (elect()) { mbar_expect(sm + CB_VX, 4096); bulk_g2s(sm + C_VX, g_att + ((s + 1) * NH + head) * AT_REC + AT_V + j * 4096, 4096, sm + CB_VX); }
                    }
                    if ((s & 3) == 1 && s + 3 < NSEG) asm volatile("prefetch.global.L2 [%0];" :: "l"(&g_flags.v[((s + 3) >> 2) * 32]));
                    if (s + 2 < NSEG && ((s & 3) != 2 || __all_sync(0xffffffffu, ld_rlx(&g_flags.v[((s + 2) >> 2) * 32 + head]) >= 2)))
                        asm volatile("prefetch.global.L2 [%0];" :: "l"(g_att + ((s + 2) * NH + head) * AT_REC + AT_V + j * 4096 + (opaque(mrd) << 3 & 0xf80)));
                } else if (s + 1 < NSEG) {
                    mbar_wait(sm + CB_OX, s & 1);
                    if (elect()) x_fill(mp, sm, s + 1, j, 1);
                }
            }
        }
        const int t2 = (opaque(mrd) >> 4 & 31) + warp * 32;
        last_blocks(mp, ar, sm, blk, t2);
        mod_tail(ar, sm + E_B, sm + EB_REL, blk, t2);
    } else {
        asm volatile("setmaxnreg.dec.sync.aligned.u32 %0;" :: "n"(REG_L));
        asm volatile("barrier.cluster.arrive.relaxed.aligned;" ::: "memory");
        if (blk < 80) {
            ModSlice<128> ms;
            ms.load(ar.wmod, ar.c, blk * 16, tid - 256); ms.partial(sm + C_QM, tid - 256);
            bar_sync(3, 128);
            if (w == 0) {
                const uint32_t v = ModSlice<128>::total(sm + C_QM, lane);
                asm volatile("st.relaxed.gpu.global.u32 [%0], %1;" :: "l"(g_flags.mod1 + blk * 8 + (lane & 7)), "r"(~v) : "memory");
            }
        }
        uint32_t m0[5][4], mm = 0;
#pragma unroll
        for (int i = 0; i < 20; i++) {
            const unsigned short* p = (const unsigned short*)ar.mem0 + (i & 3) * 2 * DM + (i >> 2) * 128 + tid - 256;
            m0[i >> 2][i & 3] = __ldg(p) | (uint32_t)__ldg(p + DM) << 16;
        }
        {
            asm volatile("barrier.cluster.wait.aligned;" ::: "memory");
            if (w == 3) {
                w_flag_wait(&g_flags.h, 96);
                if (elect()) { mbar_expect(sm + CB_XM, 8192); tma3d(sm + C_MEM, &mp.h2, 0, 0, sm + CB_XM); x_fill(mp, sm, 0, j, 0); x_fill(mp, sm, 0, j, 1); }
                __syncwarp();
            }
            if (w == 1) {
                const uint64_t ef = policy_stream();
                uint64_t en; asm("createpolicy.fractional.L2::evict_normal.b64 %0, 1.0;" : "=l"(en));
                if (WPOS) bar_sync(2, 288);
#pragma unroll 1
                for (int c = 0; c < 18; c++) {
                    const uint32_t bar = sm + EB_B + 8 * (c & 1);
                    if (c >= 2) mbar_wait(bar, (c / 2 - 1) & 1);
                    if (c == 8) { mbar_wait(bar + 8, 1); if (elect()) mbar_arrive(sm + CB_W); bar_sync(1, 288); }
                    if (c == 13 && elect()) mbar_arrive(sm + CB_W2);
                    if (c < 16 && elect()) {
                        mbar_expect(bar, c < 12 ? 20480 : c < 15 ? WO_BLK : 0);
                        if (c < 12) tma2d_ef(sm + C_WV + (c & 7) * 20480, c < 4 ? &mp.wq : c < 8 ? &mp.wk : &mp.wv, col0, (c & 3) * 160, bar, c < 8 ? ef : en);
                        else if (c < 15) tma3d(sm + C_WO + (c - 12) * WO_BLK, &mp.wo, head * DH + (j + c - 12) % 3 * 64, 7 * j, bar);
                    }
                    __syncwarp();
                }
                if (elect()) mbar_arrive(sm + CB_W3);
                w_flag_wait(&g_flags.v[head], 2);
                if (elect()) { mbar_expect(sm + CB_VX, 4096); bulk_g2s(sm + C_VX, g_att + head * AT_REC + AT_V + j * 4096, 4096, sm + CB_VX); }
            } else {
                uint32_t mw = 0;
#pragma unroll 1
                for (int c = 0; c < 2; c++) {
                    mbar_wait(sm + (c ? CB_W3 : CB_W2), 0);
                    uint32_t m = 0;
                    const uint32_t end = sm + (c ? C_XR : C_WO);
#pragma unroll 1
                    for (uint32_t a = sm + c * C_WO + (w - (w > 0)) * 4096 + lane * 16; a < end; a += 3 * 4096) {
                        float4 z[8];
#pragma unroll
                        for (int i = 0; i < 8; i++) z[i] = lds128f(a + i * 512);
#pragma unroll
                        for (int i = 0; i < 8; i++) m = amax2(amax2(amax2(amax2(m, __float_as_uint(z[i].x)), __float_as_uint(z[i].y)), __float_as_uint(z[i].z)), __float_as_uint(z[i].w));
                    }
                    mw |= amax_warp(m) << (16 * c);
                }
                asm volatile("st.shared.u32 [%0], %1;" :: "r"(sm + C_KM + w * 4), "r"(mw) : "memory");
                bar_sync(3, 96);
                if (w == 0) asm volatile("st.relaxed.gpu.global.u32 [%0], %1;" :: "l"(g_flags.wmax + blk), "r"(amax2(amax2(mw, lds32(sm + C_KM + 8)), lds32(sm + C_KM + 12)) | 0x8000) : "memory");
            }
        }
        bar_sync(9, 384);
#pragma unroll
        for (int i = 0; i < 5; i++) {
            asm volatile("st.shared.v4.u32 [%0], {%1,%2,%3,%4};" :: "r"(sm + C_MEM + (tid - 256 + i * 128) * 16), "r"(m0[i][0]), "r"(m0[i][1]), "r"(m0[i][2]), "r"(m0[i][3]) : "memory");
            mm = amax2(amax2(amax2(amax2(mm, m0[i][0]), m0[i][1]), m0[i][2]), m0[i][3]);
        }
        asm volatile("st.shared.u32 [%0], %1; st.shared.u32 [%2], 0x3f800000;" :: "r"(sm + C_MX + w * 4), "r"(amax_warp(mm)), "r"(sm + C_UN) : "memory");
        int ew = __shfl_sync(0xffffffffu, lds32(sm + C_LAG), 0), es = 0;
        const float scale = 0.07216878364870322f;
        uint32_t va[8][4], mr = memrd;
#pragma unroll
        for (int i = 0; i < 8; i++) ldsm4t(va[i], sm + C_WV + ((mi >> 1) * 8 + r) * 128 + (((2 * w + (mi & 1)) ^ r) << 4) + i * 2048);
        bar_sync(1, 384);
        for (int s = 0; s < NSEG; s++) {
            const float un = __uint_as_float((127 - es) << 23);
            if (w == 0) {
                mbar_wait(sm + CB_XD, s & 1);
                if (s + 1 < NSEG) { if (elect()) x_fill(mp, sm, s + 1, j, 0); }
                else { if (BPOS != 2) wo_half(mp, sm, blk, 0); if (BPOS != 0) wo_half(mp, sm, blk, 1); }
            } else if (w == 1 && s > 0) { BULK_WAIT(); seg_done(s - 1, head); }
            const uint32_t l0 = mr >> 4 & 31, r0 = l0 & 7, m0 = l0 >> 3;
            uint32_t kb[2][4];
            {
                const uint32_t k7 = (4 * (w & 1) + (r0 >> 2) * 2 + (r0 & 1)) ^ (r0 << 1 & 4);
                const uint32_t kxrd = sm + C_KX + (16 * (w >> 1) + (r0 << 2 & 8) + k7) * 128 + ((m0 ^ k7) << 4);
                ldsm4(kb[0], kxrd); ldsm4(kb[1], kxrd ^ 64);
            }
            float vd[4];
            {
                uint32_t c[4][4];
#pragma unroll
                for (int i = 0; i < 4; i++) ldsm4t(c[i], mr + i * 512);
                float d[2][4] = {{0, 0, 0, 0}, {0, 0, 0, 0}};
#pragma unroll
                for (int i = 0; i < 8; i++) mma16q(d[i & 1], va[i], c[i >> 1][2 * (i & 1)], c[i >> 1][2 * (i & 1) + 1]);
#pragma unroll
                for (int i = 0; i < 4; i++) vd[i] = d[0][i] + d[1][i];
            }
            uint32_t zr = 0;
            if (w == 2)
                asm volatile("atom.relaxed.gpu.global.exch.b32 %0, [%1], 0;" : "=r"(zr)
                    : "l"(g_acc + ((s & 2) ^ 2) * (ACC_PAIR / 2) + (s & 1) * 512 + (blk >> 2) * 1024 + (blk & 3) * 128 + l0 * 4) : "memory");
            __syncwarp();
            const uint32_t sco = (w >> 1) * 512 + (l0 >> 2) * 64 + (w & 1) * 32 + ((l0 >> 1) & 1) * 16;
            const uint32_t qrd = sm + C_QM + ((m0 & 1) * 2 + (m0 >> 1)) * 128 + r0 * 16;
            const uint32_t scdst = sm + C_SC + j * 1280 + sco;
            const uint32_t rbase = mapa(sm, (j + 1 + (l0 & 1)) % 3) - sm;
            const uint32_t scm = 1024 + (l0 >> 1) * 16 - sco;
            const uint32_t v7 = r0 ^ (m0 << 2 & 4), vxrd = sm + C_VX + (8 * m0 + v7) * 128 + (((2 * w) ^ v7) << 4);
            if (s == 0) {
                uint32_t t[3];
                for (int n = 0;; n++) {
#pragma unroll
                    for (int i = 0; i < 3; i++) t[i] = ld_rlx(g_flags.wmax + l0 + 32 * i);
                    if (__all_sync(0xffffffffu, t[0] && t[1] && t[2])) break;
                    cut(n, 1 << 22);
                }
                const uint32_t m = amax2(amax2(amax2(0, t[0]), t[1]), t[2]);
                const int e = 371 - (int)(__reduce_max_sync(0xffffffffu, m & 0xffffu) >> 7) - (int)(__reduce_max_sync(0xffffffffu, m >> 16) >> 7);
                ew = e << 16 | (min(e - ew, 100) & 0xffff);
            }
            mbar_wait(sm + CB_VX, s & 1);
            uint32_t vb[2][4];
            ldsm4t(vb[0], vxrd); ldsm4t(vb[1], vxrd ^ 16);
            const uint32_t word = sm + C_WO + (m0 & 1) * 4096 + ((m0 >> 1) * 8 + r0) * 64 + ((w ^ (r0 >> 1)) << 4);
            const uint32_t word6 = word + 6 * 4096 - (m0 & 1) * 3072;
            const uint32_t oxrd = sm + C_OX + l0 * 8;
            const uint32_t ord = sm + C_OX + (l0 >> 1) * 16 + w * 256 + (2 - (l0 & 1)) * 1024 + rbase;
            pin(mr, qrd, scdst, rbase, scm); pin(mr, scdst + scm + rbase, scdst + rbase, sm + CB_SC + rbase, scdst + scm); pin(mr, word, word6, oxrd, ord);
            pin(mr, __float_as_uint(vd[0]), __float_as_uint(vd[1]), __float_as_uint(vd[2]), __float_as_uint(vd[3]));
            bar_sync(2, 384);
            const bool odd = mr & 16;
            {
                uint32_t qa[2][4];
                ldsm4(qa[0], qrd); ldsm4(qa[1], qrd + 512);
                float x[4];
                if (w == 3) {
                    uint32_t km[2][4]; float y[4];
                    ldsm4(km[0], mr + (C_KM - C_MEM)); ldsm4(km[1], mr + (C_KM - C_MEM) + 512);
                    score_tile(qa, kb, odd, x); score_tile(qa, km, odd, y);
                    send_piece(x, scdst + rbase, sm + CB_SC + rbase, scdst); send_piece(y, scdst + scm + rbase, sm + CB_SC + rbase, scdst + scm);
                } else {
                    score_tile(qa, kb, odd, x);
                    send_piece(x, scdst + rbase, sm + CB_SC + rbase, scdst);
                }
            }
            bar_arrive(7, 384);
            if (elect()) mbar_arrive(sm + CB_SC);
            {
                const float4 z = lds128f(sm + C_MX);
                const int em = (int)(max(max(__float_as_uint(z.x), __float_as_uint(z.y)), max(__float_as_uint(z.z), __float_as_uint(z.w))) >> 7) - es;
                es = __shfl_sync(0xffffffffu, max(min((ew >> 16) - em, (int)(short)ew), -120), 0);
            }
            if (w == 0) PROF(4);
            const uint32_t vp = mr - (C_MEM - C_VP) + w * 512, vmst = mr + (C_VM - C_MEM) + w * 256;
            if (s + 1 == NSEG) {
                mbar_wait(sm + CB_SC, s & 1);
                bar_sync(4, 384);
                const float4 y0 = lds128f(vp), y1 = lds128f(vp + 2048);
                stsm2t(vmst, pack2((vd[0] + y0.x + y1.x) * un, (vd[1] + y0.y + y1.y) * un), pack2((vd[2] + y0.z + y1.z) * un, (vd[3] + y0.w + y1.w) * un));
                PROXY_FENCE();
                bar_sync(3, 128);
                if (w == 1) {
                    w_bulk_s2g(g_att + (s * NH + head) * AT_REC + AT_VM + j * 1024, sm + C_VM, 1024);
                    BULK_COMMIT();
                    if (BPOS == 0) wo_half(mp, sm, blk, 1);
                    BULK_WAIT(); seg_done(s, head);
                }
                __syncwarp();
                break;
            }
            cut(s + ar.D2, 0);
            mbar_wait(sm + CB_SC, s & 1);
            if (w == 0) PROF(8);
            float sv[10];
            {
                const uint32_t scrd = mr + (C_SC - C_MEM);
                float4 x[3], y[3]; float2 z[3];
#pragma unroll
                for (int p = 0; p < 3; p++) { x[p] = lds128f(scrd + p * 1280); y[p] = lds128f(scrd + p * 1280 + 512); z[p] = lds64f(oxrd + (C_SC - C_OX) + p * 1280 + 1024); }
                sv[0] = (x[0].x + x[1].x) + x[2].x; sv[1] = (x[0].y + x[1].y) + x[2].y; sv[2] = (x[0].z + x[1].z) + x[2].z; sv[3] = (x[0].w + x[1].w) + x[2].w;
                sv[4] = (y[0].x + y[1].x) + y[2].x; sv[5] = (y[0].y + y[1].y) + y[2].y; sv[6] = (y[0].z + y[1].z) + y[2].z; sv[7] = (y[0].w + y[1].w) + y[2].w;
                sv[8] = (z[0].x + z[1].x) + z[2].x; sv[9] = (z[0].y + z[1].y) + z[2].y;
            }
            float mx = fmaxf(fmaxf(fmaxf(sv[0], sv[1]), fmaxf(sv[2], sv[3])), fmaxf(fmaxf(fmaxf(sv[4], sv[5]), fmaxf(sv[6], sv[7])), fmaxf(sv[8], sv[9])));
            uint32_t a[NRING][4];
            auto frag = [&](int i) { const int p = i / 7, u = i % 7, o = (p >> 1) * WO_BLK + (p & 1) * 2048;
                                     return u == 3 ? word6 + o : word + o + (u > 3 ? 1024 + (u - 4) * 8192 : u * 8192); };
            mx = fmaxf(fmaxf(mx, __shfl_xor_sync(0xffffffffu, mx, 1)), fmaxf(__shfl_xor_sync(0xffffffffu, mx, 2), __shfl_xor_sync(0xffffffffu, mx, 3)));
            pin(mr, __float_as_uint(mx), 0, 0, 0);
            bar_sync(4, 384);
            {
                const float4 y0 = lds128f(vp), y1 = lds128f(vp + 2048);
                pin0(mr);
#pragma unroll
                for (int i = 0; i < NPRE; i++) ldsm4t(a[i], frag(i));
                pin0(mr);
                const float sl2e = scale * 1.4426950408889634f, mxl = mx * sl2e;
#pragma unroll
                for (int i = 9; i >= 0; i--) asm volatile("ex2.approx.ftz.f32 %0, %1;" : "=f"(sv[i]) : "f"(fmaf(sv[i], sl2e, -mxl)));
                const uint32_t pq[4] = {pack2(sv[0], sv[1]), pack2(sv[4], sv[5]), pack2(sv[2], sv[3]), pack2(sv[6], sv[7])}, pm = pack2(sv[8], sv[9]);
                if (w == 0) PROF(6);
                float o[2][4] = {{0, 0, 0, 0}, {0, 0, 0, 0}}, o2[2][4] = {{0, 0, 0, 0}, {0, 0, 0, 0}}, sx[4] = {0, 0, 0, 0};
                const uint32_t vm0 = pack2((vd[0] + y0.x + y1.x) * un, (vd[1] + y0.y + y1.y) * un), vm1 = pack2((vd[2] + y0.z + y1.z) * un, (vd[3] + y0.w + y1.w) * un);
                mma8(sx, pm, 0, 0x3f803f80u); mma8(o[0], pm, 0, vm0); mma8(o[1], pm, 0, vm1);
                mma16q(sx, pq, 0x3f803f80u, 0x3f803f80u);
#pragma unroll
                for (int u = 0; u < 2; u++) { mma16q(o[u], pq, vb[u][0], vb[u][1]); mma16q(o2[u], pq, vb[u][2], vb[u][3]); }
                float inv; asm("rcp.approx.ftz.f32 %0, %1;" : "=f"(inv) : "f"((sx[0] + sx[2]) * __uint_as_float((127 - es) << 23)));
                const uint32_t f0 = pack2((o[0][0] + o2[0][2]) * inv, (o[0][1] + o2[0][3]) * inv), f1 = pack2((o[1][0] + o2[1][2]) * inv, (o[1][1] + o2[1][3]) * inv);
                const uint32_t c = __shfl_xor_sync(0xffffffffu, f0, 1), d = __shfl_xor_sync(0xffffffffu, f1, 1);
                asm volatile("st.shared.v2.u32 [%0], {%1,%2};" :: "r"(oxrd + w * 256), "r"(f0), "r"(f1) : "memory");
                asm volatile("st.async.shared::cluster.mbarrier::complete_tx::bytes.v4.b32 [%0], {%1,%2,%3,%4}, [%5];"
                    :: "r"(ord), "r"(odd ? c : f0), "r"(odd ? d : f1), "r"(odd ? f0 : c), "r"(odd ? f1 : d), "r"(sm + CB_OX + rbase) : "memory");
                stsm2t(vmst, vm0, vm1);
            }
            if (w == 0) PROF(10);
#pragma unroll
            for (int i = NPRE; i < NRING; i++) ldsm4t(a[i], frag(i));
            bar_sync(3, 128);
            float e[5][4];
#pragma unroll
            for (int q = 0; q < 5; q++) e[q][0] = e[q][1] = e[q][2] = e[q][3] = 0.f;
            constexpr int LAG = 2;
            uint8_t* pdst = g_acc + ((s & 2) * (ACC_PAIR / 2) + (s & 1) * 512 + w * 2048 + j * 8192 - C_MEM - sm + mr);
#pragma unroll
            for (int h = 0; h < 3; h++) {
                uint32_t ob[4][2];
                if (h == 1) {
#pragma unroll
                    for (int i = 14 - LAG; i < 14; i++) ldsm4t(a[i % NRING], frag(i + NRING));
                    pin(mr, zr, (uint32_t)(uint64_t)pdst, (uint32_t)((uint64_t)pdst >> 32), 0);
                    mbar_wait(sm + CB_OX, s & 1);
                    if (w == 0) PROF(9);
                }
#pragma unroll
                for (int k = 0; k < 4; k++) lds64(ob[k], oxrd + h * 1024 + k * 256);
#pragma unroll
                for (int i = 14 * h; i < 14 * h + 14; i++) {
                    const int u = i % 7, k = 2 * (i / 7 & 1);
                    if (u == 3) { mma16q(e[3], a[i % NRING], ob[k][0], ob[k][1]); mma16q(e[4], a[i % NRING], ob[k + 1][0], ob[k + 1][1]); }
                    else mma16q(e[u & 3], a[i % NRING], ob[k + (u >> 2)][0], ob[k + (u >> 2)][1]);
                    if (i == B5AT) { pin(mr, a[i % NRING][0], a[i % NRING][1], a[i % NRING][2], a[i % NRING][3]); bar_arrive(5, 384); }
                    if (i >= LAG && !(i >= 14 && i < 14 + LAG) && i - LAG + NRING < 42) ldsm4t(a[(i - LAG) % NRING], frag(i - LAG + NRING));
                }
            }
            {
                const uint32_t w6 = pack2h(e[3][0] + e[4][2], e[3][1] + e[4][3]), one = 0x3c003c00u;
                asm volatile("red.relaxed.gpu.global.add.noftz.v4.f16x2 [%0], {%1,%2,%3,%4};"
                    :: "l"(pdst), "r"(pack2h(e[0][0], e[0][1])), "r"(pack2h(e[0][2], e[0][3])), "r"(pack2h(e[1][0], e[1][1])), "r"(odd ? w6 : one) : "memory");
                asm volatile("red.relaxed.gpu.global.add.noftz.v4.f16x2 [%0], {%1,%2,%3,%4};"
                    :: "l"(pdst + 1024), "r"(pack2h(e[1][2], e[1][3])), "r"(pack2h(e[2][0], e[2][1])), "r"(pack2h(e[2][2], e[2][3])), "r"(odd ? one : w6) : "memory");
            }
            const uint32_t tw = clock();
            if (w == 0) { PROF(14); PROFG(25); }
            PROXY_FENCE();
            bar_sync(6, 160);
            mr = opaque(mr);
            const uint32_t ln = mr >> 4 & 31, due = tw + lds32(sm + C_LAG);
            const uint32_t vr = sm + C_WV + ((ln >> 4) * 8 + (ln & 7)) * 128 + (((2 * w + (ln >> 3 & 1)) ^ (ln & 7)) << 4);
            const uint32_t ms0 = sm + C_MEM + w * 128 + (ln & 7) * 16 + (ln >> 3) * 512, ms1 = ms0 + (ln < 24 ? 2048 : 1536);
            if (BPOS == 2 && w == 0 && s + 2 == NSEG) wo_half(mp, sm, blk, 0);
            if (w == 2) { w_expect(sm + CB_SC, 2560); w_expect(sm + CB_OX, 2048); asm volatile("st.shared.u32 [%0], %1;" :: "r"(sm + C_UN), "r"((127 - es) << 23) : "memory"); }
            if (w == 1) { w_bulk_s2g(g_att + (s * NH + head) * AT_REC + AT_VM + j * 1024, sm + C_VM, 1024); BULK_COMMIT(); }
            const uint8_t* src = pdst - j * 8192;
            pin(mr, ms0, ms1, (uint32_t)(uint64_t)src, (uint32_t)((uint64_t)src >> 32));
            pin(mr, vr, due, 0, 0);
            cut(s + ar.D2, 1);
#pragma unroll
            for (int i = 0; i < 8; i++) ldsm4t(va[i], vr + i * 2048);
            wait_until(due);
            if (w == 0) { PROF(5); PROFG(26); }
            uint4 v[6];
            auto fetch = [&]() {
#pragma unroll
                for (int k = 0; k < 6; k++)
                    asm volatile("ld.relaxed.gpu.global.v4.u32 {%0,%1,%2,%3}, [%4];" : "=r"(v[k].x), "=r"(v[k].y), "=r"(v[k].z), "=r"(v[k].w) : "l"(src + (k >> 1) * 8192 + (k & 1) * 1024) : "memory");
            };
            fetch();
            PROFV(20 + w, 0);
            bar_sync(9, 384);
#pragma unroll 1
            for (int n = 0; __any_sync(0xffffffffu, ~((odd ? v[1].w & v[3].w & v[5].w : v[0].w & v[2].w & v[4].w)) & 0x50005000u); n++) {
                PROFV(20 + w, n + 1);
                cut(n, SPIN_LIMIT);
                fetch();
            }
            uint32_t cv[3][7];
#pragma unroll
            for (int k = 0; k < 3; k++) {
                const uint4 x = v[2 * k], y = v[2 * k + 1];
                const uint32_t u[7] = {x.x, x.y, x.z, y.x, y.y, y.z, k < 2 ? (odd ? x.w : y.w) : 0u};
#pragma unroll
                for (int i = 0; i < 7; i++) cv[k][i] = f16_to_bf16(u[i]);
                stsm4(ms0 + k * 3584, cv[k][0], cv[k][1], cv[k][2], cv[k][3]);
                if (k < 2) stsm4(ms1 + k * 3584, cv[k][4], cv[k][5], cv[k][6], cv[k][6]);
                else asm volatile("stmatrix.sync.aligned.m8n8.x2.shared.b16 [%0], {%1,%2};" :: "r"(ms1 + k * 3584), "r"(cv[k][4]), "r"(cv[k][5]) : "memory");
            }
            if (w == 0) PROF(16);
            bar_sync(1, 384);
            cut(s + ar.D2, 2);
            uint32_t mc = 0;
#pragma unroll
            for (int i = 0; i < 20; i++) mc = amax2(mc, cv[i / 7][i % 7]);
            asm volatile("st.shared.u32 [%0], %1;" :: "r"(sm + C_MX + w * 4), "r"(amax_warp(mc)) : "memory");
        }
        if (w >= 2) end_loads(mp, ar, sm, blk, w - 2);
        else bar_arrive(5, 384);
        if (w == 0) {
            const int l = mr >> 4 & 31;
            if (blk < 14) {
                uint4 k = __ldcg((const uint4*)g_key + blk * 32 + l);
#pragma unroll 1
                for (int it = 0; it < 3; it++) {
                    const uint32_t m = __reduce_max_sync(0xffffffffu, max(max(k.x, k.y), max(k.z, k.w)));
                    if (k.x == m) k.x = 0; if (k.y == m) k.y = 0; if (k.z == m) k.z = 0; if (k.w == m) k.w = 0;
                    if (m && l < 20) asm volatile("prefetch.global.L2 [%0];" :: "l"((l < 10 ? g_h2 : g_x1 - 640) + (~m & (S_TOK - 1)) * DM + l * 64));
                }
            }
            mbar_wait(sm + EB_REL, 0);
            flags_release(l);
        }
    }
}

struct SideMaps { CUtensorMap h, wv, ost, o, wo, slab3, slab2, lnp[3]; };
constexpr int SD_ST = 43008, SD_NST = 4, SD_EPI = SD_NST * SD_ST, SD_PAR = SD_EPI + 2 * 24576, SD_BAR = SD_PAR + 6400, SD_SMEM = SD_BAR + 256;
#define VLEAD 16
#define SEG_LAST 60
#define N_LIGHT 6
#define B_HELP 13
#define AUNR_ 2
constexpr int AUNR = AUNR_;
#define KSO 6
#define KSA 3
#define B_8 10
#define B_16 13
__device__ __forceinline__ int o_shift(int b) { return b >= B_16 ? 4 : b >= B_8 ? 3 : 2; }
__device__ __forceinline__ int o_split(int b) { return 1 << o_shift(b); }
__device__ __forceinline__ uint32_t o_done(int b) { return b >= B_LATE ? 160 : 4 << o_shift(b); }
__device__ __forceinline__ int next_item(int lane) {
    const int b0 = lane & 15, hi = lane >> 4;
    for (int n = 0;; n++) {
        const uint32_t w0 = ld_rlx(g_flags.qk + lane), w1 = ld_rlx(g_flags.at + lane), w2 = ld_rlx(&g_flags.c[0][0] + lane), w3 = ld_rlx(&g_flags.c[2][0] + lane), w4 = ld_rlx(&g_flags.seg[SEG_LAST * 32]);
        const uint32_t o01 = __ballot_sync(0xffffffffu, lane && w2 < 32), o23 = __ballot_sync(0xffffffffu, b0 < (hi ? 14 : B_LATE) && w3 < 2u * o_split(b0));
        const uint32_t ra = __ballot_sync(0xffffffffu, w0 >= (hi ? 64u : 192u)), rb = __ballot_sync(0xffffffffu, w1 >= (hi ? o_done(b0) : 256u));
        const int bv = __ffs(o01 | 0x10000) - 1, ba = __ffs(o01 >> 16 | 0x10000) - 1, bo = __ffs(o23 | 0x10000) - 1, bl = __ffs(o23 >> 16 | 0x10000) - 1;
        if (bl == 16 && ba == 16) return -1;
        const int bc = __ffs(~ra | 0x10000) - 1;
        const bool last = ba == 15 && w4 >= 6;
        const bool r1 = (ra & ra >> 16) >> ba & 1, r2 = (rb & 0xffff) >> bo & 1, r3 = rb >> 16 >> bl & 1;
        const int kind = ba == 16 ? (bo < 16 ? 2 : 3) : last ? 1 :
                         blockIdx.x < N_LIGHT ? (r1 ? 1 : r3 ? 3 : bv < 16 ? 0 : -1) :
                         bv < 16 && (bv <= bc + VLEAD || !r2) ? 0 : r1 && ba >= B_HELP ? 1 : r2 ? 2 : r1 ? 1 : r3 ? 3 : bo < ba ? 2 : -1;
        if (kind < 0) { if (n > (1 << 20)) __trap(); __nanosleep(300); continue; }
        const int b = kind == 3 ? bl : kind == 2 ? bo : kind == 1 ? ba : bv;
        uint32_t i = 0;
        if (lane == 0) asm volatile("atom.relaxed.gpu.global.add.u32 %0, [%1], 1;" : "=r"(i) : "l"(&g_flags.c[kind][b]) : "memory");
        i = __shfl_sync(0xffffffffu, i, 0);
        if (i < (kind < 2 ? 32u : 2u * o_split(b))) return kind << 16 | b << 8 | i | ((kind == 1 ? r1 : kind == 2 ? r2 : r3) ? 128 : 0);
    }
}

template <int NP, int CH>
__device__ __forceinline__ void tile_out(const float (&acc)[8 * NP], uint32_t eb, uint32_t efull, uint32_t eempty, int& eph, int lane) {
    const int r = lane & 7, mi = lane >> 3, row = (mi & 1) * 8 + r;
    mbar_wait(eempty, eph); eph ^= 1;
#pragma unroll
    for (int p = 0; p < NP; p++) {
        const int oc = 2 * p + (mi >> 1);
        stsm4(eb + (oc >> 3) * CH + row * 128 + (((oc & 7) ^ r) << 4), pack2(acc[8 * p], acc[8 * p + 1]), pack2(acc[8 * p + 2], acc[8 * p + 3]),
              pack2(acc[8 * p + 4], acc[8 * p + 5]), pack2(acc[8 * p + 6], acc[8 * p + 7]));
    }
    asm volatile("fence.proxy.async.shared::cta;" ::: "memory");
    __syncwarp();
    if (lane == 0) mbar_arrive(efull);
}

template <int MT>
__device__ __forceinline__ void attn_tile(uint32_t base, uint32_t dst, uint32_t eempty, int eph, int lane) {
    constexpr int NK = MT ? 5 : 3;
    const int r = lane & 7, mi = lane >> 3, g = lane >> 2, t = lane & 3;
    float sc[NK][4];
#pragma unroll
    for (int n = 0; n < NK; n++) sc[n][0] = sc[n][1] = sc[n][2] = sc[n][3] = 0.f;
#pragma unroll AUNR
    for (int k2 = 0; k2 < 6; k2++) {
        const uint32_t cb = (k2 >> 1) * 8192, c0 = (k2 & 1) * 4;
        uint32_t a0[4], a1[4], bb[NK][4];
        ldsm4(a0, base + cb + (16 * MT + (mi & 1) * 8 + r) * 128 + (((c0 + (mi >> 1)) ^ r) << 4));
        ldsm4(a1, base + cb + (16 * MT + (mi & 1) * 8 + r) * 128 + (((c0 + 2 + (mi >> 1)) ^ r) << 4));
#pragma unroll
        for (int n = 0; n < NK; n++)
            ldsm4(bb[n], n < NK - 1 ? base + 4096 + cb + (8 * n + r) * 128 + (((c0 + mi) ^ r) << 4) : base + 36864 + k2 * 512 + lane * 16);
#pragma unroll
        for (int n = 0; n < NK; n++) mma16(sc[n], a0[0], a0[1], a0[2], a0[3], bb[n][0], bb[n][1]);
#pragma unroll
        for (int n = 0; n < NK; n++) mma16(sc[n], a1[0], a1[1], a1[2], a1[3], bb[n][2], bb[n][3]);
    }
    const float scale = 0.07216878364870322f, l2e = 1.4426950408889634f;
    float v[2][2 * NK], mx[2], sum[2];
#pragma unroll
    for (int hf = 0; hf < 2; hf++) {
        mx[hf] = -INFINITY;
#pragma unroll
        for (int n = 0; n < NK; n++) {
            uint32_t u = pack2(sc[n][2 * hf], sc[n][2 * hf + 1]);
            u = pack2(lo_f(u) * scale, hi_f(u) * scale);
            const int lim = 16 * MT + 8 * hf + g - 8 * n - 2 * t;
            v[hf][2 * n] = (n < NK - 1 && lim < 0) ? -1e9f : lo_f(u);
            v[hf][2 * n + 1] = (n < NK - 1 && lim < 1) ? -1e9f : hi_f(u);
            mx[hf] = fmaxf(mx[hf], fmaxf(v[hf][2 * n], v[hf][2 * n + 1]));
        }
    }
#pragma unroll
    for (int o = 1; o < 4; o <<= 1)
#pragma unroll
        for (int hf = 0; hf < 2; hf++) mx[hf] = fmaxf(mx[hf], __shfl_xor_sync(0xffffffffu, mx[hf], o));
#pragma unroll
    for (int hf = 0; hf < 2; hf++) {
        sum[hf] = 0;
#pragma unroll
        for (int q = 0; q < 2 * NK; q++) { asm("ex2.approx.ftz.f32 %0, %1;" : "=f"(v[hf][q]) : "f"((v[hf][q] - mx[hf]) * l2e)); sum[hf] += v[hf][q]; }
    }
#pragma unroll
    for (int o = 1; o < 4; o <<= 1)
#pragma unroll
        for (int hf = 0; hf < 2; hf++) sum[hf] += __shfl_xor_sync(0xffffffffu, sum[hf], o);
    uint32_t pa[NK][2];
#pragma unroll
    for (int hf = 0; hf < 2; hf++) {
        const float inv = __fdividef(1.f, sum[hf]);
#pragma unroll
        for (int n = 0; n < NK; n++) pa[n][hf] = pack2(v[hf][2 * n] * inv, v[hf][2 * n + 1] * inv);
    }
    mbar_wait(eempty, eph);
#pragma unroll AUNR
    for (int n4 = 0; n4 < 6; n4++) {
        const uint32_t cb = (n4 >> 1) * 4096, c0 = (n4 & 1) * 4;
        uint32_t bm[4], bb[2 + 2 * MT][4];
        ldsm4t(bm, base + AT_VM + n4 * 512 + lane * 16);
#pragma unroll
        for (int u = 0; u < 2 + 2 * MT; u++) ldsm4t(bb[u], base + AT_V + cb + (16 * (u >> 1) + 8 * (mi & 1) + r) * 128 + (((c0 + 2 * (u & 1) + (mi >> 1)) ^ r) << 4));
        float o[4][4];
#pragma unroll
        for (int u = 0; u < 4; u++) { o[u][0] = o[u][1] = o[u][2] = o[u][3] = 0.f; mma8(o[u], pa[NK - 1][0], pa[NK - 1][1], bm[u]); }
#pragma unroll
        for (int u = 0; u < 4 + 4 * MT; u++) mma16(o[u & 3], pa[u >> 2 << 1][0], pa[u >> 2 << 1][1], pa[(u >> 2 << 1) + 1][0], pa[(u >> 2 << 1) + 1][1], bb[u >> 1][2 * (u & 1)], bb[u >> 1][2 * (u & 1) + 1]);
#pragma unroll
        for (int p = 0; p < 2; p++)
            stsm4(dst + (n4 >> 1) * 2048 + ((mi & 1) * 8 + r) * 128 + (((c0 + 2 * p + (mi >> 1)) ^ r) << 4), pack2(o[2 * p][0], o[2 * p][1]), pack2(o[2 * p][2], o[2 * p][3]),
                  pack2(o[2 * p + 1][0], o[2 * p + 1][1]), pack2(o[2 * p + 1][2], o[2 * p + 1][3]));
    }
}

__device__ __forceinline__ uint32_t ln_row(const uint32_t (&as)[10], const uint2 (&xin)[5], int row, uint32_t par, bf16* out, uint64_t ef, int lane) {
    const uint32_t pa = par + lane * 8;
    uint32_t xv[10], hv[10], sv[10], tv[10];
#pragma unroll
    for (int q = 0; q < 5; q++) {
        uint32_t ga[2], t[2], u[2];
        lds64(ga, pa + q * 256); lds64(t, pa + 1280 + q * 256); lds64(u, pa + 2560 + q * 256);
#pragma unroll
        for (int e = 0; e < 2; e++) {
            xv[2 * q + e] = add2(e ? xin[q].y : xin[q].x, mul2(ga[e], as[2 * q + e]));
            tv[2 * q + e] = t[e]; sv[2 * q + e] = u[e];
        }
        st_ef(g_x1 + row * DM + lane * 4 + q * 128, make_uint2(xv[2 * q], xv[2 * q + 1]), ef);
    }
    ln_mod(xv, sv, tv, hv);
    float rs = 0;
#pragma unroll
    for (int q = 0; q < 5; q++) {
        const int c = row * DM + lane * 4 + q * 128;
        const uint32_t h0 = hv[2 * q], h1 = hv[2 * q + 1];
        uint32_t gb[2], wv[2];
        lds64(gb, pa + 3840 + q * 256); lds64(wv, pa + 5120 + q * 256);
        rs += (lo_f(h0) * lo_f(wv[0]) + hi_f(h0) * hi_f(wv[0])) + (lo_f(h1) * lo_f(wv[1]) + hi_f(h1) * hi_f(wv[1]));
        st_ef(g_h2 + c, make_uint2(h0, h1), ef);
        st_ef(out + c, make_uint2(add2(xv[2 * q], mul2(gb[0], h0)), add2(xv[2 * q + 1], mul2(gb[1], h1))), ef);
    }
    const uint32_t rb = pack2(0.f, warp_sum(rs));
    return (((int)rb < 0 ? ~rb : rb | 0x80000000u) & 0xffff0000u) | (uint32_t)(2 * S_TOK - 1 - row);
}
__device__ __forceinline__ void key_out(uint32_t key) {
    __syncwarp();
    if (key) asm volatile("st.release.gpu.global.u32 [%0], %1;" :: "l"(g_key + (~key & (S_TOK - 1))), "r"(key) : "memory");
}

__global__ void __launch_bounds__(384, 1) k_side(const __grid_constant__ SideMaps mp, const bf16* __restrict__ x, const bf16* __restrict__ wr, const bf16* wmod, const bf16* cvec, bf16* __restrict__ out) {
    extern __shared__ __align__(1024) uint8_t smraw[];
    const uint32_t sm = smem_u32(smraw);
    if (sm & 1023) __trap();
    const uint32_t FULL = sm + SD_BAR, EMPTY = FULL + 32, EFULL = FULL + 64, EEMPTY = FULL + 80, IFULL = FULL + 96, IEMPTY = FULL + 128, IQ = FULL + 160, SCHED = FULL + 176, PARAM = FULL + 184;
    const int tid = threadIdx.x, warp = __shfl_sync(0xffffffffu, tid >> 5, 0), lane = tid & 31;
    const uint64_t ef = policy_stream();
    if (tid == 0) {
        for (int i = 0; i < SD_NST; i++) { mbar_init(FULL + 8 * i, 1); mbar_init(EMPTY + 8 * i, 2); }
        for (int i = 0; i < 2; i++) { mbar_init(EFULL + 8 * i, 4); mbar_init(EEMPTY + 8 * i, 1); }
        for (int i = 0; i < 4; i++) { mbar_init(IFULL + 8 * i, 1); mbar_init(IEMPTY + 8 * i, 11); }
        mbar_init(SCHED, 1); mbar_init(PARAM, 1);
        asm volatile("fence.mbarrier_init.release.cluster;" ::: "memory");
    }
    __syncthreads();
    if (warp >= 8) {
      asm volatile("setmaxnreg.dec.sync.aligned.u32 40;");
      if (warp == 8) {
        int st = 0, ph = 1;
        for (int q = 0;; q++) {
            mbar_wait(IFULL + 8 * (q & 3), (q >> 2) & 1);
            const int it = __shfl_sync(0xffffffffu, lds32(IQ + 4 * (q & 3)), 0);
            if (elect()) mbar_arrive(IEMPTY + 8 * (q & 3));
            if (it < 0) break;
            const int kind = it >> 16, b = (it >> 8) & 255, i = it & 63;
            const int nst = kind == 0 ? 10 : kind == 1 ? 4 : kind == 2 ? 192 >> o_shift(b) : b == 14 ? 4 : 2;
            const int ksched = kind == 0 ? 4 : kind == 2 ? nst - KSO : (it & 128) ? -1 : kind == 1 ? KSA : 0;
            if (ksched < 0 && elect()) mbar_arrive(SCHED);
            const bool look = !(it & 128);
            if (look && kind == 1) flag_wait(&g_flags.v[b * 32 + i], 2);
            if (look && kind == 3 && b < 14) flag_wait(&g_flags.o[b], o_done(b));
            for (int kb = 0; kb < nst; kb++) {
                mbar_wait(EMPTY + 8 * st, ph);
                const uint32_t base = sm + st * SD_ST, fb = FULL + 8 * st;
                if (look && kind == 1) flag_wait(&g_flags.seg[(b * 4 + kb) * 32 + i], 6);
                if (kb == ksched && elect()) mbar_arrive(SCHED);
                if (kind == 0) {
                    if (q == 0 && kb == 0) {
                        if (elect()) {
#pragma unroll 1
                            for (int c = 0; c < SD_NST; c++) tma3d(sm + c * SD_ST + 16384, &mp.wv, c * 64, i * 3, FULL + 8 * c);
#pragma unroll 1
                            for (int c = SD_NST; c < 10; c++)
                                asm volatile("cp.async.bulk.prefetch.tensor.3d.L2.global [%0, {0, %1, %2}];" :: "l"((uint64_t)&mp.wv), "r"(c * 64), "r"(i * 3) : "memory");
                        }
                        flag_wait(&g_flags.h, 96);
                    }
                    if (elect()) {
                        mbar_expect(fb, 40960);
                        tma2d(base, &mp.h, kb * 64, b * 128, fb);
                        if (q || kb >= SD_NST) tma3d(base + 16384, &mp.wv, kb * 64, i * 3, fb);
                    }
                } else if (kind == 1) {
                    if (elect()) {
                        mbar_expect(fb, 43008);
                        asm volatile("cp.async.bulk.shared::cluster.global.mbarrier::complete_tx::bytes.L2::cache_hint [%0], [%1], %2, [%3], %4;"
                            :: "r"(base), "l"(g_att + ((b * 4 + kb) * NH + i) * AT_REC), "r"(AT_REC), "r"(fb), "l"(ef) : "memory");
                    }
                } else if (kind == 3) {
                    if (b == 14 && !(kb & 1)) flag_wait(&g_flags.fin[(kb + (i >> 4)) * 32], 80);
                    if (elect()) { mbar_expect(fb, 40960); tma3d_ef(base, &mp.lnp[o_shift(b) - 2], i * (160 >> o_shift(b)), b * KSPLIT + (kb << o_shift(b) >> 1), fb, ef); }
                } else {
                    const int k0 = ((i >> 1) * nst + kb) * 32;
                    if (elect()) { mbar_expect(fb, 28672); tma3d(base + 8192, &mp.wo, k0, (i & 1) * 5, fb); }
                    if (look && kb % 12 == 0) flag_wait(&g_flags.pair[b * 16 + k0 / 384], 16);
                    if (elect()) tma2d_ef(base, &mp.o, k0, b * 128, fb, ef);
                }
                __syncwarp();
                if (++st == SD_NST) { st = 0; ph ^= 1; }
            }
        }
      } else if (warp == 11) {
        bool fin = false, par = false;
        for (int q = 0;; q++) {
            if (q) mbar_wait(SCHED, (q - 1) & 1);
            int it = fin ? -1 : q == 0 && blockIdx.x < 32 ? blockIdx.x : next_item(lane);
            if (it < 0 && !fin && blockIdx.x < 32) { it = 3 << 16 | 14 << 8 | blockIdx.x; fin = true; }
            if (lane == 0) {
                if (it >> 16 == 3) {
                    const int b = (it >> 8) & 255, nr = 64 >> o_shift(b);
                    asm volatile("cp.async.bulk.prefetch.L2.global [%0], %1;" :: "l"(x + (b * 128 + (it & 63) * nr) * DM), "r"(nr * DM * 2) : "memory");
                }
                mbar_wait(IEMPTY + 8 * (q & 3), ((q >> 2) & 1) ^ 1);
                asm volatile("st.shared.u32 [%0], %1;" :: "r"(IQ + 4 * (q & 3)), "r"(it) : "memory");
                mbar_arrive(IFULL + 8 * (q & 3));
            }
            if (!par && it >> 16 == 3) {
                par = true;
                flag_wait(&g_flags.mod, 64);
                if (lane == 0) { mbar_expect(PARAM, 6400); bulk_g2s(sm + SD_PAR, g_mod + 2 * DM, 5120, PARAM); bulk_g2s(sm + SD_PAR + 5120, wr, 1280, PARAM); }
            }
            __syncwarp();
            if (it < 0) break;
        }
        flags_release(lane);
      } else {
        if (lane == 0) {
            const int wg = warp - 9; int ph = 0;
            for (int q = 0;; q++) {
                mbar_wait(IFULL + 8 * (q & 3), (q >> 2) & 1);
                const int it = lds32(IQ + 4 * (q & 3));
                mbar_arrive(IEMPTY + 8 * (q & 3));
                if (it < 0) break;
                const int kind = it >> 16, b = (it >> 8) & 255, i = it & 63;
                if (kind & 1) continue;
#pragma unroll 1
                for (int rd = 0; rd < (kind == 2 ? 2 : 1); rd++) {
                    mbar_wait(EFULL + 8 * wg, ph); ph ^= 1;
                    const uint32_t src = sm + SD_EPI + wg * 24576;
                    if (kind == 2) tma3d_store(rd ? &mp.slab2 : &mp.slab3, (b * KSPLIT + (i >> 1)) * 128 + wg * 64, (i & 1) * 5 + rd * 3, src, ef, false);
                    else {
                        uint8_t* dst = g_att + ((b * 4 + wg * 2) * NH + i) * AT_REC + AT_V;
                        asm volatile("cp.async.bulk.global.shared::cta.bulk_group.L2::cache_hint [%0], [%1], 12288, %2;" :: "l"(dst), "r"(src), "l"(ef) : "memory");
                        asm volatile("cp.async.bulk.global.shared::cta.bulk_group.L2::cache_hint [%0], [%1], 12288, %2;" :: "l"(dst + NH * AT_REC), "r"(src + 12288), "l"(ef) : "memory");
                    }
                    asm volatile("cp.async.bulk.commit_group;" ::: "memory");
                    asm volatile("cp.async.bulk.wait_group.read 0;" ::: "memory");
                    mbar_arrive(EEMPTY + 8 * wg);
                }
                asm volatile("cp.async.bulk.wait_group 0;" ::: "memory");
                bump(kind == 0 ? &g_flags.v[b * 32 + i] : &g_flags.o[b]);
                if (kind == 0) bump(&g_flags.vb[b]);
            }
        }
      }
    } else {
        asm volatile("setmaxnreg.inc.sync.aligned.u32 232;");
        const int wg = warp >> 2, w = warp & 3;
        int st = 0, ph = 0, eph = 1;
        bool att = false;
        if (blockIdx.x < 32) {
            const uint32_t buf = sm + SD_EPI;
#pragma unroll 1
            for (int k = tid; k < DM; k += 256) {
                const float f = __uint_as_float((uint32_t)__ldg((const unsigned short*)cvec + k) << 16);
                asm volatile("st.shared.f32 [%0], %1;" :: "r"(buf + k * 4), "f"(bfr(__fdividef(f, 1.f + __expf(-f)))) : "memory");
            }
            const int t = min(tid, 199), k0 = t / 10 * 32;
            const bf16* wm = wmod + k0 * (6 * DM) + 2 * DM + blockIdx.x * 80 + t % 10 * 8;
            float a[8] = {0, 0, 0, 0, 0, 0, 0, 0};
#pragma unroll 1
            for (int k = 0; k < 32; k += 8) {
                uint4 z[8];
#pragma unroll
                for (int e = 0; e < 8; e++) z[e] = __ldcs((const uint4*)(wm + (k + e) * (6 * DM)));
                if (k == 0) bar_sync(1, 256);
#pragma unroll
                for (int e = 0; e < 8; e++) {
                    const float f = __uint_as_float(lds32(buf + (k0 + k + e) * 4));
                    a[0] += f * lo_f(z[e].x); a[1] += f * hi_f(z[e].x); a[2] += f * lo_f(z[e].y); a[3] += f * hi_f(z[e].y);
                    a[4] += f * lo_f(z[e].z); a[5] += f * hi_f(z[e].z); a[6] += f * lo_f(z[e].w); a[7] += f * hi_f(z[e].w);
                }
            }
            sts128f(buf + 4096 + t * 32, a[0], a[1], a[2], a[3]); sts128f(buf + 4112 + t * 32, a[4], a[5], a[6], a[7]);
            bar_sync(1, 256);
            uint32_t bad = 0;
            if (tid < 40) {
                float a0 = 0, a1 = 0;
#pragma unroll 4
                for (int g = 0; g < 20; g++) { const float2 v = lds64f(buf + 4096 + g * 320 + tid * 8); a0 += v.x; a1 += v.y; }
                uint32_t* dst = (uint32_t*)(g_mod + 2 * DM + blockIdx.x * 80) + tid;
                *dst = pack2(a0, a1);
                bad = ld_rlx(dst) ^ pack2(a0, a1);
            }
            if (warp < 2 && !__any_sync(0xffffffffu, bad) && lane == 0) bump(&g_flags.mod);
            bar_sync(1, 256);
        }
        const uint32_t eb = sm + SD_EPI + wg * 24576;
        for (int q = 0;; q++) {
            mbar_wait(IFULL + 8 * (q & 3), (q >> 2) & 1);
            const int itc = lds32(IQ + 4 * (q & 3));
            __syncwarp();
            if (lane == 0) mbar_arrive(IEMPTY + 8 * (q & 3));
            if (itc < 0) break;
            const int kind = itc >> 16, b = (itc >> 8) & 255, i = itc & 63;
            if (att && kind != 1) { bar_sync(2 + wg, 128); att = false; }
            if (kind == 0) {
                float acc[96];
#pragma unroll
                for (int n = 0; n < 96; n++) acc[n] = 0.f;
                int prev = -1;
#pragma unroll 1
                for (int kb = 0; kb < 10; kb++) {
                    mbar_wait(FULL + 8 * st, ph);
                    const uint32_t base = sm + st * SD_ST;
                    WG_FENCE();
#pragma unroll
                    for (int ks = 0; ks < 4; ks++)
                        wgmma_ss_n192_tb(acc, mkdesc(base + wg * 8192 + ks * 32, 16, 1024), mkdesc(base + 16384 + ks * 2048, 8192, 1024), (kb | ks) != 0);
                    WG_COMMIT();
                    WG_WAIT(1);
                    if (prev >= 0 && (tid & 127) == 0) mbar_arrive(EMPTY + 8 * prev);
                    prev = st;
                    if (++st == SD_NST) { st = 0; ph ^= 1; }
                }
                WG_WAIT(0);
                if ((tid & 127) == 0) mbar_arrive(EMPTY + 8 * prev);
                tile_out<12, 4096>(acc, eb + (w >> 1) * 12288 + (w & 1) * 2048, EFULL + 8 * wg, EEMPTY + 8 * wg, eph, lane);
            } else if (kind == 1) {
                const int seg = warp >> 1, mt = warp & 1;
                int sst = st + seg, sph = ph; if (sst >= SD_NST) { sst -= SD_NST; sph ^= 1; }
                ph ^= 1;
                mbar_wait(FULL + 8 * sst, sph);
                const uint32_t base = sm + sst * SD_ST;
                if (mt) attn_tile<1>(base, eb + w * 6144, EEMPTY + 8 * wg, eph, lane);
                else attn_tile<0>(base, eb + w * 6144, EEMPTY + 8 * wg, eph, lane);
                asm volatile("fence.proxy.async.shared::cta;" ::: "memory");
                __syncwarp();
                if (lane == 0) {
                    mbar_arrive(EMPTY + 8 * sst);
                    tma3d_store(&mp.ost, b * 128 + warp * 16, i * 3, eb + w * 6144, ef, false);
                    BULK_COMMIT(); BULK_WAIT();
                    bump(b == 15 ? &g_flags.half[(i & 30) + wg] : &g_flags.pair[b * 16 + (i >> 1)]); bump(&g_flags.at[b]);
                }
                __syncwarp();
                att = true;
            } else if (kind == 2) {
                float acc[96], acc2[64];
#pragma unroll
                for (int n = 0; n < 96; n++) acc[n] = 0.f;
#pragma unroll
                for (int n = 0; n < 64; n++) acc2[n] = 0.f;
                int prev = -1;
#pragma unroll 1
                for (int kb = 192 >> o_shift(b); kb > 0; kb--) {
                    const uint32_t base = sm + st * SD_ST;
                    mbar_wait(FULL + 8 * st, ph);
                    WG_FENCE();
#pragma unroll
                    for (int ks = 0; ks < 2; ks++) {
                        const uint64_t da = (mkdesc(base + wg * 4096 + ks * 32, 16, 512) & ~(3ull << 62)) | (2ull << 62);
                        wgmma_ss_n192_tb(acc, da, mkdesc(base + 8192 + ks * 2048, 4096, 1024), 1);
                        wgmma_ss_n128_tb(acc2, da, mkdesc(base + 8192 + 3 * 4096 + ks * 2048, 4096, 1024), 1);
                    }
                    WG_COMMIT();
                    WG_WAIT(1);
                    if (prev >= 0 && (tid & 127) == 0) mbar_arrive(EMPTY + 8 * prev);
                    prev = st;
                    if (++st == SD_NST) { st = 0; ph ^= 1; }
                }
                WG_WAIT(0);
                if ((tid & 127) == 0) mbar_arrive(EMPTY + 8 * prev);
                tile_out<12, 8192>(acc, eb + w * 2048, EFULL + 8 * wg, EEMPTY + 8 * wg, eph, lane);
                tile_out<8, 8192>(acc2, eb + w * 2048, EFULL + 8 * wg, EEMPTY + 8 * wg, eph, lane);
            } else {
                const int sh = o_shift(b), nr = 64 >> sh, fw = b == 14 ? wg : 0, row0 = (b + fw) * 128 + i * nr, lw = warp - 4 * fw;
                if (fw) { st += 2; if (st >= SD_NST) { st -= SD_NST; ph ^= 1; } }
                int st1 = st + 1, ph1 = ph; if (st1 == SD_NST) { st1 = 0; ph1 ^= 1; }
                uint2 xin[2][5];
                uint32_t as[2][10] = {};
#pragma unroll
                for (int q2 = 0; q2 < 10; q2++) xin[q2 & 1][q2 >> 1] = ld_ef(x + (row0 + ((warp + 8 * (q2 & 1)) & (nr - 1))) * DM + lane * 4 + (q2 >> 1) * 128, ef);
                mbar_wait(PARAM, 0); mbar_wait(FULL + 8 * st, ph); mbar_wait(FULL + 8 * st1, ph1);
#pragma unroll 1
                for (int lrow = lw + (nr & 16) / 2; lrow >= 0 && lrow < nr; lrow -= 8) {
                    float a[20];
#pragma unroll
                    for (int q2 = 0; q2 < 20; q2++) a[q2] = 0.f;
#pragma unroll 1
                    for (int k = 0; k < (1 << sh >> 1); k++) {
                        const uint32_t ad = sm + ((k << (6 - sh)) + lrow) * 1280 + lane * 8;
                        uint32_t z[10][2];
#pragma unroll
                        for (int q2 = 0; q2 < 10; q2++) lds64(z[q2], ad + (q2 < 5 ? st : st1) * SD_ST + q2 % 5 * 256);
#pragma unroll
                        for (int q2 = 0; q2 < 10; q2++) { float* p = a + q2 % 5 * 4; p[0] += lo_f(z[q2][0]); p[1] += hi_f(z[q2][0]); p[2] += lo_f(z[q2][1]); p[3] += hi_f(z[q2][1]); }
                    }
#pragma unroll
                    for (int q2 = 0; q2 < 10; q2++) { as[1][q2] = as[0][q2]; as[0][q2] = pack2(a[2 * q2], a[2 * q2 + 1]); }
                }
                bar_sync(2 + wg, 128);
                if ((tid & 127) == 0) { mbar_arrive(EMPTY + 8 * st); mbar_arrive(EMPTY + 8 * st1); }
                uint32_t key = 0;
#pragma unroll 1
                for (int lrow = lw; lrow < nr; lrow += 8) {
                    const int row = row0 + lrow;
                    const uint32_t k1 = ln_row(as[0], xin[0], row, sm + SD_PAR, out, ef, lane);
                    if (lane == lrow >> 3) key = k1;
#pragma unroll
                    for (int q2 = 0; q2 < 5; q2++) { as[0][2 * q2] = as[1][2 * q2]; as[0][2 * q2 + 1] = as[1][2 * q2 + 1]; xin[0][q2] = xin[1][q2]; }
                }
                key_out(key);
                st = st1 + 1; ph = ph1; if (st == SD_NST) { st = 0; ph ^= 1; }
            }
        }
    }
    __syncwarp();
    asm volatile("griddepcontrol.wait;" ::: "memory");
}

#define P_D1 650
#define P_DL 700
#define P_DG 29
typedef CUresult (*EncodeFn)(CUtensorMap*, CUtensorMapDataType, cuuint32_t, void*, const cuuint64_t*, const cuuint64_t*, const cuuint32_t*, const cuuint32_t*,
                             CUtensorMapInterleave, CUtensorMapSwizzle, CUtensorMapL2promotion, CUtensorMapFloatOOBfill);
static EncodeFn s_encode = nullptr;
static void make_map(CUtensorMap* m, const void* p, int rows, int cols, int box_rows, int box_cols = 64) {
    cuuint64_t dims[2] = {(cuuint64_t)cols, (cuuint64_t)rows}, strides[1] = {(cuuint64_t)cols * 2};
    cuuint32_t box[2] = {(cuuint32_t)box_cols, (cuuint32_t)box_rows}, es[2] = {1, 1};
    s_encode(m, CU_TENSOR_MAP_DATA_TYPE_BFLOAT16, 2, (void*)p, dims, strides, box, es, CU_TENSOR_MAP_INTERLEAVE_NONE,
             box_cols == 64 ? CU_TENSOR_MAP_SWIZZLE_128B : box_cols == 32 ? CU_TENSOR_MAP_SWIZZLE_64B : CU_TENSOR_MAP_SWIZZLE_NONE, CU_TENSOR_MAP_L2_PROMOTION_L2_256B, CU_TENSOR_MAP_FLOAT_OOB_FILL_NONE);
}
static void make_map3(CUtensorMap* m, const void* p, int rows, int cols, int box_rows, int box_chunks, int cw = 64) {
    cuuint64_t dims[3] = {(cuuint64_t)cw, (cuuint64_t)rows, (cuuint64_t)(cols / cw)}, strides[2] = {(cuuint64_t)cols * 2, (cuuint64_t)cw * 2};
    cuuint32_t box[3] = {(cuuint32_t)cw, (cuuint32_t)box_rows, (cuuint32_t)box_chunks}, es[3] = {1, 1, 1};
    s_encode(m, CU_TENSOR_MAP_DATA_TYPE_BFLOAT16, 3, (void*)p, dims, strides, box, es, CU_TENSOR_MAP_INTERLEAVE_NONE,
             cw == 64 ? CU_TENSOR_MAP_SWIZZLE_128B : CU_TENSOR_MAP_SWIZZLE_64B, CU_TENSOR_MAP_L2_PROMOTION_L2_256B, CU_TENSOR_MAP_FLOAT_OOB_FILL_NONE);
}
template <typename T> static void* sym(T& s) { void* p = nullptr; cudaGetSymbolAddress(&p, s); return p; }

extern "C" void kernel_launch(void* const* d_in, const int* in_sizes, int n_in, void* d_out, int out_size) {
    const bf16 *x = (const bf16*)d_in[0], *mem0 = (const bf16*)d_in[1], *Wq = (const bf16*)d_in[2], *Wk = (const bf16*)d_in[3],
               *Wv = (const bf16*)d_in[4], *Wo = (const bf16*)d_in[5], *wr = (const bf16*)d_in[8], *wgate = (const bf16*)d_in[9],
               *wup = (const bf16*)d_in[10], *wdown = (const bf16*)d_in[11], *c = (const bf16*)d_in[12], *wmod = (const bf16*)d_in[13];
    bf16* out = (bf16*)d_out;
    if (!s_encode) {
        cudaDriverEntryPointQueryResult qr;
        cudaGetDriverEntryPoint("cuTensorMapEncodeTiled", (void**)&s_encode, cudaEnableDefault, &qr);
        cudaFuncSetAttribute(k_side, cudaFuncAttributeMaxDynamicSharedMemorySize, SD_SMEM);
        cudaFuncSetAttribute(k_chain, cudaFuncAttributeMaxDynamicSharedMemorySize, C_SMEM);
    }
    ChainMaps cm; SideMaps sd;
    make_map(&sd.h, sym(g_h), S_TOK, DM, 128); make_map3(&sd.wv, Wv, DM, HD, 64, 3);
    make_map3(&sd.ost, sym(g_o), S_TOK, HD, 16, 3); make_map(&sd.o, sym(g_o), S_TOK, HD, 128, 32); make_map3(&sd.wo, Wo, HD, DM, 32, 5);
    make_map3(&sd.slab3, sym(g_slab), 16 * KSPLIT * 128, DM, 64, 3); make_map3(&sd.slab2, sym(g_slab), 16 * KSPLIT * 128, DM, 64, 2);
    make_map3(&cm.wo15, Wo, HD, DM, 192, 2); make_map3(&cm.o15, sym(g_o), S_TOK, HD, 64, 2); make_map3(&cm.slab16, sym(g_slab), 16 * KSPLIT * 128, DM, 16, 2);
    for (int i = 0; i < 3; i++) {
        cuuint64_t dims[3] = {256, 320, 16 * KSPLIT}, strides[2] = {512, 128 * DM * 2};
        cuuint32_t box[3] = {256, 40u >> i, 2u << i}, es[3] = {1, 1, 1};
        s_encode(&sd.lnp[i], CU_TENSOR_MAP_DATA_TYPE_BFLOAT16, 3, sym(g_slab), dims, strides, box, es, CU_TENSOR_MAP_INTERLEAVE_NONE,
                 CU_TENSOR_MAP_SWIZZLE_NONE, CU_TENSOR_MAP_L2_PROMOTION_L2_256B, CU_TENSOR_MAP_FLOAT_OOB_FILL_NONE);
    }
    make_map(&cm.wq, Wq, DM, HD, 160); make_map(&cm.wk, Wk, DM, HD, 160); make_map(&cm.wv, Wv, DM, HD, 160); make_map3(&cm.wo, Wo, HD, DM, 64, 7, 32);
    make_map3(&cm.h2, sym(g_h), S_TOK, DM, 32, 2);
    ChainArgs ar = {x, mem0, c, wmod, Wv, Wo, wgate, wup, wdown, out, P_D1, P_DL, P_DG};
    k_chain<<<96, 384, C_SMEM>>>(cm, ar);
    cudaLaunchConfig_t cfg = {};
    cfg.gridDim = dim3(N_SIDE); cfg.blockDim = dim3(384); cfg.dynamicSmemBytes = SD_SMEM; cfg.stream = cudaStreamPerThread;
    cudaLaunchAttribute at[1]; at[0].id = cudaLaunchAttributeProgrammaticStreamSerialization; at[0].val.programmaticStreamSerializationAllowed = 1;
    cfg.attrs = at; cfg.numAttrs = 1;
    cudaLaunchKernelEx(&cfg, k_side, sd, x, wr, wmod, c, out);
}
```

```cpp
#include <cuda_runtime.h>
#include <cuda_bf16.h>
#include <cuda.h>
#include <stdint.h>
#include <stdio.h>
#include <string.h>
#include <stdlib.h>

typedef __nv_bfloat16 bf16;
constexpr int S_TOK = 2048, DM = 640, NH = 32, DH = 192, HD = NH * DH, NSEG = 64, SEG = 32, FF = 1536;

__device__ bf16 g_mod[6 * DM];
__device__ bf16 g_h[S_TOK * DM];
constexpr int AT_REC = 43008, AT_V = 24576, AT_KM = 36864, AT_VM = 39936;
__device__ __align__(1024) uint8_t g_att[NSEG * NH * AT_REC];
__device__ bf16 g_o[S_TOK * HD];
__device__ bf16 g_A[S_TOK * DM];
__device__ bf16 g_x1[S_TOK * DM];
__device__ bf16 g_h2[S_TOK * DM];
__device__ __align__(128) uint32_t g_key[S_TOK];
__device__ int g_idx[8];
__device__ __align__(128) uint32_t g_gu[FF / 8 * 32];
constexpr int ACC_PAIR = 24 * 1024;
__device__ __align__(1024) uint8_t g_acc[2 * ACC_PAIR];
__device__ __align__(1024) uint32_t g_stamp[4 * 12 * 32];
constexpr int KSPLIT = 16;
__device__ bf16 g_slab[16 * KSPLIT * 128 * DM];
struct __align__(128) Flags {
    uint32_t qk[16], vb[16];
    uint32_t at[16], o[16];
    uint32_t c[4][16];
    uint32_t half[32];
    uint32_t fin[4 * 32];
    uint32_t v[16 * 32];
    uint32_t seg[64 * 32];
    uint32_t pair[16 * 16];
    uint32_t h, pad2[31], done, mod, pad3[30];
    uint32_t mod1[DM];
    uint32_t wmax[96];
};
__device__ Flags g_flags;

__device__ __forceinline__ uint32_t smem_u32(const void* p) { return (uint32_t)__cvta_generic_to_shared(p); }
__device__ __forceinline__ uint32_t pack2(float lo, float hi) {
    uint32_t r; asm("cvt.rn.bf16x2.f32 %0, %1, %2;" : "=r"(r) : "f"(hi), "f"(lo)); return r;
}
__device__ __forceinline__ float bfr(float x) { return __uint_as_float(pack2(0.f, x)); }
__device__ __forceinline__ float inv_std(float var) {
    float s, r; asm("sqrt.approx.f32 %0, %1;" : "=f"(s) : "f"(bfr(bfr(var) + 1e-5f))); asm("rcp.approx.f32 %0, %1;" : "=f"(r) : "f"(bfr(s))); return r;
}
__device__ __forceinline__ float lo_f(uint32_t v) { return __uint_as_float(v << 16); }
__device__ __forceinline__ float hi_f(uint32_t v) { return __uint_as_float(v & 0xffff0000u); }
__device__ __forceinline__ void mbar_init(uint32_t bar, int cnt) { asm volatile("mbarrier.init.shared::cta.b64 [%0], %1;" :: "r"(bar), "r"(cnt) : "memory"); }
__device__ __forceinline__ void mbar_expect(uint32_t bar, int bytes) { asm volatile("mbarrier.arrive.expect_tx.shared::cta.b64 _, [%0], %1;" :: "r"(bar), "r"(bytes) : "memory"); }
__device__ __forceinline__ void mbar_arrive(uint32_t bar) { asm volatile("mbarrier.arrive.shared::cta.b64 _, [%0];" :: "r"(bar) : "memory"); }
__device__ __forceinline__ bool mbar_try(uint32_t bar, int par) {
    uint32_t ok; asm volatile("{ .reg .pred p; mbarrier.try_wait.parity.shared::cta.b64 p, [%1], %2; selp.u32 %0, 1, 0, p; }" : "=r"(ok) : "r"(bar), "r"(par) : "memory"); return ok;
}
__device__ __forceinline__ bool mbar_try_cluster(uint32_t bar, int par) {
    uint32_t ok; asm volatile("{ .reg .pred p; mbarrier.try_wait.parity.acquire.cluster.shared::cta.b64 p, [%1], %2; selp.u32 %0, 1, 0, p; }" : "=r"(ok) : "r"(bar), "r"(par) : "memory"); return ok;
}
__device__ __forceinline__ bool mbar_test(uint32_t bar, uint32_t par) {
    uint32_t ok; asm volatile("{ .reg .pred p; mbarrier.test_wait.parity.shared::cta.b64 p, [%1], %2; selp.u32 %0, 1, 0, p; }" : "=r"(ok) : "r"(bar), "r"(par) : "memory"); return ok;
}
constexpr int SPIN_LIMIT = 1 << 18;
__device__ __forceinline__ void mbar_wait(uint32_t bar, uint32_t par) {
    asm volatile("{ .reg .pred p, q; .reg .u32 n; mov.u32 n, 0;\n"
                 "W_%=: mbarrier.try_wait.parity.shared::cta.b64 p, [%0], %1;\n"
                 "@p bra.uni D_%=;\n"
                 "add.u32 n, n, 1; setp.lt.u32 q, n, 0x200000; @q bra.uni W_%=;\n"
                 "trap;\n"
                 "D_%=: }" :: "r"(bar), "r"(par) : "memory");
}
__device__ __forceinline__ void tma2d(uint32_t dst, const CUtensorMap* m, int c0, int c1, uint32_t bar) {
    asm volatile("cp.async.bulk.tensor.2d.shared::cluster.global.mbarrier::complete_tx::bytes [%0], [%1, {%3, %4}], [%2];"
        :: "r"(dst), "l"((uint64_t)m), "r"(bar), "r"(c0), "r"(c1) : "memory");
}
__device__ __forceinline__ void tma2d_mc(uint32_t dst, const CUtensorMap* m, int c0, int c1, uint32_t bar, uint16_t mask) {
    asm volatile("cp.async.bulk.tensor.2d.shared::cluster.global.mbarrier::complete_tx::bytes.multicast::cluster [%0], [%1, {%3, %4}], [%2], %5;"
        :: "r"(dst), "l"((uint64_t)m), "r"(bar), "r"(c0), "r"(c1), "h"(mask) : "memory");
}
__device__ __forceinline__ uint64_t policy_stream() { uint64_t p; asm("createpolicy.fractional.L2::evict_first.b64 %0, 1.0;" : "=l"(p)); return p; }
__device__ __forceinline__ void tma2d_ef(uint32_t dst, const CUtensorMap* m, int c0, int c1, uint32_t bar, uint64_t pol) {
    asm volatile("cp.async.bulk.tensor.2d.shared::cluster.global.mbarrier::complete_tx::bytes.L2::cache_hint [%0], [%1, {%3, %4}], [%2], %5;"
        :: "r"(dst), "l"((uint64_t)m), "r"(bar), "r"(c0), "r"(c1), "l"(pol) : "memory");
}
__device__ __forceinline__ void tma3d(uint32_t dst, const CUtensorMap* m, int row, int chunk, uint32_t bar) {
    asm volatile("cp.async.bulk.tensor.3d.shared::cluster.global.mbarrier::complete_tx::bytes [%0], [%1, {0, %3, %4}], [%2];"
        :: "r"(dst), "l"((uint64_t)m), "r"(bar), "r"(row), "r"(chunk) : "memory");
}
__device__ __forceinline__ void tma3d_ef(uint32_t dst, const CUtensorMap* m, int row, int chunk, uint32_t bar, uint64_t pol) {
    asm volatile("cp.async.bulk.tensor.3d.shared::cluster.global.mbarrier::complete_tx::bytes.L2::cache_hint [%0], [%1, {0, %3, %4}], [%2], %5;"
        :: "r"(dst), "l"((uint64_t)m), "r"(bar), "r"(row), "r"(chunk), "l"(pol) : "memory");
}
__device__ __forceinline__ void tma3d_store(const CUtensorMap* m, int row, int chunk, uint32_t src, uint64_t pol, bool hint) {
    if (hint) asm volatile("cp.async.bulk.tensor.3d.global.shared::cta.bulk_group.L2::cache_hint [%0, {0, %2, %3}], [%1], %4;"
        :: "l"((uint64_t)m), "r"(src), "r"(row), "r"(chunk), "l"(pol) : "memory");
    else asm volatile("cp.async.bulk.tensor.3d.global.shared::cta.bulk_group [%0, {0, %2, %3}], [%1];"
        :: "l"((uint64_t)m), "r"(src), "r"(row), "r"(chunk) : "memory");
}
__device__ __forceinline__ bool elect() { uint32_t p; asm volatile("{ .reg .pred e; elect.sync _|e, -1; selp.u32 %0, 1, 0, e; }" : "=r"(p)); return p; }
__device__ __forceinline__ uint2 ld_ef(const void* p, uint64_t pol) {
    uint2 v; asm volatile("ld.relaxed.gpu.global.L2::cache_hint.v2.u32 {%0,%1}, [%2], %3;" : "=r"(v.x), "=r"(v.y) : "l"(p), "l"(pol)); return v;
}
__device__ __forceinline__ void st_ef(void* p, uint2 v, uint64_t pol) {
    asm volatile("st.global.L2::cache_hint.v2.u32 [%0], {%1,%2}, %3;" :: "l"(p), "r"(v.x), "r"(v.y), "l"(pol) : "memory");
}
__device__ __forceinline__ void tma2d_prefetch(const CUtensorMap* m, int c0, int c1) {
    asm volatile("cp.async.bulk.prefetch.tensor.2d.L2.global [%0, {%1, %2}];" :: "l"((uint64_t)m), "r"(c0), "r"(c1) : "memory");
}
__device__ __forceinline__ void mbar_arrive_remote(uint32_t bar) { asm volatile("mbarrier.arrive.relaxed.cluster.shared::cluster.b64 _, [%0];" :: "r"(bar) : "memory"); }
__device__ __forceinline__ void tma2d_store(const CUtensorMap* m, int c0, int c1, uint32_t src) {
    asm volatile("cp.async.bulk.tensor.2d.global.shared::cta.bulk_group [%0, {%2, %3}], [%1];"
        :: "l"((uint64_t)m), "r"(src), "r"(c0), "r"(c1) : "memory");
}
__device__ __forceinline__ void bulk_g2s(uint32_t dst, const void* src, int bytes, uint32_t bar) {
    asm volatile("cp.async.bulk.shared::cluster.global.mbarrier::complete_tx::bytes [%0], [%1], %2, [%3];" :: "r"(dst), "l"(src), "r"(bytes), "r"(bar) : "memory");
}
__device__ __forceinline__ void ldsm4(uint32_t (&r)[4], uint32_t a) {
    asm volatile("ldmatrix.sync.aligned.m8n8.x4.shared.b16 {%0,%1,%2,%3}, [%4];" : "=r"(r[0]), "=r"(r[1]), "=r"(r[2]), "=r"(r[3]) : "r"(a) : "memory");
}
__device__ __forceinline__ void ldsm4t(uint32_t (&r)[4], uint32_t a) {
    asm volatile("ldmatrix.sync.aligned.m8n8.x4.trans.shared.b16 {%0,%1,%2,%3}, [%4];" : "=r"(r[0]), "=r"(r[1]), "=r"(r[2]), "=r"(r[3]) : "r"(a) : "memory");
}
__device__ __forceinline__ void stsm4(uint32_t a, uint32_t r0, uint32_t r1, uint32_t r2, uint32_t r3) {
    asm volatile("stmatrix.sync.aligned.m8n8.x4.shared.b16 [%0], {%1,%2,%3,%4};" :: "r"(a), "r"(r0), "r"(r1), "r"(r2), "r"(r3) : "memory");
}
__device__ __forceinline__ void stsm4t(uint32_t a, uint32_t r0, uint32_t r1, uint32_t r2, uint32_t r3) {
    asm volatile("stmatrix.sync.aligned.m8n8.x4.trans.shared.b16 [%0], {%1,%2,%3,%4};" :: "r"(a), "r"(r0), "r"(r1), "r"(r2), "r"(r3) : "memory");
}
__device__ __forceinline__ void stsm2t(uint32_t a, uint32_t r0, uint32_t r1) {
    asm volatile("stmatrix.sync.aligned.m8n8.x2.trans.shared.b16 [%0], {%1,%2};" :: "r"(a), "r"(r0), "r"(r1) : "memory");
}
__device__ __forceinline__ uint32_t movm_t(uint32_t v) { uint32_t r; asm volatile("movmatrix.sync.aligned.m8n8.trans.b16 %0, %1;" : "=r"(r) : "r"(v)); return r; }
__device__ __forceinline__ void mma16(float (&d)[4], uint32_t a0, uint32_t a1, uint32_t a2, uint32_t a3, uint32_t b0, uint32_t b1) {
    asm volatile("mma.sync.aligned.m16n8k16.row.col.f32.bf16.bf16.f32 {%0,%1,%2,%3}, {%4,%5,%6,%7}, {%8,%9}, {%0,%1,%2,%3};"
        : "+f"(d[0]), "+f"(d[1]), "+f"(d[2]), "+f"(d[3]) : "r"(a0), "r"(a1), "r"(a2), "r"(a3), "r"(b0), "r"(b1));
}
__device__ __forceinline__ void mma8(float (&d)[4], uint32_t a0, uint32_t a1, uint32_t b0) {
    asm volatile("mma.sync.aligned.m16n8k8.row.col.f32.bf16.bf16.f32 {%0,%1,%2,%3}, {%4,%5}, {%6}, {%0,%1,%2,%3};"
        : "+f"(d[0]), "+f"(d[1]), "+f"(d[2]), "+f"(d[3]) : "r"(a0), "r"(a1), "r"(b0));
}
__device__ __forceinline__ uint32_t mapa(uint32_t a, uint32_t r) { uint32_t o; asm volatile("mapa.shared::cluster.u32 %0, %1, %2;" : "=r"(o) : "r"(a), "r"(r)); return o; }
__device__ __forceinline__ void bar_sync(int id, int n) { asm volatile("bar.sync %0, %1;" :: "r"(id), "r"(n) : "memory"); }
__device__ __forceinline__ void bar_arrive(int id, int n) { asm volatile("bar.arrive %0, %1;" :: "r"(id), "r"(n) : "memory"); }
__device__ __forceinline__ uint64_t mkdesc(uint32_t addr, uint32_t lbo, uint32_t sbo) {
    return (uint64_t)((addr & 0x3FFFF) >> 4) | ((uint64_t)(lbo >> 4) << 16) | ((uint64_t)(sbo >> 4) << 32) | (1ull << 62);
}
#define WG_FENCE()  asm volatile("wgmma.fence.sync.aligned;" ::: "memory")
#define WG_COMMIT() asm volatile("wgmma.commit_group.sync.aligned;" ::: "memory")
#define WG_WAIT(n)  asm volatile("wgmma.wait_group.sync.aligned %0;" :: "n"(n) : "memory")

__device__ __forceinline__ void wgmma_ss_n192_tb(float (&d)[96], uint64_t a, uint64_t b, int acc) {
    asm volatile("{ .reg .pred p; setp.ne.b32 p, %98, 0;\n"
        "wgmma.mma_async.sync.aligned.m64n192k16.f32.bf16.bf16 {%0,%1,%2,%3,%4,%5,%6,%7,%8,%9,%10,%11,%12,%13,%14,%15,%16,%17,%18,%19,%20,%21,%22,%23,%24,%25,%26,%27,%28,%29,%30,%31,%32,%33,%34,%35,%36,%37,%38,%39,%40,%41,%42,%43,%44,%45,%46,%47,%48,%49,%50,%51,%52,%53,%54,%55,%56,%57,%58,%59,%60,%61,%62,%63,%64,%65,%66,%67,%68,%69,%70,%71,%72,%73,%74,%75,%76,%77,%78,%79,%80,%81,%82,%83,%84,%85,%86,%87,%88,%89,%90,%91,%92,%93,%94,%95}, %96, %97, p, 1, 1, 0, 1; }"
        : "+f"(d[0]), "+f"(d[1]), "+f"(d[2]), "+f"(d[3]), "+f"(d[4]), "+f"(d[5]), "+f"(d[6]), "+f"(d[7]), "+f"(d[8]), "+f"(d[9]), "+f"(d[10]), "+f"(d[11]), "+f"(d[12]), "+f"(d[13]), "+f"(d[14]), "+f"(d[15]), "+f"(d[16]), "+f"(d[17]), "+f"(d[18]), "+f"(d[19]), "+f"(d[20]), "+f"(d[21]), "+f"(d[22]), "+f"(d[23]), "+f"(d[24]), "+f"(d[25]), "+f"(d[26]), "+f"(d[27]), "+f"(d[28]), "+f"(d[29]), "+f"(d[30]), "+f"(d[31]), "+f"(d[32]), "+f"(d[33]), "+f"(d[34]), "+f"(d[35]), "+f"(d[36]), "+f"(d[37]), "+f"(d[38]), "+f"(d[39]), "+f"(d[40]), "+f"(d[41]), "+f"(d[42]), "+f"(d[43]), "+f"(d[44]), "+f"(d[45]), "+f"(d[46]), "+f"(d[47]), "+f"(d[48]), "+f"(d[49]), "+f"(d[50]), "+f"(d[51]), "+f"(d[52]), "+f"(d[53]), "+f"(d[54]), "+f"(d[55]), "+f"(d[56]), "+f"(d[57]), "+f"(d[58]), "+f"(d[59]), "+f"(d[60]), "+f"(d[61]), "+f"(d[62]), "+f"(d[63]), "+f"(d[64]), "+f"(d[65]), "+f"(d[66]), "+f"(d[67]), "+f"(d[68]), "+f"(d[69]), "+f"(d[70]), "+f"(d[71]), "+f"(d[72]), "+f"(d[73]), "+f"(d[74]), "+f"(d[75]), "+f"(d[76]), "+f"(d[77]), "+f"(d[78]), "+f"(d[79]), "+f"(d[80]), "+f"(d[81]), "+f"(d[82]), "+f"(d[83]), "+f"(d[84]), "+f"(d[85]), "+f"(d[86]), "+f"(d[87]), "+f"(d[88]), "+f"(d[89]), "+f"(d[90]), "+f"(d[91]), "+f"(d[92]), "+f"(d[93]), "+f"(d[94]), "+f"(d[95])
        : "l"(a), "l"(b), "r"(acc));
}

__device__ __forceinline__ void wgmma_ss_n128_tb(float (&d)[64], uint64_t a, uint64_t b, int acc) {
    asm volatile("{ .reg .pred p; setp.ne.b32 p, %66, 0;\n"
        "wgmma.mma_async.sync.aligned.m64n128k16.f32.bf16.bf16 {%0,%1,%2,%3,%4,%5,%6,%7,%8,%9,%10,%11,%12,%13,%14,%15,%16,%17,%18,%19,%20,%21,%22,%23,%24,%25,%26,%27,%28,%29,%30,%31,%32,%33,%34,%35,%36,%37,%38,%39,%40,%41,%42,%43,%44,%45,%46,%47,%48,%49,%50,%51,%52,%53,%54,%55,%56,%57,%58,%59,%60,%61,%62,%63}, %64, %65, p, 1, 1, 0, 1; }"
        : "+f"(d[0]), "+f"(d[1]), "+f"(d[2]), "+f"(d[3]), "+f"(d[4]), "+f"(d[5]), "+f"(d[6]), "+f"(d[7]), "+f"(d[8]), "+f"(d[9]), "+f"(d[10]), "+f"(d[11]), "+f"(d[12]), "+f"(d[13]), "+f"(d[14]), "+f"(d[15]), "+f"(d[16]), "+f"(d[17]), "+f"(d[18]), "+f"(d[19]), "+f"(d[20]), "+f"(d[21]), "+f"(d[22]), "+f"(d[23]), "+f"(d[24]), "+f"(d[25]), "+f"(d[26]), "+f"(d[27]), "+f"(d[28]), "+f"(d[29]), "+f"(d[30]), "+f"(d[31]), "+f"(d[32]), "+f"(d[33]), "+f"(d[34]), "+f"(d[35]), "+f"(d[36]), "+f"(d[37]), "+f"(d[38]), "+f"(d[39]), "+f"(d[40]), "+f"(d[41]), "+f"(d[42]), "+f"(d[43]), "+f"(d[44]), "+f"(d[45]), "+f"(d[46]), "+f"(d[47]), "+f"(d[48]), "+f"(d[49]), "+f"(d[50]), "+f"(d[51]), "+f"(d[52]), "+f"(d[53]), "+f"(d[54]), "+f"(d[55]), "+f"(d[56]), "+f"(d[57]), "+f"(d[58]), "+f"(d[59]), "+f"(d[60]), "+f"(d[61]), "+f"(d[62]), "+f"(d[63])
        : "l"(a), "l"(b), "r"(acc));
}

__device__ __forceinline__ void wgmma_rs_n32(float (&d)[16], const uint32_t (&a)[4], uint64_t b, int acc) {
    asm volatile("{ .reg .pred p; setp.ne.b32 p, %21, 0;\n"
        "wgmma.mma_async.sync.aligned.m64n32k16.f32.bf16.bf16 {%0,%1,%2,%3,%4,%5,%6,%7,%8,%9,%10,%11,%12,%13,%14,%15}, {%16,%17,%18,%19}, %20, p, 1, 1, 0; }"
        : "+f"(d[0]), "+f"(d[1]), "+f"(d[2]), "+f"(d[3]), "+f"(d[4]), "+f"(d[5]), "+f"(d[6]), "+f"(d[7]), "+f"(d[8]), "+f"(d[9]), "+f"(d[10]), "+f"(d[11]), "+f"(d[12]), "+f"(d[13]), "+f"(d[14]), "+f"(d[15])
        : "r"(a[0]), "r"(a[1]), "r"(a[2]), "r"(a[3]), "l"(b), "r"(acc));
}

__device__ __forceinline__ float warp_sum(float v) {
#pragma unroll
    for (int o = 16; o; o >>= 1) v += __shfl_xor_sync(0xffffffffu, v, o);
    return v;
}
__device__ __forceinline__ uint32_t add2(uint32_t a, uint32_t b) { uint32_t r; asm("add.rn.bf16x2 %0, %1, %2;" : "=r"(r) : "r"(a), "r"(b)); return r; }
__device__ __forceinline__ uint32_t mul2(uint32_t a, uint32_t b) { uint32_t r; asm("mul.rn.bf16x2 %0, %1, %2;" : "=r"(r) : "r"(a), "r"(b)); return r; }
__device__ __forceinline__ uint32_t amax2(uint32_t m, uint32_t v) { uint32_t r; asm("max.u16x2 %0, %1, %2;" : "=r"(r) : "r"(m), "r"(v & 0x7fff7fffu)); return r; }
__device__ __forceinline__ uint32_t amax_warp(uint32_t m) { return __reduce_max_sync(0xffffffffu, max(m & 0xffffu, m >> 16)); }
__device__ __forceinline__ void ln_norm(const uint32_t (&xv)[10], uint32_t (&nv)[10]) {
    float s0 = 0, s1 = 0;
#pragma unroll
    for (int i = 0; i < 10; i++) { s0 += lo_f(xv[i]); s1 += hi_f(xv[i]); }
    const float mean = warp_sum(s0 + s1) * (1.f / DM);
    float q0 = 0, q1 = 0;
#pragma unroll
    for (int i = 0; i < 10; i++) { const float d0 = lo_f(xv[i]) - mean, d1 = hi_f(xv[i]) - mean; q0 += d0 * d0; q1 += d1 * d1; }
    const float inv = inv_std(warp_sum(q0 + q1) * (1.f / DM));
    const uint32_t mb = pack2(-mean, -mean);
#pragma unroll
    for (int i = 0; i < 10; i++) { const uint32_t d = add2(xv[i], mb); nv[i] = pack2(lo_f(d) * inv, hi_f(d) * inv); }
}
__device__ __forceinline__ void ln_mod(const uint32_t (&xv)[10], const uint32_t (&sv)[10], const uint32_t (&tv)[10], uint32_t (&hv)[10]) {
    ln_norm(xv, hv);
#pragma unroll
    for (int i = 0; i < 10; i++) hv[i] = add2(mul2(hv[i], add2(sv[i], 0x3f803f80u)), tv[i]);
}
__device__ __forceinline__ uint32_t ld_rlx(const uint32_t* f) { uint32_t v; asm volatile("ld.relaxed.gpu.global.u32 %0, [%1];" : "=r"(v) : "l"(f) : "memory"); return v; }
__device__ __forceinline__ void bump(uint32_t* f) { asm volatile("red.relaxed.gpu.global.add.u32 [%0], 1;" :: "l"(f) : "memory"); }
#define NAP 100
__device__ __forceinline__ void flag_wait(const uint32_t* f, uint32_t target) {
    for (int n = 0;; n++) {
        uint32_t v; asm volatile("ld.relaxed.gpu.global.u32 %0, [%1];" : "=r"(v) : "l"(f) : "memory");
        if (v >= target) break;
        if (n > (1 << 22)) __trap();
        __nanosleep(NAP);
    }
}
__device__ __forceinline__ void flag_add(uint32_t* f, uint32_t v = 1) { asm volatile("red.release.gpu.global.add.u32 [%0], %1;" :: "l"(f), "r"(v) : "memory"); }
constexpr int N_SIDE = 36;
__device__ __forceinline__ void flags_release(int lane) {
    uint32_t old = 0;
    if (lane == 0) asm volatile("atom.relaxed.gpu.global.add.u32 %0, [%1], 1;" : "=r"(old) : "l"(&g_flags.done) : "memory");
    if (__shfl_sync(0xffffffffu, old, 0) == 96 + N_SIDE - 1)
#pragma unroll 1
        for (int i = lane; i < (int)(sizeof(Flags) / 16); i += 32) ((uint4*)&g_flags)[i] = make_uint4(0, 0, 0, 0);
}

template <int NT> struct ModSlice {
    static constexpr int R = 2 * DM / NT;
    float sc[R]; uint4 wv[R];
    __device__ __forceinline__ void load(const bf16* wmod, const bf16* c, int col, int tid) {
        const bf16* wm = wmod + (tid >> 1) * (6 * DM) + col + (tid & 1) * 8;
#pragma unroll
        for (int i = 0; i < R; i++) {
            asm volatile("ld.global.nc.L1::no_allocate.L2::128B.v4.u32 {%0,%1,%2,%3}, [%4];" : "=r"(wv[i].x), "=r"(wv[i].y), "=r"(wv[i].z), "=r"(wv[i].w) : "l"(wm + i * (NT / 2) * (6 * DM)));
            sc[i] = __uint_as_float((uint32_t)__ldg((const unsigned short*)c + (tid >> 1) + NT / 2 * i) << 16);
        }
    }
    __device__ __forceinline__ void partial(uint32_t buf, int tid) {
        const int lane = tid & 31;
        float a[8] = {0, 0, 0, 0, 0, 0, 0, 0};
#pragma unroll
        for (int i = 0; i < R; i++) {
            const float f = bfr(__fdividef(sc[i], 1.f + __expf(-sc[i])));
            const uint32_t u[4] = {wv[i].x, wv[i].y, wv[i].z, wv[i].w};
#pragma unroll
            for (int e = 0; e < 4; e++) { a[2 * e] += f * lo_f(u[e]); a[2 * e + 1] += f * hi_f(u[e]); }
        }
#pragma unroll
        for (int h = 4; h; h >>= 1)
#pragma unroll
            for (int e = 0; e < h; e++) { const bool up = lane & (4 * h); a[e] = (up ? a[e + h] : a[e]) + __shfl_xor_sync(0xffffffffu, up ? a[e] : a[e + h], 4 * h); }
        a[0] += __shfl_xor_sync(0xffffffffu, a[0], 2);
        asm volatile("st.shared.f32 [%0], %1;" :: "r"(buf + (tid >> 5) * 64 + (lane & 1) * 32 + (lane >> 2) * 4), "f"(a[0]) : "memory");
    }
    static __device__ __forceinline__ uint32_t total(uint32_t buf, int lane) {
        float a0 = 0, a1 = 0;
#pragma unroll
        for (int i = 0; i < NT / 32; i++) { float x, y; asm volatile("ld.shared.v2.f32 {%0,%1}, [%2];" : "=f"(x), "=f"(y) : "r"(buf + i * 64 + (lane & 7) * 8) : "memory"); a0 += x; a1 += y; }
        return pack2(a0, a1);
    }
};

struct ChainMaps { CUtensorMap wq, wk, wv, wo, h2, wo15, o15, slab16; };
struct ChainArgs { const bf16 *x, *mem0, *c, *wmod, *wv, *wo, *wgate, *wup, *wdown; bf16* out; int D1, D2, DG; };
constexpr uint32_t SM_BASE = 1024;
#define NRING 10
#define FILL_AT 1
#define VF 6
#define VPRE 2
#define XORD 0
#define B5AT 41
#define QCUT 0x7f
#define NCH 2
#define ALA 1
#define VPOS 0
#define NPRE 9
#define REG_P 208
#define REG_L (504 - 2 * REG_P)
constexpr int WO_BLK = 7 * 4096;
constexpr int C_WV = 0, C_WO = 81920, C_XR = 167936, C_VP = C_XR + 7 * 4096, C_VX = C_XR + 8 * 4096, C_QX = C_VX + 4096, C_KX = C_QX + 4096,
              C_MEM = C_KX + 4096, C_OX = C_MEM + 9216, C_VM = C_OX + 3072, C_QM = C_VM + 1024, C_KM = C_QM + 1024, C_SC = C_KM + 1024, C_BAR = C_SC + 3840;
constexpr int CB_W = C_BAR, CB_W2 = C_BAR + 8, CB_SC = C_BAR + 16, CB_XD = C_BAR + 24, CB_VX = C_BAR + 32, CB_W3 = C_BAR + 40, CB_XM = C_BAR + 48, CB_OX = C_BAR + 56,
              CB_XF = C_BAR + 64, C_LAG = C_BAR + 96, C_UN = C_BAR + 100, C_MX = C_BAR + 112;
constexpr int C_SMEM = C_BAR + 128;
#define PROF(i)
#define PROFG(i)
#define PROFV(i, v)
static_assert(C_SMEM <= 232448, "chain shared memory");
__device__ __forceinline__ uint32_t umax3(uint32_t a, uint32_t b, uint32_t c) { return max(max(a, b), c); }
__device__ __forceinline__ void wait_until(uint32_t t) {
    asm volatile("{ .reg .pred p; .reg .s32 c;\nU_%=: mov.u32 c, %%clock; sub.s32 c, c, %0; setp.lt.s32 p, c, 0; @p bra.uni U_%=; }" :: "r"(t) : "memory");
}
__device__ __forceinline__ uint32_t gtime() { uint32_t c; asm volatile("mov.u32 %0, %%globaltimer_lo;" : "=r"(c)); return c; }
__device__ __forceinline__ uint32_t opaque(uint32_t v) { uint32_t r; asm volatile("shfl.sync.bfly.b32 %0, %1, 0, 31, -1;" : "=r"(r) : "r"(v)); return r; }
__device__ __forceinline__ uint32_t lds32(uint32_t a) { uint32_t v; asm volatile("ld.shared.u32 %0, [%1];" : "=r"(v) : "r"(a) : "memory"); return v; }
__device__ __forceinline__ float2 lds64f(uint32_t a) { float2 v; asm volatile("ld.shared.v2.f32 {%0,%1}, [%2];" : "=f"(v.x), "=f"(v.y) : "r"(a) : "memory"); return v; }
__device__ __forceinline__ float4 lds128f(uint32_t a) { float4 v; asm volatile("ld.shared.v4.f32 {%0,%1,%2,%3}, [%4];" : "=f"(v.x), "=f"(v.y), "=f"(v.z), "=f"(v.w) : "r"(a) : "memory"); return v; }
__device__ __forceinline__ void sts128f(uint32_t a, float x, float y, float z, float w) { asm volatile("st.shared.v4.f32 [%0], {%1,%2,%3,%4};" :: "r"(a), "f"(x), "f"(y), "f"(z), "f"(w) : "memory"); }
__device__ __forceinline__ void lds64(uint32_t (&v)[2], uint32_t a) { asm volatile("ld.shared.v2.u32 {%0,%1}, [%2];" : "=r"(v[0]), "=r"(v[1]) : "r"(a) : "memory"); }
__device__ __forceinline__ void mma16q(float (&d)[4], const uint32_t (&a)[4], uint32_t b0, uint32_t b1) { mma16(d, a[0], a[1], a[2], a[3], b0, b1); }
__device__ __forceinline__ uint32_t f16_to_bf16(uint32_t v) {
    float lo, hi; asm("{ .reg .f16 l, h; mov.b32 {l, h}, %2; cvt.f32.f16 %0, l; cvt.f32.f16 %1, h; }" : "=f"(lo), "=f"(hi) : "r"(v));
    return pack2(lo, hi);
}
__device__ __forceinline__ uint32_t pack2h(float lo, float hi) { uint32_t r; asm("cvt.rn.f16x2.f32 %0, %1, %2;" : "=r"(r) : "f"(hi), "f"(lo)); return r; }
#define SPLIT 1
__device__ __forceinline__ void cut(uint32_t never, int n) {
    asm volatile("{ .reg .pred p; setp.ne.u32 p, %0, %1; @p bra.uni C_%=; trap; C_%=: }" :: "r"(never), "r"(n) : "memory");
}
__device__ __forceinline__ void pin(uint32_t never, uint32_t a, uint32_t b, uint32_t c, uint32_t d) {
    asm volatile("{ .reg .pred p; setp.eq.u32 p, %0, 0; @p st.shared.v4.u32 [%0], {%1,%2,%3,%4}; }" :: "r"(never), "r"(a), "r"(b), "r"(c), "r"(d) : "memory");
}
__device__ __forceinline__ void pin0(uint32_t never) {
    asm volatile("{ .reg .pred p; setp.eq.u32 p, %0, 0; @p st.shared.u32 [%0], 0; }" :: "r"(never) : "memory");
}
#define ELECTED(txt) "{ .reg .pred e; elect.sync _|e, -1; @e " txt " }"
__device__ __forceinline__ void w_bulk_s2g(void* dst, uint32_t src, int bytes) {
    asm volatile(ELECTED("cp.async.bulk.global.shared::cta.bulk_group [%0], [%1], %2;") :: "l"(dst), "r"(src), "r"(bytes) : "memory");
}
__device__ __forceinline__ void w_bump(uint32_t* f) { asm volatile(ELECTED("red.relaxed.gpu.global.add.u32 [%0], 1;") :: "l"(f) : "memory"); }
__device__ __forceinline__ void w_expect(uint32_t bar, int bytes) { asm volatile(ELECTED("mbarrier.arrive.expect_tx.shared::cta.b64 _, [%0], %1;") :: "r"(bar), "r"(bytes) : "memory"); }
__device__ __forceinline__ void w_flag_wait(const uint32_t* f, uint32_t target) {
    asm volatile("{ .reg .pred p; .reg .u32 n, v; mov.u32 n, 0;\n"
                 "F_%=: ld.relaxed.gpu.global.u32 v, [%0]; setp.ge.u32 p, v, %1; vote.sync.all.pred p, p, -1; @p bra.uni G_%=;\n"
                 "nanosleep.u32 %2; add.u32 n, n, 1; setp.lt.u32 p, n, 0x400000; @p bra.uni F_%=;\ntrap;\nG_%=: }" :: "l"(f), "r"(target), "n"(NAP) : "memory");
}
#define BULK_COMMIT()    asm volatile("cp.async.bulk.commit_group;" ::: "memory")
#define BULK_WAIT()      asm volatile("cp.async.bulk.wait_group 0;" ::: "memory")
#define BULK_WAIT_READ() asm volatile("cp.async.bulk.wait_group.read 0;" ::: "memory")
#define PROXY_FENCE()    asm volatile("fence.proxy.async.shared::cta;" ::: "memory")
__device__ __forceinline__ void score_tile(const uint32_t (&qa)[2][4], const uint32_t (&kb)[2][4], bool odd, float (&x)[4]) {
    float sc[2][4] = {{0, 0, 0, 0}, {0, 0, 0, 0}};
#pragma unroll
    for (int k = 0; k < 4; k++) mma16q(sc[k & 1], qa[k >> 1], kb[k >> 1][2 * (k & 1)], kb[k >> 1][2 * (k & 1) + 1]);
    float a = sc[0][0] + sc[1][2], b = sc[0][1] + sc[1][3];
    float c = __shfl_xor_sync(0xffffffffu, a, 1), d = __shfl_xor_sync(0xffffffffu, b, 1);
    x[0] = odd ? c : a; x[1] = odd ? d : b; x[2] = odd ? a : c; x[3] = odd ? b : d;
}
__device__ __forceinline__ void send_piece(const float (&x)[4], uint32_t rdst, uint32_t rbar, uint32_t ldst) {
    asm volatile("st.async.shared::cluster.mbarrier::complete_tx::bytes.v4.f32 [%0], {%1,%2,%3,%4}, [%5];"
        :: "r"(rdst), "f"(x[0]), "f"(x[1]), "f"(x[2]), "f"(x[3]), "r"(rbar) : "memory");
    sts128f(ldst, x[0], x[1], x[2], x[3]);
}

__device__ __forceinline__ void seg_done(int n, int head) {
    w_bump(&g_flags.seg[n * 32 + head]);
    if ((n & 3) == 3) w_bump(&g_flags.qk[n >> 2]);
}
__device__ __forceinline__ void x_part(const uint32_t (&wa)[40][4], uint32_t sm, int n, int wg, int w, uint32_t ln, int head) {
    const int s = n - 1; (void)s;
    float acc[16]; uint32_t giv[8];
#pragma unroll
    for (int i = 0; i < 16; i++) acc[i] = 0.f;
    const uint32_t x0 = (uint32_t)mkdesc(SM_BASE + C_XR + wg * 4096, 16, 1024) + ln, xl[2] = {__shfl_sync(0xffffffffu, x0, 0), __shfl_sync(0xffffffffu, x0, 1)};
    auto chunk = [&](int a0, int i, int first) {
#pragma unroll
        for (int ks = 0; ks < 4; ks++)
            wgmma_rs_n32(acc, wa[a0 + 4 * i + ks], (mkdesc(0, 0, 1024) | (uint32_t)(xl[!a0] + ((((i ? (i - 1) * 8192 : C_MEM - C_XR) + ks * 32) >> 4) - !a0))), !(first && ks == 0));
    };
    mbar_wait(sm + CB_XF, n & 1);
    if (n) bar_sync(5, 384);
    if (wg == 0 && w == 0) PROF(12);
    WG_FENCE();
    chunk(20, 1, 1); chunk(20, 2, 0); chunk(20, 3, 0);
    mbar_wait(sm + CB_XM, n & 1);
    if (wg == 0 && w == 0) PROF(13);
    WG_FENCE();
    chunk(20, 0, 0);
    mbar_wait(sm + CB_XF + 8, n & 1);
    if (wg == 0 && w == 0) PROF(17);
    WG_FENCE();
    chunk(20, 4, 0);
    WG_COMMIT();
    if (n) {
        if (wg == 1 && w == 1) { BULK_WAIT(); seg_done(n - 1, head); }
        bar_sync(8, 256);
    }
    if (wg == 0 && w == 0) PROF(18);
    const uint32_t xb = sm + w * 512 + ln * 16, xw = xb + C_KX - wg * 4096, xr = xb + C_QX + wg * 4096;
    WG_WAIT(0);
#pragma unroll
    for (int i = 0; i < 8; i++) asm volatile("cvt.rn.bf16x2.f32 %0, %1, %2;" : "=r"(giv[i]) : "f"(acc[2 * i + 1]), "f"(acc[2 * i]));
#pragma unroll
    for (int p = 0; p < 2; p++) asm volatile("st.shared.v4.u32 [%0], {%1,%2,%3,%4};" :: "r"(xw + p * 2048), "r"(giv[4 * p]), "r"(giv[4 * p + 1]), "r"(giv[4 * p + 2]), "r"(giv[4 * p + 3]) : "memory");
    bar_arrive(12 + wg, 256);
    WG_FENCE();
    chunk(0, 0, 1);
    WG_COMMIT();
    chunk(0, 1, 0);
    if (XORD) chunk(0, 2, 0);
    bar_sync(13 - wg, 256);
#pragma unroll
    for (int p = 0; p < 2; p++) asm volatile("ld.shared.v4.u32 {%0,%1,%2,%3}, [%4];" : "=r"(giv[4 * p]), "=r"(giv[4 * p + 1]), "=r"(giv[4 * p + 2]), "=r"(giv[4 * p + 3]) : "r"(xr + p * 2048) : "memory");
    WG_COMMIT(); WG_WAIT(1); bar_arrive(9, 384);
    WG_FENCE();
    if (!XORD) chunk(0, 2, 0);
    chunk(0, 3, 0); chunk(0, 4, 0);
    WG_COMMIT();
    const uint32_t r = ln & 7, mi = ln >> 3, dst = sm + (wg == 0 ? C_QX : C_KX) + ((mi >> 1) * 8 + r) * 128 + (((2 * w + (mi & 1)) ^ r) << 4);
    pin(xb, giv[0], giv[4], dst, 0);
    bar_sync(10 + wg, 128);
    WG_WAIT(0);
    if (wg == 0 && w == 0) PROF(30);
    if (w == 0 && ln < 3) mbar_arrive_remote(mapa(sm + CB_XD, ln));
#pragma unroll
    for (int i = 0; i < 8; i++) { acc[2 * i] += lo_f(giv[i]); acc[2 * i + 1] += hi_f(giv[i]); }
#pragma unroll
    for (int p = 0; p < 2; p++)
        stsm4t(dst + p * 2048, pack2(acc[8 * p], acc[8 * p + 1]), pack2(acc[8 * p + 2], acc[8 * p + 3]), pack2(acc[8 * p + 4], acc[8 * p + 5]), pack2(acc[8 * p + 6], acc[8 * p + 7]));
    if (wg == 0 && w == 0) PROF(11);
}
__device__ __forceinline__ void x_fill(const ChainMaps& mp, uint32_t sm, int n, int j, int g) {
    mbar_expect(sm + CB_XF + 8 * g, g ? 8192 : 24576);
    const int c = g ? 6 : 2 * j;
    if (!g || j == 2)
        asm volatile("cp.async.bulk.tensor.3d.shared::cluster.global.mbarrier::complete_tx::bytes.multicast::cluster [%0], [%1, {0, %3, %4}], [%2], %5;"
            :: "r"(sm + C_XR + c * 4096), "l"((uint64_t)&mp.h2), "r"(sm + CB_XF + 8 * g), "r"(n * SEG), "r"(2 + c), "h"((uint16_t)7) : "memory");
}

#define WPOS 15
#define WP 8
#define WOPF 30
#define SPF 0
#define SDEL 0
#define BPOS 1
#define TPF 1
#define B_LATE 14
constexpr int E_B = C_WO, E_STG = 196608, EB_A = 229376, EB_B = C_BAR + 80, EB_REL = C_BAR + 104;
__device__ __forceinline__ uint32_t e_slot(int wg, int c) { return wg && c == 2 ? E_B + 98304 : wg * 49152 + c * 16384; }
constexpr int T_WG = 0, T_WU = 20480, T_WD = 40960, T_X = 65536, T_RED = 77824, T_KEY = 86016;
__device__ __forceinline__ void wo_half(const ChainMaps& mp, uint32_t sm, int blk, int c) {
    if (blk < 80 && elect()) { mbar_expect(sm + EB_B + 8 * c, 49152); tma3d(sm + E_B + c * 49152, &mp.wo15, blk / 5 * 384 + c * 192, blk % 5 * 2, sm + EB_B + 8 * c); }
}
__device__ __forceinline__ void end_loads(const ChainMaps& mp, const ChainArgs& ar, uint32_t sm, int blk, int wg) {
    const uint32_t bar = sm + EB_A + wg * 48;
    const int kp = blk / 5;
    if (elect()) {
#pragma unroll 1
        for (int c = 0; c < 6; c++) mbar_init(bar + 8 * c, c < 3 ? 1 : 4);
        PROXY_FENCE();
    }
    __syncwarp();
    bar_arrive(5, 384);
    if (blk >= 80) {
        if (TPF && elect()) {
#pragma unroll 1
            for (int c = 0; c < 3; c++) asm volatile("cp.async.bulk.prefetch.L2.global [%0], 61440;" :: "l"((c == 0 ? ar.wgate : c == 1 ? ar.wup : ar.wdown) + ((blk - 80) * 2 + wg) * 30720) : "memory");
        }
        return;
    }
    const uint64_t ef = policy_stream();
#pragma unroll 1
    for (int b = B_LATE; b < 16; b++) {
        w_flag_wait(b == 15 ? &g_flags.half[kp * 2 + wg] : &g_flags.pair[b * 16 + kp], b == 15 ? 8 : 16);
#pragma unroll 1
        for (int c = 0; c < 3; c++) {
            if (b > B_LATE) mbar_wait(bar + 24 + 8 * c, (b - B_LATE - 1) & 1);
            if (elect()) { mbar_expect(bar + 8 * c, 16384); tma3d_ef(sm + e_slot(wg, c), &mp.o15, b * 128 + wg * 64, kp * 6 + c * 2, bar + 8 * c, ef); }
            __syncwarp();
        }
    }
}
__device__ __forceinline__ void last_blocks(const ChainMaps& mp, const ChainArgs& ar, uint32_t sm, int blk, int tid) {
    const int warp = __shfl_sync(0xffffffffu, tid >> 5, 0), lane = tid & 31, wg = warp >> 2, w = warp & 3, kp = blk / 5, ct = blk % 5;
    const uint32_t bar = sm + EB_A + wg * 48, stg = sm + E_STG + warp * 4096;
    const uint64_t ef = policy_stream();
    bar_sync(5, 384);
    float acc[64];
#pragma unroll
    for (int n = 0; n < 64; n++) acc[n] = 0.f;
#pragma unroll 1
    for (int b = B_LATE; b < 16 && blk < 80; b++) {
#pragma unroll 1
        for (int c = 0; c < 6; c++) {
            mbar_wait(sm + EB_B + 8 * (c >= 3), 0); mbar_wait(bar + 8 * (c >> 1), (b - B_LATE) & 1);
            const uint64_t da = mkdesc(SM_BASE + e_slot(wg, c >> 1) + (c & 1) * 8192, 16, 1024), db = mkdesc(SM_BASE + E_B + (c >= 3 ? 24576 : 0) + c * 8192, 24576, 1024);
            WG_FENCE();
#pragma unroll
            for (int ks = 0; ks < 4; ks++) wgmma_ss_n128_tb(acc, da + ks * 2, db + ks * 128, c | ks);
            WG_COMMIT();
            WG_WAIT(1);
            if ((c & 1) == 0 && c && elect()) mbar_arrive(bar + 16 + 4 * c);
        }
        WG_WAIT(0);
        if (elect()) mbar_arrive(bar + 40);
        const int r = lane & 7, mi = lane >> 3;
#pragma unroll
        for (int p = 0; p < 8; p++) {
            const int oc = 2 * p + (mi >> 1);
            stsm4(stg + (oc >> 3) * 2048 + ((mi & 1) * 8 + r) * 128 + (((oc & 7) ^ r) << 4), pack2(acc[8 * p], acc[8 * p + 1]), pack2(acc[8 * p + 2], acc[8 * p + 3]),
                  pack2(acc[8 * p + 4], acc[8 * p + 5]), pack2(acc[8 * p + 6], acc[8 * p + 7]));
        }
        PROXY_FENCE();
        __syncwarp();
        if (elect()) tma3d_store(&mp.slab16, (b * KSPLIT + kp) * 128 + warp * 16, ct * 2, stg, ef, false);
        BULK_COMMIT(); BULK_WAIT();
        if (w) bar_arrive(12 + wg, 128); else { bar_sync(12 + wg, 128); w_bump(b < 14 ? &g_flags.o[b] : &g_flags.fin[((b - 14) * 2 + wg) * 32]); }
    }
    bar_sync(8, 256);
    const int o = (tid >> 1) * FF + blk * 16 + (tid & 1) * 8;
    const bf16 *pg = ar.wgate + o, *pu = ar.wup + o, *pd = ar.wdown + tid * DM + (blk < 80 ? blk : 0) * 8;
#pragma unroll
    for (int i = 0; i < 16; i++)
        asm volatile("cp.async.cg.shared.global [%0], [%1], 16;" :: "r"(sm + E_B + i * 4096 + tid * 16), "l"(i < 5 ? pg + i * 128 * FF : i < 10 ? pu + (i - 5) * 128 * FF : pd + (i - 10) * 256 * DM) : "memory");
}
__device__ __forceinline__ void mod_tail(const ChainArgs& ar, const uint32_t tb, const uint32_t bar, const int blk, const int tid) {
#define TPROF(i)
    const int warp = __shfl_sync(0xffffffffu, tid >> 5, 0), lane = tid & 31, r = lane & 7, mi = lane >> 3;
    const uint32_t kb = tb + T_KEY;
    {
        uint32_t k[8];
        for (int n = 0;; n++) {
#pragma unroll
            for (int i = 0; i < 2; i++) asm volatile("ld.relaxed.gpu.global.v4.u32 {%0,%1,%2,%3}, [%4];" : "=r"(k[4 * i]), "=r"(k[4 * i + 1]), "=r"(k[4 * i + 2]), "=r"(k[4 * i + 3]) : "l"(g_key + warp * 256 + i * 128 + lane * 4) : "memory");
            if (__all_sync(0xffffffffu, (k[0] & k[1] & k[2] & k[3] & k[4] & k[5] & k[6] & k[7] & S_TOK) != 0)) break;
            if (n > (1 << 22)) __trap();
            __nanosleep(NAP);
        }
        const uint32_t m = __reduce_max_sync(0xffffffffu, max(umax3(k[0], k[1], k[2]), max(umax3(k[3], k[4], k[5]), max(k[6], k[7]))));
        asm volatile("st.shared.u32 [%0], %1; st.shared.u32 [%2], 0;" :: "r"(kb + warp * 4), "r"(m), "r"(kb + 32) : "memory");
        asm volatile("cp.async.wait_all;" ::: "memory");
        bar_sync(1, 256);
        TPROF(1);
        const uint32_t low = __reduce_min_sync(0xffffffffu, lds32(kb + r * 4));
        uint32_t cnt = 0;
#pragma unroll
        for (int i = 0; i < 8; i++) cnt += k[i] >= low ? 4 : 0;
        if (cnt) {
            uint32_t a; asm volatile("atom.shared.add.u32 %0, [%1], %2;" : "=r"(a) : "r"(kb + 32), "r"(cnt) : "memory");
#pragma unroll
            for (int i = 0; i < 8; i++) if (k[i] >= low) { asm volatile("st.shared.u32 [%0], %1;" :: "r"(kb + 512 + a), "r"(k[i]) : "memory"); a += 4; }
        }
        if (tid == 0) mbar_arrive(bar);
        bar_sync(1, 256);
        const int nc = lds32(kb + 32);
#pragma unroll 1
        for (int c = lane * 4; c < nc; c += 128) {
            const uint32_t me = lds32(kb + 512 + c);
            int rank = 0;
#pragma unroll 2
            for (int e = 0; e < nc; e += 16) {
                const float4 z = lds128f(kb + 512 + e);
                rank += (__float_as_uint(z.x) > me) + (e + 4 < nc && __float_as_uint(z.y) > me) + (e + 8 < nc && __float_as_uint(z.z) > me) + (e + 12 < nc && __float_as_uint(z.w) > me);
            }
            if (rank < 8) asm volatile("st.shared.u32 [%0], %1;" :: "r"(kb + 64 + (warp * 8 + rank) * 4), "r"(me) : "memory");
        }
        __syncwarp();
    }
    const uint32_t k0 = lds32(kb + 64 + (warp * 8 + r) * 4), k1 = lds32(kb + 64 + (warp * 8 + (lane >> 2)) * 4);
    TPROF(2);
    const int trow = ~k1 & (S_TOK - 1), tcol = (blk < 80 ? blk : 0) * 8 + (lane & 3) * 2;
    uint2 xb[5];
#pragma unroll
    for (int h = 0; h < 5; h++) xb[h] = __ldcg((const uint2*)(g_h2 + trow * DM + (warp * 5 + h) * 16 + (lane & 3) * 4));
    const uint32_t fx1 = __ldcg((const uint32_t*)(g_x1 + trow * DM + tcol)), fh2 = __ldcg((const uint32_t*)(g_h2 + trow * DM + tcol)),
                   fgb = __ldcg((const uint32_t*)(g_mod + 5 * DM + tcol));
    const float fr = __uint_as_float(((int)k1 < 0 ? k1 ^ 0x80000000u : ~k1) & 0xffff0000u);
    {
        float dg[4] = {0, 0, 0, 0}, du[4] = {0, 0, 0, 0};
        uint32_t ag[5][4], au[5][4];
#pragma unroll
        for (int h = 0; h < 5; h++) {
            const uint32_t o = tb + ((warp * 5 + h) * 16 + (r >> 1) * 4 + (mi >> 1) * 2 + (r & 1)) * 32 + (mi & 1) * 16;
            ldsm4t(ag[h], o + T_WG); ldsm4t(au[h], o + T_WU);
        }
#pragma unroll
        for (int h = 0; h < 5; h++) { mma16q(dg, ag[h], xb[h].x, xb[h].y); mma16q(du, au[h], xb[h].x, xb[h].y); }
        TPROF(3);
        sts128f(tb + T_RED + warp * 1024 + lane * 16, dg[0], dg[1], dg[2], dg[3]); sts128f(tb + T_RED + warp * 1024 + 512 + lane * 16, du[0], du[1], du[2], du[3]);
    }
    bar_sync(1, 256);
    if (warp < 2) {
        float g2[2] = {0, 0}, u2[2] = {0, 0};
#pragma unroll
        for (int i = 0; i < 8; i++) {
            const float2 a = lds64f(tb + T_RED + i * 1024 + lane * 16 + warp * 8), b = lds64f(tb + T_RED + i * 1024 + 512 + lane * 16 + warp * 8);
            g2[0] += a.x; g2[1] += a.y; u2[0] += b.x; u2[1] += b.y;
        }
        float y[2];
#pragma unroll
        for (int i = 0; i < 2; i++) { const float gq = bfr(g2[i]); y[i] = bfr(__fdividef(gq, 1.f + __expf(-gq))) * bfr(u2[i]); }
        asm volatile("st.relaxed.gpu.global.u32 [%0], %1;" :: "l"(g_gu + (blk >> 1) * 128 + lane * 4 + warp * 2 + (blk & 1)), "r"(movm_t(pack2(y[0], y[1]))) : "memory");
    }
    TPROF(4);
    if (blk < 80) {
        uint32_t a[6][4], b[6][4];
#pragma unroll
        for (int k2 = 0; k2 < 6; k2++) ldsm4t(b[k2], tb + T_WD + (warp * 6 + k2) * 512 + lane * 16);
        for (int n = 0;; n++) {
            uint32_t m = 0;
#pragma unroll
            for (int k2 = 0; k2 < 6; k2++) asm volatile("ld.relaxed.gpu.global.v4.u32 {%0,%1,%2,%3}, [%4];" : "=r"(a[k2][0]), "=r"(a[k2][1]), "=r"(a[k2][2]), "=r"(a[k2][3]) : "l"(g_gu + (warp * 6 + k2) * 128 + lane * 4) : "memory");
#pragma unroll
            for (int k2 = 0; k2 < 6; k2++) m = umax3(umax3(m, a[k2][0], a[k2][1]), a[k2][2], a[k2][3]);
            if (!__any_sync(0xffffffffu, m == ~0u)) break;
            if (n > (1 << 22)) __trap();
        }
        TPROF(5);
        float d[2][4] = {{0, 0, 0, 0}, {0, 0, 0, 0}};
#pragma unroll
        for (int k2 = 0; k2 < 6; k2++) { mma16q(d[0], a[k2], b[k2][0], b[k2][1]); mma16q(d[1], a[k2], b[k2][2], b[k2][3]); }
        asm volatile("st.shared.v2.f32 [%0], {%1,%2};" :: "r"(tb + T_X + warp * 256 + lane * 8), "f"(d[0][0] + d[1][2]), "f"(d[0][1] + d[1][3]) : "memory");
        bar_sync(1, 256);
        if (warp == 0) {
            float y0 = 0, y1 = 0;
#pragma unroll
            for (int i = 0; i < 8; i++) { const float2 z = lds64f(tb + T_X + i * 256 + lane * 8); y0 += z.x; y1 += z.y; }
            const float sg = __fdividef(1.f, 1.f + __expf(-fr));
            *(uint32_t*)(ar.out + trow * DM + tcol) = add2(fx1, mul2(fgb, add2(fh2, mul2(pack2(y0, y1), pack2(sg, sg)))));
        }
    }
    TPROF(6);
}

__global__ void __cluster_dims__(3, 1, 1) __launch_bounds__(384, 1) k_chain(const __grid_constant__ ChainMaps mp, const __grid_constant__ ChainArgs ar) {
    const int D1 = ar.D1, DG = ar.DG;
    extern __shared__ __align__(1024) uint8_t smraw[];
    const uint32_t sm = SM_BASE + ((blockIdx.x % 3) << 24);
    if (smem_u32(smraw) != sm) __trap();
    uint32_t tid; asm volatile("mov.u32 %0, %%tid.x;" : "=r"(tid));
    const int warp = __shfl_sync(0xffffffffu, tid >> 5, 0), lane = tid & 31, wg = warp >> 2, w = warp & 3;
    const int blk = blockIdx.x, head = blk / 3, j = blk % 3;
    const int col0 = head * DH + j * 64;
    asm volatile("griddepcontrol.launch_dependents;");
#define PPROF(i)
    const int r = lane & 7, mi = lane >> 3;
    const uint32_t memrd = opaque(sm + C_MEM + lane * 16);
    if (wg < 2) {
        {
            uint32_t xv[3][10];
            const int row = blk * 8 + warp, nq = row < S_TOK - 1536 ? 3 : 2;
#pragma unroll
            for (int i = 0; i < 15; i++) {
                const uint2 v = __ldcs((const uint2*)(ar.x + (row + (i < 10 || nq == 3 ? i / 5 * 768 : 0)) * DM + lane * 4 + i % 5 * 128));
                xv[i / 5][i % 5 * 2] = v.x; xv[i / 5][i % 5 * 2 + 1] = v.y;
            }
            if (tid == 32) {
#pragma unroll 1
                for (int c = 0; c < 14; c++) if (c != 12) mbar_init(sm + C_BAR + 8 * c, c == 2 ? 5 : c == 3 ? 6 : 1);
                asm volatile("fence.mbarrier_init.release.cluster;" ::: "memory");
                mbar_expect(sm + CB_SC, 2560); mbar_expect(sm + CB_OX, 2048);
            }
            if (warp == 2) {
                const uint32_t f = blk >= 28 ? ~0u : 0u;
                ((uint4*)g_acc)[blk * 32 + lane] = make_uint4(0, 0, 0, 0);
                if (blk < 76) (blk < 12 ? (uint4*)g_stamp + blk * 32 : blk < 28 ? (uint4*)g_key + (blk - 12) * 32 : (uint4*)g_gu + (blk - 28) * 32)[lane] = make_uint4(f, f, f, f);
            }
            __syncwarp();
            asm volatile("barrier.cluster.arrive.relaxed.aligned;" ::: "memory");
            PPROF(8);
#pragma unroll 1
            for (int q = 0; q < 3; q++) {
                uint32_t nv[10];
                ln_norm(xv[0], nv);
#pragma unroll
                for (int i = 0; i < 10; i++) { xv[0][i] = xv[1][i]; xv[1][i] = xv[2][i]; xv[2][i] = nv[i]; }
            }
            PPROF(9);
            if (warp < 5) {
                uint4 u;
                for (int n = 0;; n++) {
                    asm volatile("ld.relaxed.gpu.global.v4.u32 {%0,%1,%2,%3}, [%4];" : "=r"(u.x), "=r"(u.y), "=r"(u.z), "=r"(u.w) : "l"(g_flags.mod1 + tid * 4) : "memory");
                    if (__all_sync(0xffffffffu, u.x && u.y && u.z && u.w)) break;
                    cut(n, 1 << 22);
                }
                asm volatile("st.shared.v4.u32 [%0], {%1,%2,%3,%4};" :: "r"(sm + C_KX + tid * 16), "r"(~u.x), "r"(~u.y), "r"(~u.z), "r"(~u.w) : "memory");
            }
            bar_sync(8, 256);
            PPROF(2);
            uint32_t m = 0;
#pragma unroll
            for (int i = 0; i < 5; i++) {
                uint32_t t[2], u[2];
                lds64(t, sm + C_KX + lane * 8 + i * 256); lds64(u, sm + C_KX + 1280 + lane * 8 + i * 256);
                u[0] = add2(u[0], 0x3f803f80u); u[1] = add2(u[1], 0x3f803f80u);
                m = amax2(amax2(amax2(amax2(m, t[0]), u[0]), t[1]), u[1]);
#pragma unroll
                for (int q = 0; q < 3; q++)
                    if (q < nq) *(uint2*)(g_h + (row + q * 768) * DM + lane * 4 + i * 128) = make_uint2(add2(mul2(xv[q][2 * i], u[0]), t[0]), add2(mul2(xv[q][2 * i + 1], u[1]), t[1]));
            }
            asm volatile("st.shared.u32 [%0], %1;" :: "r"(sm + C_LAG), "r"((amax_warp(m) >> 7) + 1) : "memory");
            bar_sync(8, 256);
            if (tid == 0) flag_add(&g_flags.h);
            __syncwarp();
            bar_arrive(2, 288);
            PPROF(3);
            asm volatile("barrier.cluster.wait.aligned;" ::: "memory");
        }
        asm volatile("setmaxnreg.inc.sync.aligned.u32 %0;" :: "n"(REG_P));
        uint32_t wa[40][4];
        mbar_wait(sm + CB_W, 0);
#pragma unroll
        for (int ks = 0; ks < 40; ks++)
            ldsm4t(wa[ks], sm + ((wg == 0) == (ks < 20) ? C_WV : C_WO) + ((mi >> 1) * 8 + r) * 128 + (((2 * w + (mi & 1)) ^ r) << 4) + (ks % 20 / 4 * 8 + 4 * wg + (ks & 3)) * 2048);
        PPROF(5);
        bar_arrive(1, 288);
        const uint32_t qst = opaque(sm + (wg == 0 ? C_QM : C_KM) + (2 * w + (mi & 1)) * 128 + r * 16);
        const uint32_t vrd = opaque(sm + C_WV + ((mi >> 1) * 8 + r) * 128 + (((2 * w + (mi & 1)) ^ r) << 4) + 4 * wg * 2048);
        const uint32_t mrd = opaque(memrd + wg * 1024);
        for (int s = 0; s < NSEG; s++) {
            x_part(wa, sm, s, wg, w, opaque(mrd) >> 4 & 31, head);
            cut(s + ar.D2, 0);
            bar_sync(1, 384);
            if (warp == 0) { PROF(0); PROFG(24); }
            uint32_t b[3][4], a[5][4];
            float dv[2][4] = {{0, 0, 0, 0}, {0, 0, 0, 0}};
            auto fb = [&](int n) { return mrd + (n >> 1) * 2048 + (n & 1) * 512; };
            auto fa = [&](int k) { return vrd + (k >> 2) * 16384 + (k & 3) * 2048; };
            {
                float d[2][4] = {{0, 0, 0, 0}, {0, 0, 0, 0}}, g[2][4] = {{0, 0, 0, 0}, {0, 0, 0, 0}};
                ldsm4t(b[0], fb(0)); pin0(mrd); ldsm4t(b[1], fb(1)); pin0(mrd);
#pragma unroll
                for (int n = 0; n < 10; n++) {
                    const int c1 = (NCH == 2 || n >= 8);
                    if (n < 8) ldsm4t(b[(n + 2) % 3], fb(n + 2));
                    if (n + ALA >= 2 && n + ALA < 2 + VF) ldsm4t(a[2 + (n + ALA) % 3], fa(2 * (n + ALA)));
                    if (!VPOS && n >= 9 - VPRE && n < 9) ldsm4t(a[n - 9 + VPRE], fa(16 + n - 9 + VPRE));
                    mma16q(g[0], wa[20 + 2 * n], b[n % 3][0], b[n % 3][1]); mma16q(d[0], wa[2 * n], b[n % 3][0], b[n % 3][1]);
                    if (n >= 2 && n < 2 + VF) mma16q(dv[0], a[2 + n % 3], b[n % 3][0], b[n % 3][1]);
                    mma16q(g[c1], wa[21 + 2 * n], b[n % 3][2], b[n % 3][3]); mma16q(d[c1], wa[2 * n + 1], b[n % 3][2], b[n % 3][3]);
                    if (QCUT >> n & 1) cut(s + ar.D2, 1 + n);
                }
                const uint32_t xb = mrd - wg * 1024 - (C_MEM - C_VP) + w * 512;
                const float un = __uint_as_float(lds32(sm + C_UN));
                sts128f(xb + wg * 2048, g[0][0] + g[1][0], g[0][1] + g[1][1], g[0][2] + g[1][2], g[0][3] + g[1][3]);
                bar_sync(8, 256);
                const float4 z = lds128f(xb + (wg ^ 1) * 2048);
                if (VPOS) {
                    pin0(mrd);
#pragma unroll
                    for (int i = 0; i < VPRE; i++) ldsm4t(a[i], fa(16 + i));
                }
                stsm2t(qst, pack2((d[0][0] + d[1][0] + z.x) * un, (d[0][1] + d[1][1] + z.y) * un), pack2((d[0][2] + d[1][2] + z.z) * un, (d[0][3] + d[1][3] + z.w) * un));
            }
            bar_arrive(2, 384);
            if (w == 0) PROF(1 + wg);
            {
                if (warp == 3)
                    asm volatile(ELECTED("st.relaxed.gpu.global.u32 [%0], %1;") :: "l"(g_stamp + (s & 3) * 384 + (blk >> 3) * 32 + (blk & 7)), "r"((gtime() & ~31u) | ((s >> 2) + 1)) : "memory");
                PROXY_FENCE();
                bar_sync(7, 384);
                constexpr int NR = 16 - VF, NB = 4 + 12 - 2 * VF;
                auto kst = [&](int i) { return i < 4 ? 16 + i : i < NB ? i + 2 * VF : 5 + 2 * (i - NB); };
                const uint32_t mo = mrd + 256 + (mrd & 256);
                auto fc = [&](int p) { return 2 * p < NB ? fb(p + VF) : mo + (1 + (2 * p - NB) / 2) * 2048; };
#pragma unroll
                for (int i = VPRE; i < 4; i++) ldsm4t(a[i], fa(kst(i)));
#pragma unroll
                for (int i = 0; i < NR; i++) {
                    if (i + 4 < NR) ldsm4t(a[(i + 4) % 5], fa(kst(i + 4)));
                    if (!(i & 1) && i + 4 < NR) ldsm4t(b[(i / 2 + 1) % 3], fc(i / 2 + 2));
                    mma16q(dv[~i & 1], a[i % 5], b[(i / 2 + 2) % 3][2 * (i & 1)], b[(i / 2 + 2) % 3][2 * (i & 1) + 1]);
                }
                sts128f(mrd - (C_MEM - C_VP) + wg * 1024 + w * 512, dv[0][0] + dv[1][0], dv[0][1] + dv[1][1], dv[0][2] + dv[1][2], dv[0][3] + dv[1][3]);
            }
            if (warp == 0) bar_sync(4, 384);
            else bar_arrive(4, 384);
            if (warp == 0) {
                PROF(7);
                if (s + 1 < NSEG && elect()) {
                    mbar_expect(sm + CB_XM, 8192); tma3d(sm + C_MEM, &mp.h2, (s + 1) * SEG, 0, sm + CB_XM);
                }
            } else {
                if (wg == 1) {
                    if (w == 1) {
                        uint8_t* rec = g_att + (s * NH + head) * AT_REC;
                        w_bulk_s2g(rec + j * 8192, sm + C_QX, 8192); w_bulk_s2g(rec + AT_KM + j * 1024, sm + C_KM, 1024);
                        BULK_COMMIT();
                        if (s + 1 == NSEG) { BULK_WAIT(); seg_done(s, head); }
                    }
                    if (w == 2 && blk < 10 && s + 3 < NSEG)
                        asm volatile(ELECTED("cp.async.bulk.prefetch.L2.global [%0], 4096;") :: "l"((const uint8_t*)g_h + (s + 3) * (SEG * DM * 2) + blk * 4096) : "memory");
                } else if (w == 3) { if (s + 1 < NSEG) {
                    const uint32_t l = opaque(mrd) >> 4 & 31, tag = (s >> 2) + 1, now = gtime();
                    const uint32_t* sp = g_stamp + (s & 3) * 384 + (l >> 3) * 32 + (l & 7);
                    uint32_t t[3];
                    for (int n = 0;; n++) {
#pragma unroll
                        for (int i = 0; i < 3; i++) t[i] = ld_rlx(sp + i * 128);
                        if (!__any_sync(0xffffffffu, ((t[0] ^ tag) | (t[1] ^ tag) | (t[2] ^ tag)) & 31) || n > SPIN_LIMIT) break;
                    }
                    int all = -(1 << 30), own = all;
#pragma unroll
                    for (int i = 0; i < 3; i++) { const int d = t[i] - now; all = max(all, d); if ((i * 32 + l) / 3 == head) own = d; }
                    const int lag = min(__reduce_max_sync(0xffffffffu, all) - __reduce_max_sync(0xffffffffu, own), 8000);
                    PROFV(15, lag);
                    asm volatile("st.shared.u32 [%0], %1;" :: "r"(sm + C_LAG), "r"(D1 + ((lag * DG) >> 4)) : "memory");
                    bar_arrive(6, 160); }
                } else if (w == 2) {
                    if (s + 1 < NSEG) {
                        if ((s & 3) == 3) w_flag_wait(&g_flags.v[((s + 1) >> 2) * 32 + head], 2);
                        if (elect()) { mbar_expect(sm + CB_VX, 4096); bulk_g2s(sm + C_VX, g_att + ((s + 1) * NH + head) * AT_REC + AT_V + j * 4096, 4096, sm + CB_VX); }
                    }
                    if ((s & 3) == 1 && s + 3 < NSEG) asm volatile("prefetch.global.L2 [%0];" :: "l"(&g_flags.v[((s + 3) >> 2) * 32]));
                    if (s + 2 < NSEG && ((s & 3) != 2 || __all_sync(0xffffffffu, ld_rlx(&g_flags.v[((s + 2) >> 2) * 32 + head]) >= 2)))
                        asm volatile("prefetch.global.L2 [%0];" :: "l"(g_att + ((s + 2) * NH + head) * AT_REC + AT_V + j * 4096 + (opaque(mrd) << 3 & 0xf80)));
                } else if (s + 1 < NSEG) {
                    mbar_wait(sm + CB_OX, s & 1);
                    if (elect()) x_fill(mp, sm, s + 1, j, 1);
                }
            }
        }
        const int t2 = (opaque(mrd) >> 4 & 31) + warp * 32;
        last_blocks(mp, ar, sm, blk, t2);
        mod_tail(ar, sm + E_B, sm + EB_REL, blk, t2);
    } else {
        asm volatile("setmaxnreg.dec.sync.aligned.u32 %0;" :: "n"(REG_L));
        asm volatile("barrier.cluster.arrive.relaxed.aligned;" ::: "memory");
        if (blk < 80) {
            ModSlice<128> ms;
            ms.load(ar.wmod, ar.c, blk * 16, tid - 256); ms.partial(sm + C_QM, tid - 256);
            bar_sync(3, 128);
            if (w == 0) {
                const uint32_t v = ModSlice<128>::total(sm + C_QM, lane);
                asm volatile("st.relaxed.gpu.global.u32 [%0], %1;" :: "l"(g_flags.mod1 + blk * 8 + (lane & 7)), "r"(~v) : "memory");
            }
        }
        uint32_t m0[5][4], mm = 0;
#pragma unroll
        for (int i = 0; i < 20; i++) {
            const unsigned short* p = (const unsigned short*)ar.mem0 + (i & 3) * 2 * DM + (i >> 2) * 128 + tid - 256;
            m0[i >> 2][i & 3] = __ldg(p) | (uint32_t)__ldg(p + DM) << 16;
        }
        {
            asm volatile("barrier.cluster.wait.aligned;" ::: "memory");
            if (w == 3) {
                w_flag_wait(&g_flags.h, 96);
                if (elect()) { mbar_expect(sm + CB_XM, 8192); tma3d(sm + C_MEM, &mp.h2, 0, 0, sm + CB_XM); x_fill(mp, sm, 0, j, 0); x_fill(mp, sm, 0, j, 1); }
                __syncwarp();
            }
            if (w == 1) {
                const uint64_t ef = policy_stream();
#pragma unroll 1
                for (int c = 0; c < 2 * WP + 2; c++) {
                    const uint32_t bar = sm + EB_B + 8 * (c & 1);
                    if (c == WPOS) bar_sync(2, 288);
                    if (c >= 2) mbar_wait(bar, (c / 2 - 1) & 1);
                    if (elect()) {
                        if (c < 2 * WP) { mbar_expect(bar, 81920 / WP); tma2d_ef(sm + C_WV + c * (81920 / WP), c < WP ? &mp.wq : &mp.wk, col0, c % WP * (640 / WP), bar, ef); }
                        if (c >= WOPF && c < WOPF + 3) asm volatile("cp.async.bulk.prefetch.tensor.3d.L2.global [%0, {0, %1, %2}];" :: "l"((uint64_t)&mp.wo), "r"(head * DH + (c - WOPF) * 64), "r"(7 * j) : "memory");
                    }
                    __syncwarp();
                }
                if (elect()) mbar_arrive(sm + CB_W);
                bar_sync(1, 288);
                if (elect()) {
                    mbar_expect(sm + CB_W2, 81920); mbar_expect(sm + CB_W3, 3 * WO_BLK);
#pragma unroll 1
                    for (int c = 0; c < 4; c++) tma2d(sm + C_WV + c * 20480, &mp.wv, col0, c * 160, sm + CB_W2);
#pragma unroll 1
                    for (int c = 0; c < 3; c++) tma3d(sm + C_WO + c * WO_BLK, &mp.wo, head * DH + (j + c) % 3 * 64, 7 * j, sm + CB_W3);
                }
                __syncwarp();
                w_flag_wait(&g_flags.v[head], 2);
                if (elect()) { mbar_expect(sm + CB_VX, 4096); bulk_g2s(sm + C_VX, g_att + head * AT_REC + AT_V + j * 4096, 4096, sm + CB_VX); }
            } else {
                uint32_t mw = 0;
#pragma unroll 1
                for (int c = 0; c < 2; c++) {
                    mbar_wait(sm + (c ? CB_W3 : CB_W2), 0);
                    uint32_t m = 0;
                    const uint32_t end = sm + (c ? C_XR : C_WO);
#pragma unroll 1
                    for (uint32_t a = sm + c * C_WO + (w - (w > 0)) * 4096 + lane * 16; a < end; a += 3 * 4096) {
                        float4 z[8];
#pragma unroll
                        for (int i = 0; i < 8; i++) z[i] = lds128f(a + i * 512);
#pragma unroll
                        for (int i = 0; i < 8; i++) m = amax2(amax2(amax2(amax2(m, __float_as_uint(z[i].x)), __float_as_uint(z[i].y)), __float_as_uint(z[i].z)), __float_as_uint(z[i].w));
                    }
                    mw |= amax_warp(m) << (16 * c);
                }
                asm volatile("st.shared.u32 [%0], %1;" :: "r"(sm + C_KM + w * 4), "r"(mw) : "memory");
                bar_sync(3, 96);
                if (w == 0) asm volatile("st.relaxed.gpu.global.u32 [%0], %1;" :: "l"(g_flags.wmax + blk), "r"(amax2(amax2(mw, lds32(sm + C_KM + 8)), lds32(sm + C_KM + 12)) | 0x8000) : "memory");
            }
        }
        bar_sync(9, 384);
#pragma unroll
        for (int i = 0; i < 5; i++) {
            asm volatile("st.shared.v4.u32 [%0], {%1,%2,%3,%4};" :: "r"(sm + C_MEM + (tid - 256 + i * 128) * 16), "r"(m0[i][0]), "r"(m0[i][1]), "r"(m0[i][2]), "r"(m0[i][3]) : "memory");
            mm = amax2(amax2(amax2(amax2(mm, m0[i][0]), m0[i][1]), m0[i][2]), m0[i][3]);
        }
        asm volatile("st.shared.u32 [%0], %1; st.shared.u32 [%2], 0x3f800000;" :: "r"(sm + C_MX + w * 4), "r"(amax_warp(mm)), "r"(sm + C_UN) : "memory");
        int ew = __shfl_sync(0xffffffffu, lds32(sm + C_LAG), 0), es = 0;
        const float scale = 0.07216878364870322f;
        uint32_t va[8][4], mr = memrd;
#pragma unroll
        for (int i = 0; i < 8; i++) ldsm4t(va[i], sm + C_WV + ((mi >> 1) * 8 + r) * 128 + (((2 * w + (mi & 1)) ^ r) << 4) + i * 2048);
        bar_sync(1, 384);
        for (int s = 0; s < NSEG; s++) {
            const float un = __uint_as_float((127 - es) << 23);
            if (w == 0) {
                mbar_wait(sm + CB_XD, s & 1);
                if (s + 1 < NSEG) { if (elect()) x_fill(mp, sm, s + 1, j, 0); }
                else { if (BPOS != 2) wo_half(mp, sm, blk, 0); if (BPOS != 0) wo_half(mp, sm, blk, 1); }
            } else if (w == 1 && s > 0) { BULK_WAIT(); seg_done(s - 1, head); }
            const uint32_t l0 = mr >> 4 & 31, r0 = l0 & 7, m0 = l0 >> 3;
            uint32_t kb[2][4];
            {
                const uint32_t k7 = (4 * (w & 1) + (r0 >> 2) * 2 + (r0 & 1)) ^ (r0 << 1 & 4);
                const uint32_t kxrd = sm + C_KX + (16 * (w >> 1) + (r0 << 2 & 8) + k7) * 128 + ((m0 ^ k7) << 4);
                ldsm4(kb[0], kxrd); ldsm4(kb[1], kxrd ^ 64);
            }
            float vd[4];
            {
                uint32_t c[4][4];
#pragma unroll
                for (int i = 0; i < 4; i++) ldsm4t(c[i], mr + i * 512);
                float d[2][4] = {{0, 0, 0, 0}, {0, 0, 0, 0}};
#pragma unroll
                for (int i = 0; i < 8; i++) mma16q(d[i & 1], va[i], c[i >> 1][2 * (i & 1)], c[i >> 1][2 * (i & 1) + 1]);
#pragma unroll
                for (int i = 0; i < 4; i++) vd[i] = d[0][i] + d[1][i];
            }
            uint32_t zr = 0;
            if (w == 2)
                asm volatile("atom.relaxed.gpu.global.exch.b32 %0, [%1], 0;" : "=r"(zr)
                    : "l"(g_acc + ((s & 2) ^ 2) * (ACC_PAIR / 2) + (s & 1) * 512 + (blk >> 2) * 1024 + (blk & 3) * 128 + l0 * 4) : "memory");
            __syncwarp();
            const uint32_t sco = (w >> 1) * 512 + (l0 >> 2) * 64 + (w & 1) * 32 + ((l0 >> 1) & 1) * 16;
            const uint32_t qrd = sm + C_QM + ((m0 & 1) * 2 + (m0 >> 1)) * 128 + r0 * 16;
            const uint32_t scdst = sm + C_SC + j * 1280 + sco;
            const uint32_t rbase = mapa(sm, (j + 1 + (l0 & 1)) % 3) - sm;
            const uint32_t scm = 1024 + (l0 >> 1) * 16 - sco;
            const uint32_t v7 = r0 ^ (m0 << 2 & 4), vxrd = sm + C_VX + (8 * m0 + v7) * 128 + (((2 * w) ^ v7) << 4);
            if (s == 0) {
                uint32_t t[3];
                for (int n = 0;; n++) {
#pragma unroll
                    for (int i = 0; i < 3; i++) t[i] = ld_rlx(g_flags.wmax + l0 + 32 * i);
                    if (__all_sync(0xffffffffu, t[0] && t[1] && t[2])) break;
                    cut(n, 1 << 22);
                }
                const uint32_t m = amax2(amax2(amax2(0, t[0]), t[1]), t[2]);
                const int e = 371 - (int)(__reduce_max_sync(0xffffffffu, m & 0xffffu) >> 7) - (int)(__reduce_max_sync(0xffffffffu, m >> 16) >> 7);
                ew = e << 16 | (min(e - ew, 100) & 0xffff);
            }
            mbar_wait(sm + CB_VX, s & 1);
            uint32_t vb[2][4];
            ldsm4t(vb[0], vxrd); ldsm4t(vb[1], vxrd ^ 16);
            const uint32_t word = sm + C_WO + (m0 & 1) * 4096 + ((m0 >> 1) * 8 + r0) * 64 + ((w ^ (r0 >> 1)) << 4);
            const uint32_t word6 = word + 6 * 4096 - (m0 & 1) * 3072;
            const uint32_t oxrd = sm + C_OX + l0 * 8;
            const uint32_t ord = sm + C_OX + (l0 >> 1) * 16 + w * 256 + (2 - (l0 & 1)) * 1024 + rbase;
            pin(mr, qrd, scdst, rbase, scm); pin(mr, scdst + scm + rbase, scdst + rbase, sm + CB_SC + rbase, scdst + scm); pin(mr, word, word6, oxrd, ord);
            pin(mr, __float_as_uint(vd[0]), __float_as_uint(vd[1]), __float_as_uint(vd[2]), __float_as_uint(vd[3]));
            bar_sync(2, 384);
            const bool odd = mr & 16;
            {
                uint32_t qa[2][4];
                ldsm4(qa[0], qrd); ldsm4(qa[1], qrd + 512);
                float x[4];
                if (w == 3) {
                    uint32_t km[2][4]; float y[4];
                    ldsm4(km[0], mr + (C_KM - C_MEM)); ldsm4(km[1], mr + (C_KM - C_MEM) + 512);
                    score_tile(qa, kb, odd, x); score_tile(qa, km, odd, y);
                    send_piece(x, scdst + rbase, sm + CB_SC + rbase, scdst); send_piece(y, scdst + scm + rbase, sm + CB_SC + rbase, scdst + scm);
                } else {
                    score_tile(qa, kb, odd, x);
                    send_piece(x, scdst + rbase, sm + CB_SC + rbase, scdst);
                }
            }
            bar_arrive(7, 384);
            if (elect()) mbar_arrive(sm + CB_SC);
            {
                const float4 z = lds128f(sm + C_MX);
                const int em = (int)(max(max(__float_as_uint(z.x), __float_as_uint(z.y)), max(__float_as_uint(z.z), __float_as_uint(z.w))) >> 7) - es;
                es = __shfl_sync(0xffffffffu, max(min((ew >> 16) - em, (int)(short)ew), -120), 0);
            }
            if (w == 0) PROF(4);
            const uint32_t vp = mr - (C_MEM - C_VP) + w * 512, vmst = mr + (C_VM - C_MEM) + w * 256;
            if (s + 1 == NSEG) {
                mbar_wait(sm + CB_SC, s & 1);
                bar_sync(4, 384);
                const float4 y0 = lds128f(vp), y1 = lds128f(vp + 2048);
                stsm2t(vmst, pack2((vd[0] + y0.x + y1.x) * un, (vd[1] + y0.y + y1.y) * un), pack2((vd[2] + y0.z + y1.z) * un, (vd[3] + y0.w + y1.w) * un));
                PROXY_FENCE();
                bar_sync(3, 128);
                if (w == 1) {
                    w_bulk_s2g(g_att + (s * NH + head) * AT_REC + AT_VM + j * 1024, sm + C_VM, 1024);
                    BULK_COMMIT();
                    if (BPOS == 0) wo_half(mp, sm, blk, 1);
                    BULK_WAIT(); seg_done(s, head);
                }
                __syncwarp();
                break;
            }
            cut(s + ar.D2, 0);
            mbar_wait(sm + CB_SC, s & 1);
            if (w == 0) PROF(8);
            float sv[10];
            {
                const uint32_t scrd = mr + (C_SC - C_MEM);
                float4 x[3], y[3]; float2 z[3];
#pragma unroll
                for (int p = 0; p < 3; p++) { x[p] = lds128f(scrd + p * 1280); y[p] = lds128f(scrd + p * 1280 + 512); z[p] = lds64f(oxrd + (C_SC - C_OX) + p * 1280 + 1024); }
                sv[0] = (x[0].x + x[1].x) + x[2].x; sv[1] = (x[0].y + x[1].y) + x[2].y; sv[2] = (x[0].z + x[1].z) + x[2].z; sv[3] = (x[0].w + x[1].w) + x[2].w;
                sv[4] = (y[0].x + y[1].x) + y[2].x; sv[5] = (y[0].y + y[1].y) + y[2].y; sv[6] = (y[0].z + y[1].z) + y[2].z; sv[7] = (y[0].w + y[1].w) + y[2].w;
                sv[8] = (z[0].x + z[1].x) + z[2].x; sv[9] = (z[0].y + z[1].y) + z[2].y;
            }
            float mx = fmaxf(fmaxf(fmaxf(sv[0], sv[1]), fmaxf(sv[2], sv[3])), fmaxf(fmaxf(fmaxf(sv[4], sv[5]), fmaxf(sv[6], sv[7])), fmaxf(sv[8], sv[9])));
            uint32_t a[NRING][4];
            auto frag = [&](int i) { const int p = i / 7, u = i % 7, o = (p >> 1) * WO_BLK + (p & 1) * 2048;
                                     return u == 3 ? word6 + o : word + o + (u > 3 ? 1024 + (u - 4) * 8192 : u * 8192); };
            mx = fmaxf(fmaxf(mx, __shfl_xor_sync(0xffffffffu, mx, 1)), fmaxf(__shfl_xor_sync(0xffffffffu, mx, 2), __shfl_xor_sync(0xffffffffu, mx, 3)));
            pin(mr, __float_as_uint(mx), 0, 0, 0);
            bar_sync(4, 384);
            {
                const float4 y0 = lds128f(vp), y1 = lds128f(vp + 2048);
                pin0(mr);
#pragma unroll
                for (int i = 0; i < NPRE; i++) ldsm4t(a[i], frag(i));
                pin0(mr);
                const float sl2e = scale * 1.4426950408889634f, mxl = mx * sl2e;
#pragma unroll
                for (int i = 9; i >= 0; i--) asm volatile("ex2.approx.ftz.f32 %0, %1;" : "=f"(sv[i]) : "f"(fmaf(sv[i], sl2e, -mxl)));
                const uint32_t pq[4] = {pack2(sv[0], sv[1]), pack2(sv[4], sv[5]), pack2(sv[2], sv[3]), pack2(sv[6], sv[7])}, pm = pack2(sv[8], sv[9]);
                if (w == 0) PROF(6);
                float o[2][4] = {{0, 0, 0, 0}, {0, 0, 0, 0}}, o2[2][4] = {{0, 0, 0, 0}, {0, 0, 0, 0}}, sx[4] = {0, 0, 0, 0};
                const uint32_t vm0 = pack2((vd[0] + y0.x + y1.x) * un, (vd[1] + y0.y + y1.y) * un), vm1 = pack2((vd[2] + y0.z + y1.z) * un, (vd[3] + y0.w + y1.w) * un);
                mma8(sx, pm, 0, 0x3f803f80u); mma8(o[0], pm, 0, vm0); mma8(o[1], pm, 0, vm1);
                mma16q(sx, pq, 0x3f803f80u, 0x3f803f80u);
#pragma unroll
                for (int u = 0; u < 2; u++) { mma16q(o[u], pq, vb[u][0], vb[u][1]); mma16q(o2[u], pq, vb[u][2], vb[u][3]); }
                float inv; asm("rcp.approx.ftz.f32 %0, %1;" : "=f"(inv) : "f"((sx[0] + sx[2]) * __uint_as_float((127 - es) << 23)));
                const uint32_t f0 = pack2((o[0][0] + o2[0][2]) * inv, (o[0][1] + o2[0][3]) * inv), f1 = pack2((o[1][0] + o2[1][2]) * inv, (o[1][1] + o2[1][3]) * inv);
                const uint32_t c = __shfl_xor_sync(0xffffffffu, f0, 1), d = __shfl_xor_sync(0xffffffffu, f1, 1);
                asm volatile("st.shared.v2.u32 [%0], {%1,%2};" :: "r"(oxrd + w * 256), "r"(f0), "r"(f1) : "memory");
                asm volatile("st.async.shared::cluster.mbarrier::complete_tx::bytes.v4.b32 [%0], {%1,%2,%3,%4}, [%5];"
                    :: "r"(ord), "r"(odd ? c : f0), "r"(odd ? d : f1), "r"(odd ? f0 : c), "r"(odd ? f1 : d), "r"(sm + CB_OX + rbase) : "memory");
                stsm2t(vmst, vm0, vm1);
            }
            if (w == 0) PROF(10);
#pragma unroll
            for (int i = NPRE; i < NRING; i++) ldsm4t(a[i], frag(i));
            bar_sync(3, 128);
            float e[5][4];
#pragma unroll
            for (int q = 0; q < 5; q++) e[q][0] = e[q][1] = e[q][2] = e[q][3] = 0.f;
            constexpr int LAG = 2;
            uint8_t* pdst = g_acc + ((s & 2) * (ACC_PAIR / 2) + (s & 1) * 512 + w * 2048 + j * 8192 - C_MEM - sm + mr);
#pragma unroll
            for (int h = 0; h < 3; h++) {
                uint32_t ob[4][2];
                if (h == 1) {
#pragma unroll
                    for (int i = 14 - LAG; i < 14; i++) ldsm4t(a[i % NRING], frag(i + NRING));
                    pin(mr, zr, (uint32_t)(uint64_t)pdst, (uint32_t)((uint64_t)pdst >> 32), 0);
                    mbar_wait(sm + CB_OX, s & 1);
                    if (w == 0) PROF(9);
                }
#pragma unroll
                for (int k = 0; k < 4; k++) lds64(ob[k], oxrd + h * 1024 + k * 256);
#pragma unroll
                for (int i = 14 * h; i < 14 * h + 14; i++) {
                    const int u = i % 7, k = 2 * (i / 7 & 1);
                    if (u == 3) { mma16q(e[3], a[i % NRING], ob[k][0], ob[k][1]); mma16q(e[4], a[i % NRING], ob[k + 1][0], ob[k + 1][1]); }
                    else mma16q(e[u & 3], a[i % NRING], ob[k + (u >> 2)][0], ob[k + (u >> 2)][1]);
                    if (i == B5AT) { pin(mr, a[i % NRING][0], a[i % NRING][1], a[i % NRING][2], a[i % NRING][3]); bar_arrive(5, 384); }
                    if (i >= LAG && !(i >= 14 && i < 14 + LAG) && i - LAG + NRING < 42) ldsm4t(a[(i - LAG) % NRING], frag(i - LAG + NRING));
                }
            }
            {
                const uint32_t w6 = pack2h(e[3][0] + e[4][2], e[3][1] + e[4][3]), one = 0x3c003c00u;
                asm volatile("red.relaxed.gpu.global.add.noftz.v4.f16x2 [%0], {%1,%2,%3,%4};"
                    :: "l"(pdst), "r"(pack2h(e[0][0], e[0][1])), "r"(pack2h(e[0][2], e[0][3])), "r"(pack2h(e[1][0], e[1][1])), "r"(odd ? w6 : one) : "memory");
                asm volatile("red.relaxed.gpu.global.add.noftz.v4.f16x2 [%0], {%1,%2,%3,%4};"
                    :: "l"(pdst + 1024), "r"(pack2h(e[1][2], e[1][3])), "r"(pack2h(e[2][0], e[2][1])), "r"(pack2h(e[2][2], e[2][3])), "r"(odd ? one : w6) : "memory");
            }
            const uint32_t tw = clock();
            if (w == 0) { PROF(14); PROFG(25); }
            PROXY_FENCE();
            bar_sync(6, 160);
            mr = opaque(mr);
            const uint32_t ln = mr >> 4 & 31, due = tw + lds32(sm + C_LAG);
            const uint32_t vr = sm + C_WV + ((ln >> 4) * 8 + (ln & 7)) * 128 + (((2 * w + (ln >> 3 & 1)) ^ (ln & 7)) << 4);
            const uint32_t ms0 = sm + C_MEM + w * 128 + (ln & 7) * 16 + (ln >> 3) * 512, ms1 = ms0 + (ln < 24 ? 2048 : 1536);
            if (BPOS == 2 && w == 0 && s + 2 == NSEG) wo_half(mp, sm, blk, 0);
            if (w == 2) { w_expect(sm + CB_SC, 2560); w_expect(sm + CB_OX, 2048); asm volatile("st.shared.u32 [%0], %1;" :: "r"(sm + C_UN), "r"((127 - es) << 23) : "memory"); }
            if (w == 1) { w_bulk_s2g(g_att + (s * NH + head) * AT_REC + AT_VM + j * 1024, sm + C_VM, 1024); BULK_COMMIT(); }
            const uint8_t* src = pdst - j * 8192;
            pin(mr, ms0, ms1, (uint32_t)(uint64_t)src, (uint32_t)((uint64_t)src >> 32));
            pin(mr, vr, due, 0, 0);
            cut(s + ar.D2, 1);
#pragma unroll
            for (int i = 0; i < 8; i++) ldsm4t(va[i], vr + i * 2048);
            wait_until(due);
            if (w == 0) { PROF(5); PROFG(26); }
            uint4 v[6];
            auto fetch = [&]() {
#pragma unroll
                for (int k = 0; k < 6; k++)
                    asm volatile("ld.relaxed.gpu.global.v4.u32 {%0,%1,%2,%3}, [%4];" : "=r"(v[k].x), "=r"(v[k].y), "=r"(v[k].z), "=r"(v[k].w) : "l"(src + (k >> 1) * 8192 + (k & 1) * 1024) : "memory");
            };
            fetch();
            PROFV(20 + w, 0);
            bar_sync(9, 384);
#pragma unroll 1
            for (int n = 0; __any_sync(0xffffffffu, ~((odd ? v[1].w & v[3].w & v[5].w : v[0].w & v[2].w & v[4].w)) & 0x50005000u); n++) {
                PROFV(20 + w, n + 1);
                cut(n, SPIN_LIMIT);
                fetch();
            }
            uint32_t cv[3][7];
#pragma unroll
            for (int k = 0; k < 3; k++) {
                const uint4 x = v[2 * k], y = v[2 * k + 1];
                const uint32_t u[7] = {x.x, x.y, x.z, y.x, y.y, y.z, k < 2 ? (odd ? x.w : y.w) : 0u};
#pragma unroll
                for (int i = 0; i < 7; i++) cv[k][i] = f16_to_bf16(u[i]);
                stsm4(ms0 + k * 3584, cv[k][0], cv[k][1], cv[k][2], cv[k][3]);
                if (k < 2) stsm4(ms1 + k * 3584, cv[k][4], cv[k][5], cv[k][6], cv[k][6]);
                else asm volatile("stmatrix.sync.aligned.m8n8.x2.shared.b16 [%0], {%1,%2};" :: "r"(ms1 + k * 3584), "r"(cv[k][4]), "r"(cv[k][5]) : "memory");
            }
            if (w == 0) PROF(16);
            bar_sync(1, 384);
            cut(s + ar.D2, 2);
            uint32_t mc = 0;
#pragma unroll
            for (int i = 0; i < 20; i++) mc = amax2(mc, cv[i / 7][i % 7]);
            asm volatile("st.shared.u32 [%0], %1;" :: "r"(sm + C_MX + w * 4), "r"(amax_warp(mc)) : "memory");
        }
        if (w >= 2) end_loads(mp, ar, sm, blk, w - 2);
        else bar_arrive(5, 384);
        if (w == 0) {
            const int l = mr >> 4 & 31;
            if (blk < 14) {
                uint4 k = __ldcg((const uint4*)g_key + blk * 32 + l);
#pragma unroll 1
                for (int it = 0; it < 3; it++) {
                    const uint32_t m = __reduce_max_sync(0xffffffffu, max(max(k.x, k.y), max(k.z, k.w)));
                    if (k.x == m) k.x = 0; if (k.y == m) k.y = 0; if (k.z == m) k.z = 0; if (k.w == m) k.w = 0;
                    if (m && l < 20) asm volatile("prefetch.global.L2 [%0];" :: "l"((l < 10 ? g_h2 : g_x1 - 640) + (~m & (S_TOK - 1)) * DM + l * 64));
                }
            }
            mbar_wait(sm + EB_REL, 0);
            flags_release(l);
        }
    }
}

struct SideMaps { CUtensorMap h, wv, ost, o, wo, slab3, slab2, lnp[3]; };
constexpr int SD_ST = 43008, SD_NST = 4, SD_EPI = SD_NST * SD_ST, SD_PAR = SD_EPI + 2 * 24576, SD_BAR = SD_PAR + 6400, SD_SMEM = SD_BAR + 256;
#define VLEAD 16
#define SEG_LAST 60
#define N_LIGHT 6
#define B_HELP 13
#define AUNR_ 2
constexpr int AUNR = AUNR_;
#define GEMV 1
#define KSO 6
#define KSA 3
#define B_8 10
#define B_16 13
__device__ __forceinline__ int o_shift(int b) { return b >= B_16 ? 4 : b >= B_8 ? 3 : 2; }
__device__ __forceinline__ int o_split(int b) { return 1 << o_shift(b); }
__device__ __forceinline__ uint32_t o_done(int b) { return b >= B_LATE ? 160 : 4 << o_shift(b); }
__device__ __forceinline__ int next_item(int lane) {
    const int b0 = lane & 15, hi = lane >> 4;
    for (int n = 0;; n++) {
        const uint32_t w0 = ld_rlx(g_flags.qk + lane), w1 = ld_rlx(g_flags.at + lane), w2 = ld_rlx(&g_flags.c[0][0] + lane), w3 = ld_rlx(&g_flags.c[2][0] + lane), w4 = ld_rlx(&g_flags.seg[SEG_LAST * 32]);
        const uint32_t o01 = __ballot_sync(0xffffffffu, lane && w2 < 32), o23 = __ballot_sync(0xffffffffu, b0 < (hi ? 14 : B_LATE) && w3 < 2u * o_split(b0));
        const uint32_t ra = __ballot_sync(0xffffffffu, w0 >= (hi ? 64u : 192u)), rb = __ballot_sync(0xffffffffu, w1 >= (hi ? o_done(b0) : 256u));
        const int bv = __ffs(o01 | 0x10000) - 1, ba = __ffs(o01 >> 16 | 0x10000) - 1, bo = __ffs(o23 | 0x10000) - 1, bl = __ffs(o23 >> 16 | 0x10000) - 1;
        if (bl == 16 && ba == 16) return -1;
        const int bc = __ffs(~ra | 0x10000) - 1;
        const bool last = ba == 15 && w4 >= 6;
        const bool r1 = (ra & ra >> 16) >> ba & 1, r2 = (rb & 0xffff) >> bo & 1, r3 = rb >> 16 >> bl & 1;
        const int kind = ba == 16 ? (bo < 16 ? 2 : 3) : last ? 1 :
                         blockIdx.x < N_LIGHT ? (r1 ? 1 : r3 ? 3 : bv < 16 ? 0 : -1) :
                         bv < 16 && (bv <= bc + VLEAD || !r2) ? 0 : r1 && ba >= B_HELP ? 1 : r2 ? 2 : r1 ? 1 : r3 ? 3 : bo < ba ? 2 : -1;
        if (kind < 0) { if (n > (1 << 20)) __trap(); __nanosleep(300); continue; }
        const int b = kind == 3 ? bl : kind == 2 ? bo : kind == 1 ? ba : bv;
        uint32_t i = 0;
        if (lane == 0) asm volatile("atom.relaxed.gpu.global.add.u32 %0, [%1], 1;" : "=r"(i) : "l"(&g_flags.c[kind][b]) : "memory");
        i = __shfl_sync(0xffffffffu, i, 0);
        if (i < (kind < 2 ? 32u : 2u * o_split(b))) return kind << 16 | b << 8 | i | ((kind == 1 ? r1 : kind == 2 ? r2 : r3) ? 128 : 0);
    }
}

template <int NP, int CH>
__device__ __forceinline__ void tile_out(const float (&acc)[8 * NP], uint32_t eb, uint32_t efull, uint32_t eempty, int& eph, int lane) {
    const int r = lane & 7, mi = lane >> 3, row = (mi & 1) * 8 + r;
    mbar_wait(eempty, eph); eph ^= 1;
#pragma unroll
    for (int p = 0; p < NP; p++) {
        const int oc = 2 * p + (mi >> 1);
        stsm4(eb + (oc >> 3) * CH + row * 128 + (((oc & 7) ^ r) << 4), pack2(acc[8 * p], acc[8 * p + 1]), pack2(acc[8 * p + 2], acc[8 * p + 3]),
              pack2(acc[8 * p + 4], acc[8 * p + 5]), pack2(acc[8 * p + 6], acc[8 * p + 7]));
    }
    asm volatile("fence.proxy.async.shared::cta;" ::: "memory");
    __syncwarp();
    if (lane == 0) mbar_arrive(efull);
}

template <int MT>
__device__ __forceinline__ void attn_tile(uint32_t base, uint32_t dst, uint32_t eempty, int eph, int lane) {
    constexpr int NK = MT ? 5 : 3;
    const int r = lane & 7, mi = lane >> 3, g = lane >> 2, t = lane & 3;
    float sc[NK][4];
#pragma unroll
    for (int n = 0; n < NK; n++) sc[n][0] = sc[n][1] = sc[n][2] = sc[n][3] = 0.f;
#pragma unroll AUNR
    for (int k2 = 0; k2 < 6; k2++) {
        const uint32_t cb = (k2 >> 1) * 8192, c0 = (k2 & 1) * 4;
        uint32_t a0[4], a1[4], bb[NK][4];
        ldsm4(a0, base + cb + (16 * MT + (mi & 1) * 8 + r) * 128 + (((c0 + (mi >> 1)) ^ r) << 4));
        ldsm4(a1, base + cb + (16 * MT + (mi & 1) * 8 + r) * 128 + (((c0 + 2 + (mi >> 1)) ^ r) << 4));
#pragma unroll
        for (int n = 0; n < NK; n++)
            ldsm4(bb[n], n < NK - 1 ? base + 4096 + cb + (8 * n + r) * 128 + (((c0 + mi) ^ r) << 4) : base + 36864 + k2 * 512 + lane * 16);
#pragma unroll
        for (int n = 0; n < NK; n++) mma16(sc[n], a0[0], a0[1], a0[2], a0[3], bb[n][0], bb[n][1]);
#pragma unroll
        for (int n = 0; n < NK; n++) mma16(sc[n], a1[0], a1[1], a1[2], a1[3], bb[n][2], bb[n][3]);
    }
    const float scale = 0.07216878364870322f, l2e = 1.4426950408889634f;
    float v[2][2 * NK], mx[2], sum[2];
#pragma unroll
    for (int hf = 0; hf < 2; hf++) {
        mx[hf] = -INFINITY;
#pragma unroll
        for (int n = 0; n < NK; n++) {
            uint32_t u = pack2(sc[n][2 * hf], sc[n][2 * hf + 1]);
            u = pack2(lo_f(u) * scale, hi_f(u) * scale);
            const int lim = 16 * MT + 8 * hf + g - 8 * n - 2 * t;
            v[hf][2 * n] = (n < NK - 1 && lim < 0) ? -1e9f : lo_f(u);
            v[hf][2 * n + 1] = (n < NK - 1 && lim < 1) ? -1e9f : hi_f(u);
            mx[hf] = fmaxf(mx[hf], fmaxf(v[hf][2 * n], v[hf][2 * n + 1]));
        }
    }
#pragma unroll
    for (int o = 1; o < 4; o <<= 1)
#pragma unroll
        for (int hf = 0; hf < 2; hf++) mx[hf] = fmaxf(mx[hf], __shfl_xor_sync(0xffffffffu, mx[hf], o));
#pragma unroll
    for (int hf = 0; hf < 2; hf++) {
        sum[hf] = 0;
#pragma unroll
        for (int q = 0; q < 2 * NK; q++) { asm("ex2.approx.ftz.f32 %0, %1;" : "=f"(v[hf][q]) : "f"((v[hf][q] - mx[hf]) * l2e)); sum[hf] += v[hf][q]; }
    }
#pragma unroll
    for (int o = 1; o < 4; o <<= 1)
#pragma unroll
        for (int hf = 0; hf < 2; hf++) sum[hf] += __shfl_xor_sync(0xffffffffu, sum[hf], o);
    uint32_t pa[NK][2];
#pragma unroll
    for (int hf = 0; hf < 2; hf++) {
        const float inv = __fdividef(1.f, sum[hf]);
#pragma unroll
        for (int n = 0; n < NK; n++) pa[n][hf] = pack2(v[hf][2 * n] * inv, v[hf][2 * n + 1] * inv);
    }
    mbar_wait(eempty, eph);
#pragma unroll AUNR
    for (int n4 = 0; n4 < 6; n4++) {
        const uint32_t cb = (n4 >> 1) * 4096, c0 = (n4 & 1) * 4;
        uint32_t bm[4], bb[2 + 2 * MT][4];
        ldsm4t(bm, base + AT_VM + n4 * 512 + lane * 16);
#pragma unroll
        for (int u = 0; u < 2 + 2 * MT; u++) ldsm4t(bb[u], base + AT_V + cb + (16 * (u >> 1) + 8 * (mi & 1) + r) * 128 + (((c0 + 2 * (u & 1) + (mi >> 1)) ^ r) << 4));
        float o[4][4];
#pragma unroll
        for (int u = 0; u < 4; u++) { o[u][0] = o[u][1] = o[u][2] = o[u][3] = 0.f; mma8(o[u], pa[NK - 1][0], pa[NK - 1][1], bm[u]); }
#pragma unroll
        for (int u = 0; u < 4 + 4 * MT; u++) mma16(o[u & 3], pa[u >> 2 << 1][0], pa[u >> 2 << 1][1], pa[(u >> 2 << 1) + 1][0], pa[(u >> 2 << 1) + 1][1], bb[u >> 1][2 * (u & 1)], bb[u >> 1][2 * (u & 1) + 1]);
#pragma unroll
        for (int p = 0; p < 2; p++)
            stsm4(dst + (n4 >> 1) * 2048 + ((mi & 1) * 8 + r) * 128 + (((c0 + 2 * p + (mi >> 1)) ^ r) << 4), pack2(o[2 * p][0], o[2 * p][1]), pack2(o[2 * p][2], o[2 * p][3]),
                  pack2(o[2 * p + 1][0], o[2 * p + 1][1]), pack2(o[2 * p + 1][2], o[2 * p + 1][3]));
    }
}

__device__ __forceinline__ uint32_t ln_row(const uint32_t (&as)[10], const uint2 (&xin)[5], int row, uint32_t par, bf16* out, uint64_t ef, int lane) {
    const uint32_t pa = par + lane * 8;
    uint32_t xv[10], hv[10], sv[10], tv[10];
#pragma unroll
    for (int q = 0; q < 5; q++) {
        uint32_t ga[2], t[2], u[2];
        lds64(ga, pa + q * 256); lds64(t, pa + 1280 + q * 256); lds64(u, pa + 2560 + q * 256);
#pragma unroll
        for (int e = 0; e < 2; e++) {
            xv[2 * q + e] = add2(e ? xin[q].y : xin[q].x, mul2(ga[e], as[2 * q + e]));
            tv[2 * q + e] = t[e]; sv[2 * q + e] = u[e];
        }
        st_ef(g_x1 + row * DM + lane * 4 + q * 128, make_uint2(xv[2 * q], xv[2 * q + 1]), ef);
    }
    ln_mod(xv, sv, tv, hv);
    float rs = 0;
#pragma unroll
    for (int q = 0; q < 5; q++) {
        const int c = row * DM + lane * 4 + q * 128;
        const uint32_t h0 = hv[2 * q], h1 = hv[2 * q + 1];
        uint32_t gb[2], wv[2];
        lds64(gb, pa + 3840 + q * 256); lds64(wv, pa + 5120 + q * 256);
        rs += (lo_f(h0) * lo_f(wv[0]) + hi_f(h0) * hi_f(wv[0])) + (lo_f(h1) * lo_f(wv[1]) + hi_f(h1) * hi_f(wv[1]));
        st_ef(g_h2 + c, make_uint2(h0, h1), ef);
        st_ef(out + c, make_uint2(add2(xv[2 * q], mul2(gb[0], h0)), add2(xv[2 * q + 1], mul2(gb[1], h1))), ef);
    }
    const uint32_t rb = pack2(0.f, warp_sum(rs));
    return (((int)rb < 0 ? ~rb : rb | 0x80000000u) & 0xffff0000u) | (uint32_t)(2 * S_TOK - 1 - row);
}
__device__ __forceinline__ void key_out(uint32_t key) {
    __syncwarp();
    if (key) asm volatile("st.release.gpu.global.u32 [%0], %1;" :: "l"(g_key + (~key & (S_TOK - 1))), "r"(key) : "memory");
}

__global__ void __launch_bounds__(384, 1) k_side(const __grid_constant__ SideMaps mp, const bf16* __restrict__ x, const bf16* __restrict__ wr, const bf16* wmod, const bf16* cvec, bf16* __restrict__ out) {
    extern __shared__ __align__(1024) uint8_t smraw[];
    const uint32_t sm = smem_u32(smraw);
    if (sm & 1023) __trap();
    const uint32_t FULL = sm + SD_BAR, EMPTY = FULL + 32, EFULL = FULL + 64, EEMPTY = FULL + 80, IFULL = FULL + 96, IEMPTY = FULL + 128, IQ = FULL + 160, SCHED = FULL + 176, PARAM = FULL + 184;
    const int tid = threadIdx.x, warp = __shfl_sync(0xffffffffu, tid >> 5, 0), lane = tid & 31;
    const uint64_t ef = policy_stream();
    if (tid == 0) {
        for (int i = 0; i < SD_NST; i++) { mbar_init(FULL + 8 * i, 1); mbar_init(EMPTY + 8 * i, 2); }
        for (int i = 0; i < 2; i++) { mbar_init(EFULL + 8 * i, 4); mbar_init(EEMPTY + 8 * i, 1); }
        for (int i = 0; i < 4; i++) { mbar_init(IFULL + 8 * i, 1); mbar_init(IEMPTY + 8 * i, 11); }
        mbar_init(SCHED, 1); mbar_init(PARAM, 1);
        asm volatile("fence.mbarrier_init.release.cluster;" ::: "memory");
    }
    if (SDEL) __nanosleep(SDEL);
    __syncthreads();
    if (warp >= 8) {
      asm volatile("setmaxnreg.dec.sync.aligned.u32 40;");
      if (warp == 8) {
        int st = 0, ph = 1;
        for (int q = 0;; q++) {
            mbar_wait(IFULL + 8 * (q & 3), (q >> 2) & 1);
            const int it = __shfl_sync(0xffffffffu, lds32(IQ + 4 * (q & 3)), 0);
            if (elect()) mbar_arrive(IEMPTY + 8 * (q & 3));
            if (it < 0) break;
            const int kind = it >> 16, b = (it >> 8) & 255, i = it & 63;
            const int nst = kind == 0 ? 10 : kind == 1 ? 4 : kind == 2 ? 192 >> o_shift(b) : b == 14 ? 4 : 2;
            const int ksched = kind == 0 ? 4 : kind == 2 ? nst - KSO : (it & 128) ? -1 : kind == 1 ? KSA : 0;
            if (ksched < 0 && elect()) mbar_arrive(SCHED);
            const bool look = !(it & 128);
            if (look && kind == 1) flag_wait(&g_flags.v[b * 32 + i], 2);
            if (look && kind == 3 && b < 14) flag_wait(&g_flags.o[b], o_done(b));
            for (int kb = 0; kb < nst; kb++) {
                mbar_wait(EMPTY + 8 * st, ph);
                const uint32_t base = sm + st * SD_ST, fb = FULL + 8 * st;
                if (look && kind == 1) flag_wait(&g_flags.seg[(b * 4 + kb) * 32 + i], 6);
                if (kb == ksched && elect()) mbar_arrive(SCHED);
                if (kind == 0) {
                    if (q == 0 && kb == 0) {
                        if (elect()) {
#pragma unroll 1
                            for (int c = 0; c < SD_NST; c++) tma3d(sm + c * SD_ST + 16384, &mp.wv, c * 64, i * 3, FULL + 8 * c);
#pragma unroll 1
                            for (int c = SD_NST; c < SPF; c++)
                                asm volatile("cp.async.bulk.prefetch.tensor.3d.L2.global [%0, {0, %1, %2}];" :: "l"((uint64_t)&mp.wv), "r"(c * 64), "r"(i * 3) : "memory");
                        }
                        flag_wait(&g_flags.h, 96);
                    }
                    if (elect()) {
                        mbar_expect(fb, 40960);
                        tma2d(base, &mp.h, kb * 64, b * 128, fb);
                        if (q || kb >= SD_NST) tma3d(base + 16384, &mp.wv, kb * 64, i * 3, fb);
                    }
                } else if (kind == 1) {
                    if (elect()) {
                        mbar_expect(fb, 43008);
                        asm volatile("cp.async.bulk.shared::cluster.global.mbarrier::complete_tx::bytes.L2::cache_hint [%0], [%1], %2, [%3], %4;"
                            :: "r"(base), "l"(g_att + ((b * 4 + kb) * NH + i) * AT_REC), "r"(AT_REC), "r"(fb), "l"(ef) : "memory");
                    }
                } else if (kind == 3) {
                    if (b == 14 && !(kb & 1)) flag_wait(&g_flags.fin[(kb + (i >> 4)) * 32], 80);
                    if (elect()) { mbar_expect(fb, 40960); tma3d_ef(base, &mp.lnp[o_shift(b) - 2], i * (160 >> o_shift(b)), b * KSPLIT + (kb << o_shift(b) >> 1), fb, ef); }
                } else {
                    const int k0 = ((i >> 1) * nst + kb) * 32;
                    if (elect()) { mbar_expect(fb, 28672); tma3d(base + 8192, &mp.wo, k0, (i & 1) * 5, fb); }
                    if (look && kb % 12 == 0) flag_wait(&g_flags.pair[b * 16 + k0 / 384], 16);
                    if (elect()) tma2d_ef(base, &mp.o, k0, b * 128, fb, ef);
                }
                __syncwarp();
                if (++st == SD_NST) { st = 0; ph ^= 1; }
            }
        }
      } else if (warp == 11) {
        bool fin = false, par = false;
        for (int q = 0;; q++) {
            if (q) mbar_wait(SCHED, (q - 1) & 1);
            int it = fin ? -1 : q == 0 && blockIdx.x < 32 ? blockIdx.x : next_item(lane);
            if (it < 0 && !fin && blockIdx.x < 32) { it = 3 << 16 | 14 << 8 | blockIdx.x; fin = true; }
            if (lane == 0) {
                if (it >> 16 == 3) {
                    const int b = (it >> 8) & 255, nr = 64 >> o_shift(b);
                    asm volatile("cp.async.bulk.prefetch.L2.global [%0], %1;" :: "l"(x + (b * 128 + (it & 63) * nr) * DM), "r"(nr * DM * 2) : "memory");
                }
                mbar_wait(IEMPTY + 8 * (q & 3), ((q >> 2) & 1) ^ 1);
                asm volatile("st.shared.u32 [%0], %1;" :: "r"(IQ + 4 * (q & 3)), "r"(it) : "memory");
                mbar_arrive(IFULL + 8 * (q & 3));
            }
            if (!par && it >> 16 == 3) {
                par = true;
                flag_wait(&g_flags.mod, 64 * GEMV);
                if (lane == 0) { mbar_expect(PARAM, 6400); bulk_g2s(sm + SD_PAR, g_mod + 2 * DM, 5120, PARAM); bulk_g2s(sm + SD_PAR + 5120, wr, 1280, PARAM); }
            }
            __syncwarp();
            if (it < 0) break;
        }
        flags_release(lane);
      } else {
        if (lane == 0) {
            const int wg = warp - 9; int ph = 0;
            for (int q = 0;; q++) {
                mbar_wait(IFULL + 8 * (q & 3), (q >> 2) & 1);
                const int it = lds32(IQ + 4 * (q & 3));
                mbar_arrive(IEMPTY + 8 * (q & 3));
                if (it < 0) break;
                const int kind = it >> 16, b = (it >> 8) & 255, i = it & 63;
                if (kind & 1) continue;
#pragma unroll 1
                for (int rd = 0; rd < (kind == 2 ? 2 : 1); rd++) {
                    mbar_wait(EFULL + 8 * wg, ph); ph ^= 1;
                    const uint32_t src = sm + SD_EPI + wg * 24576;
                    if (kind == 2) tma3d_store(rd ? &mp.slab2 : &mp.slab3, (b * KSPLIT + (i >> 1)) * 128 + wg * 64, (i & 1) * 5 + rd * 3, src, ef, false);
                    else {
                        uint8_t* dst = g_att + ((b * 4 + wg * 2) * NH + i) * AT_REC + AT_V;
                        asm volatile("cp.async.bulk.global.shared::cta.bulk_group.L2::cache_hint [%0], [%1], 12288, %2;" :: "l"(dst), "r"(src), "l"(ef) : "memory");
                        asm volatile("cp.async.bulk.global.shared::cta.bulk_group.L2::cache_hint [%0], [%1], 12288, %2;" :: "l"(dst + NH * AT_REC), "r"(src + 12288), "l"(ef) : "memory");
                    }
                    asm volatile("cp.async.bulk.commit_group;" ::: "memory");
                    asm volatile("cp.async.bulk.wait_group.read 0;" ::: "memory");
                    mbar_arrive(EEMPTY + 8 * wg);
                }
                asm volatile("cp.async.bulk.wait_group 0;" ::: "memory");
                bump(kind == 0 ? &g_flags.v[b * 32 + i] : &g_flags.o[b]);
                if (kind == 0) bump(&g_flags.vb[b]);
            }
        }
      }
    } else {
        asm volatile("setmaxnreg.inc.sync.aligned.u32 232;");
        const int wg = warp >> 2, w = warp & 3;
        int st = 0, ph = 0, eph = 1;
        bool att = false;
        if (blockIdx.x < 32 * GEMV) {
            const uint32_t buf = sm + SD_EPI;
#pragma unroll 1
            for (int k = tid; k < DM; k += 256) {
                const float f = __uint_as_float((uint32_t)__ldg((const unsigned short*)cvec + k) << 16);
                asm volatile("st.shared.f32 [%0], %1;" :: "r"(buf + k * 4), "f"(bfr(__fdividef(f, 1.f + __expf(-f)))) : "memory");
            }
            const int t = min(tid, 199), k0 = t / 10 * 32;
            const bf16* wm = wmod + k0 * (6 * DM) + 2 * DM + blockIdx.x * 80 + t % 10 * 8;
            float a[8] = {0, 0, 0, 0, 0, 0, 0, 0};
#pragma unroll 1
            for (int k = 0; k < 32; k += 8) {
                uint4 z[8];
#pragma unroll
                for (int e = 0; e < 8; e++) z[e] = __ldcs((const uint4*)(wm + (k + e) * (6 * DM)));
                if (k == 0) bar_sync(1, 256);
#pragma unroll
                for (int e = 0; e < 8; e++) {
                    const float f = __uint_as_float(lds32(buf + (k0 + k + e) * 4));
                    a[0] += f * lo_f(z[e].x); a[1] += f * hi_f(z[e].x); a[2] += f * lo_f(z[e].y); a[3] += f * hi_f(z[e].y);
                    a[4] += f * lo_f(z[e].z); a[5] += f * hi_f(z[e].z); a[6] += f * lo_f(z[e].w); a[7] += f * hi_f(z[e].w);
                }
            }
            sts128f(buf + 4096 + t * 32, a[0], a[1], a[2], a[3]); sts128f(buf + 4112 + t * 32, a[4], a[5], a[6], a[7]);
            bar_sync(1, 256);
            uint32_t bad = 0;
            if (tid < 40) {
                float a0 = 0, a1 = 0;
#pragma unroll 4
                for (int g = 0; g < 20; g++) { const float2 v = lds64f(buf + 4096 + g * 320 + tid * 8); a0 += v.x; a1 += v.y; }
                uint32_t* dst = (uint32_t*)(g_mod + 2 * DM + blockIdx.x * 80) + tid;
                *dst = pack2(a0, a1);
                bad = ld_rlx(dst) ^ pack2(a0, a1);
            }
            if (warp < 2 && !__any_sync(0xffffffffu, bad) && lane == 0) bump(&g_flags.mod);
            bar_sync(1, 256);
        }
        const uint32_t eb = sm + SD_EPI + wg * 24576;
        for (int q = 0;; q++) {
            mbar_wait(IFULL + 8 * (q & 3), (q >> 2) & 1);
            const int itc = lds32(IQ + 4 * (q & 3));
            __syncwarp();
            if (lane == 0) mbar_arrive(IEMPTY + 8 * (q & 3));
            if (itc < 0) break;
            const int kind = itc >> 16, b = (itc >> 8) & 255, i = itc & 63;
            if (att && kind != 1) { bar_sync(2 + wg, 128); att = false; }
            if (kind == 0) {
                float acc[96];
#pragma unroll
                for (int n = 0; n < 96; n++) acc[n] = 0.f;
                int prev = -1;
#pragma unroll 1
                for (int kb = 0; kb < 10; kb++) {
                    mbar_wait(FULL + 8 * st, ph);
                    const uint32_t base = sm + st * SD_ST;
                    WG_FENCE();
#pragma unroll
                    for (int ks = 0; ks < 4; ks++)
                        wgmma_ss_n192_tb(acc, mkdesc(base + wg * 8192 + ks * 32, 16, 1024), mkdesc(base + 16384 + ks * 2048, 8192, 1024), (kb | ks) != 0);
                    WG_COMMIT();
                    WG_WAIT(1);
                    if (prev >= 0 && (tid & 127) == 0) mbar_arrive(EMPTY + 8 * prev);
                    prev = st;
                    if (++st == SD_NST) { st = 0; ph ^= 1; }
                }
                WG_WAIT(0);
                if ((tid & 127) == 0) mbar_arrive(EMPTY + 8 * prev);
                tile_out<12, 4096>(acc, eb + (w >> 1) * 12288 + (w & 1) * 2048, EFULL + 8 * wg, EEMPTY + 8 * wg, eph, lane);
            } else if (kind == 1) {
                const int seg = warp >> 1, mt = warp & 1;
                int sst = st + seg, sph = ph; if (sst >= SD_NST) { sst -= SD_NST; sph ^= 1; }
                ph ^= 1;
                mbar_wait(FULL + 8 * sst, sph);
                const uint32_t base = sm + sst * SD_ST;
                if (mt) attn_tile<1>(base, eb + w * 6144, EEMPTY + 8 * wg, eph, lane);
                else attn_tile<0>(base, eb + w * 6144, EEMPTY + 8 * wg, eph, lane);
                asm volatile("fence.proxy.async.shared::cta;" ::: "memory");
                __syncwarp();
                if (lane == 0) {
                    mbar_arrive(EMPTY + 8 * sst);
                    tma3d_store(&mp.ost, b * 128 + warp * 16, i * 3, eb + w * 6144, ef, false);
                    BULK_COMMIT(); BULK_WAIT();
                    bump(b == 15 ? &g_flags.half[(i & 30) + wg] : &g_flags.pair[b * 16 + (i >> 1)]); bump(&g_flags.at[b]);
                }
                __syncwarp();
                att = true;
            } else if (kind == 2) {
                float acc[96], acc2[64];
#pragma unroll
                for (int n = 0; n < 96; n++) acc[n] = 0.f;
#pragma unroll
                for (int n = 0; n < 64; n++) acc2[n] = 0.f;
                int prev = -1;
#pragma unroll 1
                for (int kb = 192 >> o_shift(b); kb > 0; kb--) {
                    const uint32_t base = sm + st * SD_ST;
                    mbar_wait(FULL + 8 * st, ph);
                    WG_FENCE();
#pragma unroll
                    for (int ks = 0; ks < 2; ks++) {
                        const uint64_t da = (mkdesc(base + wg * 4096 + ks * 32, 16, 512) & ~(3ull << 62)) | (2ull << 62);
                        wgmma_ss_n192_tb(acc, da, mkdesc(base + 8192 + ks * 2048, 4096, 1024), 1);
                        wgmma_ss_n128_tb(acc2, da, mkdesc(base + 8192 + 3 * 4096 + ks * 2048, 4096, 1024), 1);
                    }
                    WG_COMMIT();
                    WG_WAIT(1);
                    if (prev >= 0 && (tid & 127) == 0) mbar_arrive(EMPTY + 8 * prev);
                    prev = st;
                    if (++st == SD_NST) { st = 0; ph ^= 1; }
                }
                WG_WAIT(0);
                if ((tid & 127) == 0) mbar_arrive(EMPTY + 8 * prev);
                tile_out<12, 8192>(acc, eb + w * 2048, EFULL + 8 * wg, EEMPTY + 8 * wg, eph, lane);
                tile_out<8, 8192>(acc2, eb + w * 2048, EFULL + 8 * wg, EEMPTY + 8 * wg, eph, lane);
            } else {
                const int sh = o_shift(b), nr = 64 >> sh, fw = b == 14 ? wg : 0, row0 = (b + fw) * 128 + i * nr, lw = warp - 4 * fw;
                if (fw) { st += 2; if (st >= SD_NST) { st -= SD_NST; ph ^= 1; } }
                int st1 = st + 1, ph1 = ph; if (st1 == SD_NST) { st1 = 0; ph1 ^= 1; }
                uint2 xin[2][5];
                uint32_t as[2][10] = {};
#pragma unroll
                for (int q2 = 0; q2 < 10; q2++) xin[q2 & 1][q2 >> 1] = ld_ef(x + (row0 + ((warp + 8 * (q2 & 1)) & (nr - 1))) * DM + lane * 4 + (q2 >> 1) * 128, ef);
                mbar_wait(PARAM, 0); mbar_wait(FULL + 8 * st, ph); mbar_wait(FULL + 8 * st1, ph1);
#pragma unroll 1
                for (int lrow = lw + (nr & 16) / 2; lrow >= 0 && lrow < nr; lrow -= 8) {
                    float a[20];
#pragma unroll
                    for (int q2 = 0; q2 < 20; q2++) a[q2] = 0.f;
#pragma unroll 1
                    for (int k = 0; k < (1 << sh >> 1); k++) {
                        const uint32_t ad = sm + ((k << (6 - sh)) + lrow) * 1280 + lane * 8;
                        uint32_t z[10][2];
#pragma unroll
                        for (int q2 = 0; q2 < 10; q2++) lds64(z[q2], ad + (q2 < 5 ? st : st1) * SD_ST + q2 % 5 * 256);
#pragma unroll
                        for (int q2 = 0; q2 < 10; q2++) { float* p = a + q2 % 5 * 4; p[0] += lo_f(z[q2][0]); p[1] += hi_f(z[q2][0]); p[2] += lo_f(z[q2][1]); p[3] += hi_f(z[q2][1]); }
                    }
#pragma unroll
                    for (int q2 = 0; q2 < 10; q2++) { as[1][q2] = as[0][q2]; as[0][q2] = pack2(a[2 * q2], a[2 * q2 + 1]); }
                }
                bar_sync(2 + wg, 128);
                if ((tid & 127) == 0) { mbar_arrive(EMPTY + 8 * st); mbar_arrive(EMPTY + 8 * st1); }
                uint32_t key = 0;
#pragma unroll 1
                for (int lrow = lw; lrow < nr; lrow += 8) {
                    const int row = row0 + lrow;
                    const uint32_t k1 = ln_row(as[0], xin[0], row, sm + SD_PAR, out, ef, lane);
                    if (lane == lrow >> 3) key = k1;
#pragma unroll
                    for (int q2 = 0; q2 < 5; q2++) { as[0][2 * q2] = as[1][2 * q2]; as[0][2 * q2 + 1] = as[1][2 * q2 + 1]; xin[0][q2] = xin[1][q2]; }
                }
                key_out(key);
                st = st1 + 1; ph = ph1; if (st == SD_NST) { st = 0; ph ^= 1; }
            }
        }
    }
    __syncwarp();
    asm volatile("griddepcontrol.wait;" ::: "memory");
}

#define P_D1 650
#define P_DL 700
#define P_DG 29
typedef CUresult (*EncodeFn)(CUtensorMap*, CUtensorMapDataType, cuuint32_t, void*, const cuuint64_t*, const cuuint64_t*, const cuuint32_t*, const cuuint32_t*,
                             CUtensorMapInterleave, CUtensorMapSwizzle, CUtensorMapL2promotion, CUtensorMapFloatOOBfill);
static EncodeFn s_encode = nullptr;
static void make_map(CUtensorMap* m, const void* p, int rows, int cols, int box_rows, int box_cols = 64) {
    cuuint64_t dims[2] = {(cuuint64_t)cols, (cuuint64_t)rows}, strides[1] = {(cuuint64_t)cols * 2};
    cuuint32_t box[2] = {(cuuint32_t)box_cols, (cuuint32_t)box_rows}, es[2] = {1, 1};
    s_encode(m, CU_TENSOR_MAP_DATA_TYPE_BFLOAT16, 2, (void*)p, dims, strides, box, es, CU_TENSOR_MAP_INTERLEAVE_NONE,
             box_cols == 64 ? CU_TENSOR_MAP_SWIZZLE_128B : box_cols == 32 ? CU_TENSOR_MAP_SWIZZLE_64B : CU_TENSOR_MAP_SWIZZLE_NONE, CU_TENSOR_MAP_L2_PROMOTION_L2_256B, CU_TENSOR_MAP_FLOAT_OOB_FILL_NONE);
}
static void make_map3(CUtensorMap* m, const void* p, int rows, int cols, int box_rows, int box_chunks, int cw = 64) {
    cuuint64_t dims[3] = {(cuuint64_t)cw, (cuuint64_t)rows, (cuuint64_t)(cols / cw)}, strides[2] = {(cuuint64_t)cols * 2, (cuuint64_t)cw * 2};
    cuuint32_t box[3] = {(cuuint32_t)cw, (cuuint32_t)box_rows, (cuuint32_t)box_chunks}, es[3] = {1, 1, 1};
    s_encode(m, CU_TENSOR_MAP_DATA_TYPE_BFLOAT16, 3, (void*)p, dims, strides, box, es, CU_TENSOR_MAP_INTERLEAVE_NONE,
             cw == 64 ? CU_TENSOR_MAP_SWIZZLE_128B : CU_TENSOR_MAP_SWIZZLE_64B, CU_TENSOR_MAP_L2_PROMOTION_L2_256B, CU_TENSOR_MAP_FLOAT_OOB_FILL_NONE);
}
template <typename T> static void* sym(T& s) { void* p = nullptr; cudaGetSymbolAddress(&p, s); return p; }

extern "C" void kernel_launch(void* const* d_in, const int* in_sizes, int n_in, void* d_out, int out_size) {
    const bf16 *x = (const bf16*)d_in[0], *mem0 = (const bf16*)d_in[1], *Wq = (const bf16*)d_in[2], *Wk = (const bf16*)d_in[3],
               *Wv = (const bf16*)d_in[4], *Wo = (const bf16*)d_in[5], *wr = (const bf16*)d_in[8], *wgate = (const bf16*)d_in[9],
               *wup = (const bf16*)d_in[10], *wdown = (const bf16*)d_in[11], *c = (const bf16*)d_in[12], *wmod = (const bf16*)d_in[13];
    bf16* out = (bf16*)d_out;
    if (!s_encode) {
        cudaDriverEntryPointQueryResult qr;
        cudaGetDriverEntryPoint("cuTensorMapEncodeTiled", (void**)&s_encode, cudaEnableDefault, &qr);
        cudaFuncSetAttribute(k_side, cudaFuncAttributeMaxDynamicSharedMemorySize, SD_SMEM);
        cudaFuncSetAttribute(k_chain, cudaFuncAttributeMaxDynamicSharedMemorySize, C_SMEM);
    }
    ChainMaps cm; SideMaps sd;
    make_map(&sd.h, sym(g_h), S_TOK, DM, 128); make_map3(&sd.wv, Wv, DM, HD, 64, 3);
    make_map3(&sd.ost, sym(g_o), S_TOK, HD, 16, 3); make_map(&sd.o, sym(g_o), S_TOK, HD, 128, 32); make_map3(&sd.wo, Wo, HD, DM, 32, 5);
    make_map3(&sd.slab3, sym(g_slab), 16 * KSPLIT * 128, DM, 64, 3); make_map3(&sd.slab2, sym(g_slab), 16 * KSPLIT * 128, DM, 64, 2);
    make_map3(&cm.wo15, Wo, HD, DM, 192, 2); make_map3(&cm.o15, sym(g_o), S_TOK, HD, 64, 2); make_map3(&cm.slab16, sym(g_slab), 16 * KSPLIT * 128, DM, 16, 2);
    for (int i = 0; i < 3; i++) {
        cuuint64_t dims[3] = {256, 320, 16 * KSPLIT}, strides[2] = {512, 128 * DM * 2};
        cuuint32_t box[3] = {256, 40u >> i, 2u << i}, es[3] = {1, 1, 1};
        s_encode(&sd.lnp[i], CU_TENSOR_MAP_DATA_TYPE_BFLOAT16, 3, sym(g_slab), dims, strides, box, es, CU_TENSOR_MAP_INTERLEAVE_NONE,
                 CU_TENSOR_MAP_SWIZZLE_NONE, CU_TENSOR_MAP_L2_PROMOTION_L2_256B, CU_TENSOR_MAP_FLOAT_OOB_FILL_NONE);
    }
    make_map(&cm.wq, Wq, DM, HD, 640 / WP); make_map(&cm.wk, Wk, DM, HD, 640 / WP); make_map(&cm.wv, Wv, DM, HD, 160); make_map3(&cm.wo, Wo, HD, DM, 64, 7, 32);
    make_map3(&cm.h2, sym(g_h), S_TOK, DM, 32, 2);
    ChainArgs ar = {x, mem0, c, wmod, Wv, Wo, wgate, wup, wdown, out, P_D1, P_DL, P_DG};
    k_chain<<<96, 384, C_SMEM>>>(cm, ar);
    cudaLaunchConfig_t cfg = {};
    cfg.gridDim = dim3(N_SIDE); cfg.blockDim = dim3(384); cfg.dynamicSmemBytes = SD_SMEM; cfg.stream = cudaStreamPerThread;
    cudaLaunchAttribute at[1]; at[0].id = cudaLaunchAttributeProgrammaticStreamSerialization; at[0].val.programmaticStreamSerializationAllowed = 1;
    cfg.attrs = at; cfg.numAttrs = 1;
    cudaLaunchKernelEx(&cfg, k_side, sd, x, wr, wmod, c, out);
}
```

```cpp
#include <cuda_runtime.h>
#include <cuda_bf16.h>
#include <cuda.h>
#include <stdint.h>
#include <stdio.h>
#include <string.h>
#include <stdlib.h>

typedef __nv_bfloat16 bf16;
constexpr int S_TOK = 2048, DM = 640, NH = 32, DH = 192, HD = NH * DH, NSEG = 64, SEG = 32, FF = 1536;

__device__ bf16 g_mod[6 * DM];
__device__ bf16 g_h[S_TOK * DM];
constexpr int AT_REC = 43008, AT_V = 24576, AT_KM = 36864, AT_VM = 39936;
__device__ __align__(1024) uint8_t g_att[NSEG * NH * AT_REC];
__device__ bf16 g_o[S_TOK * HD];
__device__ bf16 g_A[S_TOK * DM];
__device__ bf16 g_x1[S_TOK * DM];
__device__ bf16 g_h2[S_TOK * DM];
__device__ __align__(128) uint32_t g_key[S_TOK];
__device__ int g_idx[8];
__device__ __align__(128) uint32_t g_gu[FF / 8 * 32];
constexpr int ACC_PAIR = 24 * 1024;
__device__ __align__(1024) uint8_t g_acc[2 * ACC_PAIR];
__device__ __align__(1024) uint32_t g_stamp[4 * 12 * 32];
constexpr int KSPLIT = 16;
__device__ bf16 g_slab[16 * KSPLIT * 128 * DM];
struct __align__(128) Flags {
    uint32_t qk[16], vb[16];
    uint32_t at[16], o[16];
    uint32_t c[4][16];
    uint32_t half[32];
    uint32_t fin[4 * 32];
    uint32_t v[16 * 32];
    uint32_t seg[4 * 32];
    uint32_t pair[16 * 16];
    uint32_t h, pad2[31], done, pad3[31];
    uint32_t mod1[DM];
    uint32_t wmax[96];
};
__device__ Flags g_flags;

__device__ __forceinline__ uint32_t smem_u32(const void* p) { return (uint32_t)__cvta_generic_to_shared(p); }
__device__ __forceinline__ uint32_t pack2(float lo, float hi) {
    uint32_t r; asm("cvt.rn.bf16x2.f32 %0, %1, %2;" : "=r"(r) : "f"(hi), "f"(lo)); return r;
}
__device__ __forceinline__ float bfr(float x) { return __uint_as_float(pack2(0.f, x)); }
__device__ __forceinline__ float inv_std(float var) {
    float s, r; asm("sqrt.approx.f32 %0, %1;" : "=f"(s) : "f"(bfr(bfr(var) + 1e-5f))); asm("rcp.approx.f32 %0, %1;" : "=f"(r) : "f"(bfr(s))); return r;
}
__device__ __forceinline__ float lo_f(uint32_t v) { return __uint_as_float(v << 16); }
__device__ __forceinline__ float hi_f(uint32_t v) { return __uint_as_float(v & 0xffff0000u); }
__device__ __forceinline__ void mbar_init(uint32_t bar, int cnt) { asm volatile("mbarrier.init.shared::cta.b64 [%0], %1;" :: "r"(bar), "r"(cnt) : "memory"); }
__device__ __forceinline__ void mbar_expect(uint32_t bar, int bytes) { asm volatile("mbarrier.arrive.expect_tx.shared::cta.b64 _, [%0], %1;" :: "r"(bar), "r"(bytes) : "memory"); }
__device__ __forceinline__ void mbar_arrive(uint32_t bar) { asm volatile("mbarrier.arrive.shared::cta.b64 _, [%0];" :: "r"(bar) : "memory"); }
__device__ __forceinline__ bool mbar_try(uint32_t bar, int par) {
    uint32_t ok; asm volatile("{ .reg .pred p; mbarrier.try_wait.parity.shared::cta.b64 p, [%1], %2; selp.u32 %0, 1, 0, p; }" : "=r"(ok) : "r"(bar), "r"(par) : "memory"); return ok;
}
__device__ __forceinline__ bool mbar_try_cluster(uint32_t bar, int par) {
    uint32_t ok; asm volatile("{ .reg .pred p; mbarrier.try_wait.parity.acquire.cluster.shared::cta.b64 p, [%1], %2; selp.u32 %0, 1, 0, p; }" : "=r"(ok) : "r"(bar), "r"(par) : "memory"); return ok;
}
__device__ __forceinline__ bool mbar_test(uint32_t bar, uint32_t par) {
    uint32_t ok; asm volatile("{ .reg .pred p; mbarrier.test_wait.parity.shared::cta.b64 p, [%1], %2; selp.u32 %0, 1, 0, p; }" : "=r"(ok) : "r"(bar), "r"(par) : "memory"); return ok;
}
constexpr int SPIN_LIMIT = 1 << 18;
__device__ __forceinline__ void mbar_wait(uint32_t bar, uint32_t par) {
    asm volatile("{ .reg .pred p, q; .reg .u32 n; mov.u32 n, 0;\n"
                 "W_%=: mbarrier.try_wait.parity.shared::cta.b64 p, [%0], %1;\n"
                 "@p bra.uni D_%=;\n"
                 "add.u32 n, n, 1; setp.lt.u32 q, n, 0x200000; @q bra.uni W_%=;\n"
                 "trap;\n"
                 "D_%=: }" :: "r"(bar), "r"(par) : "memory");
}
__device__ __forceinline__ void tma2d(uint32_t dst, const CUtensorMap* m, int c0, int c1, uint32_t bar) {
    asm volatile("cp.async.bulk.tensor.2d.shared::cluster.global.mbarrier::complete_tx::bytes [%0], [%1, {%3, %4}], [%2];"
        :: "r"(dst), "l"((uint64_t)m), "r"(bar), "r"(c0), "r"(c1) : "memory");
}
__device__ __forceinline__ void tma2d_mc(uint32_t dst, const CUtensorMap* m, int c0, int c1, uint32_t bar, uint16_t mask) {
    asm volatile("cp.async.bulk.tensor.2d.shared::cluster.global.mbarrier::complete_tx::bytes.multicast::cluster [%0], [%1, {%3, %4}], [%2], %5;"
        :: "r"(dst), "l"((uint64_t)m), "r"(bar), "r"(c0), "r"(c1), "h"(mask) : "memory");
}
__device__ __forceinline__ uint64_t policy_stream() { uint64_t p; asm("createpolicy.fractional.L2::evict_first.b64 %0, 1.0;" : "=l"(p)); return p; }
__device__ __forceinline__ void tma2d_ef(uint32_t dst, const CUtensorMap* m, int c0, int c1, uint32_t bar, uint64_t pol) {
    asm volatile("cp.async.bulk.tensor.2d.shared::cluster.global.mbarrier::complete_tx::bytes.L2::cache_hint [%0], [%1, {%3, %4}], [%2], %5;"
        :: "r"(dst), "l"((uint64_t)m), "r"(bar), "r"(c0), "r"(c1), "l"(pol) : "memory");
}
__device__ __forceinline__ void tma3d(uint32_t dst, const CUtensorMap* m, int row, int chunk, uint32_t bar) {
    asm volatile("cp.async.bulk.tensor.3d.shared::cluster.global.mbarrier::complete_tx::bytes [%0], [%1, {0, %3, %4}], [%2];"
        :: "r"(dst), "l"((uint64_t)m), "r"(bar), "r"(row), "r"(chunk) : "memory");
}
__device__ __forceinline__ void tma3d_ef(uint32_t dst, const CUtensorMap* m, int row, int chunk, uint32_t bar, uint64_t pol) {
    asm volatile("cp.async.bulk.tensor.3d.shared::cluster.global.mbarrier::complete_tx::bytes.L2::cache_hint [%0], [%1, {0, %3, %4}], [%2], %5;"
        :: "r"(dst), "l"((uint64_t)m), "r"(bar), "r"(row), "r"(chunk), "l"(pol) : "memory");
}
__device__ __forceinline__ void tma3d_store(const CUtensorMap* m, int row, int chunk, uint32_t src, uint64_t pol, bool hint) {
    if (hint) asm volatile("cp.async.bulk.tensor.3d.global.shared::cta.bulk_group.L2::cache_hint [%0, {0, %2, %3}], [%1], %4;"
        :: "l"((uint64_t)m), "r"(src), "r"(row), "r"(chunk), "l"(pol) : "memory");
    else asm volatile("cp.async.bulk.tensor.3d.global.shared::cta.bulk_group [%0, {0, %2, %3}], [%1];"
        :: "l"((uint64_t)m), "r"(src), "r"(row), "r"(chunk) : "memory");
}
__device__ __forceinline__ bool elect() { uint32_t p; asm volatile("{ .reg .pred e; elect.sync _|e, -1; selp.u32 %0, 1, 0, e; }" : "=r"(p)); return p; }
__device__ __forceinline__ uint2 ld_ef(const void* p, uint64_t pol) {
    uint2 v; asm volatile("ld.relaxed.gpu.global.L2::cache_hint.v2.u32 {%0,%1}, [%2], %3;" : "=r"(v.x), "=r"(v.y) : "l"(p), "l"(pol)); return v;
}
__device__ __forceinline__ void st_ef(void* p, uint2 v, uint64_t pol) {
    asm volatile("st.global.L2::cache_hint.v2.u32 [%0], {%1,%2}, %3;" :: "l"(p), "r"(v.x), "r"(v.y), "l"(pol) : "memory");
}
__device__ __forceinline__ void tma2d_prefetch(const CUtensorMap* m, int c0, int c1) {
    asm volatile("cp.async.bulk.prefetch.tensor.2d.L2.global [%0, {%1, %2}];" :: "l"((uint64_t)m), "r"(c0), "r"(c1) : "memory");
}
__device__ __forceinline__ void mbar_arrive_remote(uint32_t bar) { asm volatile("mbarrier.arrive.relaxed.cluster.shared::cluster.b64 _, [%0];" :: "r"(bar) : "memory"); }
__device__ __forceinline__ void tma2d_store(const CUtensorMap* m, int c0, int c1, uint32_t src) {
    asm volatile("cp.async.bulk.tensor.2d.global.shared::cta.bulk_group [%0, {%2, %3}], [%1];"
        :: "l"((uint64_t)m), "r"(src), "r"(c0), "r"(c1) : "memory");
}
__device__ __forceinline__ void bulk_g2s(uint32_t dst, const void* src, int bytes, uint32_t bar) {
    asm volatile("cp.async.bulk.shared::cluster.global.mbarrier::complete_tx::bytes [%0], [%1], %2, [%3];" :: "r"(dst), "l"(src), "r"(bytes), "r"(bar) : "memory");
}
__device__ __forceinline__ void ldsm4(uint32_t (&r)[4], uint32_t a) {
    asm volatile("ldmatrix.sync.aligned.m8n8.x4.shared.b16 {%0,%1,%2,%3}, [%4];" : "=r"(r[0]), "=r"(r[1]), "=r"(r[2]), "=r"(r[3]) : "r"(a) : "memory");
}
__device__ __forceinline__ void ldsm4t(uint32_t (&r)[4], uint32_t a) {
    asm volatile("ldmatrix.sync.aligned.m8n8.x4.trans.shared.b16 {%0,%1,%2,%3}, [%4];" : "=r"(r[0]), "=r"(r[1]), "=r"(r[2]), "=r"(r[3]) : "r"(a) : "memory");
}
__device__ __forceinline__ void stsm4(uint32_t a, uint32_t r0, uint32_t r1, uint32_t r2, uint32_t r3) {
    asm volatile("stmatrix.sync.aligned.m8n8.x4.shared.b16 [%0], {%1,%2,%3,%4};" :: "r"(a), "r"(r0), "r"(r1), "r"(r2), "r"(r3) : "memory");
}
__device__ __forceinline__ void stsm4t(uint32_t a, uint32_t r0, uint32_t r1, uint32_t r2, uint32_t r3) {
    asm volatile("stmatrix.sync.aligned.m8n8.x4.trans.shared.b16 [%0], {%1,%2,%3,%4};" :: "r"(a), "r"(r0), "r"(r1), "r"(r2), "r"(r3) : "memory");
}
__device__ __forceinline__ void stsm2t(uint32_t a, uint32_t r0, uint32_t r1) {
    asm volatile("stmatrix.sync.aligned.m8n8.x2.trans.shared.b16 [%0], {%1,%2};" :: "r"(a), "r"(r0), "r"(r1) : "memory");
}
__device__ __forceinline__ uint32_t movm_t(uint32_t v) { uint32_t r; asm volatile("movmatrix.sync.aligned.m8n8.trans.b16 %0, %1;" : "=r"(r) : "r"(v)); return r; }
__device__ __forceinline__ void mma16(float (&d)[4], uint32_t a0, uint32_t a1, uint32_t a2, uint32_t a3, uint32_t b0, uint32_t b1) {
    asm volatile("mma.sync.aligned.m16n8k16.row.col.f32.bf16.bf16.f32 {%0,%1,%2,%3}, {%4,%5,%6,%7}, {%8,%9}, {%0,%1,%2,%3};"
        : "+f"(d[0]), "+f"(d[1]), "+f"(d[2]), "+f"(d[3]) : "r"(a0), "r"(a1), "r"(a2), "r"(a3), "r"(b0), "r"(b1));
}
__device__ __forceinline__ void mma8(float (&d)[4], uint32_t a0, uint32_t a1, uint32_t b0) {
    asm volatile("mma.sync.aligned.m16n8k8.row.col.f32.bf16.bf16.f32 {%0,%1,%2,%3}, {%4,%5}, {%6}, {%0,%1,%2,%3};"
        : "+f"(d[0]), "+f"(d[1]), "+f"(d[2]), "+f"(d[3]) : "r"(a0), "r"(a1), "r"(b0));
}
__device__ __forceinline__ uint32_t mapa(uint32_t a, uint32_t r) { uint32_t o; asm volatile("mapa.shared::cluster.u32 %0, %1, %2;" : "=r"(o) : "r"(a), "r"(r)); return o; }
__device__ __forceinline__ void bar_sync(int id, int n) { asm volatile("bar.sync %0, %1;" :: "r"(id), "r"(n) : "memory"); }
__device__ __forceinline__ void bar_arrive(int id, int n) { asm volatile("bar.arrive %0, %1;" :: "r"(id), "r"(n) : "memory"); }
__device__ __forceinline__ uint64_t mkdesc(uint32_t addr, uint32_t lbo, uint32_t sbo) {
    return (uint64_t)((addr & 0x3FFFF) >> 4) | ((uint64_t)(lbo >> 4) << 16) | ((uint64_t)(sbo >> 4) << 32) | (1ull << 62);
}
#define WG_FENCE()  asm volatile("wgmma.fence.sync.aligned;" ::: "memory")
#define WG_COMMIT() asm volatile("wgmma.commit_group.sync.aligned;" ::: "memory")
#define WG_WAIT(n)  asm volatile("wgmma.wait_group.sync.aligned %0;" :: "n"(n) : "memory")

__device__ __forceinline__ void wgmma_ss_n192_tb(float (&d)[96], uint64_t a, uint64_t b, int acc) {
    asm volatile("{ .reg .pred p; setp.ne.b32 p, %98, 0;\n"
        "wgmma.mma_async.sync.aligned.m64n192k16.f32.bf16.bf16 {%0,%1,%2,%3,%4,%5,%6,%7,%8,%9,%10,%11,%12,%13,%14,%15,%16,%17,%18,%19,%20,%21,%22,%23,%24,%25,%26,%27,%28,%29,%30,%31,%32,%33,%34,%35,%36,%37,%38,%39,%40,%41,%42,%43,%44,%45,%46,%47,%48,%49,%50,%51,%52,%53,%54,%55,%56,%57,%58,%59,%60,%61,%62,%63,%64,%65,%66,%67,%68,%69,%70,%71,%72,%73,%74,%75,%76,%77,%78,%79,%80,%81,%82,%83,%84,%85,%86,%87,%88,%89,%90,%91,%92,%93,%94,%95}, %96, %97, p, 1, 1, 0, 1; }"
        : "+f"(d[0]), "+f"(d[1]), "+f"(d[2]), "+f"(d[3]), "+f"(d[4]), "+f"(d[5]), "+f"(d[6]), "+f"(d[7]), "+f"(d[8]), "+f"(d[9]), "+f"(d[10]), "+f"(d[11]), "+f"(d[12]), "+f"(d[13]), "+f"(d[14]), "+f"(d[15]), "+f"(d[16]), "+f"(d[17]), "+f"(d[18]), "+f"(d[19]), "+f"(d[20]), "+f"(d[21]), "+f"(d[22]), "+f"(d[23]), "+f"(d[24]), "+f"(d[25]), "+f"(d[26]), "+f"(d[27]), "+f"(d[28]), "+f"(d[29]), "+f"(d[30]), "+f"(d[31]), "+f"(d[32]), "+f"(d[33]), "+f"(d[34]), "+f"(d[35]), "+f"(d[36]), "+f"(d[37]), "+f"(d[38]), "+f"(d[39]), "+f"(d[40]), "+f"(d[41]), "+f"(d[42]), "+f"(d[43]), "+f"(d[44]), "+f"(d[45]), "+f"(d[46]), "+f"(d[47]), "+f"(d[48]), "+f"(d[49]), "+f"(d[50]), "+f"(d[51]), "+f"(d[52]), "+f"(d[53]), "+f"(d[54]), "+f"(d[55]), "+f"(d[56]), "+f"(d[57]), "+f"(d[58]), "+f"(d[59]), "+f"(d[60]), "+f"(d[61]), "+f"(d[62]), "+f"(d[63]), "+f"(d[64]), "+f"(d[65]), "+f"(d[66]), "+f"(d[67]), "+f"(d[68]), "+f"(d[69]), "+f"(d[70]), "+f"(d[71]), "+f"(d[72]), "+f"(d[73]), "+f"(d[74]), "+f"(d[75]), "+f"(d[76]), "+f"(d[77]), "+f"(d[78]), "+f"(d[79]), "+f"(d[80]), "+f"(d[81]), "+f"(d[82]), "+f"(d[83]), "+f"(d[84]), "+f"(d[85]), "+f"(d[86]), "+f"(d[87]), "+f"(d[88]), "+f"(d[89]), "+f"(d[90]), "+f"(d[91]), "+f"(d[92]), "+f"(d[93]), "+f"(d[94]), "+f"(d[95])
        : "l"(a), "l"(b), "r"(acc));
}

__device__ __forceinline__ void wgmma_ss_n128_tb(float (&d)[64], uint64_t a, uint64_t b, int acc) {
    asm volatile("{ .reg .pred p; setp.ne.b32 p, %66, 0;\n"
        "wgmma.mma_async.sync.aligned.m64n128k16.f32.bf16.bf16 {%0,%1,%2,%3,%4,%5,%6,%7,%8,%9,%10,%11,%12,%13,%14,%15,%16,%17,%18,%19,%20,%21,%22,%23,%24,%25,%26,%27,%28,%29,%30,%31,%32,%33,%34,%35,%36,%37,%38,%39,%40,%41,%42,%43,%44,%45,%46,%47,%48,%49,%50,%51,%52,%53,%54,%55,%56,%57,%58,%59,%60,%61,%62,%63}, %64, %65, p, 1, 1, 0, 1; }"
        : "+f"(d[0]), "+f"(d[1]), "+f"(d[2]), "+f"(d[3]), "+f"(d[4]), "+f"(d[5]), "+f"(d[6]), "+f"(d[7]), "+f"(d[8]), "+f"(d[9]), "+f"(d[10]), "+f"(d[11]), "+f"(d[12]), "+f"(d[13]), "+f"(d[14]), "+f"(d[15]), "+f"(d[16]), "+f"(d[17]), "+f"(d[18]), "+f"(d[19]), "+f"(d[20]), "+f"(d[21]), "+f"(d[22]), "+f"(d[23]), "+f"(d[24]), "+f"(d[25]), "+f"(d[26]), "+f"(d[27]), "+f"(d[28]), "+f"(d[29]), "+f"(d[30]), "+f"(d[31]), "+f"(d[32]), "+f"(d[33]), "+f"(d[34]), "+f"(d[35]), "+f"(d[36]), "+f"(d[37]), "+f"(d[38]), "+f"(d[39]), "+f"(d[40]), "+f"(d[41]), "+f"(d[42]), "+f"(d[43]), "+f"(d[44]), "+f"(d[45]), "+f"(d[46]), "+f"(d[47]), "+f"(d[48]), "+f"(d[49]), "+f"(d[50]), "+f"(d[51]), "+f"(d[52]), "+f"(d[53]), "+f"(d[54]), "+f"(d[55]), "+f"(d[56]), "+f"(d[57]), "+f"(d[58]), "+f"(d[59]), "+f"(d[60]), "+f"(d[61]), "+f"(d[62]), "+f"(d[63])
        : "l"(a), "l"(b), "r"(acc));
}

__device__ __forceinline__ void wgmma_rs_n32(float (&d)[16], const uint32_t (&a)[4], uint64_t b, int acc) {
    asm volatile("{ .reg .pred p; setp.ne.b32 p, %21, 0;\n"
        "wgmma.mma_async.sync.aligned.m64n32k16.f32.bf16.bf16 {%0,%1,%2,%3,%4,%5,%6,%7,%8,%9,%10,%11,%12,%13,%14,%15}, {%16,%17,%18,%19}, %20, p, 1, 1, 0; }"
        : "+f"(d[0]), "+f"(d[1]), "+f"(d[2]), "+f"(d[3]), "+f"(d[4]), "+f"(d[5]), "+f"(d[6]), "+f"(d[7]), "+f"(d[8]), "+f"(d[9]), "+f"(d[10]), "+f"(d[11]), "+f"(d[12]), "+f"(d[13]), "+f"(d[14]), "+f"(d[15])
        : "r"(a[0]), "r"(a[1]), "r"(a[2]), "r"(a[3]), "l"(b), "r"(acc));
}

__device__ __forceinline__ float warp_sum(float v) {
#pragma unroll
    for (int o = 16; o; o >>= 1) v += __shfl_xor_sync(0xffffffffu, v, o);
    return v;
}
__device__ __forceinline__ uint32_t add2(uint32_t a, uint32_t b) { uint32_t r; asm("add.rn.bf16x2 %0, %1, %2;" : "=r"(r) : "r"(a), "r"(b)); return r; }
__device__ __forceinline__ uint32_t mul2(uint32_t a, uint32_t b) { uint32_t r; asm("mul.rn.bf16x2 %0, %1, %2;" : "=r"(r) : "r"(a), "r"(b)); return r; }
__device__ __forceinline__ uint32_t amax2(uint32_t m, uint32_t v) { uint32_t r; asm("max.u16x2 %0, %1, %2;" : "=r"(r) : "r"(m), "r"(v & 0x7fff7fffu)); return r; }
__device__ __forceinline__ uint32_t amax_warp(uint32_t m) { return __reduce_max_sync(0xffffffffu, max(m & 0xffffu, m >> 16)); }
__device__ __forceinline__ void ln_norm(const uint32_t (&xv)[10], uint32_t (&nv)[10]) {
    float s0 = 0, s1 = 0;
#pragma unroll
    for (int i = 0; i < 10; i++) { s0 += lo_f(xv[i]); s1 += hi_f(xv[i]); }
    const float mean = warp_sum(s0 + s1) * (1.f / DM);
    float q0 = 0, q1 = 0;
#pragma unroll
    for (int i = 0; i < 10; i++) { const float d0 = lo_f(xv[i]) - mean, d1 = hi_f(xv[i]) - mean; q0 += d0 * d0; q1 += d1 * d1; }
    const float inv = inv_std(warp_sum(q0 + q1) * (1.f / DM));
    const uint32_t mb = pack2(-mean, -mean);
#pragma unroll
    for (int i = 0; i < 10; i++) { const uint32_t d = add2(xv[i], mb); nv[i] = pack2(lo_f(d) * inv, hi_f(d) * inv); }
}
__device__ __forceinline__ void ln_mod(const uint32_t (&xv)[10], const uint32_t (&sv)[10], const uint32_t (&tv)[10], uint32_t (&hv)[10]) {
    ln_norm(xv, hv);
#pragma unroll
    for (int i = 0; i < 10; i++) hv[i] = add2(mul2(hv[i], add2(sv[i], 0x3f803f80u)), tv[i]);
}
__device__ __forceinline__ uint32_t ld_rlx(const uint32_t* f) { uint32_t v; asm volatile("ld.relaxed.gpu.global.u32 %0, [%1];" : "=r"(v) : "l"(f) : "memory"); return v; }
__device__ __forceinline__ void bump(uint32_t* f) { asm volatile("red.relaxed.gpu.global.add.u32 [%0], 1;" :: "l"(f) : "memory"); }
#define NAP 100
#define GPU_FENCE() asm volatile("fence.acq_rel.gpu;" ::: "memory")
__device__ __forceinline__ void flag_wait(const uint32_t* f, uint32_t target) {
    for (int n = 0;; n++) {
        uint32_t v; asm volatile("ld.relaxed.gpu.global.u32 %0, [%1];" : "=r"(v) : "l"(f) : "memory");
        if (v >= target) break;
        if (n > (1 << 22)) __trap();
        __nanosleep(NAP);
    }
}
__device__ __forceinline__ void flag_add(uint32_t* f, uint32_t v = 1) { asm volatile("red.release.gpu.global.add.u32 [%0], %1;" :: "l"(f), "r"(v) : "memory"); }
constexpr int N_SIDE = 36;
__device__ __forceinline__ void flags_release(int lane) {
    uint32_t old = 0;
    if (lane == 0) asm volatile("atom.relaxed.gpu.global.add.u32 %0, [%1], 1;" : "=r"(old) : "l"(&g_flags.done) : "memory");
    if (__shfl_sync(0xffffffffu, old, 0) == 96 + N_SIDE - 1)
#pragma unroll 1
        for (int i = lane; i < (int)(sizeof(Flags) / 16); i += 32) ((uint4*)&g_flags)[i] = make_uint4(0, 0, 0, 0);
}

template <int NT> struct ModSlice {
    static constexpr int R = 2 * DM / NT;
    float sc[R]; uint4 wv[R];
    __device__ __forceinline__ void load(const bf16* wmod, const bf16* c, int col, int tid) {
        const bf16* wm = wmod + (tid >> 1) * (6 * DM) + col + (tid & 1) * 8;
#pragma unroll
        for (int i = 0; i < R; i++) {
            asm volatile("ld.global.nc.L1::no_allocate.L2::128B.v4.u32 {%0,%1,%2,%3}, [%4];" : "=r"(wv[i].x), "=r"(wv[i].y), "=r"(wv[i].z), "=r"(wv[i].w) : "l"(wm + i * (NT / 2) * (6 * DM)));
            sc[i] = __uint_as_float((uint32_t)__ldg((const unsigned short*)c + (tid >> 1) + NT / 2 * i) << 16);
        }
    }
    __device__ __forceinline__ void partial(uint32_t buf, int tid) {
        const int lane = tid & 31;
        float a[8] = {0, 0, 0, 0, 0, 0, 0, 0};
#pragma unroll
        for (int i = 0; i < R; i++) {
            const float f = bfr(__fdividef(sc[i], 1.f + __expf(-sc[i])));
            const uint32_t u[4] = {wv[i].x, wv[i].y, wv[i].z, wv[i].w};
#pragma unroll
            for (int e = 0; e < 4; e++) { a[2 * e] += f * lo_f(u[e]); a[2 * e + 1] += f * hi_f(u[e]); }
        }
#pragma unroll
        for (int h = 4; h; h >>= 1)
#pragma unroll
            for (int e = 0; e < h; e++) { const bool up = lane & (4 * h); a[e] = (up ? a[e + h] : a[e]) + __shfl_xor_sync(0xffffffffu, up ? a[e] : a[e + h], 4 * h); }
        a[0] += __shfl_xor_sync(0xffffffffu, a[0], 2);
        asm volatile("st.shared.f32 [%0], %1;" :: "r"(buf + (tid >> 5) * 64 + (lane & 1) * 32 + (lane >> 2) * 4), "f"(a[0]) : "memory");
    }
    static __device__ __forceinline__ uint32_t total(uint32_t buf, int lane) {
        float a0 = 0, a1 = 0;
#pragma unroll
        for (int i = 0; i < NT / 32; i++) { float x, y; asm volatile("ld.shared.v2.f32 {%0,%1}, [%2];" : "=f"(x), "=f"(y) : "r"(buf + i * 64 + (lane & 7) * 8) : "memory"); a0 += x; a1 += y; }
        return pack2(a0, a1);
    }
};

struct ChainMaps { CUtensorMap wq, wk, wv, wo, h2, wo15, o15, slab16; };
struct ChainArgs { const bf16 *x, *mem0, *c, *wmod, *wv, *wo, *wgate, *wup, *wdown; bf16* out; int D1, D2, DG; };
constexpr uint32_t SM_BASE = 1024;
#define NRING 10
#define XORD 0
#define B5AT 41
#define QCUT 0x54
#define NCH 0
#define XA 3
#define VT 1
#define OSEND 1
#define SPOLL 0
#define NPRE 9
#define REG_P 208
#define REG_L (504 - 2 * REG_P)
constexpr int WO_BLK = 7 * 4096;
constexpr int C_WV = 0, C_WO = 81920, C_XR = 167936, C_VP = C_XR + 7 * 4096, C_VX = C_XR + 8 * 4096, C_QX = C_VX + 4096, C_KX = C_QX + 4096,
              C_MEM = C_KX + 4096, C_OX = C_MEM + 9216, C_VM = C_OX + 3072, C_QM = C_VM + 1024, C_KM = C_QM + 1024, C_SC = C_KM + 1024, C_BAR = C_SC + 3840;
constexpr int CB_W = C_BAR, CB_W2 = C_BAR + 8, CB_SC = C_BAR + 16, CB_XD = C_BAR + 24, CB_VX = C_BAR + 32, CB_W3 = C_BAR + 40, CB_XM = C_BAR + 48, CB_OX = C_BAR + 56,
              CB_XF = C_BAR + 64, C_LAG = C_BAR + 96, C_UN = C_BAR + 100, C_MX = C_BAR + 112;
constexpr int C_SMEM = C_BAR + 128;
#define PROF(i)
#define PROFG(i)
#define PROFV(i, v)
static_assert(C_SMEM <= 232448, "chain shared memory");
__device__ __forceinline__ uint32_t umax3(uint32_t a, uint32_t b, uint32_t c) { return max(max(a, b), c); }
__device__ __forceinline__ void wait_until(uint32_t t) {
    asm volatile("{ .reg .pred p; .reg .s32 c; .reg .u64 d;\nU_%=: mov.u64 d, %%clock64; cvt.u32.u64 c, d; sub.s32 c, c, %0; setp.lt.s32 p, c, 0; @p bra.uni U_%=; }" :: "r"(t) : "memory");
}
__device__ __forceinline__ uint32_t gtime() { uint32_t c; asm volatile("mov.u32 %0, %%globaltimer_lo;" : "=r"(c)); return c; }
__device__ __forceinline__ uint32_t opaque(uint32_t v) { uint32_t r; asm volatile("shfl.sync.bfly.b32 %0, %1, 0, 31, -1;" : "=r"(r) : "r"(v)); return r; }
__device__ __forceinline__ uint32_t lds32(uint32_t a) { uint32_t v; asm volatile("ld.shared.u32 %0, [%1];" : "=r"(v) : "r"(a) : "memory"); return v; }
__device__ __forceinline__ float2 lds64f(uint32_t a) { float2 v; asm volatile("ld.shared.v2.f32 {%0,%1}, [%2];" : "=f"(v.x), "=f"(v.y) : "r"(a) : "memory"); return v; }
__device__ __forceinline__ float4 lds128f(uint32_t a) { float4 v; asm volatile("ld.shared.v4.f32 {%0,%1,%2,%3}, [%4];" : "=f"(v.x), "=f"(v.y), "=f"(v.z), "=f"(v.w) : "r"(a) : "memory"); return v; }
__device__ __forceinline__ void sts128f(uint32_t a, float x, float y, float z, float w) { asm volatile("st.shared.v4.f32 [%0], {%1,%2,%3,%4};" :: "r"(a), "f"(x), "f"(y), "f"(z), "f"(w) : "memory"); }
__device__ __forceinline__ void lds64(uint32_t (&v)[2], uint32_t a) { asm volatile("ld.shared.v2.u32 {%0,%1}, [%2];" : "=r"(v[0]), "=r"(v[1]) : "r"(a) : "memory"); }
__device__ __forceinline__ void mma16q(float (&d)[4], const uint32_t (&a)[4], uint32_t b0, uint32_t b1) { mma16(d, a[0], a[1], a[2], a[3], b0, b1); }
__device__ __forceinline__ uint32_t f16_to_bf16(uint32_t v) {
    float lo, hi; asm("{ .reg .f16 l, h; mov.b32 {l, h}, %2; cvt.f32.f16 %0, l; cvt.f32.f16 %1, h; }" : "=f"(lo), "=f"(hi) : "r"(v));
    return pack2(lo, hi);
}
__device__ __forceinline__ uint32_t pack2h(float lo, float hi) { uint32_t r; asm("cvt.rn.f16x2.f32 %0, %1, %2;" : "=r"(r) : "f"(hi), "f"(lo)); return r; }
#define SPLIT 1
__device__ __forceinline__ void cut(uint32_t never, int n) {
    asm volatile("{ .reg .pred p; setp.ne.u32 p, %0, %1; @p bra.uni C_%=; trap; C_%=: }" :: "r"(never), "r"(n) : "memory");
}
__device__ __forceinline__ void pin(uint32_t never, uint32_t a, uint32_t b, uint32_t c, uint32_t d) {
    asm volatile("{ .reg .pred p; setp.eq.u32 p, %0, 0; @p st.shared.v4.u32 [%0], {%1,%2,%3,%4}; }" :: "r"(never), "r"(a), "r"(b), "r"(c), "r"(d) : "memory");
}
__device__ __forceinline__ void pin0(uint32_t never) {
    asm volatile("{ .reg .pred p; setp.eq.u32 p, %0, 0; @p st.shared.u32 [%0], 0; }" :: "r"(never) : "memory");
}
#define ELECTED(txt) "{ .reg .pred e; elect.sync _|e, -1; @e " txt " }"
__device__ __forceinline__ void w_bulk_s2g(void* dst, uint32_t src, int bytes) {
    asm volatile(ELECTED("cp.async.bulk.global.shared::cta.bulk_group [%0], [%1], %2;") :: "l"(dst), "r"(src), "r"(bytes) : "memory");
}
__device__ __forceinline__ void w_bump(uint32_t* f) { asm volatile(ELECTED("red.relaxed.gpu.global.add.u32 [%0], 1;") :: "l"(f) : "memory"); }
__device__ __forceinline__ void w_expect(uint32_t bar, int bytes) { asm volatile(ELECTED("mbarrier.arrive.expect_tx.shared::cta.b64 _, [%0], %1;") :: "r"(bar), "r"(bytes) : "memory"); }
__device__ __forceinline__ void w_flag_wait(const uint32_t* f, uint32_t target) {
    asm volatile("{ .reg .pred p; .reg .u32 n, v; mov.u32 n, 0;\n"
                 "F_%=: ld.relaxed.gpu.global.u32 v, [%0]; setp.ge.u32 p, v, %1; vote.sync.all.pred p, p, -1; @p bra.uni G_%=;\n"
                 "nanosleep.u32 %2; add.u32 n, n, 1; setp.lt.u32 p, n, 0x400000; @p bra.uni F_%=;\ntrap;\nG_%=: }" :: "l"(f), "r"(target), "n"(NAP) : "memory");
}
#define BULK_COMMIT()    asm volatile("cp.async.bulk.commit_group;" ::: "memory")
#define BULK_WAIT()      asm volatile("cp.async.bulk.wait_group 0;" ::: "memory")
#define BULK_WAIT_READ() asm volatile("cp.async.bulk.wait_group.read 0;" ::: "memory")
#define PROXY_FENCE()    asm volatile("fence.proxy.async.shared::cta;" ::: "memory")
__device__ __forceinline__ void send16(uint32_t dst, uint32_t bar, float a, float b, float c, float d) {
    asm volatile("st.async.shared::cluster.mbarrier::complete_tx::bytes.v4.f32 [%0], {%1,%2,%3,%4}, [%5];" :: "r"(dst), "f"(a), "f"(b), "f"(c), "f"(d), "r"(bar) : "memory");
}
__device__ __forceinline__ void send8(uint32_t dst, uint32_t bar, uint32_t a, uint32_t b) {
    asm volatile("st.async.shared::cluster.mbarrier::complete_tx::bytes.v2.b32 [%0], {%1,%2}, [%3];" :: "r"(dst), "r"(a), "r"(b), "r"(bar) : "memory");
}

__device__ __forceinline__ void seg_done(int n, int head) {
    if (n >= 60 || (n & 3) == 3) { GPU_FENCE(); w_bump(n >= 60 ? &g_flags.seg[(n - 60) * 32 + head] : &g_flags.qk[n >> 2]); }
}
__device__ __forceinline__ uint32_t x_base(int wg, uint32_t small, int sh) { return (uint32_t)mkdesc(SM_BASE + C_XR, 16, 1024) + wg * 256 + (small >> sh); }
__device__ __forceinline__ void x_chunk(float (&acc)[16], const uint32_t (&wa)[40][4], uint32_t xl, int a0, int i, int first) {
#pragma unroll
    for (int ks = 0; ks < 4; ks++)
        wgmma_rs_n32(acc, wa[a0 + 4 * i + ks], mkdesc(0, 0, 1024) | (uint32_t)(xl + (((i ? (i - 1) * 8192 : C_MEM - C_XR) + ks * 32) >> 4)), !(first && ks == 0));
}
__device__ __forceinline__ void x_part(float (&acc)[16], const uint32_t (&wa)[40][4], uint32_t sm, int n, int wg, int w, uint32_t ln, uint32_t small) {
    const int s = n - 1; (void)s;
    uint32_t giv[8];
    auto chunk = [&](int a0, int i, int first) { x_chunk(acc, wa, x_base(wg, small, a0 ? 21 : 22), a0, i, first); };
    mbar_wait(sm + CB_XM, n & 1);
    if (n) bar_sync(5, 384);
    if (wg == 0 && w == 0) PROF(12);
    WG_FENCE();
#pragma unroll
    for (int i = 1 + XA; i < 5; i++) chunk(20, i, 0);
    chunk(20, 0, 0);
    WG_COMMIT();
    if (n) {
        if (wg == 1 && w == 1) BULK_WAIT();
        bar_sync(8, 256);
    }
    if (wg == 0 && w == 0) PROF(18);
    const uint32_t xb = sm + w * 512 + ln * 16, xw = xb + C_KX - wg * 4096, xr = xb + C_QX + wg * 4096;
    WG_WAIT(0);
#pragma unroll
    for (int i = 0; i < 8; i++) asm volatile("cvt.rn.bf16x2.f32 %0, %1, %2;" : "=r"(giv[i]) : "f"(acc[2 * i + 1]), "f"(acc[2 * i]));
#pragma unroll
    for (int p = 0; p < 2; p++) asm volatile("st.shared.v4.u32 [%0], {%1,%2,%3,%4};" :: "r"(xw + p * 2048), "r"(giv[4 * p]), "r"(giv[4 * p + 1]), "r"(giv[4 * p + 2]), "r"(giv[4 * p + 3]) : "memory");
    bar_arrive(12 + wg, 256);
    WG_FENCE();
    chunk(0, 0, 1);
    WG_COMMIT();
    chunk(0, 1, 0);
    if (XORD) chunk(0, 2, 0);
    bar_sync(13 - wg, 256);
#pragma unroll
    for (int p = 0; p < 2; p++) asm volatile("ld.shared.v4.u32 {%0,%1,%2,%3}, [%4];" : "=r"(giv[4 * p]), "=r"(giv[4 * p + 1]), "=r"(giv[4 * p + 2]), "=r"(giv[4 * p + 3]) : "r"(xr + p * 2048) : "memory");
    WG_COMMIT(); WG_WAIT(1); bar_arrive(9, 384);
    WG_FENCE();
    if (!XORD) chunk(0, 2, 0);
    chunk(0, 3, 0); chunk(0, 4, 0);
    WG_COMMIT();
    const uint32_t r = ln & 7, mi = ln >> 3, dst = sm + (wg == 0 ? C_QX : C_KX) + ((mi >> 1) * 8 + r) * 128 + (((2 * w + (mi & 1)) ^ r) << 4);
    pin(xb, giv[0], giv[4], dst, 0);
    bar_sync(10 + wg, 128);
    WG_WAIT(0);
    if (wg == 0 && w == 0) PROF(30);
    if (w == 0 && ln < 3) mbar_arrive_remote(mapa(sm + CB_XD, ln));
#pragma unroll
    for (int i = 0; i < 8; i++) { acc[2 * i] += lo_f(giv[i]); acc[2 * i + 1] += hi_f(giv[i]); }
#pragma unroll
    for (int p = 0; p < 2; p++)
        stsm4t(dst + p * 2048, pack2(acc[8 * p], acc[8 * p + 1]), pack2(acc[8 * p + 2], acc[8 * p + 3]), pack2(acc[8 * p + 4], acc[8 * p + 5]), pack2(acc[8 * p + 6], acc[8 * p + 7]));
    if (wg == 0 && w == 0) PROF(11);
}
__device__ __forceinline__ void x_fill(const ChainMaps& mp, uint32_t sm, int n, int j) {
    mbar_expect(sm + CB_XF, 24576);
    asm volatile("cp.async.bulk.tensor.3d.shared::cluster.global.mbarrier::complete_tx::bytes.multicast::cluster [%0], [%1, {0, %3, %4}], [%2], %5;"
        :: "r"(sm + C_XR + j * 8192), "l"((uint64_t)&mp.h2), "r"(sm + CB_XF), "r"(n * SEG), "r"(2 + 2 * j), "h"((uint16_t)7) : "memory");
}
__device__ __forceinline__ void x_rest(const ChainMaps& mp, uint32_t sm, int n) {
    mbar_expect(sm + CB_XM, 16384);
    tma3d(sm + C_XR + 6 * 4096, &mp.h2, n * SEG, 8, sm + CB_XM); tma3d(sm + C_MEM, &mp.h2, n * SEG, 0, sm + CB_XM);
}

#define WPOS 15
#define WP 8
#define WOPF 30
#define SPF 0
#define SDEL 0
#define BPOS 1
#define TPF 1
#define B_LATE 14
constexpr int E_B = C_WO, E_STG = 196608, EB_A = 229376, EB_B = C_BAR + 80, EB_REL = C_BAR + 104;
__device__ __forceinline__ uint32_t e_slot(int wg, int c) { return wg && c == 2 ? E_B + 98304 : wg * 49152 + c * 16384; }
constexpr int T_WG = 0, T_WU = 20480, T_WD = 40960, T_X = 65536, T_RED = 77824, T_KEY = 86016;
__device__ __forceinline__ void wo_half(const ChainMaps& mp, uint32_t sm, int blk, int c) {
    if (blk < 80 && elect()) { mbar_expect(sm + EB_B + 8 * c, 49152); tma3d(sm + E_B + c * 49152, &mp.wo15, blk / 5 * 384 + c * 192, blk % 5 * 2, sm + EB_B + 8 * c); }
}
__device__ __forceinline__ void end_loads(const ChainMaps& mp, const ChainArgs& ar, uint32_t sm, int blk, int wg) {
    const uint32_t bar = sm + EB_A + wg * 48;
    const int kp = blk / 5;
    if (elect()) {
#pragma unroll 1
        for (int c = 0; c < 6; c++) mbar_init(bar + 8 * c, c < 3 ? 1 : 4);
        PROXY_FENCE();
    }
    __syncwarp();
    bar_arrive(5, 384);
    if (blk >= 80) {
        if (TPF && elect()) {
#pragma unroll 1
            for (int c = 0; c < 3; c++) asm volatile("cp.async.bulk.prefetch.L2.global [%0], 61440;" :: "l"((c == 0 ? ar.wgate : c == 1 ? ar.wup : ar.wdown) + ((blk - 80) * 2 + wg) * 30720) : "memory");
        }
        return;
    }
    const uint64_t ef = policy_stream();
#pragma unroll 1
    for (int b = B_LATE; b < 16; b++) {
        w_flag_wait(b == 15 ? &g_flags.half[kp * 2 + wg] : &g_flags.pair[b * 16 + kp], b == 15 ? 8 : 16);
#pragma unroll 1
        for (int c = 0; c < 3; c++) {
            if (b > B_LATE) mbar_wait(bar + 24 + 8 * c, (b - B_LATE - 1) & 1);
            if (elect()) { mbar_expect(bar + 8 * c, 16384); tma3d_ef(sm + e_slot(wg, c), &mp.o15, b * 128 + wg * 64, kp * 6 + c * 2, bar + 8 * c, ef); }
            __syncwarp();
        }
    }
}
__device__ __forceinline__ void last_blocks(const ChainMaps& mp, const ChainArgs& ar, uint32_t sm, int blk, int tid) {
    const int warp = __shfl_sync(0xffffffffu, tid >> 5, 0), lane = tid & 31, wg = warp >> 2, w = warp & 3, kp = blk / 5, ct = blk % 5;
    const uint32_t bar = sm + EB_A + wg * 48, stg = sm + E_STG + warp * 4096;
    const uint64_t ef = policy_stream();
    bar_sync(5, 384);
    float acc[64];
#pragma unroll
    for (int n = 0; n < 64; n++) acc[n] = 0.f;
#pragma unroll 1
    for (int b = B_LATE; b < 16 && blk < 80; b++) {
#pragma unroll 1
        for (int c = 0; c < 6; c++) {
            mbar_wait(sm + EB_B + 8 * (c >= 3), 0); mbar_wait(bar + 8 * (c >> 1), (b - B_LATE) & 1);
            const uint64_t da = mkdesc(SM_BASE + e_slot(wg, c >> 1) + (c & 1) * 8192, 16, 1024), db = mkdesc(SM_BASE + E_B + (c >= 3 ? 24576 : 0) + c * 8192, 24576, 1024);
            WG_FENCE();
#pragma unroll
            for (int ks = 0; ks < 4; ks++) wgmma_ss_n128_tb(acc, da + ks * 2, db + ks * 128, c | ks);
            WG_COMMIT();
            WG_WAIT(1);
            if ((c & 1) == 0 && c && elect()) mbar_arrive(bar + 16 + 4 * c);
        }
        WG_WAIT(0);
        if (elect()) mbar_arrive(bar + 40);
        const int r = lane & 7, mi = lane >> 3;
#pragma unroll
        for (int p = 0; p < 8; p++) {
            const int oc = 2 * p + (mi >> 1);
            stsm4(stg + (oc >> 3) * 2048 + ((mi & 1) * 8 + r) * 128 + (((oc & 7) ^ r) << 4), pack2(acc[8 * p], acc[8 * p + 1]), pack2(acc[8 * p + 2], acc[8 * p + 3]),
                  pack2(acc[8 * p + 4], acc[8 * p + 5]), pack2(acc[8 * p + 6], acc[8 * p + 7]));
        }
        PROXY_FENCE();
        __syncwarp();
        if (elect()) tma3d_store(&mp.slab16, (b * KSPLIT + kp) * 128 + warp * 16, ct * 2, stg, ef, false);
        BULK_COMMIT(); BULK_WAIT();
        if (w) bar_arrive(12 + wg, 128); else { bar_sync(12 + wg, 128); GPU_FENCE(); w_bump(b < 14 ? &g_flags.o[b] : &g_flags.fin[((b - 14) * 2 + wg) * 32]); }
    }
    bar_sync(8, 256);
    const int o = (tid >> 1) * FF + blk * 16 + (tid & 1) * 8;
    const bf16 *pg = ar.wgate + o, *pu = ar.wup + o, *pd = ar.wdown + tid * DM + (blk < 80 ? blk : 0) * 8;
#pragma unroll
    for (int i = 0; i < 16; i++)
        asm volatile("cp.async.cg.shared.global [%0], [%1], 16;" :: "r"(sm + E_B + i * 4096 + tid * 16), "l"(i < 5 ? pg + i * 128 * FF : i < 10 ? pu + (i - 5) * 128 * FF : pd + (i - 10) * 256 * DM) : "memory");
}
__device__ __forceinline__ void mod_tail(const ChainArgs& ar, const uint32_t tb, const uint32_t bar, const int blk, const int tid) {
#define TPROF(i)
    const int warp = __shfl_sync(0xffffffffu, tid >> 5, 0), lane = tid & 31, r = lane & 7, mi = lane >> 3;
    const uint32_t kb = tb + T_KEY;
    {
        uint32_t k[8];
        for (int n = 0;; n++) {
#pragma unroll
            for (int i = 0; i < 2; i++) asm volatile("ld.relaxed.gpu.global.v4.u32 {%0,%1,%2,%3}, [%4];" : "=r"(k[4 * i]), "=r"(k[4 * i + 1]), "=r"(k[4 * i + 2]), "=r"(k[4 * i + 3]) : "l"(g_key + warp * 256 + i * 128 + lane * 4) : "memory");
            if (__all_sync(0xffffffffu, (k[0] & k[1] & k[2] & k[3] & k[4] & k[5] & k[6] & k[7] & S_TOK) != 0)) break;
            if (n > (1 << 22)) __trap();
            __nanosleep(NAP);
        }
        const uint32_t m = __reduce_max_sync(0xffffffffu, max(umax3(k[0], k[1], k[2]), max(umax3(k[3], k[4], k[5]), max(k[6], k[7]))));
        asm volatile("st.shared.u32 [%0], %1; st.shared.u32 [%2], 0;" :: "r"(kb + warp * 4), "r"(m), "r"(kb + 32) : "memory");
        asm volatile("cp.async.wait_all;" ::: "memory");
        bar_sync(1, 256);
        TPROF(1);
        const uint32_t low = __reduce_min_sync(0xffffffffu, lds32(kb + r * 4));
        uint32_t cnt = 0;
#pragma unroll
        for (int i = 0; i < 8; i++) cnt += k[i] >= low ? 4 : 0;
        if (cnt) {
            uint32_t a; asm volatile("atom.shared.add.u32 %0, [%1], %2;" : "=r"(a) : "r"(kb + 32), "r"(cnt) : "memory");
#pragma unroll
            for (int i = 0; i < 8; i++) if (k[i] >= low) { asm volatile("st.shared.u32 [%0], %1;" :: "r"(kb + 512 + a), "r"(k[i]) : "memory"); a += 4; }
        }
        if (tid == 0) mbar_arrive(bar);
        bar_sync(1, 256);
        const int nc = lds32(kb + 32);
#pragma unroll 1
        for (int c = lane * 4; c < nc; c += 128) {
            const uint32_t me = lds32(kb + 512 + c);
            int rank = 0;
#pragma unroll 2
            for (int e = 0; e < nc; e += 16) {
                const float4 z = lds128f(kb + 512 + e);
                rank += (__float_as_uint(z.x) > me) + (e + 4 < nc && __float_as_uint(z.y) > me) + (e + 8 < nc && __float_as_uint(z.z) > me) + (e + 12 < nc && __float_as_uint(z.w) > me);
            }
            if (rank < 8) asm volatile("st.shared.u32 [%0], %1;" :: "r"(kb + 64 + (warp * 8 + rank) * 4), "r"(me) : "memory");
        }
        __syncwarp();
    }
    const uint32_t k0 = lds32(kb + 64 + (warp * 8 + r) * 4), k1 = lds32(kb + 64 + (warp * 8 + (lane >> 2)) * 4);
    TPROF(2);
    const int trow = ~k1 & (S_TOK - 1), tcol = (blk < 80 ? blk : 0) * 8 + (lane & 3) * 2;
    uint2 xb[5];
#pragma unroll
    for (int h = 0; h < 5; h++) xb[h] = __ldcg((const uint2*)(g_h2 + trow * DM + (warp * 5 + h) * 16 + (lane & 3) * 4));
    const uint32_t fx1 = __ldcg((const uint32_t*)(g_x1 + trow * DM + tcol)), fh2 = __ldcg((const uint32_t*)(g_h2 + trow * DM + tcol)),
                   fgb = __ldcg((const uint32_t*)(g_mod + 5 * DM + tcol));
    const float fr = __uint_as_float(((int)k1 < 0 ? k1 ^ 0x80000000u : ~k1) & 0xffff0000u);
    {
        float dg[4] = {0, 0, 0, 0}, du[4] = {0, 0, 0, 0};
        uint32_t ag[5][4], au[5][4];
#pragma unroll
        for (int h = 0; h < 5; h++) {
            const uint32_t o = tb + ((warp * 5 + h) * 16 + (r >> 1) * 4 + (mi >> 1) * 2 + (r & 1)) * 32 + (mi & 1) * 16;
            ldsm4t(ag[h], o + T_WG); ldsm4t(au[h], o + T_WU);
        }
#pragma unroll
        for (int h = 0; h < 5; h++) { mma16q(dg, ag[h], xb[h].x, xb[h].y); mma16q(du, au[h], xb[h].x, xb[h].y); }
        TPROF(3);
        sts128f(tb + T_RED + warp * 1024 + lane * 16, dg[0], dg[1], dg[2], dg[3]); sts128f(tb + T_RED + warp * 1024 + 512 + lane * 16, du[0], du[1], du[2], du[3]);
    }
    bar_sync(1, 256);
    if (warp < 2) {
        float g2[2] = {0, 0}, u2[2] = {0, 0};
#pragma unroll
        for (int i = 0; i < 8; i++) {
            const float2 a = lds64f(tb + T_RED + i * 1024 + lane * 16 + warp * 8), b = lds64f(tb + T_RED + i * 1024 + 512 + lane * 16 + warp * 8);
            g2[0] += a.x; g2[1] += a.y; u2[0] += b.x; u2[1] += b.y;
        }
        float y[2];
#pragma unroll
        for (int i = 0; i < 2; i++) { const float gq = bfr(g2[i]); y[i] = bfr(__fdividef(gq, 1.f + __expf(-gq))) * bfr(u2[i]); }
        asm volatile("st.relaxed.gpu.global.u32 [%0], %1;" :: "l"(g_gu + (blk >> 1) * 128 + lane * 4 + warp * 2 + (blk & 1)), "r"(movm_t(pack2(y[0], y[1]))) : "memory");
    }
    TPROF(4);
    if (blk < 80) {
        uint32_t a[6][4], b[6][4];
#pragma unroll
        for (int k2 = 0; k2 < 6; k2++) ldsm4t(b[k2], tb + T_WD + (warp * 6 + k2) * 512 + lane * 16);
        for (int n = 0;; n++) {
            uint32_t m = 0;
#pragma unroll
            for (int k2 = 0; k2 < 6; k2++) asm volatile("ld.relaxed.gpu.global.v4.u32 {%0,%1,%2,%3}, [%4];" : "=r"(a[k2][0]), "=r"(a[k2][1]), "=r"(a[k2][2]), "=r"(a[k2][3]) : "l"(g_gu + (warp * 6 + k2) * 128 + lane * 4) : "memory");
#pragma unroll
            for (int k2 = 0; k2 < 6; k2++) m = umax3(umax3(m, a[k2][0], a[k2][1]), a[k2][2], a[k2][3]);
            if (!__any_sync(0xffffffffu, m == ~0u)) break;
            if (n > (1 << 22)) __trap();
        }
        TPROF(5);
        float d[2][4] = {{0, 0, 0, 0}, {0, 0, 0, 0}};
#pragma unroll
        for (int k2 = 0; k2 < 6; k2++) { mma16q(d[0], a[k2], b[k2][0], b[k2][1]); mma16q(d[1], a[k2], b[k2][2], b[k2][3]); }
        asm volatile("st.shared.v2.f32 [%0], {%1,%2};" :: "r"(tb + T_X + warp * 256 + lane * 8), "f"(d[0][0] + d[1][2]), "f"(d[0][1] + d[1][3]) : "memory");
        bar_sync(1, 256);
        if (warp == 0) {
            float y0 = 0, y1 = 0;
#pragma unroll
            for (int i = 0; i < 8; i++) { const float2 z = lds64f(tb + T_X + i * 256 + lane * 8); y0 += z.x; y1 += z.y; }
            const float sg = __fdividef(1.f, 1.f + __expf(-fr));
            *(uint32_t*)(ar.out + trow * DM + tcol) = add2(fx1, mul2(fgb, add2(fh2, mul2(pack2(y0, y1), pack2(sg, sg)))));
        }
    }
    TPROF(6);
}

__global__ void __cluster_dims__(3, 1, 1) __launch_bounds__(384, 1) k_chain(const __grid_constant__ ChainMaps mp, const __grid_constant__ ChainArgs ar) {
    const int D1 = ar.D1, DG = ar.DG;
    extern __shared__ __align__(1024) uint8_t smraw[];
    const uint32_t sm = SM_BASE + ((blockIdx.x % 3) << 24);
    if (smem_u32(smraw) != sm) __trap();
    uint32_t tid; asm volatile("mov.u32 %0, %%tid.x;" : "=r"(tid));
    const int warp = __shfl_sync(0xffffffffu, tid >> 5, 0), lane = tid & 31, wg = warp >> 2, w = warp & 3;
    const int blk = blockIdx.x, head = blk / 3, j = blk % 3;
    const int col0 = head * DH + j * 64;
    asm volatile("griddepcontrol.launch_dependents;");
#define PPROF(i)
    const int r = lane & 7, mi = lane >> 3;
    const uint32_t memrd = opaque(sm + C_MEM + lane * 16);
    if (wg < 2) {
        {
            uint32_t xv[3][10];
            const int row = blk * 8 + warp, nq = row < S_TOK - 1536 ? 3 : 2;
#pragma unroll
            for (int i = 0; i < 15; i++) {
                const uint2 v = __ldcs((const uint2*)(ar.x + (row + (i < 10 || nq == 3 ? i / 5 * 768 : 0)) * DM + lane * 4 + i % 5 * 128));
                xv[i / 5][i % 5 * 2] = v.x; xv[i / 5][i % 5 * 2 + 1] = v.y;
            }
            if (tid == 32) {
#pragma unroll 1
                for (int c = 0; c < 14; c++) if (c != 12) mbar_init(sm + C_BAR + 8 * c, c == 2 ? 5 : c == 3 ? 6 : 1);
                asm volatile("fence.mbarrier_init.release.cluster;" ::: "memory");
                mbar_expect(sm + CB_SC, 2560); mbar_expect(sm + CB_OX, 2048);
            }
            if (warp == 2) {
                const uint32_t f = blk >= 28 ? ~0u : 0u;
                ((uint4*)g_acc)[blk * 32 + lane] = make_uint4(0, 0, 0, 0);
                if (blk < 76) (blk < 12 ? (uint4*)g_stamp + blk * 32 : blk < 28 ? (uint4*)g_key + (blk - 12) * 32 : (uint4*)g_gu + (blk - 28) * 32)[lane] = make_uint4(f, f, f, f);
            }
            __syncwarp();
            asm volatile("barrier.cluster.arrive.relaxed.aligned;" ::: "memory");
            PPROF(8);
#pragma unroll 1
            for (int q = 0; q < 3; q++) {
                uint32_t nv[10];
                ln_norm(xv[0], nv);
#pragma unroll
                for (int i = 0; i < 10; i++) { xv[0][i] = xv[1][i]; xv[1][i] = xv[2][i]; xv[2][i] = nv[i]; }
            }
            PPROF(9);
            if (warp < 5) {
                uint4 u;
                for (int n = 0;; n++) {
                    asm volatile("ld.relaxed.gpu.global.v4.u32 {%0,%1,%2,%3}, [%4];" : "=r"(u.x), "=r"(u.y), "=r"(u.z), "=r"(u.w) : "l"(g_flags.mod1 + tid * 4) : "memory");
                    if (__all_sync(0xffffffffu, u.x && u.y && u.z && u.w)) break;
                    cut(n, 1 << 22);
                }
                asm volatile("st.shared.v4.u32 [%0], {%1,%2,%3,%4};" :: "r"(sm + C_KX + tid * 16), "r"(~u.x), "r"(~u.y), "r"(~u.z), "r"(~u.w) : "memory");
            }
            bar_sync(8, 256);
            PPROF(2);
            uint32_t m = 0;
#pragma unroll
            for (int i = 0; i < 5; i++) {
                uint32_t t[2], u[2];
                lds64(t, sm + C_KX + lane * 8 + i * 256); lds64(u, sm + C_KX + 1280 + lane * 8 + i * 256);
                u[0] = add2(u[0], 0x3f803f80u); u[1] = add2(u[1], 0x3f803f80u);
                m = amax2(amax2(amax2(amax2(m, t[0]), u[0]), t[1]), u[1]);
#pragma unroll
                for (int q = 0; q < 3; q++)
                    if (q < nq) *(uint2*)(g_h + (row + q * 768) * DM + lane * 4 + i * 128) = make_uint2(add2(mul2(xv[q][2 * i], u[0]), t[0]), add2(mul2(xv[q][2 * i + 1], u[1]), t[1]));
            }
            asm volatile("st.shared.u32 [%0], %1;" :: "r"(sm + C_LAG), "r"((amax_warp(m) >> 7) + 1) : "memory");
            bar_sync(8, 256);
            if (tid == 0) flag_add(&g_flags.h);
            __syncwarp();
            bar_arrive(2, 288);
            PPROF(3);
            asm volatile("barrier.cluster.wait.aligned;" ::: "memory");
        }
        asm volatile("setmaxnreg.inc.sync.aligned.u32 %0;" :: "n"(REG_P));
        uint32_t wa[40][4];
        mbar_wait(sm + CB_W, 0);
#pragma unroll
        for (int ks = 0; ks < 40; ks++)
            ldsm4t(wa[ks], sm + ((wg == 0) == (ks < 20) ? C_WV : C_WO) + ((mi >> 1) * 8 + r) * 128 + (((2 * w + (mi & 1)) ^ r) << 4) + (ks % 20 / 4 * 8 + 4 * wg + (ks & 3)) * 2048);
        PPROF(5);
        bar_arrive(1, 288);
        const uint32_t qst = opaque(sm + (wg == 0 ? C_QM : C_KM) + (2 * w + (mi & 1)) * 128 + r * 16);
        const uint32_t vrd = opaque(sm + C_WV + ((mi >> 1) * 8 + r) * 128 + (((2 * w + (mi & 1)) ^ r) << 4) + 4 * wg * 2048);
        const uint32_t mrd = opaque(memrd + wg * 1024);
        float acc[16];
        auto fb = [&](int n) { return mrd + (n >> 1) * 2048 + (n & 1) * 512; };
        auto fa = [&](int k) { return vrd + (k >> 2) * 16384 + (k & 3) * 2048; };
        auto qk_out = [&](int n) {
            uint8_t* rec = g_att + (n * NH + head) * AT_REC;
            w_bulk_s2g(rec + j * 8192, sm + C_QX, 8192); w_bulk_s2g(rec + AT_KM + j * 1024, sm + C_KM, 1024);
            BULK_COMMIT();
        };
        for (int s = -1;; s++) {
          if (s >= 0) {
            x_part(acc, wa, sm, s, wg, w, opaque(mrd) >> 4 & 31, s + ar.D2);
            if (s == 0) mbar_wait(sm + CB_W2, 0);
            uint32_t b[3][4], a[4][4];
#pragma unroll
            for (int i = 0; i < 4; i++) ldsm4t(a[i], fa(4 + i));
            cut(s + ar.D2, 0);
            bar_sync(1, 384);
            if (warp == 0) { PROF(0); PROFG(24); }
            float dv[4] = {0, 0, 0, 0};
            const uint32_t xb = mrd - wg * 1024 - (C_MEM - C_VP) + w * 512;
            {
                float d[2][4] = {{0, 0, 0, 0}, {0, 0, 0, 0}}, g[2][4] = {{0, 0, 0, 0}, {0, 0, 0, 0}};
                ldsm4t(b[0], fb(0)); pin0(mrd); ldsm4t(b[1], fb(1)); pin0(mrd);
#pragma unroll
                for (int n = 0; n < 10; n++) {
                    const int c1 = n >= 10 - NCH;
                    if (n < 8) ldsm4t(b[(n + 2) % 3], fb(n + 2));
#pragma unroll
                    for (int e = 0; e < 2; e++) {
                        mma16q(g[e & c1], wa[20 + 2 * n + e], b[n % 3][2 * e], b[n % 3][2 * e + 1]); mma16q(d[e & c1], wa[2 * n + e], b[n % 3][2 * e], b[n % 3][2 * e + 1]);
                        if (n >= 2 && n < 10 - VT) mma16q(dv, a[(2 * n + e) & 3], b[n % 3][2 * e], b[n % 3][2 * e + 1]);
                        if (n >= 2 && n < 8) ldsm4t(a[(2 * n + e) & 3], fa(2 * n + 4 + e));
                    }
                    if (QCUT >> n & 1) cut(s + ar.D2, 1 + n);
                }
                const float un = __uint_as_float(lds32(sm + C_UN));
                sts128f(xb - 4096 + wg * 2048, g[0][0] + g[1][0], g[0][1] + g[1][1], g[0][2] + g[1][2], g[0][3] + g[1][3]);
#pragma unroll
                for (int k = 20 - 2 * VT; k < 20; k++) mma16q(dv, a[k & 3], b[k / 2 % 3][2 * (k & 1)], b[k / 2 % 3][2 * (k & 1) + 1]);
                bar_sync(8, 256);
                const float4 z = lds128f(xb - 4096 + (wg ^ 1) * 2048);
                sts128f(xb + wg * 2048, dv[0], dv[1], dv[2], dv[3]);
                stsm2t(qst, pack2((d[0][0] + d[1][0] + z.x) * un, (d[0][1] + d[1][1] + z.y) * un), pack2((d[0][2] + d[1][2] + z.z) * un, (d[0][3] + d[1][3] + z.w) * un));
            }
            bar_arrive(2, 384);
            if (w == 0) PROF(1 + wg);
            if (s + 1 == NSEG) break;
          }
          if (warp == 3 && s >= 0)
              asm volatile(ELECTED("st.relaxed.gpu.global.u32 [%0], %1;") :: "l"(g_stamp + (s & 3) * 384 + (blk >> 3) * 32 + (blk & 7)), "r"((gtime() & ~31u) | ((s >> 2) + 1)) : "memory");
          mbar_wait(sm + CB_XF, (s + 1) & 1);
          if (s >= 0) bar_sync(7, 384);
          WG_FENCE();
#pragma unroll
          for (int i = 0; i < 16; i++) acc[i] = 0.f;
#pragma unroll
          for (int i = 1; i <= XA; i++) x_chunk(acc, wa, x_base(wg, s + ar.D2, 20), 20, i, i == 1);
          WG_COMMIT();
          WG_WAIT(0);
          PROXY_FENCE();
          if (s >= 0) {
            if (warp == 5) bar_sync(8, 256); else bar_arrive(8, 256);
            if (warp == 0) {
                PROF(7);
                if (elect()) x_rest(mp, sm, s + 1);
            } else {
                if (wg == 1) {
                    if (w == 1) {
                        qk_out(s);
                    }
                    if (w == 3 && s > 0) seg_done(s - 1, head);
                    if (w == 2 && blk < 10 && s + 3 < NSEG)
                        asm volatile(ELECTED("cp.async.bulk.prefetch.L2.global [%0], 4096;") :: "l"((const uint8_t*)g_h + (s + 3) * (SEG * DM * 2) + blk * 4096) : "memory");
                } else if (w == 3) {
                    if (SPOLL) wait_until(clock() + SPOLL);
                    const uint32_t l = opaque(mrd) >> 4 & 31, tag = (s >> 2) + 1, now = gtime();
                    const uint32_t* sp = g_stamp + (s & 3) * 384 + (l >> 3) * 32 + (l & 7);
                    uint32_t t[3];
                    for (int n = 0;; n++) {
#pragma unroll
                        for (int i = 0; i < 3; i++) t[i] = ld_rlx(sp + i * 128);
                        if (!__any_sync(0xffffffffu, ((t[0] ^ tag) | (t[1] ^ tag) | (t[2] ^ tag)) & 31) || n > SPIN_LIMIT) break;
                    }
                    int all = -(1 << 30), own = all;
#pragma unroll
                    for (int i = 0; i < 3; i++) { const int d = t[i] - now; all = max(all, d); if ((i * 32 + l) / 3 == head) own = d; }
                    const int lag = min(__reduce_max_sync(0xffffffffu, all) - __reduce_max_sync(0xffffffffu, own), 8000);
                    PROFV(15, lag);
                    asm volatile("st.shared.u32 [%0], %1;" :: "r"(sm + C_LAG), "r"(D1 + ((lag * DG) >> 4)) : "memory");
                    bar_arrive(6, 160);
                } else if (w == 2) {
                    if ((s & 3) == 3) w_flag_wait(&g_flags.v[((s + 1) >> 2) * 32 + head], 2);
                    if (elect()) { mbar_expect(sm + CB_VX, 4096); bulk_g2s(sm + C_VX, g_att + ((s + 1) * NH + head) * AT_REC + AT_V + j * 4096, 4096, sm + CB_VX); }
                    if ((s & 3) == 1 && s + 3 < NSEG) asm volatile("prefetch.global.L2 [%0];" :: "l"(&g_flags.v[((s + 3) >> 2) * 32]));
                    if (s + 2 < NSEG && ((s & 3) != 2 || __all_sync(0xffffffffu, ld_rlx(&g_flags.v[((s + 2) >> 2) * 32 + head]) >= 2)))
                        asm volatile("prefetch.global.L2 [%0];" :: "l"(g_att + ((s + 2) * NH + head) * AT_REC + AT_V + j * 4096 + (opaque(mrd) << 3 & 0xf80)));
                }
            }
          }
        }
        PROXY_FENCE();
        bar_sync(8, 256);
        if (warp == 5) { qk_out(NSEG - 1); BULK_WAIT(); }
        bar_arrive(7, 384);
        const int t2 = (opaque(mrd) >> 4 & 31) + warp * 32;
        last_blocks(mp, ar, sm, blk, t2);
        mod_tail(ar, sm + E_B, sm + EB_REL, blk, t2);
    } else {
        asm volatile("setmaxnreg.dec.sync.aligned.u32 %0;" :: "n"(REG_L));
        asm volatile("barrier.cluster.arrive.relaxed.aligned;" ::: "memory");
        if (blk < 80) {
            ModSlice<128> ms;
            ms.load(ar.wmod, ar.c, blk * 16, tid - 256); ms.partial(sm + C_QM, tid - 256);
            bar_sync(3, 128);
            if (w == 0) {
                const uint32_t v = ModSlice<128>::total(sm + C_QM, lane);
                asm volatile("st.relaxed.gpu.global.u32 [%0], %1;" :: "l"(g_flags.mod1 + blk * 8 + (lane & 7)), "r"(~v) : "memory");
            }
        }
        uint32_t m0[5][4], mm = 0;
#pragma unroll
        for (int i = 0; i < 20; i++) {
            const unsigned short* p = (const unsigned short*)ar.mem0 + (i & 3) * 2 * DM + (i >> 2) * 128 + tid - 256;
            m0[i >> 2][i & 3] = __ldg(p) | (uint32_t)__ldg(p + DM) << 16;
        }
        {
            asm volatile("barrier.cluster.wait.aligned;" ::: "memory");
            if (w == 3) {
                w_flag_wait(&g_flags.h, 96);
                if (elect()) { x_fill(mp, sm, 0, j); x_rest(mp, sm, 0); }
                __syncwarp();
            }
            if (w == 1) {
                const uint64_t ef = policy_stream();
#pragma unroll 1
                for (int c = 0; c < 2 * WP + 2; c++) {
                    const uint32_t bar = sm + EB_B + 8 * (c & 1);
                    if (c == WPOS) bar_sync(2, 288);
                    if (c >= 2) mbar_wait(bar, (c / 2 - 1) & 1);
                    if (elect()) {
                        if (c < 2 * WP) { mbar_expect(bar, 81920 / WP); tma2d_ef(sm + C_WV + c * (81920 / WP), c < WP ? &mp.wq : &mp.wk, col0, c % WP * (640 / WP), bar, ef); }
                        if (c >= WOPF && c < WOPF + 3) asm volatile("cp.async.bulk.prefetch.tensor.3d.L2.global [%0, {0, %1, %2}];" :: "l"((uint64_t)&mp.wo), "r"(head * DH + (c - WOPF) * 64), "r"(7 * j) : "memory");
                    }
                    __syncwarp();
                }
                if (elect()) mbar_arrive(sm + CB_W);
                bar_sync(1, 288);
                if (elect()) {
                    mbar_expect(sm + CB_W2, 81920); mbar_expect(sm + CB_W3, 3 * WO_BLK);
#pragma unroll 1
                    for (int c = 0; c < 4; c++) tma2d(sm + C_WV + c * 20480, &mp.wv, col0, c * 160, sm + CB_W2);
#pragma unroll 1
                    for (int c = 0; c < 3; c++) tma3d(sm + C_WO + c * WO_BLK, &mp.wo, head * DH + (j + c) % 3 * 64, 7 * j, sm + CB_W3);
                }
                __syncwarp();
                w_flag_wait(&g_flags.v[head], 2);
                if (elect()) { mbar_expect(sm + CB_VX, 4096); bulk_g2s(sm + C_VX, g_att + head * AT_REC + AT_V + j * 4096, 4096, sm + CB_VX); }
            } else {
                uint32_t mw = 0;
#pragma unroll 1
                for (int c = 0; c < 2; c++) {
                    mbar_wait(sm + (c ? CB_W3 : CB_W2), 0);
                    uint32_t m = 0;
                    const uint32_t end = sm + (c ? C_XR : C_WO);
#pragma unroll 1
                    for (uint32_t a = sm + c * C_WO + (w - (w > 0)) * 4096 + lane * 16; a < end; a += 3 * 4096) {
                        float4 z[8];
#pragma unroll
                        for (int i = 0; i < 8; i++) z[i] = lds128f(a + i * 512);
#pragma unroll
                        for (int i = 0; i < 8; i++) m = amax2(amax2(amax2(amax2(m, __float_as_uint(z[i].x)), __float_as_uint(z[i].y)), __float_as_uint(z[i].z)), __float_as_uint(z[i].w));
                    }
                    mw |= amax_warp(m) << (16 * c);
                }
                asm volatile("st.shared.u32 [%0], %1;" :: "r"(sm + C_KM + w * 4), "r"(mw) : "memory");
                bar_sync(3, 96);
                if (w == 0) asm volatile("st.relaxed.gpu.global.u32 [%0], %1;" :: "l"(g_flags.wmax + blk), "r"(amax2(amax2(mw, lds32(sm + C_KM + 8)), lds32(sm + C_KM + 12)) | 0x8000) : "memory");
            }
        }
        bar_sync(9, 384);
#pragma unroll
        for (int i = 0; i < 5; i++) {
            asm volatile("st.shared.v4.u32 [%0], {%1,%2,%3,%4};" :: "r"(sm + C_MEM + (tid - 256 + i * 128) * 16), "r"(m0[i][0]), "r"(m0[i][1]), "r"(m0[i][2]), "r"(m0[i][3]) : "memory");
            mm = amax2(amax2(amax2(amax2(mm, m0[i][0]), m0[i][1]), m0[i][2]), m0[i][3]);
        }
        asm volatile("st.shared.u32 [%0], %1; st.shared.u32 [%2], 0x3f800000;" :: "r"(sm + C_MX + w * 4), "r"(amax_warp(mm)), "r"(sm + C_UN) : "memory");
        int ew = __shfl_sync(0xffffffffu, lds32(sm + C_LAG), 0), es = 0;
        const uint32_t rb1 = (uint32_t)((j + 1) % 3 - j) << 24, rb2 = (uint32_t)((j + 2) % 3 - j) << 24;
        const float scale = 0.07216878364870322f;
        uint32_t va[8][4], mr = memrd;
#pragma unroll
        for (int i = 0; i < 8; i++) ldsm4t(va[i], sm + C_WV + ((mi >> 1) * 8 + r) * 128 + (((2 * w + (mi & 1)) ^ r) << 4) + i * 2048);
        bar_sync(1, 384);
        for (int s = 0; s < NSEG; s++) {
            const float un = __uint_as_float((127 - es) << 23);
            if (w == 0) {
                mbar_wait(sm + CB_XD, s & 1);
                if (s + 1 < NSEG) { if (elect()) x_fill(mp, sm, s + 1, j); }
                else { if (BPOS != 2) wo_half(mp, sm, blk, 0); if (BPOS != 0) wo_half(mp, sm, blk, 1); }
            } else if (w == 1) { BULK_WAIT(); if (s + 1 == NSEG) seg_done(s - 1, head); }
            const uint32_t l0 = mr >> 4 & 31, r0 = l0 & 7, m0 = l0 >> 3;
            float vd[4];
            {
                uint32_t c[4][4];
#pragma unroll
                for (int i = 0; i < 4; i++) ldsm4t(c[i], mr + i * 512);
                float d[2][4] = {{0, 0, 0, 0}, {0, 0, 0, 0}};
#pragma unroll
                for (int i = 0; i < 8; i++) mma16q(d[i & 1], va[i], c[i >> 1][2 * (i & 1)], c[i >> 1][2 * (i & 1) + 1]);
#pragma unroll
                for (int i = 0; i < 4; i++) vd[i] = d[0][i] + d[1][i];
            }
            uint32_t zr = 0;
            if (w == 2)
                asm volatile("atom.relaxed.gpu.global.exch.b32 %0, [%1], 0;" : "=r"(zr)
                    : "l"(g_acc + ((s & 2) ^ 2) * (ACC_PAIR / 2) + (s & 1) * 512 + (blk >> 2) * 1024 + (blk & 3) * 128 + l0 * 4) : "memory");
            __syncwarp();
            uint32_t kb[4][4];
            {
                const uint32_t k7 = r0 ^ (m0 << 2 & 4), kxrd = sm + C_KX + (16 * (w & 1) + 8 * (m0 & 1) + k7) * 128 + (((m0 >> 1) ^ k7) << 4);
#pragma unroll
                for (int i = 0; i < 4; i++) ldsm4(kb[i], kxrd ^ (i << 5));
            }
            const uint32_t qrd = sm + C_QM + (w == 1 ? (m0 & 1) * 2 + (m0 >> 1) : m0) * 128 + r0 * 16;
            const uint32_t scdst = sm + C_SC + j * 1280 + (w == 1 ? 1024 + l0 * 8 : (w & 1) * 512 + (l0 & 2) * 128 + (l0 >> 2) * 32 + (l0 & 1) * 16);
            const uint32_t scrd = sm + C_SC + (l0 >> 4) * 256 + (l0 & 3) * 32 + (l0 >> 2 & 3) * 8;
            const uint32_t v7 = (4 * (m0 & 1) + (r0 >> 1)) ^ (r0 << 2 & 4), vxrd = sm + C_VX + (16 * (m0 >> 1) + 8 * (r0 & 1) + v7) * 128 + (((2 * w) ^ v7) << 4);
            if (s == 0) {
                uint32_t t[3];
                for (int n = 0;; n++) {
#pragma unroll
                    for (int i = 0; i < 3; i++) t[i] = ld_rlx(g_flags.wmax + l0 + 32 * i);
                    if (__all_sync(0xffffffffu, t[0] && t[1] && t[2])) break;
                    cut(n, 1 << 22);
                }
                const uint32_t m = amax2(amax2(amax2(0, t[0]), t[1]), t[2]);
                const int e = 371 - (int)(__reduce_max_sync(0xffffffffu, m & 0xffffu) >> 7) - (int)(__reduce_max_sync(0xffffffffu, m >> 16) >> 7);
                ew = e << 16 | (min(e - ew, 100) & 0xffff);
            }
            mbar_wait(sm + CB_VX, s & 1);
            uint32_t vb[2][4];
            ldsm4t(vb[0], vxrd); ldsm4t(vb[1], vxrd ^ 16);
            const uint32_t word = sm + C_WO + (m0 & 1) * 4096 + ((m0 >> 1) * 8 + r0) * 64 + ((w ^ (r0 >> 1)) << 4);
            const uint32_t word6 = word + 6 * 4096 - (m0 & 1) * 3072;
            const uint32_t oxrd = sm + C_OX + l0 * 8;
            const uint32_t ord = oxrd + w * 256;
            const uint32_t vp = mr - (C_MEM - C_VP) + w * 512, vmst = mr + (C_VM - C_MEM) + w * 256;
            pin(mr, scdst + rb1, sm + CB_SC + rb1, scdst + rb2, sm + CB_SC + rb2); pin(mr, qrd, scdst, scrd, vp); pin(mr, word, word6, oxrd, ord);
            pin(mr, __float_as_uint(vd[0]), __float_as_uint(vd[1]), __float_as_uint(vd[2]), __float_as_uint(vd[3]));
            bar_sync(2, 384);
            const bool odd = mr & 16;
            float4 y0, y1, mx4;
            {
                uint32_t qa[2][4];
                ldsm4(qa[0], qrd); ldsm4(qa[1], qrd + 512);
                float sc[2][4] = {{0, 0, 0, 0}, {0, 0, 0, 0}};
                if (w == 1) {
                    ldsm4(kb[0], mr + (C_KM - C_MEM)); ldsm4(kb[1], mr + (C_KM - C_MEM) + 512);
                    pin0(mr); y0 = lds128f(vp); y1 = lds128f(vp + 2048); mx4 = lds128f(sm + C_MX);
#pragma unroll
                    for (int k = 0; k < 4; k++) mma16q(sc[k & 1], qa[k >> 1], kb[k >> 1][2 * (k & 1)], kb[k >> 1][2 * (k & 1) + 1]);
                    const uint32_t a0 = __float_as_uint(sc[0][0] + sc[1][2]), a1 = __float_as_uint(sc[0][1] + sc[1][3]);
                    send8(scdst + rb1, sm + CB_SC + rb1, a0, a1); send8(scdst + rb2, sm + CB_SC + rb2, a0, a1);
                    asm volatile("st.shared.v2.u32 [%0], {%1,%2};" :: "r"(scdst), "r"(a0), "r"(a1) : "memory");
                } else {
                    pin0(mr); y0 = lds128f(vp); y1 = lds128f(vp + 2048); mx4 = lds128f(sm + C_MX);
                    if (w) {
#pragma unroll
                        for (int k = 0; k < 4; k++) mma16q(sc[k & 1], kb[k], qa[k >> 1][2 * (k & 1)], qa[k >> 1][2 * (k & 1) + 1]);
                        const float a0 = sc[0][0] + sc[1][0], a1 = sc[0][2] + sc[1][2], a2 = sc[0][1] + sc[1][1], a3 = sc[0][3] + sc[1][3];
                        send16(scdst + rb1, sm + CB_SC + rb1, a0, a1, a2, a3); send16(scdst + rb2, sm + CB_SC + rb2, a0, a1, a2, a3);
                        sts128f(scdst, a0, a1, a2, a3);
                    }
                }
            }
            bar_arrive(7, 384);
            if (elect()) mbar_arrive(sm + CB_SC);
            {
                const float4 z = mx4;
                const int em = (int)(max(max(__float_as_uint(z.x), __float_as_uint(z.y)), max(__float_as_uint(z.z), __float_as_uint(z.w))) >> 7) - es;
                es = __shfl_sync(0xffffffffu, max(min((ew >> 16) - em, (int)(short)ew), -120), 0);
            }
            if (w == 0) PROF(4);
            const uint32_t vm0 = pack2((vd[0] + y0.x + y1.x) * un, (vd[1] + y0.y + y1.y) * un), vm1 = pack2((vd[2] + y0.z + y1.z) * un, (vd[3] + y0.w + y1.w) * un);
            stsm2t(vmst, vm0, vm1);
            if (s + 1 == NSEG) {
                mbar_wait(sm + CB_SC, s & 1);
                PROXY_FENCE();
                bar_sync(3, 128);
                if (w == 1) {
                    w_bulk_s2g(g_att + (s * NH + head) * AT_REC + AT_VM + j * 1024, sm + C_VM, 1024);
                    BULK_COMMIT();
                    if (BPOS == 0) wo_half(mp, sm, blk, 1);
                    BULK_WAIT();
                }
                __syncwarp();
                break;
            }
            cut(s + ar.D2, 0);
            mbar_wait(sm + CB_SC, s & 1);
            if (w == 0) PROF(8);
            float sv[10];
            {
                float2 z[5][3];
#pragma unroll
                for (int u = 0; u < 5; u++)
#pragma unroll
                    for (int p = 0; p < 3; p++) z[u][p] = lds64f((u < 4 ? scrd + (u >> 1) * 512 + (u & 1) * 128 : oxrd + (C_SC - C_OX) + 1024) + p * 1280);
#pragma unroll
                for (int u = 0; u < 5; u++) { sv[2 * u] = (z[u][0].x + z[u][1].x) + z[u][2].x; sv[2 * u + 1] = (z[u][0].y + z[u][1].y) + z[u][2].y; }
            }
            float mx = fmaxf(fmaxf(fmaxf(sv[0], sv[1]), fmaxf(sv[2], sv[3])), fmaxf(fmaxf(fmaxf(sv[4], sv[5]), fmaxf(sv[6], sv[7])), fmaxf(sv[8], sv[9])));
            uint32_t a[NRING][4];
            auto frag = [&](int i) { const int p = i / 7, u = i % 7, o = (p >> 1) * WO_BLK + (p & 1) * 2048;
                                     return u == 3 ? word6 + o : word + o + (u > 3 ? 1024 + (u - 4) * 8192 : u * 8192); };
            mx = fmaxf(fmaxf(mx, __shfl_xor_sync(0xffffffffu, mx, 1)), fmaxf(__shfl_xor_sync(0xffffffffu, mx, 2), __shfl_xor_sync(0xffffffffu, mx, 3)));
            pin(mr, __float_as_uint(mx), 0, 0, 0);
            {
#pragma unroll
                for (int i = 0; i < NPRE; i++) ldsm4t(a[i], frag(i));
                pin0(mr);
                const float sl2e = scale * 1.4426950408889634f, mxl = mx * sl2e;
#pragma unroll
                for (int i = 9; i >= 0; i--) asm volatile("ex2.approx.ftz.f32 %0, %1;" : "=f"(sv[i]) : "f"(fmaf(sv[i], sl2e, -mxl)));
                const uint32_t pq[4] = {pack2(sv[0], sv[1]), pack2(sv[4], sv[5]), pack2(sv[2], sv[3]), pack2(sv[6], sv[7])}, pm = pack2(sv[8], sv[9]);
                if (w == 0) PROF(6);
                float o[2][4] = {{0, 0, 0, 0}, {0, 0, 0, 0}}, o2[2][4] = {{0, 0, 0, 0}, {0, 0, 0, 0}}, sx[4] = {0, 0, 0, 0};
                mma8(sx, pm, 0, 0x3f803f80u); mma8(o[0], pm, 0, vm0); mma8(o[1], pm, 0, vm1);
                mma16q(sx, pq, 0x3f803f80u, 0x3f803f80u);
#pragma unroll
                for (int u = 0; u < 2; u++) { mma16q(o[u], pq, vb[u][0], vb[u][1]); mma16q(o2[u], pq, vb[u][2], vb[u][3]); }
                float inv; asm("rcp.approx.ftz.f32 %0, %1;" : "=f"(inv) : "f"((sx[0] + sx[2]) * __uint_as_float((127 - es) << 23)));
                const uint32_t f0 = pack2((o[0][0] + o2[0][2]) * inv, (o[0][1] + o2[0][3]) * inv), f1 = pack2((o[1][0] + o2[1][2]) * inv, (o[1][1] + o2[1][3]) * inv);
                send8(ord + 2048 + rb1, sm + CB_OX + rb1, f0, f1); send8(ord + 1024 + rb2, sm + CB_OX + rb2, f0, f1);
                asm volatile("st.shared.v2.u32 [%0], {%1,%2};" :: "r"(ord), "r"(f0), "r"(f1) : "memory");
            }
            if (w == 0) PROF(10);
#pragma unroll
            for (int i = NPRE; i < NRING; i++) ldsm4t(a[i], frag(i));
            bar_sync(3, 128);
            float e[5][4];
#pragma unroll
            for (int q = 0; q < 5; q++) e[q][0] = e[q][1] = e[q][2] = e[q][3] = 0.f;
            constexpr int LAG = 2;
            uint8_t* pdst = g_acc + ((s & 2) * (ACC_PAIR / 2) + (s & 1) * 512 + w * 2048 + j * 8192 - C_MEM - sm + mr);
#pragma unroll
            for (int h = 0; h < 3; h++) {
                uint32_t ob[4][2];
                if (h == 1) {
#pragma unroll
                    for (int i = 14 - LAG; i < 14; i++) ldsm4t(a[i % NRING], frag(i + NRING));
                    pin(mr, zr, (uint32_t)(uint64_t)pdst, (uint32_t)((uint64_t)pdst >> 32), 0);
                    mbar_wait(sm + CB_OX, s & 1);
                    if (w == 0) PROF(9);
                }
#pragma unroll
                for (int k = 0; k < 4; k++) lds64(ob[k], oxrd + h * 1024 + k * 256);
#pragma unroll
                for (int i = 14 * h; i < 14 * h + 14; i++) {
                    const int u = i % 7, k = 2 * (i / 7 & 1);
                    if (u == 3) { mma16q(e[3], a[i % NRING], ob[k][0], ob[k][1]); mma16q(e[4], a[i % NRING], ob[k + 1][0], ob[k + 1][1]); }
                    else mma16q(e[u & 3], a[i % NRING], ob[k + (u >> 2)][0], ob[k + (u >> 2)][1]);
                    if (i == B5AT) { pin(mr, a[i % NRING][0], a[i % NRING][1], a[i % NRING][2], a[i % NRING][3]); bar_arrive(5, 384); }
                    if (i >= LAG && !(i >= 14 && i < 14 + LAG) && i - LAG + NRING < 42) ldsm4t(a[(i - LAG) % NRING], frag(i - LAG + NRING));
                }
            }
            {
                const uint32_t w6 = pack2h(e[3][0] + e[4][2], e[3][1] + e[4][3]), one = 0x3c003c00u;
                asm volatile("red.relaxed.gpu.global.add.noftz.v4.f16x2 [%0], {%1,%2,%3,%4};"
                    :: "l"(pdst), "r"(pack2h(e[0][0], e[0][1])), "r"(pack2h(e[0][2], e[0][3])), "r"(pack2h(e[1][0], e[1][1])), "r"(odd ? w6 : one) : "memory");
                asm volatile("red.relaxed.gpu.global.add.noftz.v4.f16x2 [%0], {%1,%2,%3,%4};"
                    :: "l"(pdst + 1024), "r"(pack2h(e[1][2], e[1][3])), "r"(pack2h(e[2][0], e[2][1])), "r"(pack2h(e[2][2], e[2][3])), "r"(odd ? one : w6) : "memory");
            }
            const uint32_t tw = clock();
            if (w == 0) { PROF(14); PROFG(25); }
            PROXY_FENCE();
            bar_sync(6, 160);
            mr = opaque(mr);
            const uint32_t ln = mr >> 4 & 31, due = tw + lds32(sm + C_LAG);
            const uint32_t vr = sm + C_WV + ((ln >> 4) * 8 + (ln & 7)) * 128 + (((2 * w + (ln >> 3 & 1)) ^ (ln & 7)) << 4);
            const uint32_t ms0 = sm + C_MEM + w * 128 + (ln & 7) * 16 + (ln >> 3) * 512, ms1 = ms0 + (ln < 24 ? 2048 : 1536);
            if (BPOS == 2 && w == 0 && s + 2 == NSEG) wo_half(mp, sm, blk, 0);
            if (w == 2) { w_expect(sm + CB_SC, 2560); w_expect(sm + CB_OX, 2048); asm volatile("st.shared.u32 [%0], %1;" :: "r"(sm + C_UN), "r"((127 - es) << 23) : "memory"); }
            if (w == 1) { w_bulk_s2g(g_att + (s * NH + head) * AT_REC + AT_VM + j * 1024, sm + C_VM, 1024); BULK_COMMIT(); }
            const uint8_t* src = pdst - j * 8192;
            pin(mr, ms0, ms1, (uint32_t)(uint64_t)src, (uint32_t)((uint64_t)src >> 32));
            pin(mr, vr, due, 0, 0);
            cut(s + ar.D2, 1);
#pragma unroll
            for (int i = 0; i < 8; i++) ldsm4t(va[i], vr + i * 2048);
            wait_until(due);
            if (w == 0) { PROF(5); PROFG(26); }
            uint4 v[6];
            auto fetch = [&]() {
#pragma unroll
                for (int k = 0; k < 6; k++)
                    asm volatile("ld.relaxed.gpu.global.v4.u32 {%0,%1,%2,%3}, [%4];" : "=r"(v[k].x), "=r"(v[k].y), "=r"(v[k].z), "=r"(v[k].w) : "l"(src + (k >> 1) * 8192 + (k & 1) * 1024) : "memory");
            };
            fetch();
            PROFV(20 + w, 0);
            bar_sync(9, 384);
#pragma unroll 1
            for (int n = 0; __any_sync(0xffffffffu, ~((odd ? v[1].w & v[3].w & v[5].w : v[0].w & v[2].w & v[4].w)) & 0x50005000u); n++) {
                PROFV(20 + w, n + 1);
                cut(n, SPIN_LIMIT);
                fetch();
            }
            uint32_t cv[3][7];
#pragma unroll
            for (int k = 0; k < 3; k++) {
                const uint4 x = v[2 * k], y = v[2 * k + 1];
                const uint32_t u[7] = {x.x, x.y, x.z, y.x, y.y, y.z, k < 2 ? (odd ? x.w : y.w) : 0u};
#pragma unroll
                for (int i = 0; i < 7; i++) cv[k][i] = f16_to_bf16(u[i]);
                stsm4(ms0 + k * 3584, cv[k][0], cv[k][1], cv[k][2], cv[k][3]);
                if (k < 2) stsm4(ms1 + k * 3584, cv[k][4], cv[k][5], cv[k][6], cv[k][6]);
                else asm volatile("stmatrix.sync.aligned.m8n8.x2.shared.b16 [%0], {%1,%2};" :: "r"(ms1 + k * 3584), "r"(cv[k][4]), "r"(cv[k][5]) : "memory");
            }
            if (w == 0) PROF(16);
            bar_sync(1, 384);
            cut(s + ar.D2, 2);
            uint32_t mc = 0;
#pragma unroll
            for (int i = 0; i < 20; i++) mc = amax2(mc, cv[i / 7][i % 7]);
            asm volatile("st.shared.u32 [%0], %1;" :: "r"(sm + C_MX + w * 4), "r"(amax_warp(mc)) : "memory");
        }
        if (w >= 2) end_loads(mp, ar, sm, blk, w - 2);
        else if (w == 1) { bar_sync(5, 384); seg_done(NSEG - 1, head); }
        else bar_arrive(5, 384);
        if (w == 0) {
            const int l = mr >> 4 & 31;
            if (blk < 14) {
                uint4 k = __ldcg((const uint4*)g_key + blk * 32 + l);
#pragma unroll 1
                for (int it = 0; it < 3; it++) {
                    const uint32_t m = __reduce_max_sync(0xffffffffu, max(max(k.x, k.y), max(k.z, k.w)));
                    if (k.x == m) k.x = 0; if (k.y == m) k.y = 0; if (k.z == m) k.z = 0; if (k.w == m) k.w = 0;
                    if (m && l < 20) asm volatile("prefetch.global.L2 [%0];" :: "l"((l < 10 ? g_h2 : g_x1) + (~m & (S_TOK - 1)) * DM + l % 10 * 64));
                }
            }
            mbar_wait(sm + EB_REL, 0);
            flags_release(l);
        }
    }
}

struct SideMaps { CUtensorMap h, wv, ost, o, wo, slab3, slab2, lnp[3]; };
constexpr int SD_ST = 43008, SD_NST = 4, SD_EPI = SD_NST * SD_ST, SD_PAR = SD_EPI + 2 * 24576, SD_BAR = SD_PAR + 6400, SD_SMEM = SD_BAR + 256;
#define VLEAD 16
#define EARLY15 0
#define N_LIGHT 6
#define B_HELP 13
#define AUNR_ 2
constexpr int AUNR = AUNR_;
#define GEMV 1
#define KSO 6
#define KSA 3
#define B_8 10
#define B_16 13
__device__ __forceinline__ int o_shift(int b) { return b >= B_16 ? 4 : b >= B_8 ? 3 : 2; }
__device__ __forceinline__ int o_split(int b) { return 1 << o_shift(b); }
__device__ __forceinline__ uint32_t o_done(int b) { return b >= B_LATE ? 160 : 4 << o_shift(b); }
__device__ __forceinline__ int next_item(int lane) {
    const int b0 = lane & 15, hi = lane >> 4;
    for (int n = 0;; n++) {
        const uint32_t w0 = ld_rlx(g_flags.qk + lane), w1 = ld_rlx(g_flags.at + lane), w2 = ld_rlx(&g_flags.c[0][0] + lane), w3 = ld_rlx(&g_flags.c[2][0] + lane), w4 = ld_rlx(&g_flags.seg[0]);
        const uint32_t o01 = __ballot_sync(0xffffffffu, lane && w2 < 32), o23 = __ballot_sync(0xffffffffu, b0 < (hi ? 14 : B_LATE) && w3 < 2u * o_split(b0));
        const uint32_t ra = __ballot_sync(0xffffffffu, w0 >= (hi ? 64u : 96u)), rb = __ballot_sync(0xffffffffu, w1 >= (hi ? o_done(b0) : 256u));
        const int bv = __ffs(o01 | 0x10000) - 1, ba = __ffs(o01 >> 16 | 0x10000) - 1, bo = __ffs(o23 | 0x10000) - 1, bl = __ffs(o23 >> 16 | 0x10000) - 1;
        if (bl == 16 && ba == 16) return -1;
        const int bc = __ffs(~ra | 0x10000) - 1;
        const bool last = ba == 15 && (w4 >= 3 || (EARLY15 && bc == 15));
        const bool r1 = (ra & ra >> 16) >> ba & 1, r2 = (rb & 0xffff) >> bo & 1, r3 = rb >> 16 >> bl & 1;
        const int kind = ba == 16 ? (bo < 16 ? 2 : 3) : last ? 1 :
                         blockIdx.x < N_LIGHT ? (r1 ? 1 : r3 ? 3 : bv < 16 ? 0 : -1) :
                         bv < 16 && (bv <= bc + VLEAD || !r2) ? 0 : r1 && ba >= B_HELP ? 1 : r2 ? 2 : r1 ? 1 : r3 ? 3 : bo < ba ? 2 : -1;
        if (kind < 0) { if (n > (1 << 20)) __trap(); __nanosleep(300); continue; }
        const int b = kind == 3 ? bl : kind == 2 ? bo : kind == 1 ? ba : bv;
        uint32_t i = 0;
        if (lane == 0) asm volatile("atom.relaxed.gpu.global.add.u32 %0, [%1], 1;" : "=r"(i) : "l"(&g_flags.c[kind][b]) : "memory");
        i = __shfl_sync(0xffffffffu, i, 0);
        if (i < (kind < 2 ? 32u : 2u * o_split(b))) return kind << 16 | b << 8 | i | ((kind == 1 ? r1 : kind == 2 ? r2 : r3) ? 128 : 0);
    }
}

template <int NP, int CH>
__device__ __forceinline__ void tile_out(const float (&acc)[8 * NP], uint32_t eb, uint32_t efull, uint32_t eempty, int& eph, int lane) {
    const int r = lane & 7, mi = lane >> 3, row = (mi & 1) * 8 + r;
    mbar_wait(eempty, eph); eph ^= 1;
#pragma unroll
    for (int p = 0; p < NP; p++) {
        const int oc = 2 * p + (mi >> 1);
        stsm4(eb + (oc >> 3) * CH + row * 128 + (((oc & 7) ^ r) << 4), pack2(acc[8 * p], acc[8 * p + 1]), pack2(acc[8 * p + 2], acc[8 * p + 3]),
              pack2(acc[8 * p + 4], acc[8 * p + 5]), pack2(acc[8 * p + 6], acc[8 * p + 7]));
    }
    asm volatile("fence.proxy.async.shared::cta;" ::: "memory");
    __syncwarp();
    if (lane == 0) mbar_arrive(efull);
}

template <int MT>
__device__ __forceinline__ void attn_tile(uint32_t base, uint32_t dst, uint32_t eempty, int eph, int lane) {
    constexpr int NK = MT ? 5 : 3;
    const int r = lane & 7, mi = lane >> 3, g = lane >> 2, t = lane & 3;
    float sc[NK][4];
#pragma unroll
    for (int n = 0; n < NK; n++) sc[n][0] = sc[n][1] = sc[n][2] = sc[n][3] = 0.f;
#pragma unroll AUNR
    for (int k2 = 0; k2 < 6; k2++) {
        const uint32_t cb = (k2 >> 1) * 8192, c0 = (k2 & 1) * 4;
        uint32_t a0[4], a1[4], bb[NK][4];
        ldsm4(a0, base + cb + (16 * MT + (mi & 1) * 8 + r) * 128 + (((c0 + (mi >> 1)) ^ r) << 4));
        ldsm4(a1, base + cb + (16 * MT + (mi & 1) * 8 + r) * 128 + (((c0 + 2 + (mi >> 1)) ^ r) << 4));
#pragma unroll
        for (int n = 0; n < NK; n++)
            ldsm4(bb[n], n < NK - 1 ? base + 4096 + cb + (8 * n + r) * 128 + (((c0 + mi) ^ r) << 4) : base + 36864 + k2 * 512 + lane * 16);
#pragma unroll
        for (int n = 0; n < NK; n++) mma16(sc[n], a0[0], a0[1], a0[2], a0[3], bb[n][0], bb[n][1]);
#pragma unroll
        for (int n = 0; n < NK; n++) mma16(sc[n], a1[0], a1[1], a1[2], a1[3], bb[n][2], bb[n][3]);
    }
    const float scale = 0.07216878364870322f, l2e = 1.4426950408889634f;
    float v[2][2 * NK], mx[2], sum[2];
#pragma unroll
    for (int hf = 0; hf < 2; hf++) {
        mx[hf] = -INFINITY;
#pragma unroll
        for (int n = 0; n < NK; n++) {
            uint32_t u = pack2(sc[n][2 * hf], sc[n][2 * hf + 1]);
            u = pack2(lo_f(u) * scale, hi_f(u) * scale);
            const int lim = 16 * MT + 8 * hf + g - 8 * n - 2 * t;
            v[hf][2 * n] = (n < NK - 1 && lim < 0) ? -1e9f : lo_f(u);
            v[hf][2 * n + 1] = (n < NK - 1 && lim < 1) ? -1e9f : hi_f(u);
            mx[hf] = fmaxf(mx[hf], fmaxf(v[hf][2 * n], v[hf][2 * n + 1]));
        }
    }
#pragma unroll
    for (int o = 1; o < 4; o <<= 1)
#pragma unroll
        for (int hf = 0; hf < 2; hf++) mx[hf] = fmaxf(mx[hf], __shfl_xor_sync(0xffffffffu, mx[hf], o));
#pragma unroll
    for (int hf = 0; hf < 2; hf++) {
        sum[hf] = 0;
#pragma unroll
        for (int q = 0; q < 2 * NK; q++) { asm("ex2.approx.ftz.f32 %0, %1;" : "=f"(v[hf][q]) : "f"((v[hf][q] - mx[hf]) * l2e)); sum[hf] += v[hf][q]; }
    }
#pragma unroll
    for (int o = 1; o < 4; o <<= 1)
#pragma unroll
        for (int hf = 0; hf < 2; hf++) sum[hf] += __shfl_xor_sync(0xffffffffu, sum[hf], o);
    uint32_t pa[NK][2];
#pragma unroll
    for (int hf = 0; hf < 2; hf++) {
        const float inv = __fdividef(1.f, sum[hf]);
#pragma unroll
        for (int n = 0; n < NK; n++) pa[n][hf] = pack2(v[hf][2 * n] * inv, v[hf][2 * n + 1] * inv);
    }
    mbar_wait(eempty, eph);
#pragma unroll AUNR
    for (int n4 = 0; n4 < 6; n4++) {
        const uint32_t cb = (n4 >> 1) * 4096, c0 = (n4 & 1) * 4;
        uint32_t bm[4], bb[2 + 2 * MT][4];
        ldsm4t(bm, base + AT_VM + n4 * 512 + lane * 16);
#pragma unroll
        for (int u = 0; u < 2 + 2 * MT; u++) ldsm4t(bb[u], base + AT_V + cb + (16 * (u >> 1) + 8 * (mi & 1) + r) * 128 + (((c0 + 2 * (u & 1) + (mi >> 1)) ^ r) << 4));
        float o[4][4];
#pragma unroll
        for (int u = 0; u < 4; u++) { o[u][0] = o[u][1] = o[u][2] = o[u][3] = 0.f; mma8(o[u], pa[NK - 1][0], pa[NK - 1][1], bm[u]); }
#pragma unroll
        for (int u = 0; u < 4 + 4 * MT; u++) mma16(o[u & 3], pa[u >> 2 << 1][0], pa[u >> 2 << 1][1], pa[(u >> 2 << 1) + 1][0], pa[(u >> 2 << 1) + 1][1], bb[u >> 1][2 * (u & 1)], bb[u >> 1][2 * (u & 1) + 1]);
#pragma unroll
        for (int p = 0; p < 2; p++)
            stsm4(dst + (n4 >> 1) * 2048 + ((mi & 1) * 8 + r) * 128 + (((c0 + 2 * p + (mi >> 1)) ^ r) << 4), pack2(o[2 * p][0], o[2 * p][1]), pack2(o[2 * p][2], o[2 * p][3]),
                  pack2(o[2 * p + 1][0], o[2 * p + 1][1]), pack2(o[2 * p + 1][2], o[2 * p + 1][3]));
    }
}

__device__ __forceinline__ uint32_t ln_row(const uint32_t (&as)[10], const uint2 (&xin)[5], int row, uint32_t par, bf16* out, uint64_t ef, int lane) {
    const uint32_t pa = par + lane * 8;
    uint32_t xv[10], hv[10], sv[10], tv[10];
#pragma unroll
    for (int q = 0; q < 5; q++) {
        uint32_t ga[2], t[2], u[2];
        lds64(ga, pa + q * 256); lds64(t, pa + 1280 + q * 256); lds64(u, pa + 2560 + q * 256);
#pragma unroll
        for (int e = 0; e < 2; e++) {
            xv[2 * q + e] = add2(e ? xin[q].y : xin[q].x, mul2(ga[e], as[2 * q + e]));
            tv[2 * q + e] = t[e]; sv[2 * q + e] = u[e];
        }
        st_ef(g_x1 + row * DM + lane * 4 + q * 128, make_uint2(xv[2 * q], xv[2 * q + 1]), ef);
    }
    ln_mod(xv, sv, tv, hv);
    float rs = 0;
#pragma unroll
    for (int q = 0; q < 5; q++) {
        const int c = row * DM + lane * 4 + q * 128;
        const uint32_t h0 = hv[2 * q], h1 = hv[2 * q + 1];
        uint32_t gb[2], wv[2];
        lds64(gb, pa + 3840 + q * 256); lds64(wv, pa + 5120 + q * 256);
        rs += (lo_f(h0) * lo_f(wv[0]) + hi_f(h0) * hi_f(wv[0])) + (lo_f(h1) * lo_f(wv[1]) + hi_f(h1) * hi_f(wv[1]));
        st_ef(g_h2 + c, make_uint2(h0, h1), ef);
        st_ef(out + c, make_uint2(add2(xv[2 * q], mul2(gb[0], h0)), add2(xv[2 * q + 1], mul2(gb[1], h1))), ef);
    }
    const uint32_t rb = pack2(0.f, warp_sum(rs));
    return (((int)rb < 0 ? ~rb : rb | 0x80000000u) & 0xffff0000u) | (uint32_t)(2 * S_TOK - 1 - row);
}
__device__ __forceinline__ void key_out(uint32_t key) {
    __syncwarp();
    if (key) asm volatile("st.release.gpu.global.u32 [%0], %1;" :: "l"(g_key + (~key & (S_TOK - 1))), "r"(key) : "memory");
}

__global__ void __launch_bounds__(384, 1) k_side(const __grid_constant__ SideMaps mp, const bf16* __restrict__ x, const bf16* __restrict__ wr, const bf16* wmod, const bf16* cvec, bf16* __restrict__ out) {
    extern __shared__ __align__(1024) uint8_t smraw[];
    const uint32_t sm = smem_u32(smraw);
    if (sm & 1023) __trap();
    const uint32_t FULL = sm + SD_BAR, EMPTY = FULL + 32, EFULL = FULL + 64, EEMPTY = FULL + 80, IFULL = FULL + 96, IEMPTY = FULL + 128, IQ = FULL + 160, SCHED = FULL + 176, PARAM = FULL + 184;
    const int tid = threadIdx.x, warp = __shfl_sync(0xffffffffu, tid >> 5, 0), lane = tid & 31;
    const uint64_t ef = policy_stream();
    if (tid == 0) {
        for (int i = 0; i < SD_NST; i++) { mbar_init(FULL + 8 * i, 1); mbar_init(EMPTY + 8 * i, 2); }
        for (int i = 0; i < 2; i++) { mbar_init(EFULL + 8 * i, 4); mbar_init(EEMPTY + 8 * i, 1); }
        for (int i = 0; i < 4; i++) { mbar_init(IFULL + 8 * i, 1); mbar_init(IEMPTY + 8 * i, 11); }
        mbar_init(SCHED, 1); mbar_init(PARAM, 1);
        asm volatile("fence.mbarrier_init.release.cluster;" ::: "memory");
    }
    if (SDEL) __nanosleep(SDEL);
    __syncthreads();
    if (warp >= 8) {
      asm volatile("setmaxnreg.dec.sync.aligned.u32 40;");
      if (warp == 8) {
        int st = 0, ph = 1;
        for (int q = 0;; q++) {
            mbar_wait(IFULL + 8 * (q & 3), (q >> 2) & 1);
            const int it = __shfl_sync(0xffffffffu, lds32(IQ + 4 * (q & 3)), 0);
            if (elect()) mbar_arrive(IEMPTY + 8 * (q & 3));
            if (it < 0) break;
            const int kind = it >> 16, b = (it >> 8) & 255, i = it & 63;
            const int nst = kind == 0 ? 10 : kind == 1 ? 4 : kind == 2 ? 192 >> o_shift(b) : b == 14 ? 4 : 2;
            const int ksched = kind == 0 ? 4 : kind == 2 ? nst - KSO : (it & 128) ? -1 : kind == 1 ? KSA : 0;
            if (ksched < 0 && elect()) mbar_arrive(SCHED);
            const bool look = !(it & 128);
            if (look && kind == 1) flag_wait(&g_flags.v[b * 32 + i], 2);
            if (look && kind == 3 && b < 14) flag_wait(&g_flags.o[b], o_done(b));
            for (int kb = 0; kb < nst; kb++) {
                mbar_wait(EMPTY + 8 * st, ph);
                const uint32_t base = sm + st * SD_ST, fb = FULL + 8 * st;
                if (look && kind == 1) flag_wait(&g_flags.seg[kb * 32 + i], 3);
                if (kb == ksched && elect()) mbar_arrive(SCHED);
                if (kind == 0) {
                    if (q == 0 && kb == 0) {
                        if (elect()) {
#pragma unroll 1
                            for (int c = 0; c < SD_NST; c++) tma3d(sm + c * SD_ST + 16384, &mp.wv, c * 64, i * 3, FULL + 8 * c);
#pragma unroll 1
                            for (int c = SD_NST; c < SPF; c++)
                                asm volatile("cp.async.bulk.prefetch.tensor.3d.L2.global [%0, {0, %1, %2}];" :: "l"((uint64_t)&mp.wv), "r"(c * 64), "r"(i * 3) : "memory");
                        }
                        flag_wait(&g_flags.h, 96);
                    }
                    if (elect()) {
                        mbar_expect(fb, 40960);
                        tma2d(base, &mp.h, kb * 64, b * 128, fb);
                        if (q || kb >= SD_NST) tma3d(base + 16384, &mp.wv, kb * 64, i * 3, fb);
                    }
                } else if (kind == 1) {
                    if (elect()) {
                        mbar_expect(fb, 43008);
                        asm volatile("cp.async.bulk.shared::cluster.global.mbarrier::complete_tx::bytes.L2::cache_hint [%0], [%1], %2, [%3], %4;"
                            :: "r"(base), "l"(g_att + ((b * 4 + kb) * NH + i) * AT_REC), "r"(AT_REC), "r"(fb), "l"(ef) : "memory");
                    }
                } else if (kind == 3) {
                    if (b == 14 && !(kb & 1)) flag_wait(&g_flags.fin[(kb + (i >> 4)) * 32], 80);
                    if (elect()) { mbar_expect(fb, 40960); tma3d_ef(base, &mp.lnp[o_shift(b) - 2], i * (160 >> o_shift(b)), b * KSPLIT + (kb << o_shift(b) >> 1), fb, ef); }
                } else {
                    const int k0 = ((i >> 1) * nst + kb) * 32;
                    if (elect()) { mbar_expect(fb, 28672); tma3d(base + 8192, &mp.wo, k0, (i & 1) * 5, fb); }
                    if (look && kb % 12 == 0) flag_wait(&g_flags.pair[b * 16 + k0 / 384], 16);
                    if (elect()) tma2d_ef(base, &mp.o, k0, b * 128, fb, ef);
                }
                __syncwarp();
                if (++st == SD_NST) { st = 0; ph ^= 1; }
            }
        }
      } else if (warp == 11) {
        bool fin = false, par = false;
        for (int q = 0;; q++) {
            if (q) mbar_wait(SCHED, (q - 1) & 1);
            int it = fin ? -1 : q == 0 && blockIdx.x < 32 ? (int)blockIdx.x : next_item(lane);
            if (it < 0 && !fin && blockIdx.x < 32) { it = 3 << 16 | 14 << 8 | blockIdx.x; fin = true; }
            if (lane == 0) {
                if (it >> 16 == 3) {
                    const int b = (it >> 8) & 255, nr = 64 >> o_shift(b);
                    asm volatile("cp.async.bulk.prefetch.L2.global [%0], %1;" :: "l"(x + (b * 128 + (it & 63) * nr) * DM), "r"(nr * DM * 2) : "memory");
                }
                mbar_wait(IEMPTY + 8 * (q & 3), ((q >> 2) & 1) ^ 1);
                asm volatile("st.shared.u32 [%0], %1;" :: "r"(IQ + 4 * (q & 3)), "r"(it) : "memory");
                mbar_arrive(IFULL + 8 * (q & 3));
            }
            if (!par && it >> 16 == 3) {
                par = true;
                                if (lane == 0) { mbar_expect(PARAM, 6400); bulk_g2s(sm + SD_PAR, g_mod + 2 * DM, 5120, PARAM); bulk_g2s(sm + SD_PAR + 5120, wr, 1280, PARAM); }
            }
            __syncwarp();
            if (it < 0) break;
        }
        flags_release(lane);
      } else {
        if (lane == 0) {
            const int wg = warp - 9; int ph = 0;
            for (int q = 0;; q++) {
                mbar_wait(IFULL + 8 * (q & 3), (q >> 2) & 1);
                const int it = lds32(IQ + 4 * (q & 3));
                mbar_arrive(IEMPTY + 8 * (q & 3));
                if (it < 0) break;
                const int kind = it >> 16, b = (it >> 8) & 255, i = it & 63;
                if (kind & 1) continue;
#pragma unroll 1
                for (int rd = 0; rd < (kind == 2 ? 2 : 1); rd++) {
                    mbar_wait(EFULL + 8 * wg, ph); ph ^= 1;
                    const uint32_t src = sm + SD_EPI + wg * 24576;
                    if (kind == 2) tma3d_store(rd ? &mp.slab2 : &mp.slab3, (b * KSPLIT + (i >> 1)) * 128 + wg * 64, (i & 1) * 5 + rd * 3, src, ef, false);
                    else {
                        uint8_t* dst = g_att + ((b * 4 + wg * 2) * NH + i) * AT_REC + AT_V;
                        asm volatile("cp.async.bulk.global.shared::cta.bulk_group.L2::cache_hint [%0], [%1], 12288, %2;" :: "l"(dst), "r"(src), "l"(ef) : "memory");
                        asm volatile("cp.async.bulk.global.shared::cta.bulk_group.L2::cache_hint [%0], [%1], 12288, %2;" :: "l"(dst + NH * AT_REC), "r"(src + 12288), "l"(ef) : "memory");
                    }
                    asm volatile("cp.async.bulk.commit_group;" ::: "memory");
                    asm volatile("cp.async.bulk.wait_group.read 0;" ::: "memory");
                    mbar_arrive(EEMPTY + 8 * wg);
                }
                asm volatile("cp.async.bulk.wait_group 0;" ::: "memory");
                GPU_FENCE();
                bump(kind == 0 ? &g_flags.v[b * 32 + i] : &g_flags.o[b]);
                if (kind == 0) bump(&g_flags.vb[b]);
            }
        }
      }
    } else {
        asm volatile("setmaxnreg.inc.sync.aligned.u32 232;");
        const int wg = warp >> 2, w = warp & 3;
        int st = 0, ph = 0, eph = 1;
        bool att = false;
        if (blockIdx.x < 32 * GEMV) {
            const uint32_t buf = sm + SD_EPI;
#pragma unroll 1
            for (int k = tid; k < DM; k += 256) {
                const float f = __uint_as_float((uint32_t)__ldg((const unsigned short*)cvec + k) << 16);
                asm volatile("st.shared.f32 [%0], %1;" :: "r"(buf + k * 4), "f"(bfr(__fdividef(f, 1.f + __expf(-f)))) : "memory");
            }
            const int t = min(tid, 199), k0 = t / 10 * 32;
            const bf16* wm = wmod + k0 * (6 * DM) + 2 * DM + blockIdx.x * 80 + t % 10 * 8;
            float a[8] = {0, 0, 0, 0, 0, 0, 0, 0};
#pragma unroll 1
            for (int k = 0; k < 32; k += 8) {
                uint4 z[8];
#pragma unroll
                for (int e = 0; e < 8; e++) z[e] = __ldcs((const uint4*)(wm + (k + e) * (6 * DM)));
                if (k == 0) bar_sync(1, 256);
#pragma unroll
                for (int e = 0; e < 8; e++) {
                    const float f = __uint_as_float(lds32(buf + (k0 + k + e) * 4));
                    a[0] += f * lo_f(z[e].x); a[1] += f * hi_f(z[e].x); a[2] += f * lo_f(z[e].y); a[3] += f * hi_f(z[e].y);
                    a[4] += f * lo_f(z[e].z); a[5] += f * hi_f(z[e].z); a[6] += f * lo_f(z[e].w); a[7] += f * hi_f(z[e].w);
                }
            }
            sts128f(buf + 4096 + t * 32, a[0], a[1], a[2], a[3]); sts128f(buf + 4112 + t * 32, a[4], a[5], a[6], a[7]);
            bar_sync(1, 256);
            if (tid < 40) {
                float a0 = 0, a1 = 0;
#pragma unroll 4
                for (int g = 0; g < 20; g++) { const float2 v = lds64f(buf + 4096 + g * 320 + tid * 8); a0 += v.x; a1 += v.y; }
                ((uint32_t*)(g_mod + 2 * DM + blockIdx.x * 80))[tid] = pack2(a0, a1);
            }
            bar_sync(1, 256);
        }
        const uint32_t eb = sm + SD_EPI + wg * 24576;
        for (int q = 0;; q++) {
            mbar_wait(IFULL + 8 * (q & 3), (q >> 2) & 1);
            const int itc = lds32(IQ + 4 * (q & 3));
            __syncwarp();
            if (lane == 0) mbar_arrive(IEMPTY + 8 * (q & 3));
            if (itc < 0) break;
            const int kind = itc >> 16, b = (itc >> 8) & 255, i = itc & 63;
            if (att && kind != 1) { bar_sync(1, 256); att = false; }
            if (kind == 0) {
                float acc[96];
#pragma unroll
                for (int n = 0; n < 96; n++) acc[n] = 0.f;
                int prev = -1;
#pragma unroll 1
                for (int kb = 0; kb < 10; kb++) {
                    mbar_wait(FULL + 8 * st, ph);
                    const uint32_t base = sm + st * SD_ST;
                    WG_FENCE();
#pragma unroll
                    for (int ks = 0; ks < 4; ks++)
                        wgmma_ss_n192_tb(acc, mkdesc(base + wg * 8192 + ks * 32, 16, 1024), mkdesc(base + 16384 + ks * 2048, 8192, 1024), (kb | ks) != 0);
                    WG_COMMIT();
                    WG_WAIT(1);
                    if (prev >= 0 && (tid & 127) == 0) mbar_arrive(EMPTY + 8 * prev);
                    prev = st;
                    if (++st == SD_NST) { st = 0; ph ^= 1; }
                }
                WG_WAIT(0);
                if ((tid & 127) == 0) mbar_arrive(EMPTY + 8 * prev);
                tile_out<12, 4096>(acc, eb + (w >> 1) * 12288 + (w & 1) * 2048, EFULL + 8 * wg, EEMPTY + 8 * wg, eph, lane);
            } else if (kind == 1) {
                const int seg = warp >> 1, mt = warp & 1;
                int sst = st + seg, sph = ph; if (sst >= SD_NST) { sst -= SD_NST; sph ^= 1; }
                ph ^= 1;
                mbar_wait(FULL + 8 * sst, sph);
                const uint32_t base = sm + sst * SD_ST;
                if (mt) attn_tile<1>(base, eb + w * 6144, EEMPTY + 8 * wg, eph, lane);
                else attn_tile<0>(base, eb + w * 6144, EEMPTY + 8 * wg, eph, lane);
                asm volatile("fence.proxy.async.shared::cta;" ::: "memory");
                __syncwarp();
                if (lane == 0) {
                    mbar_arrive(EMPTY + 8 * sst);
                    tma3d_store(&mp.ost, b * 128 + warp * 16, i * 3, eb + w * 6144, ef, false);
                    BULK_COMMIT(); BULK_WAIT(); GPU_FENCE();
                    bump(b == 15 ? &g_flags.half[(i & 30) + wg] : &g_flags.pair[b * 16 + (i >> 1)]); bump(&g_flags.at[b]);
                }
                __syncwarp();
                att = true;
            } else if (kind == 2) {
                float acc[96], acc2[64];
#pragma unroll
                for (int n = 0; n < 96; n++) acc[n] = 0.f;
#pragma unroll
                for (int n = 0; n < 64; n++) acc2[n] = 0.f;
                int prev = -1;
#pragma unroll 1
                for (int kb = 192 >> o_shift(b); kb > 0; kb--) {
                    const uint32_t base = sm + st * SD_ST;
                    mbar_wait(FULL + 8 * st, ph);
                    WG_FENCE();
#pragma unroll
                    for (int ks = 0; ks < 2; ks++) {
                        const uint64_t da = (mkdesc(base + wg * 4096 + ks * 32, 16, 512) & ~(3ull << 62)) | (2ull << 62);
                        wgmma_ss_n192_tb(acc, da, mkdesc(base + 8192 + ks * 2048, 4096, 1024), 1);
                        wgmma_ss_n128_tb(acc2, da, mkdesc(base + 8192 + 3 * 4096 + ks * 2048, 4096, 1024), 1);
                    }
                    WG_COMMIT();
                    WG_WAIT(1);
                    if (prev >= 0 && (tid & 127) == 0) mbar_arrive(EMPTY + 8 * prev);
                    prev = st;
                    if (++st == SD_NST) { st = 0; ph ^= 1; }
                }
                WG_WAIT(0);
                if ((tid & 127) == 0) mbar_arrive(EMPTY + 8 * prev);
                tile_out<12, 8192>(acc, eb + w * 2048, EFULL + 8 * wg, EEMPTY + 8 * wg, eph, lane);
                tile_out<8, 8192>(acc2, eb + w * 2048, EFULL + 8 * wg, EEMPTY + 8 * wg, eph, lane);
            } else {
                const int sh = o_shift(b), nr = 64 >> sh, fw = b == 14 ? wg : 0, row0 = (b + fw) * 128 + i * nr, lw = warp - 4 * fw;
                if (fw) { st += 2; if (st >= SD_NST) { st -= SD_NST; ph ^= 1; } }
                int st1 = st + 1, ph1 = ph; if (st1 == SD_NST) { st1 = 0; ph1 ^= 1; }
                uint2 xin[2][5];
                uint32_t as[2][10] = {};
#pragma unroll
                for (int q2 = 0; q2 < 10; q2++) xin[q2 & 1][q2 >> 1] = ld_ef(x + (row0 + ((warp + 8 * (q2 & 1)) & (nr - 1))) * DM + lane * 4 + (q2 >> 1) * 128, ef);
                mbar_wait(PARAM, 0); mbar_wait(FULL + 8 * st, ph); mbar_wait(FULL + 8 * st1, ph1);
#pragma unroll 1
                for (int lrow = lw + (nr & 16) / 2; lrow >= 0 && lrow < nr; lrow -= 8) {
                    float a[20];
#pragma unroll
                    for (int q2 = 0; q2 < 20; q2++) a[q2] = 0.f;
#pragma unroll 1
                    for (int k = 0; k < (1 << sh >> 1); k++) {
                        const uint32_t ad = sm + ((k << (6 - sh)) + lrow) * 1280 + lane * 8;
                        uint32_t z[10][2];
#pragma unroll
                        for (int q2 = 0; q2 < 10; q2++) lds64(z[q2], ad + (q2 < 5 ? st : st1) * SD_ST + q2 % 5 * 256);
#pragma unroll
                        for (int q2 = 0; q2 < 10; q2++) { float* p = a + q2 % 5 * 4; p[0] += lo_f(z[q2][0]); p[1] += hi_f(z[q2][0]); p[2] += lo_f(z[q2][1]); p[3] += hi_f(z[q2][1]); }
                    }
#pragma unroll
                    for (int q2 = 0; q2 < 10; q2++) { as[1][q2] = as[0][q2]; as[0][q2] = pack2(a[2 * q2], a[2 * q2 + 1]); }
                }
                bar_sync(2 + wg, 128);
                if ((tid & 127) == 0) { mbar_arrive(EMPTY + 8 * st); mbar_arrive(EMPTY + 8 * st1); }
                uint32_t key = 0;
#pragma unroll 1
                for (int lrow = lw; lrow < nr; lrow += 8) {
                    const int row = row0 + lrow;
                    const uint32_t k1 = ln_row(as[0], xin[0], row, sm + SD_PAR, out, ef, lane);
                    if (lane == lrow >> 3) key = k1;
#pragma unroll
                    for (int q2 = 0; q2 < 5; q2++) { as[0][2 * q2] = as[1][2 * q2]; as[0][2 * q2 + 1] = as[1][2 * q2 + 1]; xin[0][q2] = xin[1][q2]; }
                }
                key_out(key);
                st = st1 + 1; ph = ph1; if (st == SD_NST) { st = 0; ph ^= 1; }
            }
        }
    }
    __syncwarp();
    asm volatile("griddepcontrol.wait;" ::: "memory");
}

#define P_D1 650
#define P_DL 700
#define P_DG 29
typedef CUresult (*EncodeFn)(CUtensorMap*, CUtensorMapDataType, cuuint32_t, void*, const cuuint64_t*, const cuuint64_t*, const cuuint32_t*, const cuuint32_t*,
                             CUtensorMapInterleave, CUtensorMapSwizzle, CUtensorMapL2promotion, CUtensorMapFloatOOBfill);
static EncodeFn s_encode = nullptr;
static void make_map(CUtensorMap* m, const void* p, int rows, int cols, int box_rows, int box_cols = 64) {
    cuuint64_t dims[2] = {(cuuint64_t)cols, (cuuint64_t)rows}, strides[1] = {(cuuint64_t)cols * 2};
    cuuint32_t box[2] = {(cuuint32_t)box_cols, (cuuint32_t)box_rows}, es[2] = {1, 1};
    s_encode(m, CU_TENSOR_MAP_DATA_TYPE_BFLOAT16, 2, (void*)p, dims, strides, box, es, CU_TENSOR_MAP_INTERLEAVE_NONE,
             box_cols == 64 ? CU_TENSOR_MAP_SWIZZLE_128B : box_cols == 32 ? CU_TENSOR_MAP_SWIZZLE_64B : CU_TENSOR_MAP_SWIZZLE_NONE, CU_TENSOR_MAP_L2_PROMOTION_L2_256B, CU_TENSOR_MAP_FLOAT_OOB_FILL_NONE);
}
static void make_map3(CUtensorMap* m, const void* p, int rows, int cols, int box_rows, int box_chunks, int cw = 64) {
    cuuint64_t dims[3] = {(cuuint64_t)cw, (cuuint64_t)rows, (cuuint64_t)(cols / cw)}, strides[2] = {(cuuint64_t)cols * 2, (cuuint64_t)cw * 2};
    cuuint32_t box[3] = {(cuuint32_t)cw, (cuuint32_t)box_rows, (cuuint32_t)box_chunks}, es[3] = {1, 1, 1};
    s_encode(m, CU_TENSOR_MAP_DATA_TYPE_BFLOAT16, 3, (void*)p, dims, strides, box, es, CU_TENSOR_MAP_INTERLEAVE_NONE,
             cw == 64 ? CU_TENSOR_MAP_SWIZZLE_128B : CU_TENSOR_MAP_SWIZZLE_64B, CU_TENSOR_MAP_L2_PROMOTION_L2_256B, CU_TENSOR_MAP_FLOAT_OOB_FILL_NONE);
}
template <typename T> static void* sym(T& s) { void* p = nullptr; cudaGetSymbolAddress(&p, s); return p; }

extern "C" void kernel_launch(void* const* d_in, const int* in_sizes, int n_in, void* d_out, int out_size) {
    const bf16 *x = (const bf16*)d_in[0], *mem0 = (const bf16*)d_in[1], *Wq = (const bf16*)d_in[2], *Wk = (const bf16*)d_in[3],
               *Wv = (const bf16*)d_in[4], *Wo = (const bf16*)d_in[5], *wr = (const bf16*)d_in[8], *wgate = (const bf16*)d_in[9],
               *wup = (const bf16*)d_in[10], *wdown = (const bf16*)d_in[11], *c = (const bf16*)d_in[12], *wmod = (const bf16*)d_in[13];
    bf16* out = (bf16*)d_out;
    if (!s_encode) {
        cudaDriverEntryPointQueryResult qr;
        cudaGetDriverEntryPoint("cuTensorMapEncodeTiled", (void**)&s_encode, cudaEnableDefault, &qr);
        cudaFuncSetAttribute(k_side, cudaFuncAttributeMaxDynamicSharedMemorySize, SD_SMEM);
        cudaFuncSetAttribute(k_chain, cudaFuncAttributeMaxDynamicSharedMemorySize, C_SMEM);
    }
    ChainMaps cm; SideMaps sd;
    make_map(&sd.h, sym(g_h), S_TOK, DM, 128); make_map3(&sd.wv, Wv, DM, HD, 64, 3);
    make_map3(&sd.ost, sym(g_o), S_TOK, HD, 16, 3); make_map(&sd.o, sym(g_o), S_TOK, HD, 128, 32); make_map3(&sd.wo, Wo, HD, DM, 32, 5);
    make_map3(&sd.slab3, sym(g_slab), 16 * KSPLIT * 128, DM, 64, 3); make_map3(&sd.slab2, sym(g_slab), 16 * KSPLIT * 128, DM, 64, 2);
    make_map3(&cm.wo15, Wo, HD, DM, 192, 2); make_map3(&cm.o15, sym(g_o), S_TOK, HD, 64, 2); make_map3(&cm.slab16, sym(g_slab), 16 * KSPLIT * 128, DM, 16, 2);
    for (int i = 0; i < 3; i++) {
        cuuint64_t dims[3] = {256, 320, 16 * KSPLIT}, strides[2] = {512, 128 * DM * 2};
        cuuint32_t box[3] = {256, 40u >> i, 2u << i}, es[3] = {1, 1, 1};
        s_encode(&sd.lnp[i], CU_TENSOR_MAP_DATA_TYPE_BFLOAT16, 3, sym(g_slab), dims, strides, box, es, CU_TENSOR_MAP_INTERLEAVE_NONE,
                 CU_TENSOR_MAP_SWIZZLE_NONE, CU_TENSOR_MAP_L2_PROMOTION_L2_256B, CU_TENSOR_MAP_FLOAT_OOB_FILL_NONE);
    }
    make_map(&cm.wq, Wq, DM, HD, 640 / WP); make_map(&cm.wk, Wk, DM, HD, 640 / WP); make_map(&cm.wv, Wv, DM, HD, 160); make_map3(&cm.wo, Wo, HD, DM, 64, 7, 32);
    make_map3(&cm.h2, sym(g_h), S_TOK, DM, 32, 2);
    ChainArgs ar = {x, mem0, c, wmod, Wv, Wo, wgate, wup, wdown, out, P_D1, P_DL, P_DG};
    k_chain<<<96, 384, C_SMEM>>>(cm, ar);
    cudaLaunchConfig_t cfg = {};
    cfg.gridDim = dim3(N_SIDE); cfg.blockDim = dim3(384); cfg.dynamicSmemBytes = SD_SMEM; cfg.stream = cudaStreamPerThread;
    cudaLaunchAttribute at[1]; at[0].id = cudaLaunchAttributeProgrammaticStreamSerialization; at[0].val.programmaticStreamSerializationAllowed = 1;
    cfg.attrs = at; cfg.numAttrs = 1;
    cudaLaunchKernelEx(&cfg, k_side, sd, x, wr, wmod, c, out);
}
```

```cpp
#include <cuda_runtime.h>
#include <cuda_bf16.h>
#include <cuda.h>
#include <stdint.h>
#include <stdio.h>
#include <string.h>
#include <stdlib.h>

typedef __nv_bfloat16 bf16;
constexpr int S_TOK = 2048, DM = 640, NH = 32, DH = 192, HD = NH * DH, NSEG = 64, SEG = 32, FF = 1536;

__device__ bf16 g_mod[6 * DM];
__device__ bf16 g_h[S_TOK * DM];
constexpr int AT_REC = 43008, AT_V = 24576, AT_KM = 36864, AT_VM = 39936;
__device__ __align__(1024) uint8_t g_att[NSEG * NH * AT_REC];
__device__ bf16 g_o[S_TOK * HD];
__device__ bf16 g_A[S_TOK * DM];
__device__ bf16 g_x1[S_TOK * DM];
__device__ bf16 g_h2[S_TOK * DM];
__device__ __align__(128) uint32_t g_key[S_TOK];
__device__ int g_idx[8];
__device__ __align__(128) uint32_t g_gu[FF / 8 * 32];
constexpr int ACC_PAIR = 24 * 1024;
__device__ __align__(1024) uint8_t g_acc[2 * ACC_PAIR];
__device__ __align__(1024) uint32_t g_stamp[4 * 12 * 32];
constexpr int KSPLIT = 16;
__device__ bf16 g_slab[16 * KSPLIT * 128 * DM];
struct __align__(128) Flags {
    uint32_t qk[16], vb[16];
    uint32_t at[16], o[16];
    uint32_t c[4][16];
    uint32_t half[32];
    uint32_t fin[4 * 32];
    uint32_t v[16 * 32];
    uint32_t seg[4 * 32];
    uint32_t pair[16 * 16];
    uint32_t h, pad2[31], done, pad3[31];
    uint32_t mod1[DM];
    uint32_t wmax[96];
};
__device__ Flags g_flags;

__device__ __forceinline__ uint32_t smem_u32(const void* p) { return (uint32_t)__cvta_generic_to_shared(p); }
__device__ __forceinline__ uint32_t pack2(float lo, float hi) {
    uint32_t r; asm("cvt.rn.bf16x2.f32 %0, %1, %2;" : "=r"(r) : "f"(hi), "f"(lo)); return r;
}
__device__ __forceinline__ float bfr(float x) { return __uint_as_float(pack2(0.f, x)); }
__device__ __forceinline__ float inv_std(float var) {
    float s, r; asm("sqrt.approx.f32 %0, %1;" : "=f"(s) : "f"(bfr(bfr(var) + 1e-5f))); asm("rcp.approx.f32 %0, %1;" : "=f"(r) : "f"(bfr(s))); return r;
}
__device__ __forceinline__ float lo_f(uint32_t v) { return __uint_as_float(v << 16); }
__device__ __forceinline__ float hi_f(uint32_t v) { return __uint_as_float(v & 0xffff0000u); }
__device__ __forceinline__ void mbar_init(uint32_t bar, int cnt) { asm volatile("mbarrier.init.shared::cta.b64 [%0], %1;" :: "r"(bar), "r"(cnt) : "memory"); }
__device__ __forceinline__ void mbar_expect(uint32_t bar, int bytes) { asm volatile("mbarrier.arrive.expect_tx.shared::cta.b64 _, [%0], %1;" :: "r"(bar), "r"(bytes) : "memory"); }
__device__ __forceinline__ void mbar_arrive(uint32_t bar) { asm volatile("mbarrier.arrive.shared::cta.b64 _, [%0];" :: "r"(bar) : "memory"); }
__device__ __forceinline__ bool mbar_try(uint32_t bar, int par) {
    uint32_t ok; asm volatile("{ .reg .pred p; mbarrier.try_wait.parity.shared::cta.b64 p, [%1], %2; selp.u32 %0, 1, 0, p; }" : "=r"(ok) : "r"(bar), "r"(par) : "memory"); return ok;
}
__device__ __forceinline__ bool mbar_try_cluster(uint32_t bar, int par) {
    uint32_t ok; asm volatile("{ .reg .pred p; mbarrier.try_wait.parity.acquire.cluster.shared::cta.b64 p, [%1], %2; selp.u32 %0, 1, 0, p; }" : "=r"(ok) : "r"(bar), "r"(par) : "memory"); return ok;
}
__device__ __forceinline__ bool mbar_test(uint32_t bar, uint32_t par) {
    uint32_t ok; asm volatile("{ .reg .pred p; mbarrier.test_wait.parity.shared::cta.b64 p, [%1], %2; selp.u32 %0, 1, 0, p; }" : "=r"(ok) : "r"(bar), "r"(par) : "memory"); return ok;
}
constexpr int SPIN_LIMIT = 1 << 18;
__device__ __forceinline__ void mbar_wait(uint32_t bar, uint32_t par) {
    asm volatile("{ .reg .pred p, q; .reg .u32 n; mov.u32 n, 0;\n"
                 "W_%=: mbarrier.try_wait.parity.shared::cta.b64 p, [%0], %1;\n"
                 "@p bra.uni D_%=;\n"
                 "add.u32 n, n, 1; setp.lt.u32 q, n, 0x200000; @q bra.uni W_%=;\n"
                 "trap;\n"
                 "D_%=: }" :: "r"(bar), "r"(par) : "memory");
}
__device__ __forceinline__ void tma2d(uint32_t dst, const CUtensorMap* m, int c0, int c1, uint32_t bar) {
    asm volatile("cp.async.bulk.tensor.2d.shared::cluster.global.mbarrier::complete_tx::bytes [%0], [%1, {%3, %4}], [%2];"
        :: "r"(dst), "l"((uint64_t)m), "r"(bar), "r"(c0), "r"(c1) : "memory");
}
__device__ __forceinline__ void tma2d_mc(uint32_t dst, const CUtensorMap* m, int c0, int c1, uint32_t bar, uint16_t mask) {
    asm volatile("cp.async.bulk.tensor.2d.shared::cluster.global.mbarrier::complete_tx::bytes.multicast::cluster [%0], [%1, {%3, %4}], [%2], %5;"
        :: "r"(dst), "l"((uint64_t)m), "r"(bar), "r"(c0), "r"(c1), "h"(mask) : "memory");
}
__device__ __forceinline__ uint64_t policy_stream() { uint64_t p; asm("createpolicy.fractional.L2::evict_first.b64 %0, 1.0;" : "=l"(p)); return p; }
__device__ __forceinline__ void tma2d_ef(uint32_t dst, const CUtensorMap* m, int c0, int c1, uint32_t bar, uint64_t pol) {
    asm volatile("cp.async.bulk.tensor.2d.shared::cluster.global.mbarrier::complete_tx::bytes.L2::cache_hint [%0], [%1, {%3, %4}], [%2], %5;"
        :: "r"(dst), "l"((uint64_t)m), "r"(bar), "r"(c0), "r"(c1), "l"(pol) : "memory");
}
__device__ __forceinline__ void tma3d(uint32_t dst, const CUtensorMap* m, int row, int chunk, uint32_t bar) {
    asm volatile("cp.async.bulk.tensor.3d.shared::cluster.global.mbarrier::complete_tx::bytes [%0], [%1, {0, %3, %4}], [%2];"
        :: "r"(dst), "l"((uint64_t)m), "r"(bar), "r"(row), "r"(chunk) : "memory");
}
__device__ __forceinline__ void tma3d_ef(uint32_t dst, const CUtensorMap* m, int row, int chunk, uint32_t bar, uint64_t pol) {
    asm volatile("cp.async.bulk.tensor.3d.shared::cluster.global.mbarrier::complete_tx::bytes.L2::cache_hint [%0], [%1, {0, %3, %4}], [%2], %5;"
        :: "r"(dst), "l"((uint64_t)m), "r"(bar), "r"(row), "r"(chunk), "l"(pol) : "memory");
}
__device__ __forceinline__ void tma3d_store(const CUtensorMap* m, int row, int chunk, uint32_t src, uint64_t pol, bool hint) {
    if (hint) asm volatile("cp.async.bulk.tensor.3d.global.shared::cta.bulk_group.L2::cache_hint [%0, {0, %2, %3}], [%1], %4;"
        :: "l"((uint64_t)m), "r"(src), "r"(row), "r"(chunk), "l"(pol) : "memory");
    else asm volatile("cp.async.bulk.tensor.3d.global.shared::cta.bulk_group [%0, {0, %2, %3}], [%1];"
        :: "l"((uint64_t)m), "r"(src), "r"(row), "r"(chunk) : "memory");
}
__device__ __forceinline__ bool elect() { uint32_t p; asm volatile("{ .reg .pred e; elect.sync _|e, -1; selp.u32 %0, 1, 0, e; }" : "=r"(p)); return p; }
__device__ __forceinline__ uint2 ld_ef(const void* p, uint64_t pol) {
    uint2 v; asm volatile("ld.relaxed.gpu.global.L2::cache_hint.v2.u32 {%0,%1}, [%2], %3;" : "=r"(v.x), "=r"(v.y) : "l"(p), "l"(pol)); return v;
}
__device__ __forceinline__ void st_ef(void* p, uint2 v, uint64_t pol) {
    asm volatile("st.global.L2::cache_hint.v2.u32 [%0], {%1,%2}, %3;" :: "l"(p), "r"(v.x), "r"(v.y), "l"(pol) : "memory");
}
__device__ __forceinline__ void tma2d_prefetch(const CUtensorMap* m, int c0, int c1) {
    asm volatile("cp.async.bulk.prefetch.tensor.2d.L2.global [%0, {%1, %2}];" :: "l"((uint64_t)m), "r"(c0), "r"(c1) : "memory");
}
__device__ __forceinline__ void mbar_arrive_remote(uint32_t bar) { asm volatile("mbarrier.arrive.relaxed.cluster.shared::cluster.b64 _, [%0];" :: "r"(bar) : "memory"); }
__device__ __forceinline__ void tma2d_store(const CUtensorMap* m, int c0, int c1, uint32_t src) {
    asm volatile("cp.async.bulk.tensor.2d.global.shared::cta.bulk_group [%0, {%2, %3}], [%1];"
        :: "l"((uint64_t)m), "r"(src), "r"(c0), "r"(c1) : "memory");
}
__device__ __forceinline__ void bulk_g2s(uint32_t dst, const void* src, int bytes, uint32_t bar) {
    asm volatile("cp.async.bulk.shared::cluster.global.mbarrier::complete_tx::bytes [%0], [%1], %2, [%3];" :: "r"(dst), "l"(src), "r"(bytes), "r"(bar) : "memory");
}
__device__ __forceinline__ void ldsm4(uint32_t (&r)[4], uint32_t a) {
    asm volatile("ldmatrix.sync.aligned.m8n8.x4.shared.b16 {%0,%1,%2,%3}, [%4];" : "=r"(r[0]), "=r"(r[1]), "=r"(r[2]), "=r"(r[3]) : "r"(a) : "memory");
}
__device__ __forceinline__ void ldsm4t(uint32_t (&r)[4], uint32_t a) {
    asm volatile("ldmatrix.sync.aligned.m8n8.x4.trans.shared.b16 {%0,%1,%2,%3}, [%4];" : "=r"(r[0]), "=r"(r[1]), "=r"(r[2]), "=r"(r[3]) : "r"(a) : "memory");
}
__device__ __forceinline__ void stsm4(uint32_t a, uint32_t r0, uint32_t r1, uint32_t r2, uint32_t r3) {
    asm volatile("stmatrix.sync.aligned.m8n8.x4.shared.b16 [%0], {%1,%2,%3,%4};" :: "r"(a), "r"(r0), "r"(r1), "r"(r2), "r"(r3) : "memory");
}
__device__ __forceinline__ void stsm4t(uint32_t a, uint32_t r0, uint32_t r1, uint32_t r2, uint32_t r3) {
    asm volatile("stmatrix.sync.aligned.m8n8.x4.trans.shared.b16 [%0], {%1,%2,%3,%4};" :: "r"(a), "r"(r0), "r"(r1), "r"(r2), "r"(r3) : "memory");
}
__device__ __forceinline__ void stsm2t(uint32_t a, uint32_t r0, uint32_t r1) {
    asm volatile("stmatrix.sync.aligned.m8n8.x2.trans.shared.b16 [%0], {%1,%2};" :: "r"(a), "r"(r0), "r"(r1) : "memory");
}
__device__ __forceinline__ uint32_t movm_t(uint32_t v) { uint32_t r; asm volatile("movmatrix.sync.aligned.m8n8.trans.b16 %0, %1;" : "=r"(r) : "r"(v)); return r; }
__device__ __forceinline__ void mma16(float (&d)[4], uint32_t a0, uint32_t a1, uint32_t a2, uint32_t a3, uint32_t b0, uint32_t b1) {
    asm volatile("mma.sync.aligned.m16n8k16.row.col.f32.bf16.bf16.f32 {%0,%1,%2,%3}, {%4,%5,%6,%7}, {%8,%9}, {%0,%1,%2,%3};"
        : "+f"(d[0]), "+f"(d[1]), "+f"(d[2]), "+f"(d[3]) : "r"(a0), "r"(a1), "r"(a2), "r"(a3), "r"(b0), "r"(b1));
}
__device__ __forceinline__ void mma8(float (&d)[4], uint32_t a0, uint32_t a1, uint32_t b0) {
    asm volatile("mma.sync.aligned.m16n8k8.row.col.f32.bf16.bf16.f32 {%0,%1,%2,%3}, {%4,%5}, {%6}, {%0,%1,%2,%3};"
        : "+f"(d[0]), "+f"(d[1]), "+f"(d[2]), "+f"(d[3]) : "r"(a0), "r"(a1), "r"(b0));
}
__device__ __forceinline__ uint32_t mapa(uint32_t a, uint32_t r) { uint32_t o; asm volatile("mapa.shared::cluster.u32 %0, %1, %2;" : "=r"(o) : "r"(a), "r"(r)); return o; }
__device__ __forceinline__ void bar_sync(int id, int n) { asm volatile("bar.sync %0, %1;" :: "r"(id), "r"(n) : "memory"); }
__device__ __forceinline__ void bar_arrive(int id, int n) { asm volatile("bar.arrive %0, %1;" :: "r"(id), "r"(n) : "memory"); }
__device__ __forceinline__ uint64_t mkdesc(uint32_t addr, uint32_t lbo, uint32_t sbo) {
    return (uint64_t)((addr & 0x3FFFF) >> 4) | ((uint64_t)(lbo >> 4) << 16) | ((uint64_t)(sbo >> 4) << 32) | (1ull << 62);
}
#define WG_FENCE()  asm volatile("wgmma.fence.sync.aligned;" ::: "memory")
#define WG_COMMIT() asm volatile("wgmma.commit_group.sync.aligned;" ::: "memory")
#define WG_WAIT(n)  asm volatile("wgmma.wait_group.sync.aligned %0;" :: "n"(n) : "memory")

__device__ __forceinline__ void wgmma_ss_n192_tb(float (&d)[96], uint64_t a, uint64_t b, int acc) {
    asm volatile("{ .reg .pred p; setp.ne.b32 p, %98, 0;\n"
        "wgmma.mma_async.sync.aligned.m64n192k16.f32.bf16.bf16 {%0,%1,%2,%3,%4,%5,%6,%7,%8,%9,%10,%11,%12,%13,%14,%15,%16,%17,%18,%19,%20,%21,%22,%23,%24,%25,%26,%27,%28,%29,%30,%31,%32,%33,%34,%35,%36,%37,%38,%39,%40,%41,%42,%43,%44,%45,%46,%47,%48,%49,%50,%51,%52,%53,%54,%55,%56,%57,%58,%59,%60,%61,%62,%63,%64,%65,%66,%67,%68,%69,%70,%71,%72,%73,%74,%75,%76,%77,%78,%79,%80,%81,%82,%83,%84,%85,%86,%87,%88,%89,%90,%91,%92,%93,%94,%95}, %96, %97, p, 1, 1, 0, 1; }"
        : "+f"(d[0]), "+f"(d[1]), "+f"(d[2]), "+f"(d[3]), "+f"(d[4]), "+f"(d[5]), "+f"(d[6]), "+f"(d[7]), "+f"(d[8]), "+f"(d[9]), "+f"(d[10]), "+f"(d[11]), "+f"(d[12]), "+f"(d[13]), "+f"(d[14]), "+f"(d[15]), "+f"(d[16]), "+f"(d[17]), "+f"(d[18]), "+f"(d[19]), "+f"(d[20]), "+f"(d[21]), "+f"(d[22]), "+f"(d[23]), "+f"(d[24]), "+f"(d[25]), "+f"(d[26]), "+f"(d[27]), "+f"(d[28]), "+f"(d[29]), "+f"(d[30]), "+f"(d[31]), "+f"(d[32]), "+f"(d[33]), "+f"(d[34]), "+f"(d[35]), "+f"(d[36]), "+f"(d[37]), "+f"(d[38]), "+f"(d[39]), "+f"(d[40]), "+f"(d[41]), "+f"(d[42]), "+f"(d[43]), "+f"(d[44]), "+f"(d[45]), "+f"(d[46]), "+f"(d[47]), "+f"(d[48]), "+f"(d[49]), "+f"(d[50]), "+f"(d[51]), "+f"(d[52]), "+f"(d[53]), "+f"(d[54]), "+f"(d[55]), "+f"(d[56]), "+f"(d[57]), "+f"(d[58]), "+f"(d[59]), "+f"(d[60]), "+f"(d[61]), "+f"(d[62]), "+f"(d[63]), "+f"(d[64]), "+f"(d[65]), "+f"(d[66]), "+f"(d[67]), "+f"(d[68]), "+f"(d[69]), "+f"(d[70]), "+f"(d[71]), "+f"(d[72]), "+f"(d[73]), "+f"(d[74]), "+f"(d[75]), "+f"(d[76]), "+f"(d[77]), "+f"(d[78]), "+f"(d[79]), "+f"(d[80]), "+f"(d[81]), "+f"(d[82]), "+f"(d[83]), "+f"(d[84]), "+f"(d[85]), "+f"(d[86]), "+f"(d[87]), "+f"(d[88]), "+f"(d[89]), "+f"(d[90]), "+f"(d[91]), "+f"(d[92]), "+f"(d[93]), "+f"(d[94]), "+f"(d[95])
        : "l"(a), "l"(b), "r"(acc));
}

__device__ __forceinline__ void wgmma_ss_n128_tb(float (&d)[64], uint64_t a, uint64_t b, int acc) {
    asm volatile("{ .reg .pred p; setp.ne.b32 p, %66, 0;\n"
        "wgmma.mma_async.sync.aligned.m64n128k16.f32.bf16.bf16 {%0,%1,%2,%3,%4,%5,%6,%7,%8,%9,%10,%11,%12,%13,%14,%15,%16,%17,%18,%19,%20,%21,%22,%23,%24,%25,%26,%27,%28,%29,%30,%31,%32,%33,%34,%35,%36,%37,%38,%39,%40,%41,%42,%43,%44,%45,%46,%47,%48,%49,%50,%51,%52,%53,%54,%55,%56,%57,%58,%59,%60,%61,%62,%63}, %64, %65, p, 1, 1, 0, 1; }"
        : "+f"(d[0]), "+f"(d[1]), "+f"(d[2]), "+f"(d[3]), "+f"(d[4]), "+f"(d[5]), "+f"(d[6]), "+f"(d[7]), "+f"(d[8]), "+f"(d[9]), "+f"(d[10]), "+f"(d[11]), "+f"(d[12]), "+f"(d[13]), "+f"(d[14]), "+f"(d[15]), "+f"(d[16]), "+f"(d[17]), "+f"(d[18]), "+f"(d[19]), "+f"(d[20]), "+f"(d[21]), "+f"(d[22]), "+f"(d[23]), "+f"(d[24]), "+f"(d[25]), "+f"(d[26]), "+f"(d[27]), "+f"(d[28]), "+f"(d[29]), "+f"(d[30]), "+f"(d[31]), "+f"(d[32]), "+f"(d[33]), "+f"(d[34]), "+f"(d[35]), "+f"(d[36]), "+f"(d[37]), "+f"(d[38]), "+f"(d[39]), "+f"(d[40]), "+f"(d[41]), "+f"(d[42]), "+f"(d[43]), "+f"(d[44]), "+f"(d[45]), "+f"(d[46]), "+f"(d[47]), "+f"(d[48]), "+f"(d[49]), "+f"(d[50]), "+f"(d[51]), "+f"(d[52]), "+f"(d[53]), "+f"(d[54]), "+f"(d[55]), "+f"(d[56]), "+f"(d[57]), "+f"(d[58]), "+f"(d[59]), "+f"(d[60]), "+f"(d[61]), "+f"(d[62]), "+f"(d[63])
        : "l"(a), "l"(b), "r"(acc));
}

__device__ __forceinline__ void wgmma_rs_n32(float (&d)[16], const uint32_t (&a)[4], uint64_t b, int acc) {
    asm volatile("{ .reg .pred p; setp.ne.b32 p, %21, 0;\n"
        "wgmma.mma_async.sync.aligned.m64n32k16.f32.bf16.bf16 {%0,%1,%2,%3,%4,%5,%6,%7,%8,%9,%10,%11,%12,%13,%14,%15}, {%16,%17,%18,%19}, %20, p, 1, 1, 0; }"
        : "+f"(d[0]), "+f"(d[1]), "+f"(d[2]), "+f"(d[3]), "+f"(d[4]), "+f"(d[5]), "+f"(d[6]), "+f"(d[7]), "+f"(d[8]), "+f"(d[9]), "+f"(d[10]), "+f"(d[11]), "+f"(d[12]), "+f"(d[13]), "+f"(d[14]), "+f"(d[15])
        : "r"(a[0]), "r"(a[1]), "r"(a[2]), "r"(a[3]), "l"(b), "r"(acc));
}

__device__ __forceinline__ float warp_sum(float v) {
#pragma unroll
    for (int o = 16; o; o >>= 1) v += __shfl_xor_sync(0xffffffffu, v, o);
    return v;
}
__device__ __forceinline__ uint32_t add2(uint32_t a, uint32_t b) { uint32_t r; asm("add.rn.bf16x2 %0, %1, %2;" : "=r"(r) : "r"(a), "r"(b)); return r; }
__device__ __forceinline__ uint32_t mul2(uint32_t a, uint32_t b) { uint32_t r; asm("mul.rn.bf16x2 %0, %1, %2;" : "=r"(r) : "r"(a), "r"(b)); return r; }
__device__ __forceinline__ uint32_t amax2(uint32_t m, uint32_t v) { uint32_t r; asm("max.u16x2 %0, %1, %2;" : "=r"(r) : "r"(m), "r"(v & 0x7fff7fffu)); return r; }
__device__ __forceinline__ uint32_t amax_warp(uint32_t m) { return __reduce_max_sync(0xffffffffu, max(m & 0xffffu, m >> 16)); }
__device__ __forceinline__ void ln_norm(const uint32_t (&xv)[10], uint32_t (&nv)[10]) {
    float s0 = 0, s1 = 0;
#pragma unroll
    for (int i = 0; i < 10; i++) { s0 += lo_f(xv[i]); s1 += hi_f(xv[i]); }
    const float mean = warp_sum(s0 + s1) * (1.f / DM);
    float q0 = 0, q1 = 0;
#pragma unroll
    for (int i = 0; i < 10; i++) { const float d0 = lo_f(xv[i]) - mean, d1 = hi_f(xv[i]) - mean; q0 += d0 * d0; q1 += d1 * d1; }
    const float inv = inv_std(warp_sum(q0 + q1) * (1.f / DM));
    const uint32_t mb = pack2(-mean, -mean);
#pragma unroll
    for (int i = 0; i < 10; i++) { const uint32_t d = add2(xv[i], mb); nv[i] = pack2(lo_f(d) * inv, hi_f(d) * inv); }
}
__device__ __forceinline__ void ln_mod(const uint32_t (&xv)[10], const uint32_t (&sv)[10], const uint32_t (&tv)[10], uint32_t (&hv)[10]) {
    ln_norm(xv, hv);
#pragma unroll
    for (int i = 0; i < 10; i++) hv[i] = add2(mul2(hv[i], add2(sv[i], 0x3f803f80u)), tv[i]);
}
__device__ __forceinline__ uint32_t ld_rlx(const uint32_t* f) { uint32_t v; asm volatile("ld.relaxed.gpu.global.u32 %0, [%1];" : "=r"(v) : "l"(f) : "memory"); return v; }
__device__ __forceinline__ void bump(uint32_t* f) { asm volatile("red.relaxed.gpu.global.add.u32 [%0], 1;" :: "l"(f) : "memory"); }
#define NAP 100
#define GPU_FENCE() asm volatile("fence.acq_rel.gpu;" ::: "memory")
__device__ __forceinline__ void flag_wait(const uint32_t* f, uint32_t target) {
    for (int n = 0;; n++) {
        uint32_t v; asm volatile("ld.relaxed.gpu.global.u32 %0, [%1];" : "=r"(v) : "l"(f) : "memory");
        if (v >= target) break;
        if (n > (1 << 22)) __trap();
        __nanosleep(NAP);
    }
}
__device__ __forceinline__ void flag_add(uint32_t* f, uint32_t v = 1) { asm volatile("red.release.gpu.global.add.u32 [%0], %1;" :: "l"(f), "r"(v) : "memory"); }
constexpr int N_SIDE = 36;
__device__ __forceinline__ void flags_release(int lane) {
    uint32_t old = 0;
    if (lane == 0) asm volatile("atom.relaxed.gpu.global.add.u32 %0, [%1], 1;" : "=r"(old) : "l"(&g_flags.done) : "memory");
    if (__shfl_sync(0xffffffffu, old, 0) == 96 + N_SIDE - 1)
#pragma unroll 1
        for (int i = lane; i < (int)(sizeof(Flags) / 16); i += 32) ((uint4*)&g_flags)[i] = make_uint4(0, 0, 0, 0);
}

template <int NT> struct ModSlice {
    static constexpr int R = 2 * DM / NT;
    float sc[R]; uint4 wv[R];
    __device__ __forceinline__ void load(const bf16* wmod, const bf16* c, int col, int tid) {
        const bf16* wm = wmod + (tid >> 1) * (6 * DM) + col + (tid & 1) * 8;
#pragma unroll
        for (int i = 0; i < R; i++) {
            asm volatile("ld.global.nc.L1::no_allocate.L2::128B.v4.u32 {%0,%1,%2,%3}, [%4];" : "=r"(wv[i].x), "=r"(wv[i].y), "=r"(wv[i].z), "=r"(wv[i].w) : "l"(wm + i * (NT / 2) * (6 * DM)));
            sc[i] = __uint_as_float((uint32_t)__ldg((const unsigned short*)c + (tid >> 1) + NT / 2 * i) << 16);
        }
    }
    __device__ __forceinline__ void partial(uint32_t buf, int tid) {
        const int lane = tid & 31;
        float a[8] = {0, 0, 0, 0, 0, 0, 0, 0};
#pragma unroll
        for (int i = 0; i < R; i++) {
            const float f = bfr(__fdividef(sc[i], 1.f + __expf(-sc[i])));
            const uint32_t u[4] = {wv[i].x, wv[i].y, wv[i].z, wv[i].w};
#pragma unroll
            for (int e = 0; e < 4; e++) { a[2 * e] += f * lo_f(u[e]); a[2 * e + 1] += f * hi_f(u[e]); }
        }
#pragma unroll
        for (int h = 4; h; h >>= 1)
#pragma unroll
            for (int e = 0; e < h; e++) { const bool up = lane & (4 * h); a[e] = (up ? a[e + h] : a[e]) + __shfl_xor_sync(0xffffffffu, up ? a[e] : a[e + h], 4 * h); }
        a[0] += __shfl_xor_sync(0xffffffffu, a[0], 2);
        asm volatile("st.shared.f32 [%0], %1;" :: "r"(buf + (tid >> 5) * 64 + (lane & 1) * 32 + (lane >> 2) * 4), "f"(a[0]) : "memory");
    }
    static __device__ __forceinline__ uint32_t total(uint32_t buf, int lane) {
        float a0 = 0, a1 = 0;
#pragma unroll
        for (int i = 0; i < NT / 32; i++) { float x, y; asm volatile("ld.shared.v2.f32 {%0,%1}, [%2];" : "=f"(x), "=f"(y) : "r"(buf + i * 64 + (lane & 7) * 8) : "memory"); a0 += x; a1 += y; }
        return pack2(a0, a1);
    }
};

struct ChainMaps { CUtensorMap wq, wk, wv, wo, h2, wo15, o15, slab16; };
struct ChainArgs { const bf16 *x, *mem0, *c, *wmod, *wv, *wo, *wgate, *wup, *wdown; bf16* out; int D1, D2, DG; };
constexpr uint32_t SM_BASE = 1024;
#define NRING 10
#define XORD 0
#define B5AT 41
#define QCUT 0x54
#define NCH 0
#define XA 3
#define VT 1
#define OSEND 1
#define SPOLL 0
#define NPRE 9
#define REG_P 208
#define REG_L (504 - 2 * REG_P)
constexpr int WO_BLK = 7 * 4096;
constexpr int C_WV = 0, C_WO = 81920, C_XR = 167936, C_VP = C_XR + 7 * 4096, C_VX = C_XR + 8 * 4096, C_QX = C_VX + 4096, C_KX = C_QX + 4096,
              C_MEM = C_KX + 4096, C_OX = C_MEM + 9216, C_VM = C_OX + 3072, C_QM = C_VM + 1024, C_KM = C_QM + 1024, C_SC = C_KM + 1024, C_BAR = C_SC + 3840;
constexpr int CB_W = C_BAR, CB_W2 = C_BAR + 8, CB_SC = C_BAR + 16, CB_XD = C_BAR + 24, CB_VX = C_BAR + 32, CB_W3 = C_BAR + 40, CB_XM = C_BAR + 48, CB_OX = C_BAR + 56,
              CB_XF = C_BAR + 64, C_LAG = C_BAR + 96, C_UN = C_BAR + 100, C_MX = C_BAR + 112;
constexpr int C_SMEM = C_BAR + 128;
#define PROF(i)
#define PROFG(i)
#define PROFV(i, v)
static_assert(C_SMEM <= 232448, "chain shared memory");
__device__ __forceinline__ uint32_t umax3(uint32_t a, uint32_t b, uint32_t c) { return max(max(a, b), c); }
__device__ __forceinline__ void wait_until(uint32_t t) {
    asm volatile("{ .reg .pred p; .reg .s32 c; .reg .u64 d;\nU_%=: mov.u64 d, %%clock64; cvt.u32.u64 c, d; sub.s32 c, c, %0; setp.lt.s32 p, c, 0; @p bra.uni U_%=; }" :: "r"(t) : "memory");
}
__device__ __forceinline__ uint32_t gtime() { uint32_t c; asm volatile("mov.u32 %0, %%globaltimer_lo;" : "=r"(c)); return c; }
__device__ __forceinline__ uint32_t opaque(uint32_t v) { uint32_t r; asm volatile("shfl.sync.bfly.b32 %0, %1, 0, 31, -1;" : "=r"(r) : "r"(v)); return r; }
__device__ __forceinline__ uint32_t lds32(uint32_t a) { uint32_t v; asm volatile("ld.shared.u32 %0, [%1];" : "=r"(v) : "r"(a) : "memory"); return v; }
__device__ __forceinline__ float2 lds64f(uint32_t a) { float2 v; asm volatile("ld.shared.v2.f32 {%0,%1}, [%2];" : "=f"(v.x), "=f"(v.y) : "r"(a) : "memory"); return v; }
__device__ __forceinline__ float4 lds128f(uint32_t a) { float4 v; asm volatile("ld.shared.v4.f32 {%0,%1,%2,%3}, [%4];" : "=f"(v.x), "=f"(v.y), "=f"(v.z), "=f"(v.w) : "r"(a) : "memory"); return v; }
__device__ __forceinline__ void sts128f(uint32_t a, float x, float y, float z, float w) { asm volatile("st.shared.v4.f32 [%0], {%1,%2,%3,%4};" :: "r"(a), "f"(x), "f"(y), "f"(z), "f"(w) : "memory"); }
__device__ __forceinline__ void lds64(uint32_t (&v)[2], uint32_t a) { asm volatile("ld.shared.v2.u32 {%0,%1}, [%2];" : "=r"(v[0]), "=r"(v[1]) : "r"(a) : "memory"); }
__device__ __forceinline__ void mma16q(float (&d)[4], const uint32_t (&a)[4], uint32_t b0, uint32_t b1) { mma16(d, a[0], a[1], a[2], a[3], b0, b1); }
__device__ __forceinline__ uint32_t f16_to_bf16(uint32_t v) {
    float lo, hi; asm("{ .reg .f16 l, h; mov.b32 {l, h}, %2; cvt.f32.f16 %0, l; cvt.f32.f16 %1, h; }" : "=f"(lo), "=f"(hi) : "r"(v));
    return pack2(lo, hi);
}
__device__ __forceinline__ uint32_t pack2h(float lo, float hi) { uint32_t r; asm("cvt.rn.f16x2.f32 %0, %1, %2;" : "=r"(r) : "f"(hi), "f"(lo)); return r; }
#define SPLIT 1
__device__ __forceinline__ void cut(uint32_t never, int n) {
    asm volatile("{ .reg .pred p; setp.ne.u32 p, %0, %1; @p bra.uni C_%=; trap; C_%=: }" :: "r"(never), "r"(n) : "memory");
}
__device__ __forceinline__ void pin(uint32_t never, uint32_t a, uint32_t b, uint32_t c, uint32_t d) {
    asm volatile("{ .reg .pred p; setp.eq.u32 p, %0, 0; @p st.shared.v4.u32 [%0], {%1,%2,%3,%4}; }" :: "r"(never), "r"(a), "r"(b), "r"(c), "r"(d) : "memory");
}
__device__ __forceinline__ void pin0(uint32_t never) {
    asm volatile("{ .reg .pred p; setp.eq.u32 p, %0, 0; @p st.shared.u32 [%0], 0; }" :: "r"(never) : "memory");
}
#define ELECTED(txt) "{ .reg .pred e; elect.sync _|e, -1; @e " txt " }"
__device__ __forceinline__ void w_bulk_s2g(void* dst, uint32_t src, int bytes) {
    asm volatile(ELECTED("cp.async.bulk.global.shared::cta.bulk_group [%0], [%1], %2;") :: "l"(dst), "r"(src), "r"(bytes) : "memory");
}
__device__ __forceinline__ void w_bump(uint32_t* f) { asm volatile(ELECTED("red.relaxed.gpu.global.add.u32 [%0], 1;") :: "l"(f) : "memory"); }
__device__ __forceinline__ void w_expect(uint32_t bar, int bytes) { asm volatile(ELECTED("mbarrier.arrive.expect_tx.shared::cta.b64 _, [%0], %1;") :: "r"(bar), "r"(bytes) : "memory"); }
__device__ __forceinline__ void w_flag_wait(const uint32_t* f, uint32_t target) {
    asm volatile("{ .reg .pred p; .reg .u32 n, v; mov.u32 n, 0;\n"
                 "F_%=: ld.relaxed.gpu.global.u32 v, [%0]; setp.ge.u32 p, v, %1; vote.sync.all.pred p, p, -1; @p bra.uni G_%=;\n"
                 "nanosleep.u32 %2; add.u32 n, n, 1; setp.lt.u32 p, n, 0x400000; @p bra.uni F_%=;\ntrap;\nG_%=: }" :: "l"(f), "r"(target), "n"(NAP) : "memory");
}
#define BULK_COMMIT()    asm volatile("cp.async.bulk.commit_group;" ::: "memory")
#define BULK_WAIT()      asm volatile("cp.async.bulk.wait_group 0;" ::: "memory")
#define BULK_WAIT_READ() asm volatile("cp.async.bulk.wait_group.read 0;" ::: "memory")
#define PROXY_FENCE()    asm volatile("fence.proxy.async.shared::cta;" ::: "memory")
__device__ __forceinline__ void send16(uint32_t dst, uint32_t bar, float a, float b, float c, float d) {
    asm volatile("st.async.shared::cluster.mbarrier::complete_tx::bytes.v4.f32 [%0], {%1,%2,%3,%4}, [%5];" :: "r"(dst), "f"(a), "f"(b), "f"(c), "f"(d), "r"(bar) : "memory");
}
__device__ __forceinline__ void send8(uint32_t dst, uint32_t bar, uint32_t a, uint32_t b) {
    asm volatile("st.async.shared::cluster.mbarrier::complete_tx::bytes.v2.b32 [%0], {%1,%2}, [%3];" :: "r"(dst), "r"(a), "r"(b), "r"(bar) : "memory");
}

__device__ __forceinline__ void seg_done(int n, int head) {
    if (n >= 60 || (n & 3) == 3) { GPU_FENCE(); w_bump(n >= 60 ? &g_flags.seg[(n - 60) * 32 + head] : &g_flags.qk[n >> 2]); }
}
__device__ __forceinline__ uint32_t x_base(int wg, uint32_t small, int sh) { return (uint32_t)mkdesc(SM_BASE + C_XR, 16, 1024) + wg * 256 + (small >> sh); }
__device__ __forceinline__ void x_chunk(float (&acc)[16], const uint32_t (&wa)[40][4], uint32_t xl, int a0, int i, int first) {
#pragma unroll
    for (int ks = 0; ks < 4; ks++)
        wgmma_rs_n32(acc, wa[a0 + 4 * i + ks], mkdesc(0, 0, 1024) | (uint32_t)(xl + (((i ? (i - 1) * 8192 : C_MEM - C_XR) + ks * 32) >> 4)), !(first && ks == 0));
}
__device__ __forceinline__ void x_part(float (&acc)[16], const uint32_t (&wa)[40][4], uint32_t sm, int n, int wg, int w, uint32_t ln, uint32_t small) {
    const int s = n - 1; (void)s;
    uint32_t giv[8];
    auto chunk = [&](int a0, int i, int first) { x_chunk(acc, wa, x_base(wg, small, a0 ? 21 : 22), a0, i, first); };
    mbar_wait(sm + CB_XM, n & 1);
    if (n) bar_sync(5, 384);
    if (wg == 0 && w == 0) PROF(12);
    WG_FENCE();
#pragma unroll
    for (int i = 1 + XA; i < 5; i++) chunk(20, i, 0);
    chunk(20, 0, 0);
    WG_COMMIT();
    if (n) {
        if (wg == 1 && w == 1) BULK_WAIT();
        bar_sync(8, 256);
    }
    if (wg == 0 && w == 0) PROF(18);
    const uint32_t xb = sm + w * 512 + ln * 16, xw = xb + C_KX - wg * 4096, xr = xb + C_QX + wg * 4096;
    WG_WAIT(0);
#pragma unroll
    for (int i = 0; i < 8; i++) asm volatile("cvt.rn.bf16x2.f32 %0, %1, %2;" : "=r"(giv[i]) : "f"(acc[2 * i + 1]), "f"(acc[2 * i]));
#pragma unroll
    for (int p = 0; p < 2; p++) asm volatile("st.shared.v4.u32 [%0], {%1,%2,%3,%4};" :: "r"(xw + p * 2048), "r"(giv[4 * p]), "r"(giv[4 * p + 1]), "r"(giv[4 * p + 2]), "r"(giv[4 * p + 3]) : "memory");
    bar_arrive(12 + wg, 256);
    WG_FENCE();
    chunk(0, 0, 1);
    WG_COMMIT();
    chunk(0, 1, 0);
    if (XORD) chunk(0, 2, 0);
    bar_sync(13 - wg, 256);
#pragma unroll
    for (int p = 0; p < 2; p++) asm volatile("ld.shared.v4.u32 {%0,%1,%2,%3}, [%4];" : "=r"(giv[4 * p]), "=r"(giv[4 * p + 1]), "=r"(giv[4 * p + 2]), "=r"(giv[4 * p + 3]) : "r"(xr + p * 2048) : "memory");
    WG_COMMIT(); WG_WAIT(1); bar_arrive(9, 384);
    WG_FENCE();
    if (!XORD) chunk(0, 2, 0);
    chunk(0, 3, 0); chunk(0, 4, 0);
    WG_COMMIT();
    const uint32_t r = ln & 7, mi = ln >> 3, dst = sm + (wg == 0 ? C_QX : C_KX) + ((mi >> 1) * 8 + r) * 128 + (((2 * w + (mi & 1)) ^ r) << 4);
    pin(xb, giv[0], giv[4], dst, 0);
    bar_sync(10 + wg, 128);
    WG_WAIT(0);
    if (wg == 0 && w == 0) PROF(30);
    if (w == 0 && ln < 3) mbar_arrive_remote(mapa(sm + CB_XD, ln));
#pragma unroll
    for (int i = 0; i < 8; i++) { acc[2 * i] += lo_f(giv[i]); acc[2 * i + 1] += hi_f(giv[i]); }
#pragma unroll
    for (int p = 0; p < 2; p++)
        stsm4t(dst + p * 2048, pack2(acc[8 * p], acc[8 * p + 1]), pack2(acc[8 * p + 2], acc[8 * p + 3]), pack2(acc[8 * p + 4], acc[8 * p + 5]), pack2(acc[8 * p + 6], acc[8 * p + 7]));
    if (wg == 0 && w == 0) PROF(11);
}
__device__ __forceinline__ void x_fill(const ChainMaps& mp, uint32_t sm, int n, int j) {
    mbar_expect(sm + CB_XF, 24576);
    asm volatile("cp.async.bulk.tensor.3d.shared::cluster.global.mbarrier::complete_tx::bytes.multicast::cluster [%0], [%1, {0, %3, %4}], [%2], %5;"
        :: "r"(sm + C_XR + j * 8192), "l"((uint64_t)&mp.h2), "r"(sm + CB_XF), "r"(n * SEG), "r"(2 + 2 * j), "h"((uint16_t)7) : "memory");
}
__device__ __forceinline__ void x_rest(const ChainMaps& mp, uint32_t sm, int n) {
    mbar_expect(sm + CB_XM, 16384);
    tma3d(sm + C_XR + 6 * 4096, &mp.h2, n * SEG, 8, sm + CB_XM); tma3d(sm + C_MEM, &mp.h2, n * SEG, 0, sm + CB_XM);
}

#define WPOS 15
#define WP 8
#define WOPF 30
#define SPF 0
#define SDEL 0
#define EORD 1
#define BPOS 1
#define TPF 1
#define B_LATE 14
constexpr int E_B = C_WO, E_STG = 196608, EB_A = 229376, EB_B = C_BAR + 80, EB_REL = C_BAR + 104;
__device__ __forceinline__ uint32_t e_slot(int wg, int c) { return wg && c == 2 ? E_B + 98304 : wg * 49152 + c * 16384; }
constexpr int T_WG = 0, T_WU = 20480, T_WD = 40960, T_X = 65536, T_RED = 77824, T_KEY = 86016;
__device__ __forceinline__ void wo_half(const ChainMaps& mp, uint32_t sm, int blk, int c) {
    if (blk < 80 && elect()) { mbar_expect(sm + EB_B + 8 * c, 49152); tma3d(sm + E_B + c * 49152, &mp.wo15, blk / 5 * 384 + c * 192, blk % 5 * 2, sm + EB_B + 8 * c); }
}
__device__ __forceinline__ void end_loads(const ChainMaps& mp, const ChainArgs& ar, uint32_t sm, int blk, int wg) {
    const uint32_t bar = sm + EB_A + wg * 48;
    const int kp = blk / 5;
    if (elect()) {
#pragma unroll 1
        for (int c = 0; c < 6; c++) mbar_init(bar + 8 * c, c < 3 ? 1 : 4);
        PROXY_FENCE();
    }
    __syncwarp();
    bar_arrive(5, 384);
    if (EORD) bar_sync(6, 96);
    if (blk >= 80) {
        if (TPF && elect()) {
#pragma unroll 1
            for (int c = 0; c < 3; c++) asm volatile("cp.async.bulk.prefetch.L2.global [%0], 61440;" :: "l"((c == 0 ? ar.wgate : c == 1 ? ar.wup : ar.wdown) + ((blk - 80) * 2 + wg) * 30720) : "memory");
        }
        return;
    }
    const uint64_t ef = policy_stream();
#pragma unroll 1
    for (int b = B_LATE; b < 16; b++) {
        w_flag_wait(b == 15 ? &g_flags.half[kp * 2 + wg] : &g_flags.pair[b * 16 + kp], b == 15 ? 2 : 4);
#pragma unroll 1
        for (int c = 0; c < 3; c++) {
            if (b > B_LATE) mbar_wait(bar + 24 + 8 * c, (b - B_LATE - 1) & 1);
            if (elect()) { mbar_expect(bar + 8 * c, 16384); tma3d_ef(sm + e_slot(wg, c), &mp.o15, b * 128 + wg * 64, kp * 6 + c * 2, bar + 8 * c, ef); }
            __syncwarp();
        }
    }
}
__device__ __forceinline__ void last_blocks(const ChainMaps& mp, const ChainArgs& ar, uint32_t sm, int blk, int tid) {
    const int warp = __shfl_sync(0xffffffffu, tid >> 5, 0), lane = tid & 31, wg = warp >> 2, w = warp & 3, kp = blk / 5, ct = blk % 5;
    const uint32_t bar = sm + EB_A + wg * 48, stg = sm + E_STG + warp * 4096;
    const uint64_t ef = policy_stream();
    bar_sync(5, 384);
    float acc[64];
#pragma unroll
    for (int n = 0; n < 64; n++) acc[n] = 0.f;
#pragma unroll 1
    for (int b = B_LATE; b < 16 && blk < 80; b++) {
#pragma unroll 1
        for (int c = 0; c < 6; c++) {
            mbar_wait(sm + EB_B + 8 * (c >= 3), 0); mbar_wait(bar + 8 * (c >> 1), (b - B_LATE) & 1);
            const uint64_t da = mkdesc(SM_BASE + e_slot(wg, c >> 1) + (c & 1) * 8192, 16, 1024), db = mkdesc(SM_BASE + E_B + (c >= 3 ? 24576 : 0) + c * 8192, 24576, 1024);
            WG_FENCE();
#pragma unroll
            for (int ks = 0; ks < 4; ks++) wgmma_ss_n128_tb(acc, da + ks * 2, db + ks * 128, c | ks);
            WG_COMMIT();
            WG_WAIT(1);
            if ((c & 1) == 0 && c && elect()) mbar_arrive(bar + 16 + 4 * c);
        }
        WG_WAIT(0);
        if (elect()) mbar_arrive(bar + 40);
        const int r = lane & 7, mi = lane >> 3;
#pragma unroll
        for (int p = 0; p < 8; p++) {
            const int oc = 2 * p + (mi >> 1);
            stsm4(stg + (oc >> 3) * 2048 + ((mi & 1) * 8 + r) * 128 + (((oc & 7) ^ r) << 4), pack2(acc[8 * p], acc[8 * p + 1]), pack2(acc[8 * p + 2], acc[8 * p + 3]),
                  pack2(acc[8 * p + 4], acc[8 * p + 5]), pack2(acc[8 * p + 6], acc[8 * p + 7]));
        }
        PROXY_FENCE();
        __syncwarp();
        if (elect()) tma3d_store(&mp.slab16, (b * KSPLIT + kp) * 128 + warp * 16, ct * 2, stg, ef, false);
        BULK_COMMIT(); BULK_WAIT();
        if (w) bar_arrive(12 + wg, 128); else { bar_sync(12 + wg, 128); GPU_FENCE(); w_bump(b < 14 ? &g_flags.o[b] : &g_flags.fin[((b - 14) * 2 + wg) * 32]); }
    }
    bar_sync(8, 256);
    const int o = (tid >> 1) * FF + blk * 16 + (tid & 1) * 8;
    const bf16 *pg = ar.wgate + o, *pu = ar.wup + o, *pd = ar.wdown + tid * DM + (blk < 80 ? blk : 0) * 8;
#pragma unroll
    for (int i = 0; i < 16; i++)
        asm volatile("cp.async.cg.shared.global [%0], [%1], 16;" :: "r"(sm + E_B + i * 4096 + tid * 16), "l"(i < 5 ? pg + i * 128 * FF : i < 10 ? pu + (i - 5) * 128 * FF : pd + (i - 10) * 256 * DM) : "memory");
}
__device__ __forceinline__ void mod_tail(const ChainArgs& ar, const uint32_t tb, const uint32_t bar, const int blk, const int tid) {
#define TPROF(i)
    const int warp = __shfl_sync(0xffffffffu, tid >> 5, 0), lane = tid & 31, r = lane & 7, mi = lane >> 3;
    const uint32_t kb = tb + T_KEY;
    {
        uint32_t k[8];
        for (int n = 0;; n++) {
#pragma unroll
            for (int i = 0; i < 2; i++) asm volatile("ld.relaxed.gpu.global.v4.u32 {%0,%1,%2,%3}, [%4];" : "=r"(k[4 * i]), "=r"(k[4 * i + 1]), "=r"(k[4 * i + 2]), "=r"(k[4 * i + 3]) : "l"(g_key + warp * 256 + i * 128 + lane * 4) : "memory");
            if (__all_sync(0xffffffffu, (k[0] & k[1] & k[2] & k[3] & k[4] & k[5] & k[6] & k[7] & S_TOK) != 0)) break;
            if (n > (1 << 22)) __trap();
            __nanosleep(NAP);
        }
        const uint32_t m = __reduce_max_sync(0xffffffffu, max(umax3(k[0], k[1], k[2]), max(umax3(k[3], k[4], k[5]), max(k[6], k[7]))));
        asm volatile("st.shared.u32 [%0], %1; st.shared.u32 [%2], 0;" :: "r"(kb + warp * 4), "r"(m), "r"(kb + 32) : "memory");
        asm volatile("cp.async.wait_all;" ::: "memory");
        bar_sync(1, 256);
        TPROF(1);
        const uint32_t low = __reduce_min_sync(0xffffffffu, lds32(kb + r * 4));
        uint32_t cnt = 0;
#pragma unroll
        for (int i = 0; i < 8; i++) cnt += k[i] >= low ? 4 : 0;
        if (cnt) {
            uint32_t a; asm volatile("atom.shared.add.u32 %0, [%1], %2;" : "=r"(a) : "r"(kb + 32), "r"(cnt) : "memory");
#pragma unroll
            for (int i = 0; i < 8; i++) if (k[i] >= low) { asm volatile("st.shared.u32 [%0], %1;" :: "r"(kb + 512 + a), "r"(k[i]) : "memory"); a += 4; }
        }
        if (tid == 0) mbar_arrive(bar);
        bar_sync(1, 256);
        const int nc = lds32(kb + 32);
#pragma unroll 1
        for (int c = lane * 4; c < nc; c += 128) {
            const uint32_t me = lds32(kb + 512 + c);
            int rank = 0;
#pragma unroll 2
            for (int e = 0; e < nc; e += 16) {
                const float4 z = lds128f(kb + 512 + e);
                rank += (__float_as_uint(z.x) > me) + (e + 4 < nc && __float_as_uint(z.y) > me) + (e + 8 < nc && __float_as_uint(z.z) > me) + (e + 12 < nc && __float_as_uint(z.w) > me);
            }
            if (rank < 8) asm volatile("st.shared.u32 [%0], %1;" :: "r"(kb + 64 + (warp * 8 + rank) * 4), "r"(me) : "memory");
        }
        __syncwarp();
    }
    const uint32_t k0 = lds32(kb + 64 + (warp * 8 + r) * 4), k1 = lds32(kb + 64 + (warp * 8 + (lane >> 2)) * 4);
    TPROF(2);
    const int trow = ~k1 & (S_TOK - 1), tcol = (blk < 80 ? blk : 0) * 8 + (lane & 3) * 2;
    uint2 xb[5];
#pragma unroll
    for (int h = 0; h < 5; h++) xb[h] = __ldcg((const uint2*)(g_h2 + trow * DM + (warp * 5 + h) * 16 + (lane & 3) * 4));
    const uint32_t fx1 = __ldcg((const uint32_t*)(g_x1 + trow * DM + tcol)), fh2 = __ldcg((const uint32_t*)(g_h2 + trow * DM + tcol)),
                   fgb = __ldcg((const uint32_t*)(g_mod + 5 * DM + tcol));
    const float fr = __uint_as_float(((int)k1 < 0 ? k1 ^ 0x80000000u : ~k1) & 0xffff0000u);
    {
        float dg[4] = {0, 0, 0, 0}, du[4] = {0, 0, 0, 0};
        uint32_t ag[5][4], au[5][4];
#pragma unroll
        for (int h = 0; h < 5; h++) {
            const uint32_t o = tb + ((warp * 5 + h) * 16 + (r >> 1) * 4 + (mi >> 1) * 2 + (r & 1)) * 32 + (mi & 1) * 16;
            ldsm4t(ag[h], o + T_WG); ldsm4t(au[h], o + T_WU);
        }
#pragma unroll
        for (int h = 0; h < 5; h++) { mma16q(dg, ag[h], xb[h].x, xb[h].y); mma16q(du, au[h], xb[h].x, xb[h].y); }
        TPROF(3);
        sts128f(tb + T_RED + warp * 1024 + lane * 16, dg[0], dg[1], dg[2], dg[3]); sts128f(tb + T_RED + warp * 1024 + 512 + lane * 16, du[0], du[1], du[2], du[3]);
    }
    bar_sync(1, 256);
    if (warp < 2) {
        float g2[2] = {0, 0}, u2[2] = {0, 0};
#pragma unroll
        for (int i = 0; i < 8; i++) {
            const float2 a = lds64f(tb + T_RED + i * 1024 + lane * 16 + warp * 8), b = lds64f(tb + T_RED + i * 1024 + 512 + lane * 16 + warp * 8);
            g2[0] += a.x; g2[1] += a.y; u2[0] += b.x; u2[1] += b.y;
        }
        float y[2];
#pragma unroll
        for (int i = 0; i < 2; i++) { const float gq = bfr(g2[i]); y[i] = bfr(__fdividef(gq, 1.f + __expf(-gq))) * bfr(u2[i]); }
        asm volatile("st.relaxed.gpu.global.u32 [%0], %1;" :: "l"(g_gu + (blk >> 1) * 128 + lane * 4 + warp * 2 + (blk & 1)), "r"(movm_t(pack2(y[0], y[1]))) : "memory");
    }
    TPROF(4);
    if (blk < 80) {
        uint32_t a[6][4], b[6][4];
#pragma unroll
        for (int k2 = 0; k2 < 6; k2++) ldsm4t(b[k2], tb + T_WD + (warp * 6 + k2) * 512 + lane * 16);
        for (int n = 0;; n++) {
            uint32_t m = 0;
#pragma unroll
            for (int k2 = 0; k2 < 6; k2++) asm volatile("ld.relaxed.gpu.global.v4.u32 {%0,%1,%2,%3}, [%4];" : "=r"(a[k2][0]), "=r"(a[k2][1]), "=r"(a[k2][2]), "=r"(a[k2][3]) : "l"(g_gu + (warp * 6 + k2) * 128 + lane * 4) : "memory");
#pragma unroll
            for (int k2 = 0; k2 < 6; k2++) m = umax3(umax3(m, a[k2][0], a[k2][1]), a[k2][2], a[k2][3]);
            if (!__any_sync(0xffffffffu, m == ~0u)) break;
            if (n > (1 << 22)) __trap();
        }
        TPROF(5);
        float d[2][4] = {{0, 0, 0, 0}, {0, 0, 0, 0}};
#pragma unroll
        for (int k2 = 0; k2 < 6; k2++) { mma16q(d[0], a[k2], b[k2][0], b[k2][1]); mma16q(d[1], a[k2], b[k2][2], b[k2][3]); }
        asm volatile("st.shared.v2.f32 [%0], {%1,%2};" :: "r"(tb + T_X + warp * 256 + lane * 8), "f"(d[0][0] + d[1][2]), "f"(d[0][1] + d[1][3]) : "memory");
        bar_sync(1, 256);
        if (warp == 0) {
            float y0 = 0, y1 = 0;
#pragma unroll
            for (int i = 0; i < 8; i++) { const float2 z = lds64f(tb + T_X + i * 256 + lane * 8); y0 += z.x; y1 += z.y; }
            const float sg = __fdividef(1.f, 1.f + __expf(-fr));
            *(uint32_t*)(ar.out + trow * DM + tcol) = add2(fx1, mul2(fgb, add2(fh2, mul2(pack2(y0, y1), pack2(sg, sg)))));
        }
    }
    TPROF(6);
}

__global__ void __cluster_dims__(3, 1, 1) __launch_bounds__(384, 1) k_chain(const __grid_constant__ ChainMaps mp, const __grid_constant__ ChainArgs ar) {
    const int D1 = ar.D1, DG = ar.DG;
    extern __shared__ __align__(1024) uint8_t smraw[];
    const uint32_t sm = SM_BASE + ((blockIdx.x % 3) << 24);
    if (smem_u32(smraw) != sm) __trap();
    uint32_t tid; asm volatile("mov.u32 %0, %%tid.x;" : "=r"(tid));
    const int warp = __shfl_sync(0xffffffffu, tid >> 5, 0), lane = tid & 31, wg = warp >> 2, w = warp & 3;
    const int blk = blockIdx.x, head = blk / 3, j = blk % 3;
    const int col0 = head * DH + j * 64;
    asm volatile("griddepcontrol.launch_dependents;");
#define PPROF(i)
    const int r = lane & 7, mi = lane >> 3;
    const uint32_t memrd = opaque(sm + C_MEM + lane * 16);
    if (wg < 2) {
        {
            uint32_t xv[3][10];
            const int row = blk * 8 + warp, nq = row < S_TOK - 1536 ? 3 : 2;
#pragma unroll
            for (int i = 0; i < 15; i++) {
                const uint2 v = __ldcs((const uint2*)(ar.x + (row + (i < 10 || nq == 3 ? i / 5 * 768 : 0)) * DM + lane * 4 + i % 5 * 128));
                xv[i / 5][i % 5 * 2] = v.x; xv[i / 5][i % 5 * 2 + 1] = v.y;
            }
            if (tid == 32) {
#pragma unroll 1
                for (int c = 0; c < 14; c++) if (c != 12) mbar_init(sm + C_BAR + 8 * c, c == 2 ? 5 : c == 3 ? 6 : 1);
                asm volatile("fence.mbarrier_init.release.cluster;" ::: "memory");
                mbar_expect(sm + CB_SC, 2560); mbar_expect(sm + CB_OX, 2048);
            }
            if (warp == 2) {
                const uint32_t f = blk >= 28 ? ~0u : 0u;
                ((uint4*)g_acc)[blk * 32 + lane] = make_uint4(0, 0, 0, 0);
                if (blk < 76) (blk < 12 ? (uint4*)g_stamp + blk * 32 : blk < 28 ? (uint4*)g_key + (blk - 12) * 32 : (uint4*)g_gu + (blk - 28) * 32)[lane] = make_uint4(f, f, f, f);
            }
            __syncwarp();
            asm volatile("barrier.cluster.arrive.relaxed.aligned;" ::: "memory");
            PPROF(8);
#pragma unroll 1
            for (int q = 0; q < 3; q++) {
                uint32_t nv[10];
                ln_norm(xv[0], nv);
#pragma unroll
                for (int i = 0; i < 10; i++) { xv[0][i] = xv[1][i]; xv[1][i] = xv[2][i]; xv[2][i] = nv[i]; }
            }
            PPROF(9);
            if (warp < 5) {
                uint4 u;
                for (int n = 0;; n++) {
                    asm volatile("ld.relaxed.gpu.global.v4.u32 {%0,%1,%2,%3}, [%4];" : "=r"(u.x), "=r"(u.y), "=r"(u.z), "=r"(u.w) : "l"(g_flags.mod1 + tid * 4) : "memory");
                    if (__all_sync(0xffffffffu, u.x && u.y && u.z && u.w)) break;
                    cut(n, 1 << 22);
                }
                asm volatile("st.shared.v4.u32 [%0], {%1,%2,%3,%4};" :: "r"(sm + C_KX + tid * 16), "r"(~u.x), "r"(~u.y), "r"(~u.z), "r"(~u.w) : "memory");
            }
            bar_sync(8, 256);
            PPROF(2);
            uint32_t m = 0;
#pragma unroll
            for (int i = 0; i < 5; i++) {
                uint32_t t[2], u[2];
                lds64(t, sm + C_KX + lane * 8 + i * 256); lds64(u, sm + C_KX + 1280 + lane * 8 + i * 256);
                u[0] = add2(u[0], 0x3f803f80u); u[1] = add2(u[1], 0x3f803f80u);
                m = amax2(amax2(amax2(amax2(m, t[0]), u[0]), t[1]), u[1]);
#pragma unroll
                for (int q = 0; q < 3; q++)
                    if (q < nq) *(uint2*)(g_h + (row + q * 768) * DM + lane * 4 + i * 128) = make_uint2(add2(mul2(xv[q][2 * i], u[0]), t[0]), add2(mul2(xv[q][2 * i + 1], u[1]), t[1]));
            }
            asm volatile("st.shared.u32 [%0], %1;" :: "r"(sm + C_LAG), "r"((amax_warp(m) >> 7) + 1) : "memory");
            bar_sync(8, 256);
            if (tid == 0) flag_add(&g_flags.h);
            __syncwarp();
            bar_arrive(2, 288);
            PPROF(3);
            asm volatile("barrier.cluster.wait.aligned;" ::: "memory");
        }
        asm volatile("setmaxnreg.inc.sync.aligned.u32 %0;" :: "n"(REG_P));
        uint32_t wa[40][4];
        mbar_wait(sm + CB_W, 0);
#pragma unroll
        for (int ks = 0; ks < 40; ks++)
            ldsm4t(wa[ks], sm + ((wg == 0) == (ks < 20) ? C_WV : C_WO) + ((mi >> 1) * 8 + r) * 128 + (((2 * w + (mi & 1)) ^ r) << 4) + (ks % 20 / 4 * 8 + 4 * wg + (ks & 3)) * 2048);
        PPROF(5);
        bar_arrive(1, 288);
        const uint32_t qst = opaque(sm + (wg == 0 ? C_QM : C_KM) + (2 * w + (mi & 1)) * 128 + r * 16);
        const uint32_t vrd = opaque(sm + C_WV + ((mi >> 1) * 8 + r) * 128 + (((2 * w + (mi & 1)) ^ r) << 4) + 4 * wg * 2048);
        const uint32_t mrd = opaque(memrd + wg * 1024);
        float acc[16];
        auto fb = [&](int n) { return mrd + (n >> 1) * 2048 + (n & 1) * 512; };
        auto fa = [&](int k) { return vrd + (k >> 2) * 16384 + (k & 3) * 2048; };
        auto qk_out = [&](int n) {
            uint8_t* rec = g_att + (n * NH + head) * AT_REC;
            w_bulk_s2g(rec + j * 8192, sm + C_QX, 8192); w_bulk_s2g(rec + AT_KM + j * 1024, sm + C_KM, 1024);
            BULK_COMMIT();
        };
        for (int s = -1;; s++) {
          if (s >= 0) {
            x_part(acc, wa, sm, s, wg, w, opaque(mrd) >> 4 & 31, s + ar.D2);
            if (s == 0) mbar_wait(sm + CB_W2, 0);
            uint32_t b[3][4], a[4][4];
#pragma unroll
            for (int i = 0; i < 4; i++) ldsm4t(a[i], fa(4 + i));
            cut(s + ar.D2, 0);
            bar_sync(1, 384);
            if (warp == 0) { PROF(0); PROFG(24); }
            float dv[4] = {0, 0, 0, 0};
            const uint32_t xb = mrd - wg * 1024 - (C_MEM - C_VP) + w * 512;
            {
                float d[2][4] = {{0, 0, 0, 0}, {0, 0, 0, 0}}, g[2][4] = {{0, 0, 0, 0}, {0, 0, 0, 0}};
                ldsm4t(b[0], fb(0)); pin0(mrd); ldsm4t(b[1], fb(1)); pin0(mrd);
#pragma unroll
                for (int n = 0; n < 10; n++) {
                    const int c1 = n >= 10 - NCH;
                    if (n < 8) ldsm4t(b[(n + 2) % 3], fb(n + 2));
#pragma unroll
                    for (int e = 0; e < 2; e++) {
                        mma16q(g[e & c1], wa[20 + 2 * n + e], b[n % 3][2 * e], b[n % 3][2 * e + 1]); mma16q(d[e & c1], wa[2 * n + e], b[n % 3][2 * e], b[n % 3][2 * e + 1]);
                        if (n >= 2 && n < 10 - VT) mma16q(dv, a[(2 * n + e) & 3], b[n % 3][2 * e], b[n % 3][2 * e + 1]);
                        if (n >= 2 && n < 8) ldsm4t(a[(2 * n + e) & 3], fa(2 * n + 4 + e));
                    }
                    if (QCUT >> n & 1) cut(s + ar.D2, 1 + n);
                }
                const float un = __uint_as_float(lds32(sm + C_UN));
                sts128f(xb - 4096 + wg * 2048, g[0][0] + g[1][0], g[0][1] + g[1][1], g[0][2] + g[1][2], g[0][3] + g[1][3]);
#pragma unroll
                for (int k = 20 - 2 * VT; k < 20; k++) mma16q(dv, a[k & 3], b[k / 2 % 3][2 * (k & 1)], b[k / 2 % 3][2 * (k & 1) + 1]);
                bar_sync(8, 256);
                const float4 z = lds128f(xb - 4096 + (wg ^ 1) * 2048);
                sts128f(xb + wg * 2048, dv[0], dv[1], dv[2], dv[3]);
                stsm2t(qst, pack2((d[0][0] + d[1][0] + z.x) * un, (d[0][1] + d[1][1] + z.y) * un), pack2((d[0][2] + d[1][2] + z.z) * un, (d[0][3] + d[1][3] + z.w) * un));
            }
            bar_arrive(2, 384);
            if (w == 0) PROF(1 + wg);
            if (s + 1 == NSEG) break;
          }
          if (warp == 3 && s >= 0)
              asm volatile(ELECTED("st.relaxed.gpu.global.u32 [%0], %1;") :: "l"(g_stamp + (s & 3) * 384 + (blk >> 3) * 32 + (blk & 7)), "r"((gtime() & ~31u) | ((s >> 2) + 1)) : "memory");
          mbar_wait(sm + CB_XF, (s + 1) & 1);
          if (s >= 0) bar_sync(7, 384);
          WG_FENCE();
#pragma unroll
          for (int i = 0; i < 16; i++) acc[i] = 0.f;
#pragma unroll
          for (int i = 1; i <= XA; i++) x_chunk(acc, wa, x_base(wg, s + ar.D2, 20), 20, i, i == 1);
          WG_COMMIT();
          WG_WAIT(0);
          PROXY_FENCE();
          if (s >= 0) {
            if (warp == 5) bar_sync(8, 256); else bar_arrive(8, 256);
            if (warp == 0) {
                PROF(7);
                if (elect()) x_rest(mp, sm, s + 1);
            } else {
                if (wg == 1) {
                    if (w == 1) {
                        qk_out(s);
                    }
                    if (w == 3 && s > 0) seg_done(s - 1, head);
                    if (w == 2 && blk < 10 && s + 3 < NSEG)
                        asm volatile(ELECTED("cp.async.bulk.prefetch.L2.global [%0], 4096;") :: "l"((const uint8_t*)g_h + (s + 3) * (SEG * DM * 2) + blk * 4096) : "memory");
                } else if (w == 3) {
                    if (SPOLL) wait_until(clock() + SPOLL);
                    const uint32_t l = opaque(mrd) >> 4 & 31, tag = (s >> 2) + 1, now = gtime();
                    const uint32_t* sp = g_stamp + (s & 3) * 384 + (l >> 3) * 32 + (l & 7);
                    uint32_t t[3];
                    for (int n = 0;; n++) {
#pragma unroll
                        for (int i = 0; i < 3; i++) t[i] = ld_rlx(sp + i * 128);
                        if (!__any_sync(0xffffffffu, ((t[0] ^ tag) | (t[1] ^ tag) | (t[2] ^ tag)) & 31) || n > SPIN_LIMIT) break;
                    }
                    int all = -(1 << 30), own = all;
#pragma unroll
                    for (int i = 0; i < 3; i++) { const int d = t[i] - now; all = max(all, d); if ((i * 32 + l) / 3 == head) own = d; }
                    const int lag = min(__reduce_max_sync(0xffffffffu, all) - __reduce_max_sync(0xffffffffu, own), 8000);
                    PROFV(15, lag);
                    asm volatile("st.shared.u32 [%0], %1;" :: "r"(sm + C_LAG), "r"(D1 + ((lag * DG) >> 4)) : "memory");
                    bar_arrive(6, 160);
                } else if (w == 2) {
                    if ((s & 3) == 3) w_flag_wait(&g_flags.v[((s + 1) >> 2) * 32 + head], 2);
                    if (elect()) { mbar_expect(sm + CB_VX, 4096); bulk_g2s(sm + C_VX, g_att + ((s + 1) * NH + head) * AT_REC + AT_V + j * 4096, 4096, sm + CB_VX); }
                    if ((s & 3) == 1 && s + 3 < NSEG) asm volatile("prefetch.global.L2 [%0];" :: "l"(&g_flags.v[((s + 3) >> 2) * 32]));
                    if (s + 2 < NSEG && ((s & 3) != 2 || __all_sync(0xffffffffu, ld_rlx(&g_flags.v[((s + 2) >> 2) * 32 + head]) >= 2)))
                        asm volatile("prefetch.global.L2 [%0];" :: "l"(g_att + ((s + 2) * NH + head) * AT_REC + AT_V + j * 4096 + (opaque(mrd) << 3 & 0xf80)));
                }
            }
          }
        }
        PROXY_FENCE();
        bar_sync(8, 256);
        if (warp == 5) { qk_out(NSEG - 1); BULK_WAIT(); }
        bar_arrive(7, 384);
        const int t2 = (opaque(mrd) >> 4 & 31) + warp * 32;
        last_blocks(mp, ar, sm, blk, t2);
        mod_tail(ar, sm + E_B, sm + EB_REL, blk, t2);
    } else {
        asm volatile("setmaxnreg.dec.sync.aligned.u32 %0;" :: "n"(REG_L));
        asm volatile("barrier.cluster.arrive.relaxed.aligned;" ::: "memory");
        if (blk < 80) {
            ModSlice<128> ms;
            ms.load(ar.wmod, ar.c, blk * 16, tid - 256); ms.partial(sm + C_QM, tid - 256);
            bar_sync(3, 128);
            if (w == 0) {
                const uint32_t v = ModSlice<128>::total(sm + C_QM, lane);
                asm volatile("st.relaxed.gpu.global.u32 [%0], %1;" :: "l"(g_flags.mod1 + blk * 8 + (lane & 7)), "r"(~v) : "memory");
            }
        }
        uint32_t m0[5][4], mm = 0;
#pragma unroll
        for (int i = 0; i < 20; i++) {
            const unsigned short* p = (const unsigned short*)ar.mem0 + (i & 3) * 2 * DM + (i >> 2) * 128 + tid - 256;
            m0[i >> 2][i & 3] = __ldg(p) | (uint32_t)__ldg(p + DM) << 16;
        }
        {
            asm volatile("barrier.cluster.wait.aligned;" ::: "memory");
            if (w == 3) {
                w_flag_wait(&g_flags.h, 96);
                if (elect()) { x_fill(mp, sm, 0, j); x_rest(mp, sm, 0); }
                __syncwarp();
            }
            if (w == 1) {
                const uint64_t ef = policy_stream();
#pragma unroll 1
                for (int c = 0; c < 2 * WP + 2; c++) {
                    const uint32_t bar = sm + EB_B + 8 * (c & 1);
                    if (c == WPOS) bar_sync(2, 288);
                    if (c >= 2) mbar_wait(bar, (c / 2 - 1) & 1);
                    if (elect()) {
                        if (c < 2 * WP) { mbar_expect(bar, 81920 / WP); tma2d_ef(sm + C_WV + c * (81920 / WP), c < WP ? &mp.wq : &mp.wk, col0, c % WP * (640 / WP), bar, ef); }
                        if (c >= WOPF && c < WOPF + 3) asm volatile("cp.async.bulk.prefetch.tensor.3d.L2.global [%0, {0, %1, %2}];" :: "l"((uint64_t)&mp.wo), "r"(head * DH + (c - WOPF) * 64), "r"(7 * j) : "memory");
                    }
                    __syncwarp();
                }
                if (elect()) mbar_arrive(sm + CB_W);
                bar_sync(1, 288);
                if (elect()) {
                    mbar_expect(sm + CB_W2, 81920); mbar_expect(sm + CB_W3, 3 * WO_BLK);
#pragma unroll 1
                    for (int c = 0; c < 4; c++) tma2d(sm + C_WV + c * 20480, &mp.wv, col0, c * 160, sm + CB_W2);
#pragma unroll 1
                    for (int c = 0; c < 3; c++) tma3d(sm + C_WO + c * WO_BLK, &mp.wo, head * DH + (j + c) % 3 * 64, 7 * j, sm + CB_W3);
                }
                __syncwarp();
                w_flag_wait(&g_flags.v[head], 2);
                if (elect()) { mbar_expect(sm + CB_VX, 4096); bulk_g2s(sm + C_VX, g_att + head * AT_REC + AT_V + j * 4096, 4096, sm + CB_VX); }
            } else {
                uint32_t mw = 0;
#pragma unroll 1
                for (int c = 0; c < 2; c++) {
                    mbar_wait(sm + (c ? CB_W3 : CB_W2), 0);
                    uint32_t m = 0;
                    const uint32_t end = sm + (c ? C_XR : C_WO);
#pragma unroll 1
                    for (uint32_t a = sm + c * C_WO + (w - (w > 0)) * 4096 + lane * 16; a < end; a += 3 * 4096) {
                        float4 z[8];
#pragma unroll
                        for (int i = 0; i < 8; i++) z[i] = lds128f(a + i * 512);
#pragma unroll
                        for (int i = 0; i < 8; i++) m = amax2(amax2(amax2(amax2(m, __float_as_uint(z[i].x)), __float_as_uint(z[i].y)), __float_as_uint(z[i].z)), __float_as_uint(z[i].w));
                    }
                    mw |= amax_warp(m) << (16 * c);
                }
                asm volatile("st.shared.u32 [%0], %1;" :: "r"(sm + C_KM + w * 4), "r"(mw) : "memory");
                bar_sync(3, 96);
                if (w == 0) asm volatile("st.relaxed.gpu.global.u32 [%0], %1;" :: "l"(g_flags.wmax + blk), "r"(amax2(amax2(mw, lds32(sm + C_KM + 8)), lds32(sm + C_KM + 12)) | 0x8000) : "memory");
            }
        }
        bar_sync(9, 384);
#pragma unroll
        for (int i = 0; i < 5; i++) {
            asm volatile("st.shared.v4.u32 [%0], {%1,%2,%3,%4};" :: "r"(sm + C_MEM + (tid - 256 + i * 128) * 16), "r"(m0[i][0]), "r"(m0[i][1]), "r"(m0[i][2]), "r"(m0[i][3]) : "memory");
            mm = amax2(amax2(amax2(amax2(mm, m0[i][0]), m0[i][1]), m0[i][2]), m0[i][3]);
        }
        asm volatile("st.shared.u32 [%0], %1; st.shared.u32 [%2], 0x3f800000;" :: "r"(sm + C_MX + w * 4), "r"(amax_warp(mm)), "r"(sm + C_UN) : "memory");
        int ew = __shfl_sync(0xffffffffu, lds32(sm + C_LAG), 0), es = 0;
        const uint32_t rb1 = (uint32_t)((j + 1) % 3 - j) << 24, rb2 = (uint32_t)((j + 2) % 3 - j) << 24;
        const float scale = 0.07216878364870322f;
        uint32_t va[8][4], mr = memrd;
#pragma unroll
        for (int i = 0; i < 8; i++) ldsm4t(va[i], sm + C_WV + ((mi >> 1) * 8 + r) * 128 + (((2 * w + (mi & 1)) ^ r) << 4) + i * 2048);
        bar_sync(1, 384);
        for (int s = 0; s < NSEG; s++) {
            const float un = __uint_as_float((127 - es) << 23);
            if (w == 0) {
                mbar_wait(sm + CB_XD, s & 1);
                if (s + 1 < NSEG) { if (elect()) x_fill(mp, sm, s + 1, j); }
                else { if (BPOS != 2) wo_half(mp, sm, blk, 0); if (BPOS != 0) wo_half(mp, sm, blk, 1); }
            } else if (w == 1) { BULK_WAIT(); if (s + 1 == NSEG) seg_done(s - 1, head); }
            const uint32_t l0 = mr >> 4 & 31, r0 = l0 & 7, m0 = l0 >> 3;
            float vd[4];
            {
                uint32_t c[4][4];
#pragma unroll
                for (int i = 0; i < 4; i++) ldsm4t(c[i], mr + i * 512);
                float d[2][4] = {{0, 0, 0, 0}, {0, 0, 0, 0}};
#pragma unroll
                for (int i = 0; i < 8; i++) mma16q(d[i & 1], va[i], c[i >> 1][2 * (i & 1)], c[i >> 1][2 * (i & 1) + 1]);
#pragma unroll
                for (int i = 0; i < 4; i++) vd[i] = d[0][i] + d[1][i];
            }
            uint32_t zr = 0;
            if (w == 2)
                asm volatile("atom.relaxed.gpu.global.exch.b32 %0, [%1], 0;" : "=r"(zr)
                    : "l"(g_acc + ((s & 2) ^ 2) * (ACC_PAIR / 2) + (s & 1) * 512 + (blk >> 2) * 1024 + (blk & 3) * 128 + l0 * 4) : "memory");
            __syncwarp();
            uint32_t kb[4][4];
            {
                const uint32_t k7 = r0 ^ (m0 << 2 & 4), kxrd = sm + C_KX + (16 * (w & 1) + 8 * (m0 & 1) + k7) * 128 + (((m0 >> 1) ^ k7) << 4);
#pragma unroll
                for (int i = 0; i < 4; i++) ldsm4(kb[i], kxrd ^ (i << 5));
            }
            const uint32_t qrd = sm + C_QM + (w == 1 ? (m0 & 1) * 2 + (m0 >> 1) : m0) * 128 + r0 * 16;
            const uint32_t scdst = sm + C_SC + j * 1280 + (w == 1 ? 1024 + l0 * 8 : (w & 1) * 512 + (l0 & 2) * 128 + (l0 >> 2) * 32 + (l0 & 1) * 16);
            const uint32_t scrd = sm + C_SC + (l0 >> 4) * 256 + (l0 & 3) * 32 + (l0 >> 2 & 3) * 8;
            const uint32_t v7 = (4 * (m0 & 1) + (r0 >> 1)) ^ (r0 << 2 & 4), vxrd = sm + C_VX + (16 * (m0 >> 1) + 8 * (r0 & 1) + v7) * 128 + (((2 * w) ^ v7) << 4);
            if (s == 0) {
                uint32_t t[3];
                for (int n = 0;; n++) {
#pragma unroll
                    for (int i = 0; i < 3; i++) t[i] = ld_rlx(g_flags.wmax + l0 + 32 * i);
                    if (__all_sync(0xffffffffu, t[0] && t[1] && t[2])) break;
                    cut(n, 1 << 22);
                }
                const uint32_t m = amax2(amax2(amax2(0, t[0]), t[1]), t[2]);
                const int e = 371 - (int)(__reduce_max_sync(0xffffffffu, m & 0xffffu) >> 7) - (int)(__reduce_max_sync(0xffffffffu, m >> 16) >> 7);
                ew = e << 16 | (min(e - ew, 100) & 0xffff);
            }
            mbar_wait(sm + CB_VX, s & 1);
            uint32_t vb[2][4];
            ldsm4t(vb[0], vxrd); ldsm4t(vb[1], vxrd ^ 16);
            const uint32_t word = sm + C_WO + (m0 & 1) * 4096 + ((m0 >> 1) * 8 + r0) * 64 + ((w ^ (r0 >> 1)) << 4);
            const uint32_t word6 = word + 6 * 4096 - (m0 & 1) * 3072;
            const uint32_t oxrd = sm + C_OX + l0 * 8;
            const uint32_t ord = oxrd + w * 256;
            const uint32_t vp = mr - (C_MEM - C_VP) + w * 512, vmst = mr + (C_VM - C_MEM) + w * 256;
            pin(mr, scdst + rb1, sm + CB_SC + rb1, scdst + rb2, sm + CB_SC + rb2); pin(mr, qrd, scdst, scrd, vp); pin(mr, word, word6, oxrd, ord);
            pin(mr, __float_as_uint(vd[0]), __float_as_uint(vd[1]), __float_as_uint(vd[2]), __float_as_uint(vd[3]));
            bar_sync(2, 384);
            const bool odd = mr & 16;
            float4 y0, y1, mx4;
            {
                uint32_t qa[2][4];
                ldsm4(qa[0], qrd); ldsm4(qa[1], qrd + 512);
                float sc[2][4] = {{0, 0, 0, 0}, {0, 0, 0, 0}};
                if (w == 1) {
                    ldsm4(kb[0], mr + (C_KM - C_MEM)); ldsm4(kb[1], mr + (C_KM - C_MEM) + 512);
                    pin0(mr); y0 = lds128f(vp); y1 = lds128f(vp + 2048); mx4 = lds128f(sm + C_MX);
#pragma unroll
                    for (int k = 0; k < 4; k++) mma16q(sc[k & 1], qa[k >> 1], kb[k >> 1][2 * (k & 1)], kb[k >> 1][2 * (k & 1) + 1]);
                    const uint32_t a0 = __float_as_uint(sc[0][0] + sc[1][2]), a1 = __float_as_uint(sc[0][1] + sc[1][3]);
                    send8(scdst + rb1, sm + CB_SC + rb1, a0, a1); send8(scdst + rb2, sm + CB_SC + rb2, a0, a1);
                    asm volatile("st.shared.v2.u32 [%0], {%1,%2};" :: "r"(scdst), "r"(a0), "r"(a1) : "memory");
                } else {
                    pin0(mr); y0 = lds128f(vp); y1 = lds128f(vp + 2048); mx4 = lds128f(sm + C_MX);
                    if (w) {
#pragma unroll
                        for (int k = 0; k < 4; k++) mma16q(sc[k & 1], kb[k], qa[k >> 1][2 * (k & 1)], qa[k >> 1][2 * (k & 1) + 1]);
                        const float a0 = sc[0][0] + sc[1][0], a1 = sc[0][2] + sc[1][2], a2 = sc[0][1] + sc[1][1], a3 = sc[0][3] + sc[1][3];
                        send16(scdst + rb1, sm + CB_SC + rb1, a0, a1, a2, a3); send16(scdst + rb2, sm + CB_SC + rb2, a0, a1, a2, a3);
                        sts128f(scdst, a0, a1, a2, a3);
                    }
                }
            }
            bar_arrive(7, 384);
            if (elect()) mbar_arrive(sm + CB_SC);
            {
                const float4 z = mx4;
                const int em = (int)(max(max(__float_as_uint(z.x), __float_as_uint(z.y)), max(__float_as_uint(z.z), __float_as_uint(z.w))) >> 7) - es;
                es = __shfl_sync(0xffffffffu, max(min((ew >> 16) - em, (int)(short)ew), -120), 0);
            }
            if (w == 0) PROF(4);
            const uint32_t vm0 = pack2((vd[0] + y0.x + y1.x) * un, (vd[1] + y0.y + y1.y) * un), vm1 = pack2((vd[2] + y0.z + y1.z) * un, (vd[3] + y0.w + y1.w) * un);
            stsm2t(vmst, vm0, vm1);
            if (s + 1 == NSEG) {
                mbar_wait(sm + CB_SC, s & 1);
                PROXY_FENCE();
                bar_sync(3, 128);
                if (w == 1) {
                    w_bulk_s2g(g_att + (s * NH + head) * AT_REC + AT_VM + j * 1024, sm + C_VM, 1024);
                    BULK_COMMIT();
                    BULK_WAIT();
                }
                __syncwarp();
                break;
            }
            cut(s + ar.D2, 0);
            mbar_wait(sm + CB_SC, s & 1);
            if (w == 0) PROF(8);
            float sv[10];
            {
                float2 z[5][3];
#pragma unroll
                for (int u = 0; u < 5; u++)
#pragma unroll
                    for (int p = 0; p < 3; p++) z[u][p] = lds64f((u < 4 ? scrd + (u >> 1) * 512 + (u & 1) * 128 : oxrd + (C_SC - C_OX) + 1024) + p * 1280);
#pragma unroll
                for (int u = 0; u < 5; u++) { sv[2 * u] = (z[u][0].x + z[u][1].x) + z[u][2].x; sv[2 * u + 1] = (z[u][0].y + z[u][1].y) + z[u][2].y; }
            }
            float mx = fmaxf(fmaxf(fmaxf(sv[0], sv[1]), fmaxf(sv[2], sv[3])), fmaxf(fmaxf(fmaxf(sv[4], sv[5]), fmaxf(sv[6], sv[7])), fmaxf(sv[8], sv[9])));
            uint32_t a[NRING][4];
            auto frag = [&](int i) { const int p = i / 7, u = i % 7, o = (p >> 1) * WO_BLK + (p & 1) * 2048;
                                     return u == 3 ? word6 + o : word + o + (u > 3 ? 1024 + (u - 4) * 8192 : u * 8192); };
            mx = fmaxf(fmaxf(mx, __shfl_xor_sync(0xffffffffu, mx, 1)), fmaxf(__shfl_xor_sync(0xffffffffu, mx, 2), __shfl_xor_sync(0xffffffffu, mx, 3)));
            pin(mr, __float_as_uint(mx), 0, 0, 0);
            {
#pragma unroll
                for (int i = 0; i < NPRE; i++) ldsm4t(a[i], frag(i));
                pin0(mr);
                const float sl2e = scale * 1.4426950408889634f, mxl = mx * sl2e;
#pragma unroll
                for (int i = 9; i >= 0; i--) asm volatile("ex2.approx.ftz.f32 %0, %1;" : "=f"(sv[i]) : "f"(fmaf(sv[i], sl2e, -mxl)));
                const uint32_t pq[4] = {pack2(sv[0], sv[1]), pack2(sv[4], sv[5]), pack2(sv[2], sv[3]), pack2(sv[6], sv[7])}, pm = pack2(sv[8], sv[9]);
                if (w == 0) PROF(6);
                float o[2][4] = {{0, 0, 0, 0}, {0, 0, 0, 0}}, o2[2][4] = {{0, 0, 0, 0}, {0, 0, 0, 0}}, sx[4] = {0, 0, 0, 0};
                mma8(sx, pm, 0, 0x3f803f80u); mma8(o[0], pm, 0, vm0); mma8(o[1], pm, 0, vm1);
                mma16q(sx, pq, 0x3f803f80u, 0x3f803f80u);
#pragma unroll
                for (int u = 0; u < 2; u++) { mma16q(o[u], pq, vb[u][0], vb[u][1]); mma16q(o2[u], pq, vb[u][2], vb[u][3]); }
                float inv; asm("rcp.approx.ftz.f32 %0, %1;" : "=f"(inv) : "f"((sx[0] + sx[2]) * __uint_as_float((127 - es) << 23)));
                const uint32_t f0 = pack2((o[0][0] + o2[0][2]) * inv, (o[0][1] + o2[0][3]) * inv), f1 = pack2((o[1][0] + o2[1][2]) * inv, (o[1][1] + o2[1][3]) * inv);
                send8(ord + 2048 + rb1, sm + CB_OX + rb1, f0, f1); send8(ord + 1024 + rb2, sm + CB_OX + rb2, f0, f1);
                asm volatile("st.shared.v2.u32 [%0], {%1,%2};" :: "r"(ord), "r"(f0), "r"(f1) : "memory");
            }
            if (w == 0) PROF(10);
#pragma unroll
            for (int i = NPRE; i < NRING; i++) ldsm4t(a[i], frag(i));
            bar_sync(3, 128);
            float e[5][4];
#pragma unroll
            for (int q = 0; q < 5; q++) e[q][0] = e[q][1] = e[q][2] = e[q][3] = 0.f;
            constexpr int LAG = 2;
            uint8_t* pdst = g_acc + ((s & 2) * (ACC_PAIR / 2) + (s & 1) * 512 + w * 2048 + j * 8192 - C_MEM - sm + mr);
#pragma unroll
            for (int h = 0; h < 3; h++) {
                uint32_t ob[4][2];
                if (h == 1) {
#pragma unroll
                    for (int i = 14 - LAG; i < 14; i++) ldsm4t(a[i % NRING], frag(i + NRING));
                    pin(mr, zr, (uint32_t)(uint64_t)pdst, (uint32_t)((uint64_t)pdst >> 32), 0);
                    mbar_wait(sm + CB_OX, s & 1);
                    if (w == 0) PROF(9);
                }
#pragma unroll
                for (int k = 0; k < 4; k++) lds64(ob[k], oxrd + h * 1024 + k * 256);
#pragma unroll
                for (int i = 14 * h; i < 14 * h + 14; i++) {
                    const int u = i % 7, k = 2 * (i / 7 & 1);
                    if (u == 3) { mma16q(e[3], a[i % NRING], ob[k][0], ob[k][1]); mma16q(e[4], a[i % NRING], ob[k + 1][0], ob[k + 1][1]); }
                    else mma16q(e[u & 3], a[i % NRING], ob[k + (u >> 2)][0], ob[k + (u >> 2)][1]);
                    if (i == B5AT) { pin(mr, a[i % NRING][0], a[i % NRING][1], a[i % NRING][2], a[i % NRING][3]); bar_arrive(5, 384); }
                    if (i >= LAG && !(i >= 14 && i < 14 + LAG) && i - LAG + NRING < 42) ldsm4t(a[(i - LAG) % NRING], frag(i - LAG + NRING));
                }
            }
            {
                const uint32_t w6 = pack2h(e[3][0] + e[4][2], e[3][1] + e[4][3]), one = 0x3c003c00u;
                asm volatile("red.relaxed.gpu.global.add.noftz.v4.f16x2 [%0], {%1,%2,%3,%4};"
                    :: "l"(pdst), "r"(pack2h(e[0][0], e[0][1])), "r"(pack2h(e[0][2], e[0][3])), "r"(pack2h(e[1][0], e[1][1])), "r"(odd ? w6 : one) : "memory");
                asm volatile("red.relaxed.gpu.global.add.noftz.v4.f16x2 [%0], {%1,%2,%3,%4};"
                    :: "l"(pdst + 1024), "r"(pack2h(e[1][2], e[1][3])), "r"(pack2h(e[2][0], e[2][1])), "r"(pack2h(e[2][2], e[2][3])), "r"(odd ? one : w6) : "memory");
            }
            const uint32_t tw = clock();
            if (w == 0) { PROF(14); PROFG(25); }
            PROXY_FENCE();
            bar_sync(6, 160);
            mr = opaque(mr);
            const uint32_t ln = mr >> 4 & 31, due = tw + lds32(sm + C_LAG);
            const uint32_t vr = sm + C_WV + ((ln >> 4) * 8 + (ln & 7)) * 128 + (((2 * w + (ln >> 3 & 1)) ^ (ln & 7)) << 4);
            const uint32_t ms0 = sm + C_MEM + w * 128 + (ln & 7) * 16 + (ln >> 3) * 512, ms1 = ms0 + (ln < 24 ? 2048 : 1536);
            if (BPOS == 2 && w == 0 && s + 2 == NSEG) wo_half(mp, sm, blk, 0);
            if (w == 2) { w_expect(sm + CB_SC, 2560); w_expect(sm + CB_OX, 2048); asm volatile("st.shared.u32 [%0], %1;" :: "r"(sm + C_UN), "r"((127 - es) << 23) : "memory"); }
            if (w == 1) { w_bulk_s2g(g_att + (s * NH + head) * AT_REC + AT_VM + j * 1024, sm + C_VM, 1024); BULK_COMMIT(); }
            const uint8_t* src = pdst - j * 8192;
            pin(mr, ms0, ms1, (uint32_t)(uint64_t)src, (uint32_t)((uint64_t)src >> 32));
            pin(mr, vr, due, 0, 0);
            cut(s + ar.D2, 1);
#pragma unroll
            for (int i = 0; i < 8; i++) ldsm4t(va[i], vr + i * 2048);
            wait_until(due);
            if (w == 0) { PROF(5); PROFG(26); }
            uint4 v[6];
            auto fetch = [&]() {
#pragma unroll
                for (int k = 0; k < 6; k++)
                    asm volatile("ld.relaxed.gpu.global.v4.u32 {%0,%1,%2,%3}, [%4];" : "=r"(v[k].x), "=r"(v[k].y), "=r"(v[k].z), "=r"(v[k].w) : "l"(src + (k >> 1) * 8192 + (k & 1) * 1024) : "memory");
            };
            fetch();
            PROFV(20 + w, 0);
            bar_sync(9, 384);
#pragma unroll 1
            for (int n = 0; __any_sync(0xffffffffu, ~((odd ? v[1].w & v[3].w & v[5].w : v[0].w & v[2].w & v[4].w)) & 0x50005000u); n++) {
                PROFV(20 + w, n + 1);
                cut(n, SPIN_LIMIT);
                fetch();
            }
            uint32_t cv[3][7];
#pragma unroll
            for (int k = 0; k < 3; k++) {
                const uint4 x = v[2 * k], y = v[2 * k + 1];
                const uint32_t u[7] = {x.x, x.y, x.z, y.x, y.y, y.z, k < 2 ? (odd ? x.w : y.w) : 0u};
#pragma unroll
                for (int i = 0; i < 7; i++) cv[k][i] = f16_to_bf16(u[i]);
                stsm4(ms0 + k * 3584, cv[k][0], cv[k][1], cv[k][2], cv[k][3]);
                if (k < 2) stsm4(ms1 + k * 3584, cv[k][4], cv[k][5], cv[k][6], cv[k][6]);
                else asm volatile("stmatrix.sync.aligned.m8n8.x2.shared.b16 [%0], {%1,%2};" :: "r"(ms1 + k * 3584), "r"(cv[k][4]), "r"(cv[k][5]) : "memory");
            }
            if (w == 0) PROF(16);
            bar_sync(1, 384);
            cut(s + ar.D2, 2);
            uint32_t mc = 0;
#pragma unroll
            for (int i = 0; i < 20; i++) mc = amax2(mc, cv[i / 7][i % 7]);
            asm volatile("st.shared.u32 [%0], %1;" :: "r"(sm + C_MX + w * 4), "r"(amax_warp(mc)) : "memory");
        }
        if (w >= 2) end_loads(mp, ar, sm, blk, w - 2);
        else if (w == 1) { bar_sync(5, 384); seg_done(NSEG - 1, head); if (EORD) bar_arrive(6, 96); if (BPOS == 0) wo_half(mp, sm, blk, 1); }
        else bar_arrive(5, 384);
        if (w == 0) {
            const int l = mr >> 4 & 31;
            if (blk < 14) {
                uint4 k = __ldcg((const uint4*)g_key + blk * 32 + l);
#pragma unroll 1
                for (int it = 0; it < 3; it++) {
                    const uint32_t m = __reduce_max_sync(0xffffffffu, max(max(k.x, k.y), max(k.z, k.w)));
                    if (k.x == m) k.x = 0; if (k.y == m) k.y = 0; if (k.z == m) k.z = 0; if (k.w == m) k.w = 0;
                    if (m && l < 20) asm volatile("prefetch.global.L2 [%0];" :: "l"((l < 10 ? g_h2 : g_x1) + (~m & (S_TOK - 1)) * DM + l % 10 * 64));
                }
            }
            mbar_wait(sm + EB_REL, 0);
            flags_release(l);
        }
    }
}

struct SideMaps { CUtensorMap h, wv, ost, o, wo, slab3, slab2, lnp[3]; };
constexpr int SD_ST = 43008, SD_NST = 4, SD_EPI = SD_NST * SD_ST, SD_PAR = SD_EPI + 2 * 24576, SD_BAR = SD_PAR + 6400, SD_SMEM = SD_BAR + 256;
#define VLEAD 16
#define EARLY15 0
#define N_LIGHT 6
#define B_HELP 13
#define AUNR_ 2
constexpr int AUNR = AUNR_;
#define GEMV 1
#define KSO 6
#define KSA 3
#define B_8 10
#define B_16 13
__device__ __forceinline__ int o_shift(int b) { return b >= B_16 ? 4 : b >= B_8 ? 3 : 2; }
__device__ __forceinline__ int o_split(int b) { return 1 << o_shift(b); }
__device__ __forceinline__ uint32_t o_done(int b) { return b >= B_LATE ? 160 : 4 << o_shift(b); }
__device__ __forceinline__ int next_item(int lane) {
    const int b0 = lane & 15, hi = lane >> 4;
    for (int n = 0;; n++) {
        const uint32_t w0 = ld_rlx(g_flags.qk + lane), w1 = ld_rlx(g_flags.at + lane), w2 = ld_rlx(&g_flags.c[0][0] + lane), w3 = ld_rlx(&g_flags.c[2][0] + lane), w4 = ld_rlx(&g_flags.seg[0]);
        const uint32_t o01 = __ballot_sync(0xffffffffu, lane && w2 < 32), o23 = __ballot_sync(0xffffffffu, b0 < (hi ? 14 : B_LATE) && w3 < 2u * o_split(b0));
        const uint32_t ra = __ballot_sync(0xffffffffu, w0 >= (hi ? 64u : 96u)), rb = __ballot_sync(0xffffffffu, w1 >= (hi ? o_done(b0) : 64u));
        const int bv = __ffs(o01 | 0x10000) - 1, ba = __ffs(o01 >> 16 | 0x10000) - 1, bo = __ffs(o23 | 0x10000) - 1, bl = __ffs(o23 >> 16 | 0x10000) - 1;
        if (bl == 16 && ba == 16) return -1;
        const int bc = __ffs(~ra | 0x10000) - 1;
        const bool last = ba == 15 && (w4 >= 3 || (EARLY15 && bc == 15));
        const bool r1 = (ra & ra >> 16) >> ba & 1, r2 = (rb & 0xffff) >> bo & 1, r3 = rb >> 16 >> bl & 1;
        const int kind = ba == 16 ? (bo < 16 ? 2 : 3) : last ? 1 :
                         blockIdx.x < N_LIGHT ? (r1 ? 1 : r3 ? 3 : bv < 16 ? 0 : -1) :
                         bv < 16 && (bv <= bc + VLEAD || !r2) ? 0 : r1 && ba >= B_HELP ? 1 : r2 ? 2 : r1 ? 1 : r3 ? 3 : bo < ba ? 2 : -1;
        if (kind < 0) { if (n > (1 << 20)) __trap(); __nanosleep(300); continue; }
        const int b = kind == 3 ? bl : kind == 2 ? bo : kind == 1 ? ba : bv;
        uint32_t i = 0;
        if (lane == 0) asm volatile("atom.relaxed.gpu.global.add.u32 %0, [%1], 1;" : "=r"(i) : "l"(&g_flags.c[kind][b]) : "memory");
        i = __shfl_sync(0xffffffffu, i, 0);
        if (i < (kind < 2 ? 32u : 2u * o_split(b))) return kind << 16 | b << 8 | i | ((kind == 1 ? r1 : kind == 2 ? r2 : r3) ? 128 : 0);
    }
}

template <int NP, int CH>
__device__ __forceinline__ void tile_out(const float (&acc)[8 * NP], uint32_t eb, uint32_t efull, uint32_t eempty, int& eph, int lane) {
    const int r = lane & 7, mi = lane >> 3, row = (mi & 1) * 8 + r;
    mbar_wait(eempty, eph); eph ^= 1;
#pragma unroll
    for (int p = 0; p < NP; p++) {
        const int oc = 2 * p + (mi >> 1);
        stsm4(eb + (oc >> 3) * CH + row * 128 + (((oc & 7) ^ r) << 4), pack2(acc[8 * p], acc[8 * p + 1]), pack2(acc[8 * p + 2], acc[8 * p + 3]),
              pack2(acc[8 * p + 4], acc[8 * p + 5]), pack2(acc[8 * p + 6], acc[8 * p + 7]));
    }
    asm volatile("fence.proxy.async.shared::cta;" ::: "memory");
    __syncwarp();
    if (lane == 0) mbar_arrive(efull);
}

template <int MT>
__device__ __forceinline__ void attn_tile(uint32_t base, uint32_t dst, uint32_t eempty, int eph, int lane) {
    constexpr int NK = MT ? 5 : 3;
    const int r = lane & 7, mi = lane >> 3, g = lane >> 2, t = lane & 3;
    float sc[NK][4];
#pragma unroll
    for (int n = 0; n < NK; n++) sc[n][0] = sc[n][1] = sc[n][2] = sc[n][3] = 0.f;
#pragma unroll AUNR
    for (int k2 = 0; k2 < 6; k2++) {
        const uint32_t cb = (k2 >> 1) * 8192, c0 = (k2 & 1) * 4;
        uint32_t a0[4], a1[4], bb[NK][4];
        ldsm4(a0, base + cb + (16 * MT + (mi & 1) * 8 + r) * 128 + (((c0 + (mi >> 1)) ^ r) << 4));
        ldsm4(a1, base + cb + (16 * MT + (mi & 1) * 8 + r) * 128 + (((c0 + 2 + (mi >> 1)) ^ r) << 4));
#pragma unroll
        for (int n = 0; n < NK; n++)
            ldsm4(bb[n], n < NK - 1 ? base + 4096 + cb + (8 * n + r) * 128 + (((c0 + mi) ^ r) << 4) : base + 36864 + k2 * 512 + lane * 16);
#pragma unroll
        for (int n = 0; n < NK; n++) mma16(sc[n], a0[0], a0[1], a0[2], a0[3], bb[n][0], bb[n][1]);
#pragma unroll
        for (int n = 0; n < NK; n++) mma16(sc[n], a1[0], a1[1], a1[2], a1[3], bb[n][2], bb[n][3]);
    }
    const float scale = 0.07216878364870322f, l2e = 1.4426950408889634f;
    float v[2][2 * NK], mx[2], sum[2];
#pragma unroll
    for (int hf = 0; hf < 2; hf++) {
        mx[hf] = -INFINITY;
#pragma unroll
        for (int n = 0; n < NK; n++) {
            uint32_t u = pack2(sc[n][2 * hf], sc[n][2 * hf + 1]);
            u = pack2(lo_f(u) * scale, hi_f(u) * scale);
            const int lim = 16 * MT + 8 * hf + g - 8 * n - 2 * t;
            v[hf][2 * n] = (n < NK - 1 && lim < 0) ? -1e9f : lo_f(u);
            v[hf][2 * n + 1] = (n < NK - 1 && lim < 1) ? -1e9f : hi_f(u);
            mx[hf] = fmaxf(mx[hf], fmaxf(v[hf][2 * n], v[hf][2 * n + 1]));
        }
    }
#pragma unroll
    for (int o = 1; o < 4; o <<= 1)
#pragma unroll
        for (int hf = 0; hf < 2; hf++) mx[hf] = fmaxf(mx[hf], __shfl_xor_sync(0xffffffffu, mx[hf], o));
#pragma unroll
    for (int hf = 0; hf < 2; hf++) {
        sum[hf] = 0;
#pragma unroll
        for (int q = 0; q < 2 * NK; q++) { asm("ex2.approx.ftz.f32 %0, %1;" : "=f"(v[hf][q]) : "f"((v[hf][q] - mx[hf]) * l2e)); sum[hf] += v[hf][q]; }
    }
#pragma unroll
    for (int o = 1; o < 4; o <<= 1)
#pragma unroll
        for (int hf = 0; hf < 2; hf++) sum[hf] += __shfl_xor_sync(0xffffffffu, sum[hf], o);
    uint32_t pa[NK][2];
#pragma unroll
    for (int hf = 0; hf < 2; hf++) {
        const float inv = __fdividef(1.f, sum[hf]);
#pragma unroll
        for (int n = 0; n < NK; n++) pa[n][hf] = pack2(v[hf][2 * n] * inv, v[hf][2 * n + 1] * inv);
    }
    mbar_wait(eempty, eph);
#pragma unroll AUNR
    for (int n4 = 0; n4 < 6; n4++) {
        const uint32_t cb = (n4 >> 1) * 4096, c0 = (n4 & 1) * 4;
        uint32_t bm[4], bb[2 + 2 * MT][4];
        ldsm4t(bm, base + AT_VM + n4 * 512 + lane * 16);
#pragma unroll
        for (int u = 0; u < 2 + 2 * MT; u++) ldsm4t(bb[u], base + AT_V + cb + (16 * (u >> 1) + 8 * (mi & 1) + r) * 128 + (((c0 + 2 * (u & 1) + (mi >> 1)) ^ r) << 4));
        float o[4][4];
#pragma unroll
        for (int u = 0; u < 4; u++) { o[u][0] = o[u][1] = o[u][2] = o[u][3] = 0.f; mma8(o[u], pa[NK - 1][0], pa[NK - 1][1], bm[u]); }
#pragma unroll
        for (int u = 0; u < 4 + 4 * MT; u++) mma16(o[u & 3], pa[u >> 2 << 1][0], pa[u >> 2 << 1][1], pa[(u >> 2 << 1) + 1][0], pa[(u >> 2 << 1) + 1][1], bb[u >> 1][2 * (u & 1)], bb[u >> 1][2 * (u & 1) + 1]);
#pragma unroll
        for (int p = 0; p < 2; p++)
            stsm4(dst + (n4 >> 1) * 2048 + ((mi & 1) * 8 + r) * 128 + (((c0 + 2 * p + (mi >> 1)) ^ r) << 4), pack2(o[2 * p][0], o[2 * p][1]), pack2(o[2 * p][2], o[2 * p][3]),
                  pack2(o[2 * p + 1][0], o[2 * p + 1][1]), pack2(o[2 * p + 1][2], o[2 * p + 1][3]));
    }
}

__device__ __forceinline__ uint32_t ln_row(const uint32_t (&as)[10], const uint2 (&xin)[5], int row, uint32_t par, bf16* out, uint64_t ef, int lane) {
    const uint32_t pa = par + lane * 8;
    uint32_t xv[10], hv[10], sv[10], tv[10];
#pragma unroll
    for (int q = 0; q < 5; q++) {
        uint32_t ga[2], t[2], u[2];
        lds64(ga, pa + q * 256); lds64(t, pa + 1280 + q * 256); lds64(u, pa + 2560 + q * 256);
#pragma unroll
        for (int e = 0; e < 2; e++) {
            xv[2 * q + e] = add2(e ? xin[q].y : xin[q].x, mul2(ga[e], as[2 * q + e]));
            tv[2 * q + e] = t[e]; sv[2 * q + e] = u[e];
        }
        st_ef(g_x1 + row * DM + lane * 4 + q * 128, make_uint2(xv[2 * q], xv[2 * q + 1]), ef);
    }
    ln_mod(xv, sv, tv, hv);
    float rs = 0;
#pragma unroll
    for (int q = 0; q < 5; q++) {
        const int c = row * DM + lane * 4 + q * 128;
        const uint32_t h0 = hv[2 * q], h1 = hv[2 * q + 1];
        uint32_t gb[2], wv[2];
        lds64(gb, pa + 3840 + q * 256); lds64(wv, pa + 5120 + q * 256);
        rs += (lo_f(h0) * lo_f(wv[0]) + hi_f(h0) * hi_f(wv[0])) + (lo_f(h1) * lo_f(wv[1]) + hi_f(h1) * hi_f(wv[1]));
        st_ef(g_h2 + c, make_uint2(h0, h1), ef);
        st_ef(out + c, make_uint2(add2(xv[2 * q], mul2(gb[0], h0)), add2(xv[2 * q + 1], mul2(gb[1], h1))), ef);
    }
    const uint32_t rb = pack2(0.f, warp_sum(rs));
    return (((int)rb < 0 ? ~rb : rb | 0x80000000u) & 0xffff0000u) | (uint32_t)(2 * S_TOK - 1 - row);
}
__device__ __forceinline__ void key_out(uint32_t key) {
    __syncwarp();
    if (key) asm volatile("st.release.gpu.global.u32 [%0], %1;" :: "l"(g_key + (~key & (S_TOK - 1))), "r"(key) : "memory");
}

__global__ void __launch_bounds__(384, 1) k_side(const __grid_constant__ SideMaps mp, const bf16* __restrict__ x, const bf16* __restrict__ wr, const bf16* wmod, const bf16* cvec, bf16* __restrict__ out) {
    extern __shared__ __align__(1024) uint8_t smraw[];
    const uint32_t sm = smem_u32(smraw);
    if (sm & 1023) __trap();
    const uint32_t FULL = sm + SD_BAR, EMPTY = FULL + 32, EFULL = FULL + 64, EEMPTY = FULL + 80, IFULL = FULL + 96, IEMPTY = FULL + 128, IQ = FULL + 160, SCHED = FULL + 176, PARAM = FULL + 184, ADONE = FULL + 192;
    const int tid = threadIdx.x, warp = __shfl_sync(0xffffffffu, tid >> 5, 0), lane = tid & 31;
    const uint64_t ef = policy_stream();
    if (tid == 0) {
        for (int i = 0; i < SD_NST; i++) { mbar_init(FULL + 8 * i, 1); mbar_init(EMPTY + 8 * i, 2); }
        for (int i = 0; i < 2; i++) { mbar_init(EFULL + 8 * i, 4); mbar_init(EEMPTY + 8 * i, 1); }
        for (int i = 0; i < 4; i++) { mbar_init(IFULL + 8 * i, 1); mbar_init(IEMPTY + 8 * i, 11); }
        mbar_init(SCHED, 1); mbar_init(PARAM, 1);
        sts128f(ADONE, 0, 0, 0, 0); sts128f(ADONE + 16, 0, 0, 0, 0);
        asm volatile("fence.mbarrier_init.release.cluster;" ::: "memory");
    }
    if (SDEL) __nanosleep(SDEL);
    __syncthreads();
    if (warp >= 8) {
      asm volatile("setmaxnreg.dec.sync.aligned.u32 40;");
      if (warp == 8) {
        int st = 0, ph = 1;
        for (int q = 0;; q++) {
            mbar_wait(IFULL + 8 * (q & 3), (q >> 2) & 1);
            const int it = __shfl_sync(0xffffffffu, lds32(IQ + 4 * (q & 3)), 0);
            if (elect()) mbar_arrive(IEMPTY + 8 * (q & 3));
            if (it < 0) break;
            const int kind = it >> 16, b = (it >> 8) & 255, i = it & 63;
            const int nst = kind == 0 ? 10 : kind == 1 ? 4 : kind == 2 ? 192 >> o_shift(b) : b == 14 ? 4 : 2;
            const int ksched = kind == 0 ? 4 : kind == 2 ? nst - KSO : (it & 128) ? -1 : kind == 1 ? KSA : 0;
            if (ksched < 0 && elect()) mbar_arrive(SCHED);
            const bool look = !(it & 128);
            if (look && kind == 1) flag_wait(&g_flags.v[b * 32 + i], 2);
            if (look && kind == 3 && b < 14) flag_wait(&g_flags.o[b], o_done(b));
            for (int kb = 0; kb < nst; kb++) {
                mbar_wait(EMPTY + 8 * st, ph);
                const uint32_t base = sm + st * SD_ST, fb = FULL + 8 * st;
                if (look && kind == 1) flag_wait(&g_flags.seg[kb * 32 + i], 3);
                if (kb == ksched && elect()) mbar_arrive(SCHED);
                if (kind == 0) {
                    if (q == 0 && kb == 0) {
                        if (elect()) {
#pragma unroll 1
                            for (int c = 0; c < SD_NST; c++) tma3d(sm + c * SD_ST + 16384, &mp.wv, c * 64, i * 3, FULL + 8 * c);
#pragma unroll 1
                            for (int c = SD_NST; c < SPF; c++)
                                asm volatile("cp.async.bulk.prefetch.tensor.3d.L2.global [%0, {0, %1, %2}];" :: "l"((uint64_t)&mp.wv), "r"(c * 64), "r"(i * 3) : "memory");
                        }
                        flag_wait(&g_flags.h, 96);
                    }
                    if (elect()) {
                        mbar_expect(fb, 40960);
                        tma2d(base, &mp.h, kb * 64, b * 128, fb);
                        if (q || kb >= SD_NST) tma3d(base + 16384, &mp.wv, kb * 64, i * 3, fb);
                    }
                } else if (kind == 1) {
                    if (elect()) {
                        mbar_expect(fb, 43008);
                        asm volatile("cp.async.bulk.shared::cluster.global.mbarrier::complete_tx::bytes.L2::cache_hint [%0], [%1], %2, [%3], %4;"
                            :: "r"(base), "l"(g_att + ((b * 4 + kb) * NH + i) * AT_REC), "r"(AT_REC), "r"(fb), "l"(ef) : "memory");
                    }
                } else if (kind == 3) {
                    if (b == 14 && !(kb & 1)) flag_wait(&g_flags.fin[(kb + (i >> 4)) * 32], 80);
                    if (elect()) { mbar_expect(fb, 40960); tma3d_ef(base, &mp.lnp[o_shift(b) - 2], i * (160 >> o_shift(b)), b * KSPLIT + (kb << o_shift(b) >> 1), fb, ef); }
                } else {
                    const int k0 = ((i >> 1) * nst + kb) * 32;
                    if (elect()) { mbar_expect(fb, 28672); tma3d(base + 8192, &mp.wo, k0, (i & 1) * 5, fb); }
                    if (look && kb % 12 == 0) flag_wait(&g_flags.pair[b * 16 + k0 / 384], 4);
                    if (elect()) tma2d_ef(base, &mp.o, k0, b * 128, fb, ef);
                }
                __syncwarp();
                if (++st == SD_NST) { st = 0; ph ^= 1; }
            }
        }
      } else if (warp == 11) {
        bool fin = false, par = false;
        for (int q = 0;; q++) {
            if (q) mbar_wait(SCHED, (q - 1) & 1);
            int it = fin ? -1 : q == 0 && blockIdx.x < 32 ? (int)blockIdx.x : next_item(lane);
            if (it < 0 && !fin && blockIdx.x < 32) { it = 3 << 16 | 14 << 8 | blockIdx.x; fin = true; }
            if (lane == 0) {
                if (it >> 16 == 3) {
                    const int b = (it >> 8) & 255, nr = 64 >> o_shift(b);
                    asm volatile("cp.async.bulk.prefetch.L2.global [%0], %1;" :: "l"(x + (b * 128 + (it & 63) * nr) * DM), "r"(nr * DM * 2) : "memory");
                }
                mbar_wait(IEMPTY + 8 * (q & 3), ((q >> 2) & 1) ^ 1);
                asm volatile("st.shared.u32 [%0], %1;" :: "r"(IQ + 4 * (q & 3)), "r"(it) : "memory");
                mbar_arrive(IFULL + 8 * (q & 3));
            }
            if (!par && it >> 16 == 3) {
                par = true;
                                if (lane == 0) { mbar_expect(PARAM, 6400); bulk_g2s(sm + SD_PAR, g_mod + 2 * DM, 5120, PARAM); bulk_g2s(sm + SD_PAR + 5120, wr, 1280, PARAM); }
            }
            __syncwarp();
            if (it < 0) break;
        }
        flags_release(lane);
      } else {
        if (lane == 0) {
            const int wg = warp - 9; int ph = 0;
            for (int q = 0;; q++) {
                mbar_wait(IFULL + 8 * (q & 3), (q >> 2) & 1);
                const int it = lds32(IQ + 4 * (q & 3));
                mbar_arrive(IEMPTY + 8 * (q & 3));
                if (it < 0) break;
                const int kind = it >> 16, b = (it >> 8) & 255, i = it & 63;
                if (kind == 3) continue;
                if (kind == 1) {
                    for (int n = 0;; n++) {
                        uint32_t d0, d1, d2, d3;
                        asm volatile("ld.volatile.shared.v4.u32 {%0,%1,%2,%3}, [%4];" : "=r"(d0), "=r"(d1), "=r"(d2), "=r"(d3) : "r"(ADONE + wg * 16) : "memory");
                        if (min(min(d0, d1), min(d2, d3)) > q) break;
                        if (n > (1 << 24)) __trap();
                        __nanosleep(40);
                    }
                    GPU_FENCE();
                    bump(b == 15 ? &g_flags.half[(i & 30) + wg] : &g_flags.pair[b * 16 + (i >> 1)]); bump(&g_flags.at[b]);
                    continue;
                }
#pragma unroll 1
                for (int rd = 0; rd < (kind == 2 ? 2 : 1); rd++) {
                    mbar_wait(EFULL + 8 * wg, ph); ph ^= 1;
                    const uint32_t src = sm + SD_EPI + wg * 24576;
                    if (kind == 2) tma3d_store(rd ? &mp.slab2 : &mp.slab3, (b * KSPLIT + (i >> 1)) * 128 + wg * 64, (i & 1) * 5 + rd * 3, src, ef, false);
                    else {
                        uint8_t* dst = g_att + ((b * 4 + wg * 2) * NH + i) * AT_REC + AT_V;
                        asm volatile("cp.async.bulk.global.shared::cta.bulk_group.L2::cache_hint [%0], [%1], 12288, %2;" :: "l"(dst), "r"(src), "l"(ef) : "memory");
                        asm volatile("cp.async.bulk.global.shared::cta.bulk_group.L2::cache_hint [%0], [%1], 12288, %2;" :: "l"(dst + NH * AT_REC), "r"(src + 12288), "l"(ef) : "memory");
                    }
                    asm volatile("cp.async.bulk.commit_group;" ::: "memory");
                    asm volatile("cp.async.bulk.wait_group.read 0;" ::: "memory");
                    mbar_arrive(EEMPTY + 8 * wg);
                }
                asm volatile("cp.async.bulk.wait_group 0;" ::: "memory");
                GPU_FENCE();
                bump(kind == 0 ? &g_flags.v[b * 32 + i] : &g_flags.o[b]);
                if (kind == 0) bump(&g_flags.vb[b]);
            }
        }
      }
    } else {
        asm volatile("setmaxnreg.inc.sync.aligned.u32 232;");
        const int wg = warp >> 2, w = warp & 3;
        int st = 0, ph = 0, eph = 1;
        bool att = false;
        if (blockIdx.x < 32 * GEMV) {
            const uint32_t buf = sm + SD_EPI;
#pragma unroll 1
            for (int k = tid; k < DM; k += 256) {
                const float f = __uint_as_float((uint32_t)__ldg((const unsigned short*)cvec + k) << 16);
                asm volatile("st.shared.f32 [%0], %1;" :: "r"(buf + k * 4), "f"(bfr(__fdividef(f, 1.f + __expf(-f)))) : "memory");
            }
            const int t = min(tid, 199), k0 = t / 10 * 32;
            const bf16* wm = wmod + k0 * (6 * DM) + 2 * DM + blockIdx.x * 80 + t % 10 * 8;
            float a[8] = {0, 0, 0, 0, 0, 0, 0, 0};
#pragma unroll 1
            for (int k = 0; k < 32; k += 8) {
                uint4 z[8];
#pragma unroll
                for (int e = 0; e < 8; e++) z[e] = __ldcs((const uint4*)(wm + (k + e) * (6 * DM)));
                if (k == 0) bar_sync(1, 256);
#pragma unroll
                for (int e = 0; e < 8; e++) {
                    const float f = __uint_as_float(lds32(buf + (k0 + k + e) * 4));
                    a[0] += f * lo_f(z[e].x); a[1] += f * hi_f(z[e].x); a[2] += f * lo_f(z[e].y); a[3] += f * hi_f(z[e].y);
                    a[4] += f * lo_f(z[e].z); a[5] += f * hi_f(z[e].z); a[6] += f * lo_f(z[e].w); a[7] += f * hi_f(z[e].w);
                }
            }
            sts128f(buf + 4096 + t * 32, a[0], a[1], a[2], a[3]); sts128f(buf + 4112 + t * 32, a[4], a[5], a[6], a[7]);
            bar_sync(1, 256);
            if (tid < 40) {
                float a0 = 0, a1 = 0;
#pragma unroll 4
                for (int g = 0; g < 20; g++) { const float2 v = lds64f(buf + 4096 + g * 320 + tid * 8); a0 += v.x; a1 += v.y; }
                ((uint32_t*)(g_mod + 2 * DM + blockIdx.x * 80))[tid] = pack2(a0, a1);
            }
            bar_sync(1, 256);
        }
        const uint32_t eb = sm + SD_EPI + wg * 24576;
        for (int q = 0;; q++) {
            mbar_wait(IFULL + 8 * (q & 3), (q >> 2) & 1);
            const int itc = lds32(IQ + 4 * (q & 3));
            __syncwarp();
            if (lane == 0) mbar_arrive(IEMPTY + 8 * (q & 3));
            if (itc < 0) break;
            const int kind = itc >> 16, b = (itc >> 8) & 255, i = itc & 63;
            if (att && kind != 1) { bar_sync(1, 256); att = false; }
            if (kind == 0) {
                float acc[96];
#pragma unroll
                for (int n = 0; n < 96; n++) acc[n] = 0.f;
                int prev = -1;
#pragma unroll 1
                for (int kb = 0; kb < 10; kb++) {
                    mbar_wait(FULL + 8 * st, ph);
                    const uint32_t base = sm + st * SD_ST;
                    WG_FENCE();
#pragma unroll
                    for (int ks = 0; ks < 4; ks++)
                        wgmma_ss_n192_tb(acc, mkdesc(base + wg * 8192 + ks * 32, 16, 1024), mkdesc(base + 16384 + ks * 2048, 8192, 1024), (kb | ks) != 0);
                    WG_COMMIT();
                    WG_WAIT(1);
                    if (prev >= 0 && (tid & 127) == 0) mbar_arrive(EMPTY + 8 * prev);
                    prev = st;
                    if (++st == SD_NST) { st = 0; ph ^= 1; }
                }
                WG_WAIT(0);
                if ((tid & 127) == 0) mbar_arrive(EMPTY + 8 * prev);
                tile_out<12, 4096>(acc, eb + (w >> 1) * 12288 + (w & 1) * 2048, EFULL + 8 * wg, EEMPTY + 8 * wg, eph, lane);
            } else if (kind == 1) {
                const int seg = warp >> 1, mt = warp & 1;
                int sst = st + seg, sph = ph; if (sst >= SD_NST) { sst -= SD_NST; sph ^= 1; }
                ph ^= 1;
                mbar_wait(FULL + 8 * sst, sph);
                const uint32_t base = sm + sst * SD_ST;
                if (mt) attn_tile<1>(base, eb + w * 6144, EEMPTY + 8 * wg, eph, lane);
                else attn_tile<0>(base, eb + w * 6144, EEMPTY + 8 * wg, eph, lane);
                asm volatile("fence.proxy.async.shared::cta;" ::: "memory");
                __syncwarp();
                if (lane == 0) {
                    mbar_arrive(EMPTY + 8 * sst);
                    tma3d_store(&mp.ost, b * 128 + warp * 16, i * 3, eb + w * 6144, ef, false);
                    BULK_COMMIT(); BULK_WAIT();
                    asm volatile("st.release.cta.shared.u32 [%0], %1;" :: "r"(ADONE + warp * 4), "r"(q + 1) : "memory");
                }
                __syncwarp();
                att = true;
            } else if (kind == 2) {
                float acc[96], acc2[64];
#pragma unroll
                for (int n = 0; n < 96; n++) acc[n] = 0.f;
#pragma unroll
                for (int n = 0; n < 64; n++) acc2[n] = 0.f;
                int prev = -1;
#pragma unroll 1
                for (int kb = 192 >> o_shift(b); kb > 0; kb--) {
                    const uint32_t base = sm + st * SD_ST;
                    mbar_wait(FULL + 8 * st, ph);
                    WG_FENCE();
#pragma unroll
                    for (int ks = 0; ks < 2; ks++) {
                        const uint64_t da = (mkdesc(base + wg * 4096 + ks * 32, 16, 512) & ~(3ull << 62)) | (2ull << 62);
                        wgmma_ss_n192_tb(acc, da, mkdesc(base + 8192 + ks * 2048, 4096, 1024), 1);
                        wgmma_ss_n128_tb(acc2, da, mkdesc(base + 8192 + 3 * 4096 + ks * 2048, 4096, 1024), 1);
                    }
                    WG_COMMIT();
                    WG_WAIT(1);
                    if (prev >= 0 && (tid & 127) == 0) mbar_arrive(EMPTY + 8 * prev);
                    prev = st;
                    if (++st == SD_NST) { st = 0; ph ^= 1; }
                }
                WG_WAIT(0);
                if ((tid & 127) == 0) mbar_arrive(EMPTY + 8 * prev);
                tile_out<12, 8192>(acc, eb + w * 2048, EFULL + 8 * wg, EEMPTY + 8 * wg, eph, lane);
                tile_out<8, 8192>(acc2, eb + w * 2048, EFULL + 8 * wg, EEMPTY + 8 * wg, eph, lane);
            } else {
                const int sh = o_shift(b), nr = 64 >> sh, fw = b == 14 ? wg : 0, row0 = (b + fw) * 128 + i * nr, lw = warp - 4 * fw;
                if (fw) { st += 2; if (st >= SD_NST) { st -= SD_NST; ph ^= 1; } }
                int st1 = st + 1, ph1 = ph; if (st1 == SD_NST) { st1 = 0; ph1 ^= 1; }
                uint2 xin[2][5];
                uint32_t as[2][10] = {};
#pragma unroll
                for (int q2 = 0; q2 < 10; q2++) xin[q2 & 1][q2 >> 1] = ld_ef(x + (row0 + ((warp + 8 * (q2 & 1)) & (nr - 1))) * DM + lane * 4 + (q2 >> 1) * 128, ef);
                mbar_wait(PARAM, 0); mbar_wait(FULL + 8 * st, ph); mbar_wait(FULL + 8 * st1, ph1);
#pragma unroll 1
                for (int lrow = lw + (nr & 16) / 2; lrow >= 0 && lrow < nr; lrow -= 8) {
                    float a[20];
#pragma unroll
                    for (int q2 = 0; q2 < 20; q2++) a[q2] = 0.f;
#pragma unroll 1
                    for (int k = 0; k < (1 << sh >> 1); k++) {
                        const uint32_t ad = sm + ((k << (6 - sh)) + lrow) * 1280 + lane * 8;
                        uint32_t z[10][2];
#pragma unroll
                        for (int q2 = 0; q2 < 10; q2++) lds64(z[q2], ad + (q2 < 5 ? st : st1) * SD_ST + q2 % 5 * 256);
#pragma unroll
                        for (int q2 = 0; q2 < 10; q2++) { float* p = a + q2 % 5 * 4; p[0] += lo_f(z[q2][0]); p[1] += hi_f(z[q2][0]); p[2] += lo_f(z[q2][1]); p[3] += hi_f(z[q2][1]); }
                    }
#pragma unroll
                    for (int q2 = 0; q2 < 10; q2++) { as[1][q2] = as[0][q2]; as[0][q2] = pack2(a[2 * q2], a[2 * q2 + 1]); }
                }
                bar_sync(2 + wg, 128);
                if ((tid & 127) == 0) { mbar_arrive(EMPTY + 8 * st); mbar_arrive(EMPTY + 8 * st1); }
                uint32_t key = 0;
#pragma unroll 1
                for (int lrow = lw; lrow < nr; lrow += 8) {
                    const int row = row0 + lrow;
                    const uint32_t k1 = ln_row(as[0], xin[0], row, sm + SD_PAR, out, ef, lane);
                    if (lane == lrow >> 3) key = k1;
#pragma unroll
                    for (int q2 = 0; q2 < 5; q2++) { as[0][2 * q2] = as[1][2 * q2]; as[0][2 * q2 + 1] = as[1][2 * q2 + 1]; xin[0][q2] = xin[1][q2]; }
                }
                key_out(key);
                st = st1 + 1; ph = ph1; if (st == SD_NST) { st = 0; ph ^= 1; }
            }
        }
    }
    __syncwarp();
    asm volatile("griddepcontrol.wait;" ::: "memory");
}

#define P_D1 550
#define P_DL 700
#define P_DG 29
typedef CUresult (*EncodeFn)(CUtensorMap*, CUtensorMapDataType, cuuint32_t, void*, const cuuint64_t*, const cuuint64_t*, const cuuint32_t*, const cuuint32_t*,
                             CUtensorMapInterleave, CUtensorMapSwizzle, CUtensorMapL2promotion, CUtensorMapFloatOOBfill);
static EncodeFn s_encode = nullptr;
static void make_map(CUtensorMap* m, const void* p, int rows, int cols, int box_rows, int box_cols = 64) {
    cuuint64_t dims[2] = {(cuuint64_t)cols, (cuuint64_t)rows}, strides[1] = {(cuuint64_t)cols * 2};
    cuuint32_t box[2] = {(cuuint32_t)box_cols, (cuuint32_t)box_rows}, es[2] = {1, 1};
    s_encode(m, CU_TENSOR_MAP_DATA_TYPE_BFLOAT16, 2, (void*)p, dims, strides, box, es, CU_TENSOR_MAP_INTERLEAVE_NONE,
             box_cols == 64 ? CU_TENSOR_MAP_SWIZZLE_128B : box_cols == 32 ? CU_TENSOR_MAP_SWIZZLE_64B : CU_TENSOR_MAP_SWIZZLE_NONE, CU_TENSOR_MAP_L2_PROMOTION_L2_256B, CU_TENSOR_MAP_FLOAT_OOB_FILL_NONE);
}
static void make_map3(CUtensorMap* m, const void* p, int rows, int cols, int box_rows, int box_chunks, int cw = 64) {
    cuuint64_t dims[3] = {(cuuint64_t)cw, (cuuint64_t)rows, (cuuint64_t)(cols / cw)}, strides[2] = {(cuuint64_t)cols * 2, (cuuint64_t)cw * 2};
    cuuint32_t box[3] = {(cuuint32_t)cw, (cuuint32_t)box_rows, (cuuint32_t)box_chunks}, es[3] = {1, 1, 1};
    s_encode(m, CU_TENSOR_MAP_DATA_TYPE_BFLOAT16, 3, (void*)p, dims, strides, box, es, CU_TENSOR_MAP_INTERLEAVE_NONE,
             cw == 64 ? CU_TENSOR_MAP_SWIZZLE_128B : CU_TENSOR_MAP_SWIZZLE_64B, CU_TENSOR_MAP_L2_PROMOTION_L2_256B, CU_TENSOR_MAP_FLOAT_OOB_FILL_NONE);
}
template <typename T> static void* sym(T& s) { void* p = nullptr; cudaGetSymbolAddress(&p, s); return p; }

extern "C" void kernel_launch(void* const* d_in, const int* in_sizes, int n_in, void* d_out, int out_size) {
    const bf16 *x = (const bf16*)d_in[0], *mem0 = (const bf16*)d_in[1], *Wq = (const bf16*)d_in[2], *Wk = (const bf16*)d_in[3],
               *Wv = (const bf16*)d_in[4], *Wo = (const bf16*)d_in[5], *wr = (const bf16*)d_in[8], *wgate = (const bf16*)d_in[9],
               *wup = (const bf16*)d_in[10], *wdown = (const bf16*)d_in[11], *c = (const bf16*)d_in[12], *wmod = (const bf16*)d_in[13];
    bf16* out = (bf16*)d_out;
    if (!s_encode) {
        cudaDriverEntryPointQueryResult qr;
        cudaGetDriverEntryPoint("cuTensorMapEncodeTiled", (void**)&s_encode, cudaEnableDefault, &qr);
        cudaFuncSetAttribute(k_side, cudaFuncAttributeMaxDynamicSharedMemorySize, SD_SMEM);
        cudaFuncSetAttribute(k_chain, cudaFuncAttributeMaxDynamicSharedMemorySize, C_SMEM);
    }
    ChainMaps cm; SideMaps sd;
    make_map(&sd.h, sym(g_h), S_TOK, DM, 128); make_map3(&sd.wv, Wv, DM, HD, 64, 3);
    make_map3(&sd.ost, sym(g_o), S_TOK, HD, 16, 3); make_map(&sd.o, sym(g_o), S_TOK, HD, 128, 32); make_map3(&sd.wo, Wo, HD, DM, 32, 5);
    make_map3(&sd.slab3, sym(g_slab), 16 * KSPLIT * 128, DM, 64, 3); make_map3(&sd.slab2, sym(g_slab), 16 * KSPLIT * 128, DM, 64, 2);
    make_map3(&cm.wo15, Wo, HD, DM, 192, 2); make_map3(&cm.o15, sym(g_o), S_TOK, HD, 64, 2); make_map3(&cm.slab16, sym(g_slab), 16 * KSPLIT * 128, DM, 16, 2);
    for (int i = 0; i < 3; i++) {
        cuuint64_t dims[3] = {256, 320, 16 * KSPLIT}, strides[2] = {512, 128 * DM * 2};
        cuuint32_t box[3] = {256, 40u >> i, 2u << i}, es[3] = {1, 1, 1};
        s_encode(&sd.lnp[i], CU_TENSOR_MAP_DATA_TYPE_BFLOAT16, 3, sym(g_slab), dims, strides, box, es, CU_TENSOR_MAP_INTERLEAVE_NONE,
                 CU_TENSOR_MAP_SWIZZLE_NONE, CU_TENSOR_MAP_L2_PROMOTION_L2_256B, CU_TENSOR_MAP_FLOAT_OOB_FILL_NONE);
    }
    make_map(&cm.wq, Wq, DM, HD, 640 / WP); make_map(&cm.wk, Wk, DM, HD, 640 / WP); make_map(&cm.wv, Wv, DM, HD, 160); make_map3(&cm.wo, Wo, HD, DM, 64, 7, 32);
    make_map3(&cm.h2, sym(g_h), S_TOK, DM, 32, 2);
    ChainArgs ar = {x, mem0, c, wmod, Wv, Wo, wgate, wup, wdown, out, P_D1, P_DL, P_DG};
    k_chain<<<96, 384, C_SMEM>>>(cm, ar);
    cudaLaunchConfig_t cfg = {};
    cfg.gridDim = dim3(N_SIDE); cfg.blockDim = dim3(384); cfg.dynamicSmemBytes = SD_SMEM; cfg.stream = cudaStreamPerThread;
    cudaLaunchAttribute at[1]; at[0].id = cudaLaunchAttributeProgrammaticStreamSerialization; at[0].val.programmaticStreamSerializationAllowed = 1;
    cfg.attrs = at; cfg.numAttrs = 1;
    cudaLaunchKernelEx(&cfg, k_side, sd, x, wr, wmod, c, out);
}
```

```cpp
#include <cuda_runtime.h>
#include <cuda_bf16.h>
#include <cuda.h>
#include <stdint.h>
#include <stdio.h>
#include <string.h>
#include <stdlib.h>

typedef __nv_bfloat16 bf16;
constexpr int S_TOK = 2048, DM = 640, NH = 32, DH = 192, HD = NH * DH, NSEG = 64, SEG = 32, FF = 1536;

__device__ bf16 g_mod[6 * DM];
__device__ bf16 g_h[S_TOK * DM];
constexpr int AT_REC = 43008, AT_V = 24576, AT_KM = 36864, AT_VM = 39936;
__device__ __align__(1024) uint8_t g_att[NSEG * NH * AT_REC];
__device__ bf16 g_o[S_TOK * HD];
__device__ bf16 g_A[S_TOK * DM];
__device__ bf16 g_x1[S_TOK * DM];
__device__ bf16 g_h2[S_TOK * DM];
__device__ __align__(128) uint32_t g_key[S_TOK];
__device__ int g_idx[8];
__device__ __align__(128) uint32_t g_gu[FF / 8 * 32];
constexpr int ACC_PAIR = 24 * 1024;
__device__ __align__(1024) uint8_t g_acc[2 * ACC_PAIR];
__device__ __align__(1024) uint32_t g_stamp[4 * 12 * 32];
constexpr int KSPLIT = 16;
__device__ bf16 g_slab[16 * KSPLIT * 128 * DM];
struct __align__(128) Flags {
    uint32_t qk[16], vb[16];
    uint32_t at[16], o[16];
    uint32_t c[4][16];
    uint32_t half[32];
    uint32_t fin[4 * 32];
    uint32_t v[16 * 32];
    uint32_t seg[4 * 32];
    uint32_t pair[16 * 16];
    uint32_t h, pad2[31], done, pad3[31];
    uint32_t mod1[DM];
    uint32_t wmax[96];
};
__device__ Flags g_flags;

__device__ __forceinline__ uint32_t smem_u32(const void* p) { return (uint32_t)__cvta_generic_to_shared(p); }
__device__ __forceinline__ uint32_t pack2(float lo, float hi) {
    uint32_t r; asm("cvt.rn.bf16x2.f32 %0, %1, %2;" : "=r"(r) : "f"(hi), "f"(lo)); return r;
}
__device__ __forceinline__ float bfr(float x) { return __uint_as_float(pack2(0.f, x)); }
__device__ __forceinline__ float inv_std(float var) {
    float s, r; asm("sqrt.approx.f32 %0, %1;" : "=f"(s) : "f"(bfr(bfr(var) + 1e-5f))); asm("rcp.approx.f32 %0, %1;" : "=f"(r) : "f"(bfr(s))); return r;
}
__device__ __forceinline__ float lo_f(uint32_t v) { return __uint_as_float(v << 16); }
__device__ __forceinline__ float hi_f(uint32_t v) { return __uint_as_float(v & 0xffff0000u); }
__device__ __forceinline__ void mbar_init(uint32_t bar, int cnt) { asm volatile("mbarrier.init.shared::cta.b64 [%0], %1;" :: "r"(bar), "r"(cnt) : "memory"); }
__device__ __forceinline__ void mbar_expect(uint32_t bar, int bytes) { asm volatile("mbarrier.arrive.expect_tx.shared::cta.b64 _, [%0], %1;" :: "r"(bar), "r"(bytes) : "memory"); }
__device__ __forceinline__ void mbar_arrive(uint32_t bar) { asm volatile("mbarrier.arrive.shared::cta.b64 _, [%0];" :: "r"(bar) : "memory"); }
__device__ __forceinline__ bool mbar_try(uint32_t bar, int par) {
    uint32_t ok; asm volatile("{ .reg .pred p; mbarrier.try_wait.parity.shared::cta.b64 p, [%1], %2; selp.u32 %0, 1, 0, p; }" : "=r"(ok) : "r"(bar), "r"(par) : "memory"); return ok;
}
__device__ __forceinline__ bool mbar_try_cluster(uint32_t bar, int par) {
    uint32_t ok; asm volatile("{ .reg .pred p; mbarrier.try_wait.parity.acquire.cluster.shared::cta.b64 p, [%1], %2; selp.u32 %0, 1, 0, p; }" : "=r"(ok) : "r"(bar), "r"(par) : "memory"); return ok;
}
__device__ __forceinline__ bool mbar_test(uint32_t bar, uint32_t par) {
    uint32_t ok; asm volatile("{ .reg .pred p; mbarrier.test_wait.parity.shared::cta.b64 p, [%1], %2; selp.u32 %0, 1, 0, p; }" : "=r"(ok) : "r"(bar), "r"(par) : "memory"); return ok;
}
constexpr int SPIN_LIMIT = 1 << 18;
__device__ __forceinline__ void mbar_wait(uint32_t bar, uint32_t par) {
    asm volatile("{ .reg .pred p, q; .reg .u32 n; mov.u32 n, 0;\n"
                 "W_%=: mbarrier.try_wait.parity.shared::cta.b64 p, [%0], %1;\n"
                 "@p bra.uni D_%=;\n"
                 "add.u32 n, n, 1; setp.lt.u32 q, n, 0x200000; @q bra.uni W_%=;\n"
                 "trap;\n"
                 "D_%=: }" :: "r"(bar), "r"(par) : "memory");
}
__device__ __forceinline__ void tma2d(uint32_t dst, const CUtensorMap* m, int c0, int c1, uint32_t bar) {
    asm volatile("cp.async.bulk.tensor.2d.shared::cluster.global.mbarrier::complete_tx::bytes [%0], [%1, {%3, %4}], [%2];"
        :: "r"(dst), "l"((uint64_t)m), "r"(bar), "r"(c0), "r"(c1) : "memory");
}
__device__ __forceinline__ void tma2d_mc(uint32_t dst, const CUtensorMap* m, int c0, int c1, uint32_t bar, uint16_t mask) {
    asm volatile("cp.async.bulk.tensor.2d.shared::cluster.global.mbarrier::complete_tx::bytes.multicast::cluster [%0], [%1, {%3, %4}], [%2], %5;"
        :: "r"(dst), "l"((uint64_t)m), "r"(bar), "r"(c0), "r"(c1), "h"(mask) : "memory");
}
__device__ __forceinline__ uint64_t policy_stream() { uint64_t p; asm("createpolicy.fractional.L2::evict_first.b64 %0, 1.0;" : "=l"(p)); return p; }
__device__ __forceinline__ void tma2d_ef(uint32_t dst, const CUtensorMap* m, int c0, int c1, uint32_t bar, uint64_t pol) {
    asm volatile("cp.async.bulk.tensor.2d.shared::cluster.global.mbarrier::complete_tx::bytes.L2::cache_hint [%0], [%1, {%3, %4}], [%2], %5;"
        :: "r"(dst), "l"((uint64_t)m), "r"(bar), "r"(c0), "r"(c1), "l"(pol) : "memory");
}
__device__ __forceinline__ void tma3d(uint32_t dst, const CUtensorMap* m, int row, int chunk, uint32_t bar) {
    asm volatile("cp.async.bulk.tensor.3d.shared::cluster.global.mbarrier::complete_tx::bytes [%0], [%1, {0, %3, %4}], [%2];"
        :: "r"(dst), "l"((uint64_t)m), "r"(bar), "r"(row), "r"(chunk) : "memory");
}
__device__ __forceinline__ void tma3d_ef(uint32_t dst, const CUtensorMap* m, int row, int chunk, uint32_t bar, uint64_t pol) {
    asm volatile("cp.async.bulk.tensor.3d.shared::cluster.global.mbarrier::complete_tx::bytes.L2::cache_hint [%0], [%1, {0, %3, %4}], [%2], %5;"
        :: "r"(dst), "l"((uint64_t)m), "r"(bar), "r"(row), "r"(chunk), "l"(pol) : "memory");
}
__device__ __forceinline__ void tma3d_store(const CUtensorMap* m, int row, int chunk, uint32_t src, uint64_t pol, bool hint) {
    if (hint) asm volatile("cp.async.bulk.tensor.3d.global.shared::cta.bulk_group.L2::cache_hint [%0, {0, %2, %3}], [%1], %4;"
        :: "l"((uint64_t)m), "r"(src), "r"(row), "r"(chunk), "l"(pol) : "memory");
    else asm volatile("cp.async.bulk.tensor.3d.global.shared::cta.bulk_group [%0, {0, %2, %3}], [%1];"
        :: "l"((uint64_t)m), "r"(src), "r"(row), "r"(chunk) : "memory");
}
__device__ __forceinline__ bool elect() { uint32_t p; asm volatile("{ .reg .pred e; elect.sync _|e, -1; selp.u32 %0, 1, 0, e; }" : "=r"(p)); return p; }
__device__ __forceinline__ uint2 ld_ef(const void* p, uint64_t pol) {
    uint2 v; asm volatile("ld.relaxed.gpu.global.L2::cache_hint.v2.u32 {%0,%1}, [%2], %3;" : "=r"(v.x), "=r"(v.y) : "l"(p), "l"(pol)); return v;
}
__device__ __forceinline__ void st_ef(void* p, uint2 v, uint64_t pol) {
    asm volatile("st.global.L2::cache_hint.v2.u32 [%0], {%1,%2}, %3;" :: "l"(p), "r"(v.x), "r"(v.y), "l"(pol) : "memory");
}
__device__ __forceinline__ void tma2d_prefetch(const CUtensorMap* m, int c0, int c1) {
    asm volatile("cp.async.bulk.prefetch.tensor.2d.L2.global [%0, {%1, %2}];" :: "l"((uint64_t)m), "r"(c0), "r"(c1) : "memory");
}
__device__ __forceinline__ void mbar_arrive_remote(uint32_t bar) { asm volatile("mbarrier.arrive.relaxed.cluster.shared::cluster.b64 _, [%0];" :: "r"(bar) : "memory"); }
__device__ __forceinline__ void tma2d_store(const CUtensorMap* m, int c0, int c1, uint32_t src) {
    asm volatile("cp.async.bulk.tensor.2d.global.shared::cta.bulk_group [%0, {%2, %3}], [%1];"
        :: "l"((uint64_t)m), "r"(src), "r"(c0), "r"(c1) : "memory");
}
__device__ __forceinline__ void bulk_g2s(uint32_t dst, const void* src, int bytes, uint32_t bar) {
    asm volatile("cp.async.bulk.shared::cluster.global.mbarrier::complete_tx::bytes [%0], [%1], %2, [%3];" :: "r"(dst), "l"(src), "r"(bytes), "r"(bar) : "memory");
}
__device__ __forceinline__ void ldsm4(uint32_t (&r)[4], uint32_t a) {
    asm volatile("ldmatrix.sync.aligned.m8n8.x4.shared.b16 {%0,%1,%2,%3}, [%4];" : "=r"(r[0]), "=r"(r[1]), "=r"(r[2]), "=r"(r[3]) : "r"(a) : "memory");
}
__device__ __forceinline__ void ldsm4t(uint32_t (&r)[4], uint32_t a) {
    asm volatile("ldmatrix.sync.aligned.m8n8.x4.trans.shared.b16 {%0,%1,%2,%3}, [%4];" : "=r"(r[0]), "=r"(r[1]), "=r"(r[2]), "=r"(r[3]) : "r"(a) : "memory");
}
__device__ __forceinline__ void stsm4(uint32_t a, uint32_t r0, uint32_t r1, uint32_t r2, uint32_t r3) {
    asm volatile("stmatrix.sync.aligned.m8n8.x4.shared.b16 [%0], {%1,%2,%3,%4};" :: "r"(a), "r"(r0), "r"(r1), "r"(r2), "r"(r3) : "memory");
}
__device__ __forceinline__ void stsm4t(uint32_t a, uint32_t r0, uint32_t r1, uint32_t r2, uint32_t r3) {
    asm volatile("stmatrix.sync.aligned.m8n8.x4.trans.shared.b16 [%0], {%1,%2,%3,%4};" :: "r"(a), "r"(r0), "r"(r1), "r"(r2), "r"(r3) : "memory");
}
__device__ __forceinline__ void stsm2t(uint32_t a, uint32_t r0, uint32_t r1) {
    asm volatile("stmatrix.sync.aligned.m8n8.x2.trans.shared.b16 [%0], {%1,%2};" :: "r"(a), "r"(r0), "r"(r1) : "memory");
}
__device__ __forceinline__ uint32_t movm_t(uint32_t v) { uint32_t r; asm volatile("movmatrix.sync.aligned.m8n8.trans.b16 %0, %1;" : "=r"(r) : "r"(v)); return r; }
__device__ __forceinline__ void mma16(float (&d)[4], uint32_t a0, uint32_t a1, uint32_t a2, uint32_t a3, uint32_t b0, uint32_t b1) {
    asm volatile("mma.sync.aligned.m16n8k16.row.col.f32.bf16.bf16.f32 {%0,%1,%2,%3}, {%4,%5,%6,%7}, {%8,%9}, {%0,%1,%2,%3};"
        : "+f"(d[0]), "+f"(d[1]), "+f"(d[2]), "+f"(d[3]) : "r"(a0), "r"(a1), "r"(a2), "r"(a3), "r"(b0), "r"(b1));
}
__device__ __forceinline__ void mma8(float (&d)[4], uint32_t a0, uint32_t a1, uint32_t b0) {
    asm volatile("mma.sync.aligned.m16n8k8.row.col.f32.bf16.bf16.f32 {%0,%1,%2,%3}, {%4,%5}, {%6}, {%0,%1,%2,%3};"
        : "+f"(d[0]), "+f"(d[1]), "+f"(d[2]), "+f"(d[3]) : "r"(a0), "r"(a1), "r"(b0));
}
__device__ __forceinline__ uint32_t mapa(uint32_t a, uint32_t r) { uint32_t o; asm volatile("mapa.shared::cluster.u32 %0, %1, %2;" : "=r"(o) : "r"(a), "r"(r)); return o; }
__device__ __forceinline__ void bar_sync(int id, int n) { asm volatile("bar.sync %0, %1;" :: "r"(id), "r"(n) : "memory"); }
__device__ __forceinline__ void bar_arrive(int id, int n) { asm volatile("bar.arrive %0, %1;" :: "r"(id), "r"(n) : "memory"); }
__device__ __forceinline__ uint64_t mkdesc(uint32_t addr, uint32_t lbo, uint32_t sbo) {
    return (uint64_t)((addr & 0x3FFFF) >> 4) | ((uint64_t)(lbo >> 4) << 16) | ((uint64_t)(sbo >> 4) << 32) | (1ull << 62);
}
#define WG_FENCE()  asm volatile("wgmma.fence.sync.aligned;" ::: "memory")
#define WG_COMMIT() asm volatile("wgmma.commit_group.sync.aligned;" ::: "memory")
#define WG_WAIT(n)  asm volatile("wgmma.wait_group.sync.aligned %0;" :: "n"(n) : "memory")

__device__ __forceinline__ void wgmma_ss_n192_tb(float (&d)[96], uint64_t a, uint64_t b, int acc) {
    asm volatile("{ .reg .pred p; setp.ne.b32 p, %98, 0;\n"
        "wgmma.mma_async.sync.aligned.m64n192k16.f32.bf16.bf16 {%0,%1,%2,%3,%4,%5,%6,%7,%8,%9,%10,%11,%12,%13,%14,%15,%16,%17,%18,%19,%20,%21,%22,%23,%24,%25,%26,%27,%28,%29,%30,%31,%32,%33,%34,%35,%36,%37,%38,%39,%40,%41,%42,%43,%44,%45,%46,%47,%48,%49,%50,%51,%52,%53,%54,%55,%56,%57,%58,%59,%60,%61,%62,%63,%64,%65,%66,%67,%68,%69,%70,%71,%72,%73,%74,%75,%76,%77,%78,%79,%80,%81,%82,%83,%84,%85,%86,%87,%88,%89,%90,%91,%92,%93,%94,%95}, %96, %97, p, 1, 1, 0, 1; }"
        : "+f"(d[0]), "+f"(d[1]), "+f"(d[2]), "+f"(d[3]), "+f"(d[4]), "+f"(d[5]), "+f"(d[6]), "+f"(d[7]), "+f"(d[8]), "+f"(d[9]), "+f"(d[10]), "+f"(d[11]), "+f"(d[12]), "+f"(d[13]), "+f"(d[14]), "+f"(d[15]), "+f"(d[16]), "+f"(d[17]), "+f"(d[18]), "+f"(d[19]), "+f"(d[20]), "+f"(d[21]), "+f"(d[22]), "+f"(d[23]), "+f"(d[24]), "+f"(d[25]), "+f"(d[26]), "+f"(d[27]), "+f"(d[28]), "+f"(d[29]), "+f"(d[30]), "+f"(d[31]), "+f"(d[32]), "+f"(d[33]), "+f"(d[34]), "+f"(d[35]), "+f"(d[36]), "+f"(d[37]), "+f"(d[38]), "+f"(d[39]), "+f"(d[40]), "+f"(d[41]), "+f"(d[42]), "+f"(d[43]), "+f"(d[44]), "+f"(d[45]), "+f"(d[46]), "+f"(d[47]), "+f"(d[48]), "+f"(d[49]), "+f"(d[50]), "+f"(d[51]), "+f"(d[52]), "+f"(d[53]), "+f"(d[54]), "+f"(d[55]), "+f"(d[56]), "+f"(d[57]), "+f"(d[58]), "+f"(d[59]), "+f"(d[60]), "+f"(d[61]), "+f"(d[62]), "+f"(d[63]), "+f"(d[64]), "+f"(d[65]), "+f"(d[66]), "+f"(d[67]), "+f"(d[68]), "+f"(d[69]), "+f"(d[70]), "+f"(d[71]), "+f"(d[72]), "+f"(d[73]), "+f"(d[74]), "+f"(d[75]), "+f"(d[76]), "+f"(d[77]), "+f"(d[78]), "+f"(d[79]), "+f"(d[80]), "+f"(d[81]), "+f"(d[82]), "+f"(d[83]), "+f"(d[84]), "+f"(d[85]), "+f"(d[86]), "+f"(d[87]), "+f"(d[88]), "+f"(d[89]), "+f"(d[90]), "+f"(d[91]), "+f"(d[92]), "+f"(d[93]), "+f"(d[94]), "+f"(d[95])
        : "l"(a), "l"(b), "r"(acc));
}

__device__ __forceinline__ void wgmma_ss_n128_tb(float (&d)[64], uint64_t a, uint64_t b, int acc) {
    asm volatile("{ .reg .pred p; setp.ne.b32 p, %66, 0;\n"
        "wgmma.mma_async.sync.aligned.m64n128k16.f32.bf16.bf16 {%0,%1,%2,%3,%4,%5,%6,%7,%8,%9,%10,%11,%12,%13,%14,%15,%16,%17,%18,%19,%20,%21,%22,%23,%24,%25,%26,%27,%28,%29,%30,%31,%32,%33,%34,%35,%36,%37,%38,%39,%40,%41,%42,%43,%44,%45,%46,%47,%48,%49,%50,%51,%52,%53,%54,%55,%56,%57,%58,%59,%60,%61,%62,%63}, %64, %65, p, 1, 1, 0, 1; }"
        : "+f"(d[0]), "+f"(d[1]), "+f"(d[2]), "+f"(d[3]), "+f"(d[4]), "+f"(d[5]), "+f"(d[6]), "+f"(d[7]), "+f"(d[8]), "+f"(d[9]), "+f"(d[10]), "+f"(d[11]), "+f"(d[12]), "+f"(d[13]), "+f"(d[14]), "+f"(d[15]), "+f"(d[16]), "+f"(d[17]), "+f"(d[18]), "+f"(d[19]), "+f"(d[20]), "+f"(d[21]), "+f"(d[22]), "+f"(d[23]), "+f"(d[24]), "+f"(d[25]), "+f"(d[26]), "+f"(d[27]), "+f"(d[28]), "+f"(d[29]), "+f"(d[30]), "+f"(d[31]), "+f"(d[32]), "+f"(d[33]), "+f"(d[34]), "+f"(d[35]), "+f"(d[36]), "+f"(d[37]), "+f"(d[38]), "+f"(d[39]), "+f"(d[40]), "+f"(d[41]), "+f"(d[42]), "+f"(d[43]), "+f"(d[44]), "+f"(d[45]), "+f"(d[46]), "+f"(d[47]), "+f"(d[48]), "+f"(d[49]), "+f"(d[50]), "+f"(d[51]), "+f"(d[52]), "+f"(d[53]), "+f"(d[54]), "+f"(d[55]), "+f"(d[56]), "+f"(d[57]), "+f"(d[58]), "+f"(d[59]), "+f"(d[60]), "+f"(d[61]), "+f"(d[62]), "+f"(d[63])
        : "l"(a), "l"(b), "r"(acc));
}

__device__ __forceinline__ void wgmma_rs_n32(float (&d)[16], const uint32_t (&a)[4], uint64_t b, int acc) {
    asm volatile("{ .reg .pred p; setp.ne.b32 p, %21, 0;\n"
        "wgmma.mma_async.sync.aligned.m64n32k16.f32.bf16.bf16 {%0,%1,%2,%3,%4,%5,%6,%7,%8,%9,%10,%11,%12,%13,%14,%15}, {%16,%17,%18,%19}, %20, p, 1, 1, 0; }"
        : "+f"(d[0]), "+f"(d[1]), "+f"(d[2]), "+f"(d[3]), "+f"(d[4]), "+f"(d[5]), "+f"(d[6]), "+f"(d[7]), "+f"(d[8]), "+f"(d[9]), "+f"(d[10]), "+f"(d[11]), "+f"(d[12]), "+f"(d[13]), "+f"(d[14]), "+f"(d[15])
        : "r"(a[0]), "r"(a[1]), "r"(a[2]), "r"(a[3]), "l"(b), "r"(acc));
}

__device__ __forceinline__ float warp_sum(float v) {
#pragma unroll
    for (int o = 16; o; o >>= 1) v += __shfl_xor_sync(0xffffffffu, v, o);
    return v;
}
__device__ __forceinline__ uint32_t add2(uint32_t a, uint32_t b) { uint32_t r; asm("add.rn.bf16x2 %0, %1, %2;" : "=r"(r) : "r"(a), "r"(b)); return r; }
__device__ __forceinline__ uint32_t mul2(uint32_t a, uint32_t b) { uint32_t r; asm("mul.rn.bf16x2 %0, %1, %2;" : "=r"(r) : "r"(a), "r"(b)); return r; }
__device__ __forceinline__ uint32_t amax2(uint32_t m, uint32_t v) { uint32_t r; asm("max.u16x2 %0, %1, %2;" : "=r"(r) : "r"(m), "r"(v & 0x7fff7fffu)); return r; }
__device__ __forceinline__ uint32_t amax_warp(uint32_t m) { return __reduce_max_sync(0xffffffffu, max(m & 0xffffu, m >> 16)); }
__device__ __forceinline__ void ln_norm(const uint32_t (&xv)[10], uint32_t (&nv)[10]) {
    float s0 = 0, s1 = 0;
#pragma unroll
    for (int i = 0; i < 10; i++) { s0 += lo_f(xv[i]); s1 += hi_f(xv[i]); }
    const float mean = warp_sum(s0 + s1) * (1.f / DM);
    float q0 = 0, q1 = 0;
#pragma unroll
    for (int i = 0; i < 10; i++) { const float d0 = lo_f(xv[i]) - mean, d1 = hi_f(xv[i]) - mean; q0 += d0 * d0; q1 += d1 * d1; }
    const float inv = inv_std(warp_sum(q0 + q1) * (1.f / DM));
    const uint32_t mb = pack2(-mean, -mean);
#pragma unroll
    for (int i = 0; i < 10; i++) { const uint32_t d = add2(xv[i], mb); nv[i] = pack2(lo_f(d) * inv, hi_f(d) * inv); }
}
__device__ __forceinline__ void ln_mod(const uint32_t (&xv)[10], const uint32_t (&sv)[10], const uint32_t (&tv)[10], uint32_t (&hv)[10]) {
    ln_norm(xv, hv);
#pragma unroll
    for (int i = 0; i < 10; i++) hv[i] = add2(mul2(hv[i], add2(sv[i], 0x3f803f80u)), tv[i]);
}
__device__ __forceinline__ uint32_t ld_rlx(const uint32_t* f) { uint32_t v; asm volatile("ld.relaxed.gpu.global.u32 %0, [%1];" : "=r"(v) : "l"(f) : "memory"); return v; }
__device__ __forceinline__ void bump(uint32_t* f) { asm volatile("red.relaxed.gpu.global.add.u32 [%0], 1;" :: "l"(f) : "memory"); }
#define NAP 100
#define GPU_FENCE() asm volatile("fence.acq_rel.gpu;" ::: "memory")
__device__ __forceinline__ void flag_wait(const uint32_t* f, uint32_t target) {
    for (int n = 0;; n++) {
        uint32_t v; asm volatile("ld.relaxed.gpu.global.u32 %0, [%1];" : "=r"(v) : "l"(f) : "memory");
        if (v >= target) break;
        if (n > (1 << 22)) __trap();
        __nanosleep(NAP);
    }
}
__device__ __forceinline__ void flag_add(uint32_t* f, uint32_t v = 1) { asm volatile("red.release.gpu.global.add.u32 [%0], %1;" :: "l"(f), "r"(v) : "memory"); }
constexpr int N_SIDE = 36;
__device__ __forceinline__ void flags_release(int lane) {
    uint32_t old = 0;
    if (lane == 0) asm volatile("atom.relaxed.gpu.global.add.u32 %0, [%1], 1;" : "=r"(old) : "l"(&g_flags.done) : "memory");
    if (__shfl_sync(0xffffffffu, old, 0) == 96 + N_SIDE - 1)
#pragma unroll 1
        for (int i = lane; i < (int)(sizeof(Flags) / 16); i += 32) ((uint4*)&g_flags)[i] = make_uint4(0, 0, 0, 0);
}

template <int NT> struct ModSlice {
    static constexpr int R = 2 * DM / NT;
    float sc[R]; uint4 wv[R];
    __device__ __forceinline__ void load(const bf16* wmod, const bf16* c, int col, int tid) {
        const bf16* wm = wmod + (tid >> 1) * (6 * DM) + col + (tid & 1) * 8;
#pragma unroll
        for (int i = 0; i < R; i++) {
            asm volatile("ld.global.nc.L1::no_allocate.L2::128B.v4.u32 {%0,%1,%2,%3}, [%4];" : "=r"(wv[i].x), "=r"(wv[i].y), "=r"(wv[i].z), "=r"(wv[i].w) : "l"(wm + i * (NT / 2) * (6 * DM)));
            sc[i] = __uint_as_float((uint32_t)__ldg((const unsigned short*)c + (tid >> 1) + NT / 2 * i) << 16);
        }
    }
    __device__ __forceinline__ void partial(uint32_t buf, int tid) {
        const int lane = tid & 31;
        float a[8] = {0, 0, 0, 0, 0, 0, 0, 0};
#pragma unroll
        for (int i = 0; i < R; i++) {
            const float f = bfr(__fdividef(sc[i], 1.f + __expf(-sc[i])));
            const uint32_t u[4] = {wv[i].x, wv[i].y, wv[i].z, wv[i].w};
#pragma unroll
            for (int e = 0; e < 4; e++) { a[2 * e] += f * lo_f(u[e]); a[2 * e + 1] += f * hi_f(u[e]); }
        }
#pragma unroll
        for (int h = 4; h; h >>= 1)
#pragma unroll
            for (int e = 0; e < h; e++) { const bool up = lane & (4 * h); a[e] = (up ? a[e + h] : a[e]) + __shfl_xor_sync(0xffffffffu, up ? a[e] : a[e + h], 4 * h); }
        a[0] += __shfl_xor_sync(0xffffffffu, a[0], 2);
        asm volatile("st.shared.f32 [%0], %1;" :: "r"(buf + (tid >> 5) * 64 + (lane & 1) * 32 + (lane >> 2) * 4), "f"(a[0]) : "memory");
    }
    static __device__ __forceinline__ uint32_t total(uint32_t buf, int lane) {
        float a0 = 0, a1 = 0;
#pragma unroll
        for (int i = 0; i < NT / 32; i++) { float x, y; asm volatile("ld.shared.v2.f32 {%0,%1}, [%2];" : "=f"(x), "=f"(y) : "r"(buf + i * 64 + (lane & 7) * 8) : "memory"); a0 += x; a1 += y; }
        return pack2(a0, a1);
    }
};

struct ChainMaps { CUtensorMap wq, wk, wv, wo, h2, wo15, o15, slab16; };
struct ChainArgs { const bf16 *x, *mem0, *c, *wmod, *wv, *wo, *wgate, *wup, *wdown; bf16* out; int D1, D2, DG; };
constexpr uint32_t SM_BASE = 1024;
#define NRING 10
#define XORD 0
#define B5AT 41
#define QCUT 0x54
#define NCH 0
#define XA 2
#define VT 1
#define OSEND 1
#define SPOLL 0
#define NOF 0
#define FW 2
#define NPRE 9
#define REG_P 208
#define REG_L (504 - 2 * REG_P)
constexpr int WO_BLK = 7 * 4096;
constexpr int C_WV = 0, C_WO = 81920, C_XR = 167936, C_VP = C_XR + 7 * 4096, C_VX = C_XR + 8 * 4096, C_QX = C_VX + 4096, C_KX = C_QX + 4096,
              C_MEM = C_KX + 4096, C_OX = C_MEM + 9216, C_VM = C_OX + 3072, C_QM = C_VM + 1024, C_KM = C_QM + 1024, C_SC = C_KM + 1024, C_BAR = C_SC + 3840;
constexpr int CB_W = C_BAR, CB_W2 = C_BAR + 8, CB_SC = C_BAR + 16, CB_XD = C_BAR + 24, CB_VX = C_BAR + 32, CB_W3 = C_BAR + 40, CB_XM = C_BAR + 48, CB_OX = C_BAR + 56,
              CB_XF = C_BAR + 64, C_LAG = C_BAR + 96, C_UN = C_BAR + 100, C_MX = C_BAR + 112;
constexpr int C_SMEM = C_BAR + 128;
#define PROF(i)
#define PROFG(i)
#define PROFV(i, v)
static_assert(C_SMEM <= 232448, "chain shared memory");
__device__ __forceinline__ uint32_t umax3(uint32_t a, uint32_t b, uint32_t c) { return max(max(a, b), c); }
__device__ __forceinline__ void wait_until(uint32_t t) {
    asm volatile("{ .reg .pred p; .reg .s32 c; .reg .u64 d;\nU_%=: mov.u64 d, %%clock64; cvt.u32.u64 c, d; sub.s32 c, c, %0; setp.lt.s32 p, c, 0; @p bra.uni U_%=; }" :: "r"(t) : "memory");
}
__device__ __forceinline__ uint32_t gtime() { uint32_t c; asm volatile("mov.u32 %0, %%globaltimer_lo;" : "=r"(c)); return c; }
__device__ __forceinline__ uint32_t opaque(uint32_t v) { uint32_t r; asm volatile("shfl.sync.bfly.b32 %0, %1, 0, 31, -1;" : "=r"(r) : "r"(v)); return r; }
__device__ __forceinline__ uint32_t lds32(uint32_t a) { uint32_t v; asm volatile("ld.shared.u32 %0, [%1];" : "=r"(v) : "r"(a) : "memory"); return v; }
__device__ __forceinline__ float2 lds64f(uint32_t a) { float2 v; asm volatile("ld.shared.v2.f32 {%0,%1}, [%2];" : "=f"(v.x), "=f"(v.y) : "r"(a) : "memory"); return v; }
__device__ __forceinline__ float4 lds128f(uint32_t a) { float4 v; asm volatile("ld.shared.v4.f32 {%0,%1,%2,%3}, [%4];" : "=f"(v.x), "=f"(v.y), "=f"(v.z), "=f"(v.w) : "r"(a) : "memory"); return v; }
__device__ __forceinline__ void sts128f(uint32_t a, float x, float y, float z, float w) { asm volatile("st.shared.v4.f32 [%0], {%1,%2,%3,%4};" :: "r"(a), "f"(x), "f"(y), "f"(z), "f"(w) : "memory"); }
__device__ __forceinline__ void lds64(uint32_t (&v)[2], uint32_t a) { asm volatile("ld.shared.v2.u32 {%0,%1}, [%2];" : "=r"(v[0]), "=r"(v[1]) : "r"(a) : "memory"); }
__device__ __forceinline__ void mma16q(float (&d)[4], const uint32_t (&a)[4], uint32_t b0, uint32_t b1) { mma16(d, a[0], a[1], a[2], a[3], b0, b1); }
__device__ __forceinline__ uint32_t f16_to_bf16(uint32_t v) {
    float lo, hi; asm("{ .reg .f16 l, h; mov.b32 {l, h}, %2; cvt.f32.f16 %0, l; cvt.f32.f16 %1, h; }" : "=f"(lo), "=f"(hi) : "r"(v));
    return pack2(lo, hi);
}
__device__ __forceinline__ uint32_t pack2h(float lo, float hi) { uint32_t r; asm("cvt.rn.f16x2.f32 %0, %1, %2;" : "=r"(r) : "f"(hi), "f"(lo)); return r; }
#define SPLIT 1
__device__ __forceinline__ void cut(uint32_t never, int n) {
    asm volatile("{ .reg .pred p; setp.ne.u32 p, %0, %1; @p bra.uni C_%=; trap; C_%=: }" :: "r"(never), "r"(n) : "memory");
}
__device__ __forceinline__ void pin(uint32_t never, uint32_t a, uint32_t b, uint32_t c, uint32_t d) {
    asm volatile("{ .reg .pred p; setp.eq.u32 p, %0, 0; @p st.shared.v4.u32 [%0], {%1,%2,%3,%4}; }" :: "r"(never), "r"(a), "r"(b), "r"(c), "r"(d) : "memory");
}
__device__ __forceinline__ void pin0(uint32_t never) {
    asm volatile("{ .reg .pred p; setp.eq.u32 p, %0, 0; @p st.shared.u32 [%0], 0; }" :: "r"(never) : "memory");
}
#define ELECTED(txt) "{ .reg .pred e; elect.sync _|e, -1; @e " txt " }"
__device__ __forceinline__ void w_bulk_s2g(void* dst, uint32_t src, int bytes) {
    asm volatile(ELECTED("cp.async.bulk.global.shared::cta.bulk_group [%0], [%1], %2;") :: "l"(dst), "r"(src), "r"(bytes) : "memory");
}
__device__ __forceinline__ void w_bump(uint32_t* f) { asm volatile(ELECTED("red.relaxed.gpu.global.add.u32 [%0], 1;") :: "l"(f) : "memory"); }
__device__ __forceinline__ void w_expect(uint32_t bar, int bytes) { asm volatile(ELECTED("mbarrier.arrive.expect_tx.shared::cta.b64 _, [%0], %1;") :: "r"(bar), "r"(bytes) : "memory"); }
__device__ __forceinline__ void w_flag_wait(const uint32_t* f, uint32_t target) {
    asm volatile("{ .reg .pred p; .reg .u32 n, v; mov.u32 n, 0;\n"
                 "F_%=: ld.relaxed.gpu.global.u32 v, [%0]; setp.ge.u32 p, v, %1; vote.sync.all.pred p, p, -1; @p bra.uni G_%=;\n"
                 "nanosleep.u32 %2; add.u32 n, n, 1; setp.lt.u32 p, n, 0x400000; @p bra.uni F_%=;\ntrap;\nG_%=: }" :: "l"(f), "r"(target), "n"(NAP) : "memory");
}
#define BULK_COMMIT()    asm volatile("cp.async.bulk.commit_group;" ::: "memory")
#define BULK_WAIT()      asm volatile("cp.async.bulk.wait_group 0;" ::: "memory")
#define BULK_WAIT_READ() asm volatile("cp.async.bulk.wait_group.read 0;" ::: "memory")
#define PROXY_FENCE()    asm volatile("fence.proxy.async.shared::cta;" ::: "memory")
__device__ __forceinline__ void send16(uint32_t dst, uint32_t bar, float a, float b, float c, float d) {
    asm volatile("st.async.shared::cluster.mbarrier::complete_tx::bytes.v4.f32 [%0], {%1,%2,%3,%4}, [%5];" :: "r"(dst), "f"(a), "f"(b), "f"(c), "f"(d), "r"(bar) : "memory");
}
__device__ __forceinline__ void send8(uint32_t dst, uint32_t bar, uint32_t a, uint32_t b) {
    asm volatile("st.async.shared::cluster.mbarrier::complete_tx::bytes.v2.b32 [%0], {%1,%2}, [%3];" :: "r"(dst), "r"(a), "r"(b), "r"(bar) : "memory");
}

__device__ __forceinline__ void seg_done(int n, int head) {
    if (n >= 60 || (n & 3) == 3) { if (!NOF) GPU_FENCE(); w_bump(n >= 60 ? &g_flags.seg[(n - 60) * 32 + head] : &g_flags.qk[n >> 2]); }
}
__device__ __forceinline__ uint32_t x_base(int wg, uint32_t small, int sh) { return (uint32_t)mkdesc(SM_BASE + C_XR, 16, 1024) + wg * 256 + (small >> sh); }
__device__ __forceinline__ void x_chunk(float (&acc)[16], const uint32_t (&wa)[40][4], uint32_t xl, int a0, int i, int first) {
#pragma unroll
    for (int ks = 0; ks < 4; ks++)
        wgmma_rs_n32(acc, wa[a0 + 4 * i + ks], mkdesc(0, 0, 1024) | (uint32_t)(xl + (((i ? (i - 1) * 8192 : C_MEM - C_XR) + ks * 32) >> 4)), !(first && ks == 0));
}
__device__ __forceinline__ void x_part(float (&acc)[16], const uint32_t (&wa)[40][4], uint32_t sm, int n, int wg, int w, uint32_t ln, uint32_t small) {
    const int s = n - 1; (void)s;
    uint32_t giv[8];
    auto chunk = [&](int a0, int i, int first) { x_chunk(acc, wa, x_base(wg, small, a0 ? 21 : 22), a0, i, first); };
    mbar_wait(sm + CB_XM, n & 1);
    if (n) bar_sync(5, 384);
    if (wg == 0 && w == 0) PROF(12);
    WG_FENCE();
#pragma unroll
    for (int i = 1 + XA; i < 5; i++) chunk(20, i, 0);
    chunk(20, 0, 0);
    WG_COMMIT();
    if (n) {
        if (wg == 1 && w == 1) BULK_WAIT();
        bar_sync(8, 256);
    }
    if (wg == 0 && w == 0) PROF(18);
    const uint32_t xb = sm + w * 512 + ln * 16, xw = xb + C_KX - wg * 4096, xr = xb + C_QX + wg * 4096;
    WG_WAIT(0);
#pragma unroll
    for (int i = 0; i < 8; i++) asm volatile("cvt.rn.bf16x2.f32 %0, %1, %2;" : "=r"(giv[i]) : "f"(acc[2 * i + 1]), "f"(acc[2 * i]));
#pragma unroll
    for (int p = 0; p < 2; p++) asm volatile("st.shared.v4.u32 [%0], {%1,%2,%3,%4};" :: "r"(xw + p * 2048), "r"(giv[4 * p]), "r"(giv[4 * p + 1]), "r"(giv[4 * p + 2]), "r"(giv[4 * p + 3]) : "memory");
    bar_arrive(12 + wg, 256);
    WG_FENCE();
    chunk(0, 0, 1);
    WG_COMMIT();
    chunk(0, 1, 0);
    if (XORD) chunk(0, 2, 0);
    bar_sync(13 - wg, 256);
#pragma unroll
    for (int p = 0; p < 2; p++) asm volatile("ld.shared.v4.u32 {%0,%1,%2,%3}, [%4];" : "=r"(giv[4 * p]), "=r"(giv[4 * p + 1]), "=r"(giv[4 * p + 2]), "=r"(giv[4 * p + 3]) : "r"(xr + p * 2048) : "memory");
    WG_COMMIT(); WG_WAIT(1); bar_arrive(9, 384);
    WG_FENCE();
    if (!XORD) chunk(0, 2, 0);
    chunk(0, 3, 0); chunk(0, 4, 0);
    WG_COMMIT();
    const uint32_t r = ln & 7, mi = ln >> 3, dst = sm + (wg == 0 ? C_QX : C_KX) + ((mi >> 1) * 8 + r) * 128 + (((2 * w + (mi & 1)) ^ r) << 4);
    pin(xb, giv[0], giv[4], dst, 0);
    bar_sync(10 + wg, 128);
    WG_WAIT(0);
    if (wg == 0 && w == 0) PROF(30);
    if (w == 0 && ln < 3) mbar_arrive_remote(mapa(sm + CB_XD, ln));
#pragma unroll
    for (int i = 0; i < 8; i++) { acc[2 * i] += lo_f(giv[i]); acc[2 * i + 1] += hi_f(giv[i]); }
#pragma unroll
    for (int p = 0; p < 2; p++)
        stsm4t(dst + p * 2048, pack2(acc[8 * p], acc[8 * p + 1]), pack2(acc[8 * p + 2], acc[8 * p + 3]), pack2(acc[8 * p + 4], acc[8 * p + 5]), pack2(acc[8 * p + 6], acc[8 * p + 7]));
    if (wg == 0 && w == 0) PROF(11);
}
__device__ __forceinline__ void x_fill(const ChainMaps& mp, uint32_t sm, int n, int j) {
    mbar_expect(sm + CB_XF, 24576);
    asm volatile("cp.async.bulk.tensor.3d.shared::cluster.global.mbarrier::complete_tx::bytes.multicast::cluster [%0], [%1, {0, %3, %4}], [%2], %5;"
        :: "r"(sm + C_XR + j * 8192), "l"((uint64_t)&mp.h2), "r"(sm + CB_XF), "r"(n * SEG), "r"(2 + 2 * j), "h"((uint16_t)7) : "memory");
}
__device__ __forceinline__ void x_rest(const ChainMaps& mp, uint32_t sm, int n) {
    mbar_expect(sm + CB_XM, 16384);
    tma3d(sm + C_XR + 6 * 4096, &mp.h2, n * SEG, 8, sm + CB_XM); tma3d(sm + C_MEM, &mp.h2, n * SEG, 0, sm + CB_XM);
}

#define WPOS 15
#define WP 8
#define WOPF 30
#define SPF 0
#define SDEL 0
#define EORD 1
#define BPOS 1
#define TPF 1
#define B_LATE 14
constexpr int E_B = C_WO, E_STG = 196608, EB_A = 229376, EB_B = C_BAR + 80, EB_REL = C_BAR + 104;
__device__ __forceinline__ uint32_t e_slot(int wg, int c) { return wg && c == 2 ? E_B + 98304 : wg * 49152 + c * 16384; }
constexpr int T_WG = 0, T_WU = 20480, T_WD = 40960, T_X = 65536, T_RED = 77824, T_KEY = 86016;
__device__ __forceinline__ void wo_half(const ChainMaps& mp, uint32_t sm, int blk, int c) {
    if (blk < 80 && elect()) { mbar_expect(sm + EB_B + 8 * c, 49152); tma3d(sm + E_B + c * 49152, &mp.wo15, blk / 5 * 384 + c * 192, blk % 5 * 2, sm + EB_B + 8 * c); }
}
__device__ __forceinline__ void end_loads(const ChainMaps& mp, const ChainArgs& ar, uint32_t sm, int blk, int wg) {
    const uint32_t bar = sm + EB_A + wg * 48;
    const int kp = blk / 5;
    if (elect()) {
#pragma unroll 1
        for (int c = 0; c < 6; c++) mbar_init(bar + 8 * c, c < 3 ? 1 : 4);
        PROXY_FENCE();
    }
    __syncwarp();
    bar_arrive(5, 384);
    if (EORD) bar_sync(6, 96);
    if (blk >= 80) {
        if (TPF && elect()) {
#pragma unroll 1
            for (int c = 0; c < 3; c++) asm volatile("cp.async.bulk.prefetch.L2.global [%0], 61440;" :: "l"((c == 0 ? ar.wgate : c == 1 ? ar.wup : ar.wdown) + ((blk - 80) * 2 + wg) * 30720) : "memory");
        }
        return;
    }
    const uint64_t ef = policy_stream();
#pragma unroll 1
    for (int b = B_LATE; b < 16; b++) {
        w_flag_wait(b == 15 ? &g_flags.half[kp * 2 + wg] : &g_flags.pair[b * 16 + kp], b == 15 ? 2 : 4);
#pragma unroll 1
        for (int c = 0; c < 3; c++) {
            if (b > B_LATE) mbar_wait(bar + 24 + 8 * c, (b - B_LATE - 1) & 1);
            if (elect()) { mbar_expect(bar + 8 * c, 16384); tma3d_ef(sm + e_slot(wg, c), &mp.o15, b * 128 + wg * 64, kp * 6 + c * 2, bar + 8 * c, ef); }
            __syncwarp();
        }
    }
}
__device__ __forceinline__ void last_blocks(const ChainMaps& mp, const ChainArgs& ar, uint32_t sm, int blk, int tid) {
    const int warp = __shfl_sync(0xffffffffu, tid >> 5, 0), lane = tid & 31, wg = warp >> 2, w = warp & 3, kp = blk / 5, ct = blk % 5;
    const uint32_t bar = sm + EB_A + wg * 48, stg = sm + E_STG + warp * 4096;
    const uint64_t ef = policy_stream();
    bar_sync(5, 384);
    float acc[64];
#pragma unroll
    for (int n = 0; n < 64; n++) acc[n] = 0.f;
#pragma unroll 1
    for (int b = B_LATE; b < 16 && blk < 80; b++) {
#pragma unroll 1
        for (int c = 0; c < 6; c++) {
            mbar_wait(sm + EB_B + 8 * (c >= 3), 0); mbar_wait(bar + 8 * (c >> 1), (b - B_LATE) & 1);
            const uint64_t da = mkdesc(SM_BASE + e_slot(wg, c >> 1) + (c & 1) * 8192, 16, 1024), db = mkdesc(SM_BASE + E_B + (c >= 3 ? 24576 : 0) + c * 8192, 24576, 1024);
            WG_FENCE();
#pragma unroll
            for (int ks = 0; ks < 4; ks++) wgmma_ss_n128_tb(acc, da + ks * 2, db + ks * 128, c | ks);
            WG_COMMIT();
            WG_WAIT(1);
            if ((c & 1) == 0 && c && elect()) mbar_arrive(bar + 16 + 4 * c);
        }
        WG_WAIT(0);
        if (elect()) mbar_arrive(bar + 40);
        const int r = lane & 7, mi = lane >> 3;
#pragma unroll
        for (int p = 0; p < 8; p++) {
            const int oc = 2 * p + (mi >> 1);
            stsm4(stg + (oc >> 3) * 2048 + ((mi & 1) * 8 + r) * 128 + (((oc & 7) ^ r) << 4), pack2(acc[8 * p], acc[8 * p + 1]), pack2(acc[8 * p + 2], acc[8 * p + 3]),
                  pack2(acc[8 * p + 4], acc[8 * p + 5]), pack2(acc[8 * p + 6], acc[8 * p + 7]));
        }
        PROXY_FENCE();
        __syncwarp();
        if (elect()) tma3d_store(&mp.slab16, (b * KSPLIT + kp) * 128 + warp * 16, ct * 2, stg, ef, false);
        BULK_COMMIT(); BULK_WAIT();
        if (w) bar_arrive(12 + wg, 128); else { bar_sync(12 + wg, 128); GPU_FENCE(); w_bump(b < 14 ? &g_flags.o[b] : &g_flags.fin[((b - 14) * 2 + wg) * 32]); }
    }
    bar_sync(8, 256);
    const int o = (tid >> 1) * FF + blk * 16 + (tid & 1) * 8;
    const bf16 *pg = ar.wgate + o, *pu = ar.wup + o, *pd = ar.wdown + tid * DM + (blk < 80 ? blk : 0) * 8;
#pragma unroll
    for (int i = 0; i < 16; i++)
        asm volatile("cp.async.cg.shared.global [%0], [%1], 16;" :: "r"(sm + E_B + i * 4096 + tid * 16), "l"(i < 5 ? pg + i * 128 * FF : i < 10 ? pu + (i - 5) * 128 * FF : pd + (i - 10) * 256 * DM) : "memory");
}
__device__ __forceinline__ void mod_tail(const ChainArgs& ar, const uint32_t tb, const uint32_t bar, const int blk, const int tid) {
#define TPROF(i)
    const int warp = __shfl_sync(0xffffffffu, tid >> 5, 0), lane = tid & 31, r = lane & 7, mi = lane >> 3;
    const uint32_t kb = tb + T_KEY;
    {
        uint32_t k[8];
        for (int n = 0;; n++) {
#pragma unroll
            for (int i = 0; i < 2; i++) asm volatile("ld.relaxed.gpu.global.v4.u32 {%0,%1,%2,%3}, [%4];" : "=r"(k[4 * i]), "=r"(k[4 * i + 1]), "=r"(k[4 * i + 2]), "=r"(k[4 * i + 3]) : "l"(g_key + warp * 256 + i * 128 + lane * 4) : "memory");
            if (__all_sync(0xffffffffu, (k[0] & k[1] & k[2] & k[3] & k[4] & k[5] & k[6] & k[7] & S_TOK) != 0)) break;
            if (n > (1 << 22)) __trap();
            __nanosleep(NAP);
        }
        const uint32_t m = __reduce_max_sync(0xffffffffu, max(umax3(k[0], k[1], k[2]), max(umax3(k[3], k[4], k[5]), max(k[6], k[7]))));
        asm volatile("st.shared.u32 [%0], %1; st.shared.u32 [%2], 0;" :: "r"(kb + warp * 4), "r"(m), "r"(kb + 32) : "memory");
        asm volatile("cp.async.wait_all;" ::: "memory");
        bar_sync(1, 256);
        TPROF(1);
        const uint32_t low = __reduce_min_sync(0xffffffffu, lds32(kb + r * 4));
        uint32_t cnt = 0;
#pragma unroll
        for (int i = 0; i < 8; i++) cnt += k[i] >= low ? 4 : 0;
        if (cnt) {
            uint32_t a; asm volatile("atom.shared.add.u32 %0, [%1], %2;" : "=r"(a) : "r"(kb + 32), "r"(cnt) : "memory");
#pragma unroll
            for (int i = 0; i < 8; i++) if (k[i] >= low) { asm volatile("st.shared.u32 [%0], %1;" :: "r"(kb + 512 + a), "r"(k[i]) : "memory"); a += 4; }
        }
        if (tid == 0) mbar_arrive(bar);
        bar_sync(1, 256);
        const int nc = lds32(kb + 32);
#pragma unroll 1
        for (int c = lane * 4; c < nc; c += 128) {
            const uint32_t me = lds32(kb + 512 + c);
            int rank = 0;
#pragma unroll 2
            for (int e = 0; e < nc; e += 16) {
                const float4 z = lds128f(kb + 512 + e);
                rank += (__float_as_uint(z.x) > me) + (e + 4 < nc && __float_as_uint(z.y) > me) + (e + 8 < nc && __float_as_uint(z.z) > me) + (e + 12 < nc && __float_as_uint(z.w) > me);
            }
            if (rank < 8) asm volatile("st.shared.u32 [%0], %1;" :: "r"(kb + 64 + (warp * 8 + rank) * 4), "r"(me) : "memory");
        }
        __syncwarp();
    }
    const uint32_t k0 = lds32(kb + 64 + (warp * 8 + r) * 4), k1 = lds32(kb + 64 + (warp * 8 + (lane >> 2)) * 4);
    TPROF(2);
    const int trow = ~k1 & (S_TOK - 1), tcol = (blk < 80 ? blk : 0) * 8 + (lane & 3) * 2;
    uint2 xb[5];
#pragma unroll
    for (int h = 0; h < 5; h++) xb[h] = __ldcg((const uint2*)(g_h2 + trow * DM + (warp * 5 + h) * 16 + (lane & 3) * 4));
    const uint32_t fx1 = __ldcg((const uint32_t*)(g_x1 + trow * DM + tcol)), fh2 = __ldcg((const uint32_t*)(g_h2 + trow * DM + tcol)),
                   fgb = __ldcg((const uint32_t*)(g_mod + 5 * DM + tcol));
    const float fr = __uint_as_float(((int)k1 < 0 ? k1 ^ 0x80000000u : ~k1) & 0xffff0000u);
    {
        float dg[4] = {0, 0, 0, 0}, du[4] = {0, 0, 0, 0};
        uint32_t ag[5][4], au[5][4];
#pragma unroll
        for (int h = 0; h < 5; h++) {
            const uint32_t o = tb + ((warp * 5 + h) * 16 + (r >> 1) * 4 + (mi >> 1) * 2 + (r & 1)) * 32 + (mi & 1) * 16;
            ldsm4t(ag[h], o + T_WG); ldsm4t(au[h], o + T_WU);
        }
#pragma unroll
        for (int h = 0; h < 5; h++) { mma16q(dg, ag[h], xb[h].x, xb[h].y); mma16q(du, au[h], xb[h].x, xb[h].y); }
        TPROF(3);
        sts128f(tb + T_RED + warp * 1024 + lane * 16, dg[0], dg[1], dg[2], dg[3]); sts128f(tb + T_RED + warp * 1024 + 512 + lane * 16, du[0], du[1], du[2], du[3]);
    }
    bar_sync(1, 256);
    if (warp < 2) {
        float g2[2] = {0, 0}, u2[2] = {0, 0};
#pragma unroll
        for (int i = 0; i < 8; i++) {
            const float2 a = lds64f(tb + T_RED + i * 1024 + lane * 16 + warp * 8), b = lds64f(tb + T_RED + i * 1024 + 512 + lane * 16 + warp * 8);
            g2[0] += a.x; g2[1] += a.y; u2[0] += b.x; u2[1] += b.y;
        }
        float y[2];
#pragma unroll
        for (int i = 0; i < 2; i++) { const float gq = bfr(g2[i]); y[i] = bfr(__fdividef(gq, 1.f + __expf(-gq))) * bfr(u2[i]); }
        asm volatile("st.relaxed.gpu.global.u32 [%0], %1;" :: "l"(g_gu + (blk >> 1) * 128 + lane * 4 + warp * 2 + (blk & 1)), "r"(movm_t(pack2(y[0], y[1]))) : "memory");
    }
    TPROF(4);
    if (blk < 80) {
        uint32_t a[6][4], b[6][4];
#pragma unroll
        for (int k2 = 0; k2 < 6; k2++) ldsm4t(b[k2], tb + T_WD + (warp * 6 + k2) * 512 + lane * 16);
        for (int n = 0;; n++) {
            uint32_t m = 0;
#pragma unroll
            for (int k2 = 0; k2 < 6; k2++) asm volatile("ld.relaxed.gpu.global.v4.u32 {%0,%1,%2,%3}, [%4];" : "=r"(a[k2][0]), "=r"(a[k2][1]), "=r"(a[k2][2]), "=r"(a[k2][3]) : "l"(g_gu + (warp * 6 + k2) * 128 + lane * 4) : "memory");
#pragma unroll
            for (int k2 = 0; k2 < 6; k2++) m = umax3(umax3(m, a[k2][0], a[k2][1]), a[k2][2], a[k2][3]);
            if (!__any_sync(0xffffffffu, m == ~0u)) break;
            if (n > (1 << 22)) __trap();
        }
        TPROF(5);
        float d[2][4] = {{0, 0, 0, 0}, {0, 0, 0, 0}};
#pragma unroll
        for (int k2 = 0; k2 < 6; k2++) { mma16q(d[0], a[k2], b[k2][0], b[k2][1]); mma16q(d[1], a[k2], b[k2][2], b[k2][3]); }
        asm volatile("st.shared.v2.f32 [%0], {%1,%2};" :: "r"(tb + T_X + warp * 256 + lane * 8), "f"(d[0][0] + d[1][2]), "f"(d[0][1] + d[1][3]) : "memory");
        bar_sync(1, 256);
        if (warp == 0) {
            float y0 = 0, y1 = 0;
#pragma unroll
            for (int i = 0; i < 8; i++) { const float2 z = lds64f(tb + T_X + i * 256 + lane * 8); y0 += z.x; y1 += z.y; }
            const float sg = __fdividef(1.f, 1.f + __expf(-fr));
            *(uint32_t*)(ar.out + trow * DM + tcol) = add2(fx1, mul2(fgb, add2(fh2, mul2(pack2(y0, y1), pack2(sg, sg)))));
        }
    }
    TPROF(6);
}

__global__ void __cluster_dims__(3, 1, 1) __launch_bounds__(384, 1) k_chain(const __grid_constant__ ChainMaps mp, const __grid_constant__ ChainArgs ar) {
    const int D1 = ar.D1, DG = ar.DG;
    extern __shared__ __align__(1024) uint8_t smraw[];
    const uint32_t sm = SM_BASE + ((blockIdx.x % 3) << 24);
    if (smem_u32(smraw) != sm) __trap();
    uint32_t tid; asm volatile("mov.u32 %0, %%tid.x;" : "=r"(tid));
    const int warp = __shfl_sync(0xffffffffu, tid >> 5, 0), lane = tid & 31, wg = warp >> 2, w = warp & 3;
    const int blk = blockIdx.x, head = blk / 3, j = blk % 3;
    const int col0 = head * DH + j * 64;
    asm volatile("griddepcontrol.launch_dependents;");
#define PPROF(i)
    const int r = lane & 7, mi = lane >> 3;
    const uint32_t memrd = opaque(sm + C_MEM + lane * 16);
    if (wg < 2) {
        {
            uint32_t xv[3][10];
            const int row = blk * 8 + warp, nq = row < S_TOK - 1536 ? 3 : 2;
#pragma unroll
            for (int i = 0; i < 15; i++) {
                const uint2 v = __ldcs((const uint2*)(ar.x + (row + (i < 10 || nq == 3 ? i / 5 * 768 : 0)) * DM + lane * 4 + i % 5 * 128));
                xv[i / 5][i % 5 * 2] = v.x; xv[i / 5][i % 5 * 2 + 1] = v.y;
            }
            if (tid == 32) {
#pragma unroll 1
                for (int c = 0; c < 14; c++) if (c != 12) mbar_init(sm + C_BAR + 8 * c, c == 2 ? 5 : c == 3 ? 6 : 1);
                asm volatile("fence.mbarrier_init.release.cluster;" ::: "memory");
                mbar_expect(sm + CB_SC, 2560); mbar_expect(sm + CB_OX, 2048);
            }
            if (warp == 2) {
                const uint32_t f = blk >= 28 ? ~0u : 0u;
                ((uint4*)g_acc)[blk * 32 + lane] = make_uint4(0, 0, 0, 0);
                if (blk < 76) (blk < 12 ? (uint4*)g_stamp + blk * 32 : blk < 28 ? (uint4*)g_key + (blk - 12) * 32 : (uint4*)g_gu + (blk - 28) * 32)[lane] = make_uint4(f, f, f, f);
            }
            __syncwarp();
            asm volatile("barrier.cluster.arrive.relaxed.aligned;" ::: "memory");
            PPROF(8);
#pragma unroll 1
            for (int q = 0; q < 3; q++) {
                uint32_t nv[10];
                ln_norm(xv[0], nv);
#pragma unroll
                for (int i = 0; i < 10; i++) { xv[0][i] = xv[1][i]; xv[1][i] = xv[2][i]; xv[2][i] = nv[i]; }
            }
            PPROF(9);
            if (warp < 5) {
                uint4 u;
                for (int n = 0;; n++) {
                    asm volatile("ld.relaxed.gpu.global.v4.u32 {%0,%1,%2,%3}, [%4];" : "=r"(u.x), "=r"(u.y), "=r"(u.z), "=r"(u.w) : "l"(g_flags.mod1 + tid * 4) : "memory");
                    if (__all_sync(0xffffffffu, u.x && u.y && u.z && u.w)) break;
                    cut(n, 1 << 22);
                }
                asm volatile("st.shared.v4.u32 [%0], {%1,%2,%3,%4};" :: "r"(sm + C_KX + tid * 16), "r"(~u.x), "r"(~u.y), "r"(~u.z), "r"(~u.w) : "memory");
            }
            bar_sync(8, 256);
            PPROF(2);
            uint32_t m = 0;
#pragma unroll
            for (int i = 0; i < 5; i++) {
                uint32_t t[2], u[2];
                lds64(t, sm + C_KX + lane * 8 + i * 256); lds64(u, sm + C_KX + 1280 + lane * 8 + i * 256);
                u[0] = add2(u[0], 0x3f803f80u); u[1] = add2(u[1], 0x3f803f80u);
                m = amax2(amax2(amax2(amax2(m, t[0]), u[0]), t[1]), u[1]);
#pragma unroll
                for (int q = 0; q < 3; q++)
                    if (q < nq) *(uint2*)(g_h + (row + q * 768) * DM + lane * 4 + i * 128) = make_uint2(add2(mul2(xv[q][2 * i], u[0]), t[0]), add2(mul2(xv[q][2 * i + 1], u[1]), t[1]));
            }
            asm volatile("st.shared.u32 [%0], %1;" :: "r"(sm + C_LAG), "r"((amax_warp(m) >> 7) + 1) : "memory");
            bar_sync(8, 256);
            if (tid == 0) flag_add(&g_flags.h);
            __syncwarp();
            bar_arrive(2, 288);
            PPROF(3);
            asm volatile("barrier.cluster.wait.aligned;" ::: "memory");
        }
        asm volatile("setmaxnreg.inc.sync.aligned.u32 %0;" :: "n"(REG_P));
        uint32_t wa[40][4];
        mbar_wait(sm + CB_W, 0);
#pragma unroll
        for (int ks = 0; ks < 40; ks++)
            ldsm4t(wa[ks], sm + ((wg == 0) == (ks < 20) ? C_WV : C_WO) + ((mi >> 1) * 8 + r) * 128 + (((2 * w + (mi & 1)) ^ r) << 4) + (ks % 20 / 4 * 8 + 4 * wg + (ks & 3)) * 2048);
        PPROF(5);
        bar_arrive(1, 288);
        const uint32_t qst = opaque(sm + (wg == 0 ? C_QM : C_KM) + (2 * w + (mi & 1)) * 128 + r * 16);
        const uint32_t vrd = opaque(sm + C_WV + ((mi >> 1) * 8 + r) * 128 + (((2 * w + (mi & 1)) ^ r) << 4) + 4 * wg * 2048);
        const uint32_t mrd = opaque(memrd + wg * 1024);
        float acc[16];
        auto fb = [&](int n) { return mrd + (n >> 1) * 2048 + (n & 1) * 512; };
        auto fa = [&](int k) { return vrd + (k >> 2) * 16384 + (k & 3) * 2048; };
        auto qk_out = [&](int n) {
            uint8_t* rec = g_att + (n * NH + head) * AT_REC;
            w_bulk_s2g(rec + j * 8192, sm + C_QX, 8192); w_bulk_s2g(rec + AT_KM + j * 1024, sm + C_KM, 1024);
            BULK_COMMIT();
        };
        for (int s = -1;; s++) {
          if (s >= 0) {
            x_part(acc, wa, sm, s, wg, w, opaque(mrd) >> 4 & 31, s + ar.D2);
            if (s == 0) mbar_wait(sm + CB_W2, 0);
            uint32_t b[3][4], a[4][4];
#pragma unroll
            for (int i = 0; i < 4; i++) ldsm4t(a[i], fa(4 + i));
            cut(s + ar.D2, 0);
            bar_sync(1, 384);
            if (warp == 0) { PROF(0); PROFG(24); }
            float dv[4] = {0, 0, 0, 0};
            const uint32_t xb = mrd - wg * 1024 - (C_MEM - C_VP) + w * 512;
            {
                float d[2][4] = {{0, 0, 0, 0}, {0, 0, 0, 0}}, g[2][4] = {{0, 0, 0, 0}, {0, 0, 0, 0}};
                ldsm4t(b[0], fb(0)); pin0(mrd); ldsm4t(b[1], fb(1)); pin0(mrd);
#pragma unroll
                for (int n = 0; n < 10; n++) {
                    const int c1 = n >= 10 - NCH;
                    if (n < 8) ldsm4t(b[(n + 2) % 3], fb(n + 2));
#pragma unroll
                    for (int e = 0; e < 2; e++) {
                        mma16q(g[e & c1], wa[20 + 2 * n + e], b[n % 3][2 * e], b[n % 3][2 * e + 1]); mma16q(d[e & c1], wa[2 * n + e], b[n % 3][2 * e], b[n % 3][2 * e + 1]);
                        if (n >= 2 && n < 10 - VT) mma16q(dv, a[(2 * n + e) & 3], b[n % 3][2 * e], b[n % 3][2 * e + 1]);
                        if (n >= 2 && n < 8) ldsm4t(a[(2 * n + e) & 3], fa(2 * n + 4 + e));
                    }
                    if (QCUT >> n & 1) cut(s + ar.D2, 1 + n);
                }
                const float un = __uint_as_float(lds32(sm + C_UN));
                sts128f(xb - 4096 + wg * 2048, g[0][0] + g[1][0], g[0][1] + g[1][1], g[0][2] + g[1][2], g[0][3] + g[1][3]);
#pragma unroll
                for (int k = 20 - 2 * VT; k < 20; k++) mma16q(dv, a[k & 3], b[k / 2 % 3][2 * (k & 1)], b[k / 2 % 3][2 * (k & 1) + 1]);
                bar_sync(8, 256);
                const float4 z = lds128f(xb - 4096 + (wg ^ 1) * 2048);
                sts128f(xb + wg * 2048, dv[0], dv[1], dv[2], dv[3]);
                stsm2t(qst, pack2((d[0][0] + d[1][0] + z.x) * un, (d[0][1] + d[1][1] + z.y) * un), pack2((d[0][2] + d[1][2] + z.z) * un, (d[0][3] + d[1][3] + z.w) * un));
            }
            bar_arrive(2, 384);
            if (w == 0) PROF(1 + wg);
            if (s + 1 == NSEG) break;
          }
          if (warp == 3 && s >= 0)
              asm volatile(ELECTED("st.relaxed.gpu.global.u32 [%0], %1;") :: "l"(g_stamp + (s & 3) * 384 + (blk >> 3) * 32 + (blk & 7)), "r"((gtime() & ~31u) | ((s >> 2) + 1)) : "memory");
          PROXY_FENCE();
          mbar_wait(sm + CB_XF, (s + 1) & 1);
          if (s >= 0) bar_sync(7, 384);
          WG_FENCE();
#pragma unroll
          for (int i = 0; i < 16; i++) acc[i] = 0.f;
#pragma unroll
          for (int i = 1; i <= XA; i++) x_chunk(acc, wa, x_base(wg, s + ar.D2, 20), 20, i, i == 1);
          WG_COMMIT();
          if (warp == FW && s > 0) seg_done(s - 1, head);
          WG_WAIT(0);
          if (s >= 0) {
            if (warp == 0) {
                PROF(7);
                if (elect()) x_rest(mp, sm, s + 1);
            } else {
                if (wg == 1) {
                    if (w == 1) {
                        qk_out(s);
                    }
                    if (w == 2 && blk < 10 && s + 3 < NSEG)
                        asm volatile(ELECTED("cp.async.bulk.prefetch.L2.global [%0], 4096;") :: "l"((const uint8_t*)g_h + (s + 3) * (SEG * DM * 2) + blk * 4096) : "memory");
                } else if (w == 3) {
                    if (SPOLL) wait_until(clock() + SPOLL);
                    const uint32_t l = opaque(mrd) >> 4 & 31, tag = (s >> 2) + 1, now = gtime();
                    const uint32_t* sp = g_stamp + (s & 3) * 384 + (l >> 3) * 32 + (l & 7);
                    uint32_t t[3];
                    for (int n = 0;; n++) {
#pragma unroll
                        for (int i = 0; i < 3; i++) t[i] = ld_rlx(sp + i * 128);
                        if (!__any_sync(0xffffffffu, ((t[0] ^ tag) | (t[1] ^ tag) | (t[2] ^ tag)) & 31) || n > SPIN_LIMIT) break;
                    }
                    int all = -(1 << 30), own = all;
#pragma unroll
                    for (int i = 0; i < 3; i++) { const int d = t[i] - now; all = max(all, d); if ((i * 32 + l) / 3 == head) own = d; }
                    const int lag = min(__reduce_max_sync(0xffffffffu, all) - __reduce_max_sync(0xffffffffu, own), 8000);
                    PROFV(15, lag);
                    asm volatile("st.shared.u32 [%0], %1;" :: "r"(sm + C_LAG), "r"(D1 + ((lag * DG) >> 4)) : "memory");
                    bar_arrive(6, 160);
                } else if (w == 2) {
                    if ((s & 3) == 3) w_flag_wait(&g_flags.v[((s + 1) >> 2) * 32 + head], 2);
                    if (elect()) { mbar_expect(sm + CB_VX, 4096); bulk_g2s(sm + C_VX, g_att + ((s + 1) * NH + head) * AT_REC + AT_V + j * 4096, 4096, sm + CB_VX); }
                    if ((s & 3) == 1 && s + 3 < NSEG) asm volatile("prefetch.global.L2 [%0];" :: "l"(&g_flags.v[((s + 3) >> 2) * 32]));
                    if (s + 2 < NSEG && ((s & 3) != 2 || __all_sync(0xffffffffu, ld_rlx(&g_flags.v[((s + 2) >> 2) * 32 + head]) >= 2)))
                        asm volatile("prefetch.global.L2 [%0];" :: "l"(g_att + ((s + 2) * NH + head) * AT_REC + AT_V + j * 4096 + (opaque(mrd) << 3 & 0xf80)));
                }
            }
          }
        }
        PROXY_FENCE();
        bar_sync(8, 256);
        if (warp == 5) { qk_out(NSEG - 1); BULK_WAIT(); }
        if (warp == 7) seg_done(NSEG - 2, head);
        bar_arrive(7, 384);
        const int t2 = (opaque(mrd) >> 4 & 31) + warp * 32;
        last_blocks(mp, ar, sm, blk, t2);
        mod_tail(ar, sm + E_B, sm + EB_REL, blk, t2);
    } else {
        asm volatile("setmaxnreg.dec.sync.aligned.u32 %0;" :: "n"(REG_L));
        asm volatile("barrier.cluster.arrive.relaxed.aligned;" ::: "memory");
        if (blk < 80) {
            ModSlice<128> ms;
            ms.load(ar.wmod, ar.c, blk * 16, tid - 256); ms.partial(sm + C_QM, tid - 256);
            bar_sync(3, 128);
            if (w == 0) {
                const uint32_t v = ModSlice<128>::total(sm + C_QM, lane);
                asm volatile("st.relaxed.gpu.global.u32 [%0], %1;" :: "l"(g_flags.mod1 + blk * 8 + (lane & 7)), "r"(~v) : "memory");
            }
        }
        uint32_t m0[5][4], mm = 0;
#pragma unroll
        for (int i = 0; i < 20; i++) {
            const unsigned short* p = (const unsigned short*)ar.mem0 + (i & 3) * 2 * DM + (i >> 2) * 128 + tid - 256;
            m0[i >> 2][i & 3] = __ldg(p) | (uint32_t)__ldg(p + DM) << 16;
        }
        {
            asm volatile("barrier.cluster.wait.aligned;" ::: "memory");
            if (w == 3) {
                w_flag_wait(&g_flags.h, 96);
                if (elect()) { x_fill(mp, sm, 0, j); x_rest(mp, sm, 0); }
                __syncwarp();
            }
            if (w == 1) {
                const uint64_t ef = policy_stream();
#pragma unroll 1
                for (int c = 0; c < 2 * WP + 2; c++) {
                    const uint32_t bar = sm + EB_B + 8 * (c & 1);
                    if (c == WPOS) bar_sync(2, 288);
                    if (c >= 2) mbar_wait(bar, (c / 2 - 1) & 1);
                    if (elect()) {
                        if (c < 2 * WP) { mbar_expect(bar, 81920 / WP); tma2d_ef(sm + C_WV + c * (81920 / WP), c < WP ? &mp.wq : &mp.wk, col0, c % WP * (640 / WP), bar, ef); }
                        if (c >= WOPF && c < WOPF + 3) asm volatile("cp.async.bulk.prefetch.tensor.3d.L2.global [%0, {0, %1, %2}];" :: "l"((uint64_t)&mp.wo), "r"(head * DH + (c - WOPF) * 64), "r"(7 * j) : "memory");
                    }
                    __syncwarp();
                }
                if (elect()) mbar_arrive(sm + CB_W);
                bar_sync(1, 288);
                if (elect()) {
                    mbar_expect(sm + CB_W2, 81920); mbar_expect(sm + CB_W3, 3 * WO_BLK);
#pragma unroll 1
                    for (int c = 0; c < 4; c++) tma2d(sm + C_WV + c * 20480, &mp.wv, col0, c * 160, sm + CB_W2);
#pragma unroll 1
                    for (int c = 0; c < 3; c++) tma3d(sm + C_WO + c * WO_BLK, &mp.wo, head * DH + (j + c) % 3 * 64, 7 * j, sm + CB_W3);
                }
                __syncwarp();
                w_flag_wait(&g_flags.v[head], 2);
                if (elect()) { mbar_expect(sm + CB_VX, 4096); bulk_g2s(sm + C_VX, g_att + head * AT_REC + AT_V + j * 4096, 4096, sm + CB_VX); }
            } else {
                uint32_t mw = 0;
#pragma unroll 1
                for (int c = 0; c < 2; c++) {
                    mbar_wait(sm + (c ? CB_W3 : CB_W2), 0);
                    uint32_t m = 0;
                    const uint32_t end = sm + (c ? C_XR : C_WO);
#pragma unroll 1
                    for (uint32_t a = sm + c * C_WO + (w - (w > 0)) * 4096 + lane * 16; a < end; a += 3 * 4096) {
                        float4 z[8];
#pragma unroll
                        for (int i = 0; i < 8; i++) z[i] = lds128f(a + i * 512);
#pragma unroll
                        for (int i = 0; i < 8; i++) m = amax2(amax2(amax2(amax2(m, __float_as_uint(z[i].x)), __float_as_uint(z[i].y)), __float_as_uint(z[i].z)), __float_as_uint(z[i].w));
                    }
                    mw |= amax_warp(m) << (16 * c);
                }
                asm volatile("st.shared.u32 [%0], %1;" :: "r"(sm + C_KM + w * 4), "r"(mw) : "memory");
                bar_sync(3, 96);
                if (w == 0) asm volatile("st.relaxed.gpu.global.u32 [%0], %1;" :: "l"(g_flags.wmax + blk), "r"(amax2(amax2(mw, lds32(sm + C_KM + 8)), lds32(sm + C_KM + 12)) | 0x8000) : "memory");
            }
        }
        bar_sync(9, 384);
#pragma unroll
        for (int i = 0; i < 5; i++) {
            asm volatile("st.shared.v4.u32 [%0], {%1,%2,%3,%4};" :: "r"(sm + C_MEM + (tid - 256 + i * 128) * 16), "r"(m0[i][0]), "r"(m0[i][1]), "r"(m0[i][2]), "r"(m0[i][3]) : "memory");
            mm = amax2(amax2(amax2(amax2(mm, m0[i][0]), m0[i][1]), m0[i][2]), m0[i][3]);
        }
        asm volatile("st.shared.u32 [%0], %1; st.shared.u32 [%2], 0x3f800000;" :: "r"(sm + C_MX + w * 4), "r"(amax_warp(mm)), "r"(sm + C_UN) : "memory");
        int ew = __shfl_sync(0xffffffffu, lds32(sm + C_LAG), 0), es = 0;
        const uint32_t rb1 = (uint32_t)((j + 1) % 3 - j) << 24, rb2 = (uint32_t)((j + 2) % 3 - j) << 24;
        const float scale = 0.07216878364870322f;
        uint32_t va[8][4], mr = memrd;
#pragma unroll
        for (int i = 0; i < 8; i++) ldsm4t(va[i], sm + C_WV + ((mi >> 1) * 8 + r) * 128 + (((2 * w + (mi & 1)) ^ r) << 4) + i * 2048);
        bar_sync(1, 384);
        for (int s = 0; s < NSEG; s++) {
            const float un = __uint_as_float((127 - es) << 23);
            if (w == 1) {
                mbar_wait(sm + CB_XD, s & 1);
                if (s + 1 < NSEG) { if (elect()) x_fill(mp, sm, s + 1, j); }
                else { if (BPOS != 2) wo_half(mp, sm, blk, 0); if (BPOS != 0) wo_half(mp, sm, blk, 1); }
            }
            const uint32_t l0 = mr >> 4 & 31, r0 = l0 & 7, m0 = l0 >> 3;
            float vd[4];
            {
                uint32_t c[4][4];
#pragma unroll
                for (int i = 0; i < 4; i++) ldsm4t(c[i], mr + i * 512);
                float d[2][4] = {{0, 0, 0, 0}, {0, 0, 0, 0}};
#pragma unroll
                for (int i = 0; i < 8; i++) mma16q(d[i & 1], va[i], c[i >> 1][2 * (i & 1)], c[i >> 1][2 * (i & 1) + 1]);
#pragma unroll
                for (int i = 0; i < 4; i++) vd[i] = d[0][i] + d[1][i];
            }
            uint32_t zr = 0;
            if (w == 2)
                asm volatile("atom.relaxed.gpu.global.exch.b32 %0, [%1], 0;" : "=r"(zr)
                    : "l"(g_acc + ((s & 2) ^ 2) * (ACC_PAIR / 2) + (s & 1) * 512 + (blk >> 2) * 1024 + (blk & 3) * 128 + l0 * 4) : "memory");
            __syncwarp();
            uint32_t kb[4][4];
            {
                const uint32_t k7 = r0 ^ (m0 << 2 & 4), kxrd = sm + C_KX + (16 * (w & 1) + 8 * (m0 & 1) + k7) * 128 + (((m0 >> 1) ^ k7) << 4);
#pragma unroll
                for (int i = 0; i < 4; i++) ldsm4(kb[i], kxrd ^ (i << 5));
            }
            const uint32_t qrd = sm + C_QM + (w == 1 ? (m0 & 1) * 2 + (m0 >> 1) : m0) * 128 + r0 * 16;
            const uint32_t scdst = sm + C_SC + j * 1280 + (w == 1 ? 1024 + l0 * 8 : (w & 1) * 512 + (l0 & 2) * 128 + (l0 >> 2) * 32 + (l0 & 1) * 16);
            const uint32_t scrd = sm + C_SC + (l0 >> 4) * 256 + (l0 & 3) * 32 + (l0 >> 2 & 3) * 8;
            const uint32_t v7 = (4 * (m0 & 1) + (r0 >> 1)) ^ (r0 << 2 & 4), vxrd = sm + C_VX + (16 * (m0 >> 1) + 8 * (r0 & 1) + v7) * 128 + (((2 * w) ^ v7) << 4);
            if (s == 0) {
                uint32_t t[3];
                for (int n = 0;; n++) {
#pragma unroll
                    for (int i = 0; i < 3; i++) t[i] = ld_rlx(g_flags.wmax + l0 + 32 * i);
                    if (__all_sync(0xffffffffu, t[0] && t[1] && t[2])) break;
                    cut(n, 1 << 22);
                }
                const uint32_t m = amax2(amax2(amax2(0, t[0]), t[1]), t[2]);
                const int e = 371 - (int)(__reduce_max_sync(0xffffffffu, m & 0xffffu) >> 7) - (int)(__reduce_max_sync(0xffffffffu, m >> 16) >> 7);
                ew = e << 16 | (min(e - ew, 100) & 0xffff);
            }
            mbar_wait(sm + CB_VX, s & 1);
            uint32_t vb[2][4];
            ldsm4t(vb[0], vxrd); ldsm4t(vb[1], vxrd ^ 16);
            const uint32_t word = sm + C_WO + (m0 & 1) * 4096 + ((m0 >> 1) * 8 + r0) * 64 + ((w ^ (r0 >> 1)) << 4);
            const uint32_t word6 = word + 6 * 4096 - (m0 & 1) * 3072;
            const uint32_t oxrd = sm + C_OX + l0 * 8;
            const uint32_t ord = oxrd + w * 256;
            const uint32_t vp = mr - (C_MEM - C_VP) + w * 512, vmst = mr + (C_VM - C_MEM) + w * 256;
            pin(mr, scdst + rb1, sm + CB_SC + rb1, scdst + rb2, sm + CB_SC + rb2); pin(mr, qrd, scdst, scrd, vp); pin(mr, word, word6, oxrd, ord);
            pin(mr, __float_as_uint(vd[0]), __float_as_uint(vd[1]), __float_as_uint(vd[2]), __float_as_uint(vd[3]));
            bar_sync(2, 384);
            const bool odd = mr & 16;
            float4 y0, y1, mx4;
            {
                uint32_t qa[2][4];
                ldsm4(qa[0], qrd); ldsm4(qa[1], qrd + 512);
                float sc[2][4] = {{0, 0, 0, 0}, {0, 0, 0, 0}};
                if (w == 1) {
                    ldsm4(kb[0], mr + (C_KM - C_MEM)); ldsm4(kb[1], mr + (C_KM - C_MEM) + 512);
                    pin0(mr); y0 = lds128f(vp); y1 = lds128f(vp + 2048); mx4 = lds128f(sm + C_MX);
#pragma unroll
                    for (int k = 0; k < 4; k++) mma16q(sc[k & 1], qa[k >> 1], kb[k >> 1][2 * (k & 1)], kb[k >> 1][2 * (k & 1) + 1]);
                    const uint32_t a0 = __float_as_uint(sc[0][0] + sc[1][2]), a1 = __float_as_uint(sc[0][1] + sc[1][3]);
                    send8(scdst + rb1, sm + CB_SC + rb1, a0, a1); send8(scdst + rb2, sm + CB_SC + rb2, a0, a1);
                    asm volatile("st.shared.v2.u32 [%0], {%1,%2};" :: "r"(scdst), "r"(a0), "r"(a1) : "memory");
                } else {
                    pin0(mr); y0 = lds128f(vp); y1 = lds128f(vp + 2048); mx4 = lds128f(sm + C_MX);
                    if (w) {
#pragma unroll
                        for (int k = 0; k < 4; k++) mma16q(sc[k & 1], kb[k], qa[k >> 1][2 * (k & 1)], qa[k >> 1][2 * (k & 1) + 1]);
                        const float a0 = sc[0][0] + sc[1][0], a1 = sc[0][2] + sc[1][2], a2 = sc[0][1] + sc[1][1], a3 = sc[0][3] + sc[1][3];
                        send16(scdst + rb1, sm + CB_SC + rb1, a0, a1, a2, a3); send16(scdst + rb2, sm + CB_SC + rb2, a0, a1, a2, a3);
                        sts128f(scdst, a0, a1, a2, a3);
                    }
                }
            }
            bar_arrive(7, 384);
            if (elect()) mbar_arrive(sm + CB_SC);
            {
                const float4 z = mx4;
                const int em = (int)(max(max(__float_as_uint(z.x), __float_as_uint(z.y)), max(__float_as_uint(z.z), __float_as_uint(z.w))) >> 7) - es;
                es = __shfl_sync(0xffffffffu, max(min((ew >> 16) - em, (int)(short)ew), -120), 0);
            }
            if (w == 0) PROF(4);
            const uint32_t vm0 = pack2((vd[0] + y0.x + y1.x) * un, (vd[1] + y0.y + y1.y) * un), vm1 = pack2((vd[2] + y0.z + y1.z) * un, (vd[3] + y0.w + y1.w) * un);
            stsm2t(vmst, vm0, vm1);
            if (s + 1 == NSEG) {
                mbar_wait(sm + CB_SC, s & 1);
                PROXY_FENCE();
                bar_sync(3, 128);
                if (w == 1) {
                    w_bulk_s2g(g_att + (s * NH + head) * AT_REC + AT_VM + j * 1024, sm + C_VM, 1024);
                    BULK_COMMIT();
                    BULK_WAIT();
                }
                __syncwarp();
                break;
            }
            cut(s + ar.D2, 0);
            mbar_wait(sm + CB_SC, s & 1);
            if (w == 0) PROF(8);
            float sv[10];
            {
                float2 z[5][3];
#pragma unroll
                for (int u = 0; u < 5; u++)
#pragma unroll
                    for (int p = 0; p < 3; p++) z[u][p] = lds64f((u < 4 ? scrd + (u >> 1) * 512 + (u & 1) * 128 : oxrd + (C_SC - C_OX) + 1024) + p * 1280);
#pragma unroll
                for (int u = 0; u < 5; u++) { sv[2 * u] = (z[u][0].x + z[u][1].x) + z[u][2].x; sv[2 * u + 1] = (z[u][0].y + z[u][1].y) + z[u][2].y; }
            }
            float mx = fmaxf(fmaxf(fmaxf(sv[0], sv[1]), fmaxf(sv[2], sv[3])), fmaxf(fmaxf(fmaxf(sv[4], sv[5]), fmaxf(sv[6], sv[7])), fmaxf(sv[8], sv[9])));
            uint32_t a[NRING][4];
            auto frag = [&](int i) { const int p = i / 7, u = i % 7, o = (p >> 1) * WO_BLK + (p & 1) * 2048;
                                     return u == 3 ? word6 + o : word + o + (u > 3 ? 1024 + (u - 4) * 8192 : u * 8192); };
            mx = fmaxf(fmaxf(mx, __shfl_xor_sync(0xffffffffu, mx, 1)), fmaxf(__shfl_xor_sync(0xffffffffu, mx, 2), __shfl_xor_sync(0xffffffffu, mx, 3)));
            pin(mr, __float_as_uint(mx), 0, 0, 0);
            {
#pragma unroll
                for (int i = 0; i < NPRE; i++) ldsm4t(a[i], frag(i));
                pin0(mr);
                const float sl2e = scale * 1.4426950408889634f, mxl = mx * sl2e;
#pragma unroll
                for (int i = 9; i >= 0; i--) asm volatile("ex2.approx.ftz.f32 %0, %1;" : "=f"(sv[i]) : "f"(fmaf(sv[i], sl2e, -mxl)));
                const uint32_t pq[4] = {pack2(sv[0], sv[1]), pack2(sv[4], sv[5]), pack2(sv[2], sv[3]), pack2(sv[6], sv[7])}, pm = pack2(sv[8], sv[9]);
                if (w == 0) PROF(6);
                float o[2][4] = {{0, 0, 0, 0}, {0, 0, 0, 0}}, o2[2][4] = {{0, 0, 0, 0}, {0, 0, 0, 0}}, sx[4] = {0, 0, 0, 0};
                mma8(sx, pm, 0, 0x3f803f80u); mma8(o[0], pm, 0, vm0); mma8(o[1], pm, 0, vm1);
                mma16q(sx, pq, 0x3f803f80u, 0x3f803f80u);
#pragma unroll
                for (int u = 0; u < 2; u++) { mma16q(o[u], pq, vb[u][0], vb[u][1]); mma16q(o2[u], pq, vb[u][2], vb[u][3]); }
                float inv; asm("rcp.approx.ftz.f32 %0, %1;" : "=f"(inv) : "f"((sx[0] + sx[2]) * __uint_as_float((127 - es) << 23)));
                const uint32_t f0 = pack2((o[0][0] + o2[0][2]) * inv, (o[0][1] + o2[0][3]) * inv), f1 = pack2((o[1][0] + o2[1][2]) * inv, (o[1][1] + o2[1][3]) * inv);
                send8(ord + 2048 + rb1, sm + CB_OX + rb1, f0, f1); send8(ord + 1024 + rb2, sm + CB_OX + rb2, f0, f1);
                asm volatile("st.shared.v2.u32 [%0], {%1,%2};" :: "r"(ord), "r"(f0), "r"(f1) : "memory");
            }
            if (w == 0) PROF(10);
#pragma unroll
            for (int i = NPRE; i < NRING; i++) ldsm4t(a[i], frag(i));
            bar_sync(3, 128);
            float e[5][4];
#pragma unroll
            for (int q = 0; q < 5; q++) e[q][0] = e[q][1] = e[q][2] = e[q][3] = 0.f;
            constexpr int LAG = 2;
            uint8_t* pdst = g_acc + ((s & 2) * (ACC_PAIR / 2) + (s & 1) * 512 + w * 2048 + j * 8192 - C_MEM - sm + mr);
#pragma unroll
            for (int h = 0; h < 3; h++) {
                uint32_t ob[4][2];
                if (h == 1) {
#pragma unroll
                    for (int i = 14 - LAG; i < 14; i++) ldsm4t(a[i % NRING], frag(i + NRING));
                    pin(mr, zr, (uint32_t)(uint64_t)pdst, (uint32_t)((uint64_t)pdst >> 32), 0);
                    mbar_wait(sm + CB_OX, s & 1);
                    if (w == 0) PROF(9);
                }
#pragma unroll
                for (int k = 0; k < 4; k++) lds64(ob[k], oxrd + h * 1024 + k * 256);
#pragma unroll
                for (int i = 14 * h; i < 14 * h + 14; i++) {
                    const int u = i % 7, k = 2 * (i / 7 & 1);
                    if (u == 3) { mma16q(e[3], a[i % NRING], ob[k][0], ob[k][1]); mma16q(e[4], a[i % NRING], ob[k + 1][0], ob[k + 1][1]); }
                    else mma16q(e[u & 3], a[i % NRING], ob[k + (u >> 2)][0], ob[k + (u >> 2)][1]);
                    if (i == B5AT) { pin(mr, a[i % NRING][0], a[i % NRING][1], a[i % NRING][2], a[i % NRING][3]); bar_arrive(5, 384); }
                    if (i >= LAG && !(i >= 14 && i < 14 + LAG) && i - LAG + NRING < 42) ldsm4t(a[(i - LAG) % NRING], frag(i - LAG + NRING));
                }
            }
            {
                const uint32_t w6 = pack2h(e[3][0] + e[4][2], e[3][1] + e[4][3]), one = 0x3c003c00u;
                asm volatile("red.relaxed.gpu.global.add.noftz.v4.f16x2 [%0], {%1,%2,%3,%4};"
                    :: "l"(pdst), "r"(pack2h(e[0][0], e[0][1])), "r"(pack2h(e[0][2], e[0][3])), "r"(pack2h(e[1][0], e[1][1])), "r"(odd ? w6 : one) : "memory");
                asm volatile("red.relaxed.gpu.global.add.noftz.v4.f16x2 [%0], {%1,%2,%3,%4};"
                    :: "l"(pdst + 1024), "r"(pack2h(e[1][2], e[1][3])), "r"(pack2h(e[2][0], e[2][1])), "r"(pack2h(e[2][2], e[2][3])), "r"(odd ? one : w6) : "memory");
            }
            const uint32_t tw = clock();
            if (w == 0) { PROF(14); PROFG(25); }
            PROXY_FENCE();
            bar_sync(6, 160);
            mr = opaque(mr);
            const uint32_t ln = mr >> 4 & 31, due = tw + lds32(sm + C_LAG);
            const uint32_t vr = sm + C_WV + ((ln >> 4) * 8 + (ln & 7)) * 128 + (((2 * w + (ln >> 3 & 1)) ^ (ln & 7)) << 4);
            const uint32_t ms0 = sm + C_MEM + w * 128 + (ln & 7) * 16 + (ln >> 3) * 512, ms1 = ms0 + (ln < 24 ? 2048 : 1536);
            if (BPOS == 2 && w == 0 && s + 2 == NSEG) wo_half(mp, sm, blk, 0);
            if (w == 2) { w_expect(sm + CB_SC, 2560); w_expect(sm + CB_OX, 2048); asm volatile("st.shared.u32 [%0], %1;" :: "r"(sm + C_UN), "r"((127 - es) << 23) : "memory"); }
            if (w == 0) { w_bulk_s2g(g_att + (s * NH + head) * AT_REC + AT_VM + j * 1024, sm + C_VM, 1024); BULK_COMMIT(); }
            const uint8_t* src = pdst - j * 8192;
            pin(mr, ms0, ms1, (uint32_t)(uint64_t)src, (uint32_t)((uint64_t)src >> 32));
            pin(mr, vr, due, 0, 0);
            cut(s + ar.D2, 1);
#pragma unroll
            for (int i = 0; i < 8; i++) ldsm4t(va[i], vr + i * 2048);
            wait_until(due);
            if (w == 0) { PROF(5); PROFG(26); }
            uint4 v[6];
            auto fetch = [&]() {
#pragma unroll
                for (int k = 0; k < 6; k++)
                    asm volatile("ld.relaxed.gpu.global.v4.u32 {%0,%1,%2,%3}, [%4];" : "=r"(v[k].x), "=r"(v[k].y), "=r"(v[k].z), "=r"(v[k].w) : "l"(src + (k >> 1) * 8192 + (k & 1) * 1024) : "memory");
            };
            fetch();
            PROFV(20 + w, 0);
            bar_sync(9, 384);
#pragma unroll 1
            for (int n = 0; __any_sync(0xffffffffu, ~((odd ? v[1].w & v[3].w & v[5].w : v[0].w & v[2].w & v[4].w)) & 0x50005000u); n++) {
                PROFV(20 + w, n + 1);
                cut(n, SPIN_LIMIT);
                fetch();
            }
            uint32_t cv[3][7];
#pragma unroll
            for (int k = 0; k < 3; k++) {
                const uint4 x = v[2 * k], y = v[2 * k + 1];
                const uint32_t u[7] = {x.x, x.y, x.z, y.x, y.y, y.z, k < 2 ? (odd ? x.w : y.w) : 0u};
#pragma unroll
                for (int i = 0; i < 7; i++) cv[k][i] = f16_to_bf16(u[i]);
                stsm4(ms0 + k * 3584, cv[k][0], cv[k][1], cv[k][2], cv[k][3]);
                if (k < 2) stsm4(ms1 + k * 3584, cv[k][4], cv[k][5], cv[k][6], cv[k][6]);
                else asm volatile("stmatrix.sync.aligned.m8n8.x2.shared.b16 [%0], {%1,%2};" :: "r"(ms1 + k * 3584), "r"(cv[k][4]), "r"(cv[k][5]) : "memory");
            }
            if (w == 0) PROF(16);
            bar_sync(1, 384);
            if (w == 0) BULK_WAIT();
            cut(s + ar.D2, 2);
            uint32_t mc = 0;
#pragma unroll
            for (int i = 0; i < 20; i++) mc = amax2(mc, cv[i / 7][i % 7]);
            asm volatile("st.shared.u32 [%0], %1;" :: "r"(sm + C_MX + w * 4), "r"(amax_warp(mc)) : "memory");
        }
        if (w >= 2) end_loads(mp, ar, sm, blk, w - 2);
        else if (w == 1) { bar_sync(5, 384); seg_done(NSEG - 1, head); if (EORD) bar_arrive(6, 96); if (BPOS == 0) wo_half(mp, sm, blk, 1); }
        else bar_arrive(5, 384);
        if (w == 0) {
            const int l = mr >> 4 & 31;
            if (blk < 14) {
                uint4 k = __ldcg((const uint4*)g_key + blk * 32 + l);
#pragma unroll 1
                for (int it = 0; it < 3; it++) {
                    const uint32_t m = __reduce_max_sync(0xffffffffu, max(max(k.x, k.y), max(k.z, k.w)));
                    if (k.x == m) k.x = 0; if (k.y == m) k.y = 0; if (k.z == m) k.z = 0; if (k.w == m) k.w = 0;
                    if (m && l < 20) asm volatile("prefetch.global.L2 [%0];" :: "l"((l < 10 ? g_h2 : g_x1) + (~m & (S_TOK - 1)) * DM + l % 10 * 64));
                }
            }
            mbar_wait(sm + EB_REL, 0);
            flags_release(l);
        }
    }
}

struct SideMaps { CUtensorMap h, wv, ost, o, wo, slab3, slab2, lnp[3]; };
constexpr int SD_ST = 43008, SD_NST = 4, SD_EPI = SD_NST * SD_ST, SD_PAR = SD_EPI + 2 * 24576, SD_BAR = SD_PAR + 6400, SD_SMEM = SD_BAR + 256;
#define VLEAD 16
#define EARLY15 0
#define N_LIGHT 6
#define B_HELP 13
#define AUNR_ 2
constexpr int AUNR = AUNR_;
#define GEMV 1
#define KSO 6
#define KSA 3
#define B_8 10
#define B_16 13
__device__ __forceinline__ int o_shift(int b) { return b >= B_16 ? 4 : b >= B_8 ? 3 : 2; }
__device__ __forceinline__ int o_split(int b) { return 1 << o_shift(b); }
__device__ __forceinline__ uint32_t o_done(int b) { return b >= B_LATE ? 160 : 4 << o_shift(b); }
__device__ __forceinline__ int next_item(int lane) {
    const int b0 = lane & 15, hi = lane >> 4;
    for (int n = 0;; n++) {
        const uint32_t w0 = ld_rlx(g_flags.qk + lane), w1 = ld_rlx(g_flags.at + lane), w2 = ld_rlx(&g_flags.c[0][0] + lane), w3 = ld_rlx(&g_flags.c[2][0] + lane), w4 = ld_rlx(&g_flags.seg[0]);
        const uint32_t o01 = __ballot_sync(0xffffffffu, lane && w2 < 32), o23 = __ballot_sync(0xffffffffu, b0 < (hi ? 14 : B_LATE) && w3 < 2u * o_split(b0));
        const uint32_t ra = __ballot_sync(0xffffffffu, w0 >= (hi ? 64u : 96u)), rb = __ballot_sync(0xffffffffu, w1 >= (hi ? o_done(b0) : 64u));
        const int bv = __ffs(o01 | 0x10000) - 1, ba = __ffs(o01 >> 16 | 0x10000) - 1, bo = __ffs(o23 | 0x10000) - 1, bl = __ffs(o23 >> 16 | 0x10000) - 1;
        if (bl == 16 && ba == 16) return -1;
        const int bc = __ffs(~ra | 0x10000) - 1;
        const bool last = ba == 15 && (w4 >= 3 || (EARLY15 && bc == 15));
        const bool r1 = (ra & ra >> 16) >> ba & 1, r2 = (rb & 0xffff) >> bo & 1, r3 = rb >> 16 >> bl & 1;
        const int kind = ba == 16 ? (bo < 16 ? 2 : 3) : last ? 1 :
                         blockIdx.x < N_LIGHT ? (r1 ? 1 : r3 ? 3 : bv < 16 ? 0 : -1) :
                         bv < 16 && (bv <= bc + VLEAD || !r2) ? 0 : r1 && ba >= B_HELP ? 1 : r2 ? 2 : r1 ? 1 : r3 ? 3 : bo < ba ? 2 : -1;
        if (kind < 0) { if (n > (1 << 20)) __trap(); __nanosleep(300); continue; }
        const int b = kind == 3 ? bl : kind == 2 ? bo : kind == 1 ? ba : bv;
        uint32_t i = 0;
        if (lane == 0) asm volatile("atom.relaxed.gpu.global.add.u32 %0, [%1], 1;" : "=r"(i) : "l"(&g_flags.c[kind][b]) : "memory");
        i = __shfl_sync(0xffffffffu, i, 0);
        if (i < (kind < 2 ? 32u : 2u * o_split(b))) return kind << 16 | b << 8 | i | ((kind == 1 ? r1 : kind == 2 ? r2 : r3) ? 128 : 0);
    }
}

template <int NP, int CH>
__device__ __forceinline__ void tile_out(const float (&acc)[8 * NP], uint32_t eb, uint32_t efull, uint32_t eempty, int& eph, int lane) {
    const int r = lane & 7, mi = lane >> 3, row = (mi & 1) * 8 + r;
    mbar_wait(eempty, eph); eph ^= 1;
#pragma unroll
    for (int p = 0; p < NP; p++) {
        const int oc = 2 * p + (mi >> 1);
        stsm4(eb + (oc >> 3) * CH + row * 128 + (((oc & 7) ^ r) << 4), pack2(acc[8 * p], acc[8 * p + 1]), pack2(acc[8 * p + 2], acc[8 * p + 3]),
              pack2(acc[8 * p + 4], acc[8 * p + 5]), pack2(acc[8 * p + 6], acc[8 * p + 7]));
    }
    asm volatile("fence.proxy.async.shared::cta;" ::: "memory");
    __syncwarp();
    if (lane == 0) mbar_arrive(efull);
}

template <int MT>
__device__ __forceinline__ void attn_tile(uint32_t base, uint32_t dst, uint32_t eempty, int eph, int lane) {
    constexpr int NK = MT ? 5 : 3;
    const int r = lane & 7, mi = lane >> 3, g = lane >> 2, t = lane & 3;
    float sc[NK][4];
#pragma unroll
    for (int n = 0; n < NK; n++) sc[n][0] = sc[n][1] = sc[n][2] = sc[n][3] = 0.f;
#pragma unroll AUNR
    for (int k2 = 0; k2 < 6; k2++) {
        const uint32_t cb = (k2 >> 1) * 8192, c0 = (k2 & 1) * 4;
        uint32_t a0[4], a1[4], bb[NK][4];
        ldsm4(a0, base + cb + (16 * MT + (mi & 1) * 8 + r) * 128 + (((c0 + (mi >> 1)) ^ r) << 4));
        ldsm4(a1, base + cb + (16 * MT + (mi & 1) * 8 + r) * 128 + (((c0 + 2 + (mi >> 1)) ^ r) << 4));
#pragma unroll
        for (int n = 0; n < NK; n++)
            ldsm4(bb[n], n < NK - 1 ? base + 4096 + cb + (8 * n + r) * 128 + (((c0 + mi) ^ r) << 4) : base + 36864 + k2 * 512 + lane * 16);
#pragma unroll
        for (int n = 0; n < NK; n++) mma16(sc[n], a0[0], a0[1], a0[2], a0[3], bb[n][0], bb[n][1]);
#pragma unroll
        for (int n = 0; n < NK; n++) mma16(sc[n], a1[0], a1[1], a1[2], a1[3], bb[n][2], bb[n][3]);
    }
    const float scale = 0.07216878364870322f, l2e = 1.4426950408889634f;
    float v[2][2 * NK], mx[2], sum[2];
#pragma unroll
    for (int hf = 0; hf < 2; hf++) {
        mx[hf] = -INFINITY;
#pragma unroll
        for (int n = 0; n < NK; n++) {
            uint32_t u = pack2(sc[n][2 * hf], sc[n][2 * hf + 1]);
            u = pack2(lo_f(u) * scale, hi_f(u) * scale);
            const int lim = 16 * MT + 8 * hf + g - 8 * n - 2 * t;
            v[hf][2 * n] = (n < NK - 1 && lim < 0) ? -1e9f : lo_f(u);
            v[hf][2 * n + 1] = (n < NK - 1 && lim < 1) ? -1e9f : hi_f(u);
            mx[hf] = fmaxf(mx[hf], fmaxf(v[hf][2 * n], v[hf][2 * n + 1]));
        }
    }
#pragma unroll
    for (int o = 1; o < 4; o <<= 1)
#pragma unroll
        for (int hf = 0; hf < 2; hf++) mx[hf] = fmaxf(mx[hf], __shfl_xor_sync(0xffffffffu, mx[hf], o));
#pragma unroll
    for (int hf = 0; hf < 2; hf++) {
        sum[hf] = 0;
#pragma unroll
        for (int q = 0; q < 2 * NK; q++) { asm("ex2.approx.ftz.f32 %0, %1;" : "=f"(v[hf][q]) : "f"((v[hf][q] - mx[hf]) * l2e)); sum[hf] += v[hf][q]; }
    }
#pragma unroll
    for (int o = 1; o < 4; o <<= 1)
#pragma unroll
        for (int hf = 0; hf < 2; hf++) sum[hf] += __shfl_xor_sync(0xffffffffu, sum[hf], o);
    uint32_t pa[NK][2];
#pragma unroll
    for (int hf = 0; hf < 2; hf++) {
        const float inv = __fdividef(1.f, sum[hf]);
#pragma unroll
        for (int n = 0; n < NK; n++) pa[n][hf] = pack2(v[hf][2 * n] * inv, v[hf][2 * n + 1] * inv);
    }
    mbar_wait(eempty, eph);
#pragma unroll AUNR
    for (int n4 = 0; n4 < 6; n4++) {
        const uint32_t cb = (n4 >> 1) * 4096, c0 = (n4 & 1) * 4;
        uint32_t bm[4], bb[2 + 2 * MT][4];
        ldsm4t(bm, base + AT_VM + n4 * 512 + lane * 16);
#pragma unroll
        for (int u = 0; u < 2 + 2 * MT; u++) ldsm4t(bb[u], base + AT_V + cb + (16 * (u >> 1) + 8 * (mi & 1) + r) * 128 + (((c0 + 2 * (u & 1) + (mi >> 1)) ^ r) << 4));
        float o[4][4];
#pragma unroll
        for (int u = 0; u < 4; u++) { o[u][0] = o[u][1] = o[u][2] = o[u][3] = 0.f; mma8(o[u], pa[NK - 1][0], pa[NK - 1][1], bm[u]); }
#pragma unroll
        for (int u = 0; u < 4 + 4 * MT; u++) mma16(o[u & 3], pa[u >> 2 << 1][0], pa[u >> 2 << 1][1], pa[(u >> 2 << 1) + 1][0], pa[(u >> 2 << 1) + 1][1], bb[u >> 1][2 * (u & 1)], bb[u >> 1][2 * (u & 1) + 1]);
#pragma unroll
        for (int p = 0; p < 2; p++)
            stsm4(dst + (n4 >> 1) * 2048 + ((mi & 1) * 8 + r) * 128 + (((c0 + 2 * p + (mi >> 1)) ^ r) << 4), pack2(o[2 * p][0], o[2 * p][1]), pack2(o[2 * p][2], o[2 * p][3]),
                  pack2(o[2 * p + 1][0], o[2 * p + 1][1]), pack2(o[2 * p + 1][2], o[2 * p + 1][3]));
    }
}

__device__ __forceinline__ uint32_t ln_row(const uint32_t (&as)[10], const uint2 (&xin)[5], int row, uint32_t par, bf16* out, uint64_t ef, int lane) {
    const uint32_t pa = par + lane * 8;
    uint32_t xv[10], hv[10], sv[10], tv[10];
#pragma unroll
    for (int q = 0; q < 5; q++) {
        uint32_t ga[2], t[2], u[2];
        lds64(ga, pa + q * 256); lds64(t, pa + 1280 + q * 256); lds64(u, pa + 2560 + q * 256);
#pragma unroll
        for (int e = 0; e < 2; e++) {
            xv[2 * q + e] = add2(e ? xin[q].y : xin[q].x, mul2(ga[e], as[2 * q + e]));
            tv[2 * q + e] = t[e]; sv[2 * q + e] = u[e];
        }
        st_ef(g_x1 + row * DM + lane * 4 + q * 128, make_uint2(xv[2 * q], xv[2 * q + 1]), ef);
    }
    ln_mod(xv, sv, tv, hv);
    float rs = 0;
#pragma unroll
    for (int q = 0; q < 5; q++) {
        const int c = row * DM + lane * 4 + q * 128;
        const uint32_t h0 = hv[2 * q], h1 = hv[2 * q + 1];
        uint32_t gb[2], wv[2];
        lds64(gb, pa + 3840 + q * 256); lds64(wv, pa + 5120 + q * 256);
        rs += (lo_f(h0) * lo_f(wv[0]) + hi_f(h0) * hi_f(wv[0])) + (lo_f(h1) * lo_f(wv[1]) + hi_f(h1) * hi_f(wv[1]));
        st_ef(g_h2 + c, make_uint2(h0, h1), ef);
        st_ef(out + c, make_uint2(add2(xv[2 * q], mul2(gb[0], h0)), add2(xv[2 * q + 1], mul2(gb[1], h1))), ef);
    }
    const uint32_t rb = pack2(0.f, warp_sum(rs));
    return (((int)rb < 0 ? ~rb : rb | 0x80000000u) & 0xffff0000u) | (uint32_t)(2 * S_TOK - 1 - row);
}
__device__ __forceinline__ void key_out(uint32_t key) {
    __syncwarp();
    if (key) asm volatile("st.release.gpu.global.u32 [%0], %1;" :: "l"(g_key + (~key & (S_TOK - 1))), "r"(key) : "memory");
}

__global__ void __launch_bounds__(384, 1) k_side(const __grid_constant__ SideMaps mp, const bf16* __restrict__ x, const bf16* __restrict__ wr, const bf16* wmod, const bf16* cvec, bf16* __restrict__ out) {
    extern __shared__ __align__(1024) uint8_t smraw[];
    const uint32_t sm = smem_u32(smraw);
    if (sm & 1023) __trap();
    const uint32_t FULL = sm + SD_BAR, EMPTY = FULL + 32, EFULL = FULL + 64, EEMPTY = FULL + 80, IFULL = FULL + 96, IEMPTY = FULL + 128, IQ = FULL + 160, SCHED = FULL + 176, PARAM = FULL + 184, ADONE = FULL + 192;
    const int tid = threadIdx.x, warp = __shfl_sync(0xffffffffu, tid >> 5, 0), lane = tid & 31;
    const uint64_t ef = policy_stream();
    if (tid == 0) {
        for (int i = 0; i < SD_NST; i++) { mbar_init(FULL + 8 * i, 1); mbar_init(EMPTY + 8 * i, 2); }
        for (int i = 0; i < 2; i++) { mbar_init(EFULL + 8 * i, 4); mbar_init(EEMPTY + 8 * i, 1); }
        for (int i = 0; i < 4; i++) { mbar_init(IFULL + 8 * i, 1); mbar_init(IEMPTY + 8 * i, 11); }
        mbar_init(SCHED, 1); mbar_init(PARAM, 1);
        sts128f(ADONE, 0, 0, 0, 0); sts128f(ADONE + 16, 0, 0, 0, 0);
        asm volatile("fence.mbarrier_init.release.cluster;" ::: "memory");
    }
    if (SDEL) __nanosleep(SDEL);
    __syncthreads();
    if (warp >= 8) {
      asm volatile("setmaxnreg.dec.sync.aligned.u32 40;");
      if (warp == 8) {
        int st = 0, ph = 1;
        for (int q = 0;; q++) {
            mbar_wait(IFULL + 8 * (q & 3), (q >> 2) & 1);
            const int it = __shfl_sync(0xffffffffu, lds32(IQ + 4 * (q & 3)), 0);
            if (elect()) mbar_arrive(IEMPTY + 8 * (q & 3));
            if (it < 0) break;
            const int kind = it >> 16, b = (it >> 8) & 255, i = it & 63;
            const int nst = kind == 0 ? 10 : kind == 1 ? 4 : kind == 2 ? 192 >> o_shift(b) : b == 14 ? 4 : 2;
            const int ksched = kind == 0 ? 4 : kind == 2 ? nst - KSO : (it & 128) ? -1 : kind == 1 ? KSA : 0;
            if (ksched < 0 && elect()) mbar_arrive(SCHED);
            const bool look = !(it & 128);
            if (look && kind == 1) flag_wait(&g_flags.v[b * 32 + i], 2);
            if (look && kind == 3 && b < 14) flag_wait(&g_flags.o[b], o_done(b));
            for (int kb = 0; kb < nst; kb++) {
                mbar_wait(EMPTY + 8 * st, ph);
                const uint32_t base = sm + st * SD_ST, fb = FULL + 8 * st;
                if (look && kind == 1) flag_wait(&g_flags.seg[kb * 32 + i], 3);
                if (kb == ksched && elect()) mbar_arrive(SCHED);
                if (kind == 0) {
                    if (q == 0 && kb == 0) {
                        if (elect()) {
#pragma unroll 1
                            for (int c = 0; c < SD_NST; c++) tma3d(sm + c * SD_ST + 16384, &mp.wv, c * 64, i * 3, FULL + 8 * c);
#pragma unroll 1
                            for (int c = SD_NST; c < SPF; c++)
                                asm volatile("cp.async.bulk.prefetch.tensor.3d.L2.global [%0, {0, %1, %2}];" :: "l"((uint64_t)&mp.wv), "r"(c * 64), "r"(i * 3) : "memory");
                        }
                        flag_wait(&g_flags.h, 96);
                    }
                    if (elect()) {
                        mbar_expect(fb, 40960);
                        tma2d(base, &mp.h, kb * 64, b * 128, fb);
                        if (q || kb >= SD_NST) tma3d(base + 16384, &mp.wv, kb * 64, i * 3, fb);
                    }
                } else if (kind == 1) {
                    if (elect()) {
                        mbar_expect(fb, 43008);
                        asm volatile("cp.async.bulk.shared::cluster.global.mbarrier::complete_tx::bytes.L2::cache_hint [%0], [%1], %2, [%3], %4;"
                            :: "r"(base), "l"(g_att + ((b * 4 + kb) * NH + i) * AT_REC), "r"(AT_REC), "r"(fb), "l"(ef) : "memory");
                    }
                } else if (kind == 3) {
                    if (b == 14 && !(kb & 1)) flag_wait(&g_flags.fin[(kb + (i >> 4)) * 32], 80);
                    if (elect()) { mbar_expect(fb, 40960); tma3d_ef(base, &mp.lnp[o_shift(b) - 2], i * (160 >> o_shift(b)), b * KSPLIT + (kb << o_shift(b) >> 1), fb, ef); }
                } else {
                    const int k0 = ((i >> 1) * nst + kb) * 32;
                    if (elect()) { mbar_expect(fb, 28672); tma3d(base + 8192, &mp.wo, k0, (i & 1) * 5, fb); }
                    if (look && kb % 12 == 0) flag_wait(&g_flags.pair[b * 16 + k0 / 384], 4);
                    if (elect()) tma2d_ef(base, &mp.o, k0, b * 128, fb, ef);
                }
                __syncwarp();
                if (++st == SD_NST) { st = 0; ph ^= 1; }
            }
        }
      } else if (warp == 11) {
        bool fin = false, par = false;
        for (int q = 0;; q++) {
            if (q) mbar_wait(SCHED, (q - 1) & 1);
            int it = fin ? -1 : q == 0 && blockIdx.x < 32 ? (int)blockIdx.x : next_item(lane);
            if (it < 0 && !fin && blockIdx.x < 32) { it = 3 << 16 | 14 << 8 | blockIdx.x; fin = true; }
            if (lane == 0) {
                if (it >> 16 == 3) {
                    const int b = (it >> 8) & 255, nr = 64 >> o_shift(b);
                    asm volatile("cp.async.bulk.prefetch.L2.global [%0], %1;" :: "l"(x + (b * 128 + (it & 63) * nr) * DM), "r"(nr * DM * 2) : "memory");
                }
                mbar_wait(IEMPTY + 8 * (q & 3), ((q >> 2) & 1) ^ 1);
                asm volatile("st.shared.u32 [%0], %1;" :: "r"(IQ + 4 * (q & 3)), "r"(it) : "memory");
                mbar_arrive(IFULL + 8 * (q & 3));
            }
            if (!par && it >> 16 == 3) {
                par = true;
                                if (lane == 0) { mbar_expect(PARAM, 6400); bulk_g2s(sm + SD_PAR, g_mod + 2 * DM, 5120, PARAM); bulk_g2s(sm + SD_PAR + 5120, wr, 1280, PARAM); }
            }
            __syncwarp();
            if (it < 0) break;
        }
        flags_release(lane);
      } else {
        if (lane == 0) {
            const int wg = warp - 9; int ph = 0;
            for (int q = 0;; q++) {
                mbar_wait(IFULL + 8 * (q & 3), (q >> 2) & 1);
                const int it = lds32(IQ + 4 * (q & 3));
                mbar_arrive(IEMPTY + 8 * (q & 3));
                if (it < 0) break;
                const int kind = it >> 16, b = (it >> 8) & 255, i = it & 63;
                if (kind == 3) continue;
                if (kind == 1) {
                    for (int n = 0;; n++) {
                        uint32_t d0, d1, d2, d3;
                        asm volatile("ld.volatile.shared.v4.u32 {%0,%1,%2,%3}, [%4];" : "=r"(d0), "=r"(d1), "=r"(d2), "=r"(d3) : "r"(ADONE + wg * 16) : "memory");
                        if (min(min(d0, d1), min(d2, d3)) > q) break;
                        if (n > (1 << 24)) __trap();
                        __nanosleep(40);
                    }
                    GPU_FENCE();
                    bump(b == 15 ? &g_flags.half[(i & 30) + wg] : &g_flags.pair[b * 16 + (i >> 1)]); bump(&g_flags.at[b]);
                    continue;
                }
#pragma unroll 1
                for (int rd = 0; rd < (kind == 2 ? 2 : 1); rd++) {
                    mbar_wait(EFULL + 8 * wg, ph); ph ^= 1;
                    const uint32_t src = sm + SD_EPI + wg * 24576;
                    if (kind == 2) tma3d_store(rd ? &mp.slab2 : &mp.slab3, (b * KSPLIT + (i >> 1)) * 128 + wg * 64, (i & 1) * 5 + rd * 3, src, ef, false);
                    else {
                        uint8_t* dst = g_att + ((b * 4 + wg * 2) * NH + i) * AT_REC + AT_V;
                        asm volatile("cp.async.bulk.global.shared::cta.bulk_group.L2::cache_hint [%0], [%1], 12288, %2;" :: "l"(dst), "r"(src), "l"(ef) : "memory");
                        asm volatile("cp.async.bulk.global.shared::cta.bulk_group.L2::cache_hint [%0], [%1], 12288, %2;" :: "l"(dst + NH * AT_REC), "r"(src + 12288), "l"(ef) : "memory");
                    }
                    asm volatile("cp.async.bulk.commit_group;" ::: "memory");
                    asm volatile("cp.async.bulk.wait_group.read 0;" ::: "memory");
                    mbar_arrive(EEMPTY + 8 * wg);
                }
                asm volatile("cp.async.bulk.wait_group 0;" ::: "memory");
                GPU_FENCE();
                bump(kind == 0 ? &g_flags.v[b * 32 + i] : &g_flags.o[b]);
                if (kind == 0) bump(&g_flags.vb[b]);
            }
        }
      }
    } else {
        asm volatile("setmaxnreg.inc.sync.aligned.u32 232;");
        const int wg = warp >> 2, w = warp & 3;
        int st = 0, ph = 0, eph = 1;
        bool att = false;
        if (blockIdx.x < 32 * GEMV) {
            const uint32_t buf = sm + SD_EPI;
#pragma unroll 1
            for (int k = tid; k < DM; k += 256) {
                const float f = __uint_as_float((uint32_t)__ldg((const unsigned short*)cvec + k) << 16);
                asm volatile("st.shared.f32 [%0], %1;" :: "r"(buf + k * 4), "f"(bfr(__fdividef(f, 1.f + __expf(-f)))) : "memory");
            }
            const int t = min(tid, 199), k0 = t / 10 * 32;
            const bf16* wm = wmod + k0 * (6 * DM) + 2 * DM + blockIdx.x * 80 + t % 10 * 8;
            float a[8] = {0, 0, 0, 0, 0, 0, 0, 0};
#pragma unroll 1
            for (int k = 0; k < 32; k += 8) {
                uint4 z[8];
#pragma unroll
                for (int e = 0; e < 8; e++) z[e] = __ldcs((const uint4*)(wm + (k + e) * (6 * DM)));
                if (k == 0) bar_sync(1, 256);
#pragma unroll
                for (int e = 0; e < 8; e++) {
                    const float f = __uint_as_float(lds32(buf + (k0 + k + e) * 4));
                    a[0] += f * lo_f(z[e].x); a[1] += f * hi_f(z[e].x); a[2] += f * lo_f(z[e].y); a[3] += f * hi_f(z[e].y);
                    a[4] += f * lo_f(z[e].z); a[5] += f * hi_f(z[e].z); a[6] += f * lo_f(z[e].w); a[7] += f * hi_f(z[e].w);
                }
            }
            sts128f(buf + 4096 + t * 32, a[0], a[1], a[2], a[3]); sts128f(buf + 4112 + t * 32, a[4], a[5], a[6], a[7]);
            bar_sync(1, 256);
            if (tid < 40) {
                float a0 = 0, a1 = 0;
#pragma unroll 4
                for (int g = 0; g < 20; g++) { const float2 v = lds64f(buf + 4096 + g * 320 + tid * 8); a0 += v.x; a1 += v.y; }
                ((uint32_t*)(g_mod + 2 * DM + blockIdx.x * 80))[tid] = pack2(a0, a1);
            }
            bar_sync(1, 256);
        }
        const uint32_t eb = sm + SD_EPI + wg * 24576;
        for (int q = 0;; q++) {
            mbar_wait(IFULL + 8 * (q & 3), (q >> 2) & 1);
            const int itc = lds32(IQ + 4 * (q & 3));
            __syncwarp();
            if (lane == 0) mbar_arrive(IEMPTY + 8 * (q & 3));
            if (itc < 0) break;
            const int kind = itc >> 16, b = (itc >> 8) & 255, i = itc & 63;
            if (att && kind != 1) { bar_sync(1, 256); att = false; }
            if (kind == 0) {
                float acc[96];
#pragma unroll
                for (int n = 0; n < 96; n++) acc[n] = 0.f;
                int prev = -1;
#pragma unroll 1
                for (int kb = 0; kb < 10; kb++) {
                    mbar_wait(FULL + 8 * st, ph);
                    const uint32_t base = sm + st * SD_ST;
                    WG_FENCE();
#pragma unroll
                    for (int ks = 0; ks < 4; ks++)
                        wgmma_ss_n192_tb(acc, mkdesc(base + wg * 8192 + ks * 32, 16, 1024), mkdesc(base + 16384 + ks * 2048, 8192, 1024), (kb | ks) != 0);
                    WG_COMMIT();
                    WG_WAIT(1);
                    if (prev >= 0 && (tid & 127) == 0) mbar_arrive(EMPTY + 8 * prev);
                    prev = st;
                    if (++st == SD_NST) { st = 0; ph ^= 1; }
                }
                WG_WAIT(0);
                if ((tid & 127) == 0) mbar_arrive(EMPTY + 8 * prev);
                tile_out<12, 4096>(acc, eb + (w >> 1) * 12288 + (w & 1) * 2048, EFULL + 8 * wg, EEMPTY + 8 * wg, eph, lane);
            } else if (kind == 1) {
                const int seg = warp >> 1, mt = warp & 1;
                int sst = st + seg, sph = ph; if (sst >= SD_NST) { sst -= SD_NST; sph ^= 1; }
                ph ^= 1;
                mbar_wait(FULL + 8 * sst, sph);
                const uint32_t base = sm + sst * SD_ST;
                if (mt) attn_tile<1>(base, eb + w * 6144, EEMPTY + 8 * wg, eph, lane);
                else attn_tile<0>(base, eb + w * 6144, EEMPTY + 8 * wg, eph, lane);
                asm volatile("fence.proxy.async.shared::cta;" ::: "memory");
                __syncwarp();
                if (lane == 0) {
                    mbar_arrive(EMPTY + 8 * sst);
                    tma3d_store(&mp.ost, b * 128 + warp * 16, i * 3, eb + w * 6144, ef, false);
                    BULK_COMMIT(); BULK_WAIT();
                    asm volatile("st.release.cta.shared.u32 [%0], %1;" :: "r"(ADONE + warp * 4), "r"(q + 1) : "memory");
                }
                __syncwarp();
                att = true;
            } else if (kind == 2) {
                float acc[96], acc2[64];
#pragma unroll
                for (int n = 0; n < 96; n++) acc[n] = 0.f;
#pragma unroll
                for (int n = 0; n < 64; n++) acc2[n] = 0.f;
                int prev = -1;
#pragma unroll 1
                for (int kb = 192 >> o_shift(b); kb > 0; kb--) {
                    const uint32_t base = sm + st * SD_ST;
                    mbar_wait(FULL + 8 * st, ph);
                    WG_FENCE();
#pragma unroll
                    for (int ks = 0; ks < 2; ks++) {
                        const uint64_t da = (mkdesc(base + wg * 4096 + ks * 32, 16, 512) & ~(3ull << 62)) | (2ull << 62);
                        wgmma_ss_n192_tb(acc, da, mkdesc(base + 8192 + ks * 2048, 4096, 1024), 1);
                        wgmma_ss_n128_tb(acc2, da, mkdesc(base + 8192 + 3 * 4096 + ks * 2048, 4096, 1024), 1);
                    }
                    WG_COMMIT();
                    WG_WAIT(1);
                    if (prev >= 0 && (tid & 127) == 0) mbar_arrive(EMPTY + 8 * prev);
                    prev = st;
                    if (++st == SD_NST) { st = 0; ph ^= 1; }
                }
                WG_WAIT(0);
                if ((tid & 127) == 0) mbar_arrive(EMPTY + 8 * prev);
                tile_out<12, 8192>(acc, eb + w * 2048, EFULL + 8 * wg, EEMPTY + 8 * wg, eph, lane);
                tile_out<8, 8192>(acc2, eb + w * 2048, EFULL + 8 * wg, EEMPTY + 8 * wg, eph, lane);
            } else {
                const int sh = o_shift(b), nr = 64 >> sh, fw = b == 14 ? wg : 0, row0 = (b + fw) * 128 + i * nr, lw = warp - 4 * fw;
                if (fw) { st += 2; if (st >= SD_NST) { st -= SD_NST; ph ^= 1; } }
                int st1 = st + 1, ph1 = ph; if (st1 == SD_NST) { st1 = 0; ph1 ^= 1; }
                uint2 xin[2][5];
                uint32_t as[2][10] = {};
#pragma unroll
                for (int q2 = 0; q2 < 10; q2++) xin[q2 & 1][q2 >> 1] = ld_ef(x + (row0 + ((warp + 8 * (q2 & 1)) & (nr - 1))) * DM + lane * 4 + (q2 >> 1) * 128, ef);
                mbar_wait(PARAM, 0); mbar_wait(FULL + 8 * st, ph); mbar_wait(FULL + 8 * st1, ph1);
#pragma unroll 1
                for (int lrow = lw + (nr & 16) / 2; lrow >= 0 && lrow < nr; lrow -= 8) {
                    float a[20];
#pragma unroll
                    for (int q2 = 0; q2 < 20; q2++) a[q2] = 0.f;
#pragma unroll 1
                    for (int k = 0; k < (1 << sh >> 1); k++) {
                        const uint32_t ad = sm + ((k << (6 - sh)) + lrow) * 1280 + lane * 8;
                        uint32_t z[10][2];
#pragma unroll
                        for (int q2 = 0; q2 < 10; q2++) lds64(z[q2], ad + (q2 < 5 ? st : st1) * SD_ST + q2 % 5 * 256);
#pragma unroll
                        for (int q2 = 0; q2 < 10; q2++) { float* p = a + q2 % 5 * 4; p[0] += lo_f(z[q2][0]); p[1] += hi_f(z[q2][0]); p[2] += lo_f(z[q2][1]); p[3] += hi_f(z[q2][1]); }
                    }
#pragma unroll
                    for (int q2 = 0; q2 < 10; q2++) { as[1][q2] = as[0][q2]; as[0][q2] = pack2(a[2 * q2], a[2 * q2 + 1]); }
                }
                bar_sync(2 + wg, 128);
                if ((tid & 127) == 0) { mbar_arrive(EMPTY + 8 * st); mbar_arrive(EMPTY + 8 * st1); }
                uint32_t key = 0;
#pragma unroll 1
                for (int lrow = lw; lrow < nr; lrow += 8) {
                    const int row = row0 + lrow;
                    const uint32_t k1 = ln_row(as[0], xin[0], row, sm + SD_PAR, out, ef, lane);
                    if (lane == lrow >> 3) key = k1;
#pragma unroll
                    for (int q2 = 0; q2 < 5; q2++) { as[0][2 * q2] = as[1][2 * q2]; as[0][2 * q2 + 1] = as[1][2 * q2 + 1]; xin[0][q2] = xin[1][q2]; }
                }
                key_out(key);
                st = st1 + 1; ph = ph1; if (st == SD_NST) { st = 0; ph ^= 1; }
            }
        }
    }
    __syncwarp();
    asm volatile("griddepcontrol.wait;" ::: "memory");
}

#define P_D1 550
#define P_DL 700
#define P_DG 29
typedef CUresult (*EncodeFn)(CUtensorMap*, CUtensorMapDataType, cuuint32_t, void*, const cuuint64_t*, const cuuint64_t*, const cuuint32_t*, const cuuint32_t*,
                             CUtensorMapInterleave, CUtensorMapSwizzle, CUtensorMapL2promotion, CUtensorMapFloatOOBfill);
static EncodeFn s_encode = nullptr;
static void make_map(CUtensorMap* m, const void* p, int rows, int cols, int box_rows, int box_cols = 64) {
    cuuint64_t dims[2] = {(cuuint64_t)cols, (cuuint64_t)rows}, strides[1] = {(cuuint64_t)cols * 2};
    cuuint32_t box[2] = {(cuuint32_t)box_cols, (cuuint32_t)box_rows}, es[2] = {1, 1};
    s_encode(m, CU_TENSOR_MAP_DATA_TYPE_BFLOAT16, 2, (void*)p, dims, strides, box, es, CU_TENSOR_MAP_INTERLEAVE_NONE,
             box_cols == 64 ? CU_TENSOR_MAP_SWIZZLE_128B : box_cols == 32 ? CU_TENSOR_MAP_SWIZZLE_64B : CU_TENSOR_MAP_SWIZZLE_NONE, CU_TENSOR_MAP_L2_PROMOTION_L2_256B, CU_TENSOR_MAP_FLOAT_OOB_FILL_NONE);
}
static void make_map3(CUtensorMap* m, const void* p, int rows, int cols, int box_rows, int box_chunks, int cw = 64) {
    cuuint64_t dims[3] = {(cuuint64_t)cw, (cuuint64_t)rows, (cuuint64_t)(cols / cw)}, strides[2] = {(cuuint64_t)cols * 2, (cuuint64_t)cw * 2};
    cuuint32_t box[3] = {(cuuint32_t)cw, (cuuint32_t)box_rows, (cuuint32_t)box_chunks}, es[3] = {1, 1, 1};
    s_encode(m, CU_TENSOR_MAP_DATA_TYPE_BFLOAT16, 3, (void*)p, dims, strides, box, es, CU_TENSOR_MAP_INTERLEAVE_NONE,
             cw == 64 ? CU_TENSOR_MAP_SWIZZLE_128B : CU_TENSOR_MAP_SWIZZLE_64B, CU_TENSOR_MAP_L2_PROMOTION_L2_256B, CU_TENSOR_MAP_FLOAT_OOB_FILL_NONE);
}
template <typename T> static void* sym(T& s) { void* p = nullptr; cudaGetSymbolAddress(&p, s); return p; }

extern "C" void kernel_launch(void* const* d_in, const int* in_sizes, int n_in, void* d_out, int out_size) {
    const bf16 *x = (const bf16*)d_in[0], *mem0 = (const bf16*)d_in[1], *Wq = (const bf16*)d_in[2], *Wk = (const bf16*)d_in[3],
               *Wv = (const bf16*)d_in[4], *Wo = (const bf16*)d_in[5], *wr = (const bf16*)d_in[8], *wgate = (const bf16*)d_in[9],
               *wup = (const bf16*)d_in[10], *wdown = (const bf16*)d_in[11], *c = (const bf16*)d_in[12], *wmod = (const bf16*)d_in[13];
    bf16* out = (bf16*)d_out;
    if (!s_encode) {
        cudaDriverEntryPointQueryResult qr;
        cudaGetDriverEntryPoint("cuTensorMapEncodeTiled", (void**)&s_encode, cudaEnableDefault, &qr);
        cudaFuncSetAttribute(k_side, cudaFuncAttributeMaxDynamicSharedMemorySize, SD_SMEM);
        cudaFuncSetAttribute(k_chain, cudaFuncAttributeMaxDynamicSharedMemorySize, C_SMEM);
    }
    ChainMaps cm; SideMaps sd;
    make_map(&sd.h, sym(g_h), S_TOK, DM, 128); make_map3(&sd.wv, Wv, DM, HD, 64, 3);
    make_map3(&sd.ost, sym(g_o), S_TOK, HD, 16, 3); make_map(&sd.o, sym(g_o), S_TOK, HD, 128, 32); make_map3(&sd.wo, Wo, HD, DM, 32, 5);
    make_map3(&sd.slab3, sym(g_slab), 16 * KSPLIT * 128, DM, 64, 3); make_map3(&sd.slab2, sym(g_slab), 16 * KSPLIT * 128, DM, 64, 2);
    make_map3(&cm.wo15, Wo, HD, DM, 192, 2); make_map3(&cm.o15, sym(g_o), S_TOK, HD, 64, 2); make_map3(&cm.slab16, sym(g_slab), 16 * KSPLIT * 128, DM, 16, 2);
    for (int i = 0; i < 3; i++) {
        cuuint64_t dims[3] = {256, 320, 16 * KSPLIT}, strides[2] = {512, 128 * DM * 2};
        cuuint32_t box[3] = {256, 40u >> i, 2u << i}, es[3] = {1, 1, 1};
        s_encode(&sd.lnp[i], CU_TENSOR_MAP_DATA_TYPE_BFLOAT16, 3, sym(g_slab), dims, strides, box, es, CU_TENSOR_MAP_INTERLEAVE_NONE,
                 CU_TENSOR_MAP_SWIZZLE_NONE, CU_TENSOR_MAP_L2_PROMOTION_L2_256B, CU_TENSOR_MAP_FLOAT_OOB_FILL_NONE);
    }
    make_map(&cm.wq, Wq, DM, HD, 640 / WP); make_map(&cm.wk, Wk, DM, HD, 640 / WP); make_map(&cm.wv, Wv, DM, HD, 160); make_map3(&cm.wo, Wo, HD, DM, 64, 7, 32);
    make_map3(&cm.h2, sym(g_h), S_TOK, DM, 32, 2);
    ChainArgs ar = {x, mem0, c, wmod, Wv, Wo, wgate, wup, wdown, out, P_D1, P_DL, P_DG};
    k_chain<<<96, 384, C_SMEM>>>(cm, ar);
    cudaLaunchConfig_t cfg = {};
    cfg.gridDim = dim3(N_SIDE); cfg.blockDim = dim3(384); cfg.dynamicSmemBytes = SD_SMEM; cfg.stream = cudaStreamPerThread;
    cudaLaunchAttribute at[1]; at[0].id = cudaLaunchAttributeProgrammaticStreamSerialization; at[0].val.programmaticStreamSerializationAllowed = 1;
    cfg.attrs = at; cfg.numAttrs = 1;
    cudaLaunchKernelEx(&cfg, k_side, sd, x, wr, wmod, c, out);
}
```

```cpp
#include <cuda_runtime.h>
#include <cuda_bf16.h>
#include <cuda.h>
#include <stdint.h>
#include <stdio.h>
#include <string.h>
#include <stdlib.h>

typedef __nv_bfloat16 bf16;
constexpr int S_TOK = 2048, DM = 640, NH = 32, DH = 192, HD = NH * DH, NSEG = 64, SEG = 32, FF = 1536;

__device__ bf16 g_mod[6 * DM];
__device__ bf16 g_h[S_TOK * DM];
constexpr int AT_REC = 43008, AT_V = 24576, AT_KM = 36864, AT_VM = 39936;
__device__ __align__(1024) uint8_t g_att[NSEG * NH * AT_REC];
__device__ bf16 g_o[S_TOK * HD];
__device__ bf16 g_A[S_TOK * DM];
__device__ bf16 g_x1[S_TOK * DM];
__device__ bf16 g_h2[S_TOK * DM];
__device__ __align__(128) uint32_t g_key[S_TOK];
__device__ int g_idx[8];
__device__ __align__(128) uint32_t g_gu[FF / 8 * 32];
constexpr int ACC_PAIR = 24 * 1024;
__device__ __align__(1024) uint8_t g_acc[2 * ACC_PAIR];
__device__ __align__(1024) uint32_t g_stamp[4 * 12 * 32];
constexpr int KSPLIT = 16;
__device__ bf16 g_slab[16 * KSPLIT * 128 * DM];
struct __align__(128) Flags {
    uint32_t qk[16], vb[16];
    uint32_t at[16], o[16];
    uint32_t c[4][16];
    uint32_t half[32];
    uint32_t fin[4 * 32];
    uint32_t v[16 * 32];
    uint32_t seg[4 * 32];
    uint32_t pair[16 * 16];
    uint32_t h, pad2[31], done, pad3[31];
    uint32_t mod1[DM];
    uint32_t wmax[96];
};
__device__ Flags g_flags;

__device__ __forceinline__ uint32_t smem_u32(const void* p) { return (uint32_t)__cvta_generic_to_shared(p); }
__device__ __forceinline__ uint32_t pack2(float lo, float hi) {
    uint32_t r; asm("cvt.rn.bf16x2.f32 %0, %1, %2;" : "=r"(r) : "f"(hi), "f"(lo)); return r;
}
__device__ __forceinline__ float bfr(float x) { return __uint_as_float(pack2(0.f, x)); }
__device__ __forceinline__ float inv_std(float var) {
    float s, r; asm("sqrt.approx.f32 %0, %1;" : "=f"(s) : "f"(bfr(bfr(var) + 1e-5f))); asm("rcp.approx.f32 %0, %1;" : "=f"(r) : "f"(bfr(s))); return r;
}
__device__ __forceinline__ float lo_f(uint32_t v) { return __uint_as_float(v << 16); }
__device__ __forceinline__ float hi_f(uint32_t v) { return __uint_as_float(v & 0xffff0000u); }
__device__ __forceinline__ void mbar_init(uint32_t bar, int cnt) { asm volatile("mbarrier.init.shared::cta.b64 [%0], %1;" :: "r"(bar), "r"(cnt) : "memory"); }
__device__ __forceinline__ void mbar_expect(uint32_t bar, int bytes) { asm volatile("mbarrier.arrive.expect_tx.shared::cta.b64 _, [%0], %1;" :: "r"(bar), "r"(bytes) : "memory"); }
__device__ __forceinline__ void mbar_arrive(uint32_t bar) { asm volatile("mbarrier.arrive.shared::cta.b64 _, [%0];" :: "r"(bar) : "memory"); }
__device__ __forceinline__ bool mbar_try(uint32_t bar, int par) {
    uint32_t ok; asm volatile("{ .reg .pred p; mbarrier.try_wait.parity.shared::cta.b64 p, [%1], %2; selp.u32 %0, 1, 0, p; }" : "=r"(ok) : "r"(bar), "r"(par) : "memory"); return ok;
}
__device__ __forceinline__ bool mbar_try_cluster(uint32_t bar, int par) {
    uint32_t ok; asm volatile("{ .reg .pred p; mbarrier.try_wait.parity.acquire.cluster.shared::cta.b64 p, [%1], %2; selp.u32 %0, 1, 0, p; }" : "=r"(ok) : "r"(bar), "r"(par) : "memory"); return ok;
}
__device__ __forceinline__ bool mbar_test(uint32_t bar, uint32_t par) {
    uint32_t ok; asm volatile("{ .reg .pred p; mbarrier.test_wait.parity.shared::cta.b64 p, [%1], %2; selp.u32 %0, 1, 0, p; }" : "=r"(ok) : "r"(bar), "r"(par) : "memory"); return ok;
}
constexpr int SPIN_LIMIT = 1 << 18;
__device__ __forceinline__ void mbar_wait(uint32_t bar, uint32_t par) {
    asm volatile("{ .reg .pred p, q; .reg .u32 n; mov.u32 n, 0;\n"
                 "W_%=: mbarrier.try_wait.parity.shared::cta.b64 p, [%0], %1;\n"
                 "@p bra.uni D_%=;\n"
                 "add.u32 n, n, 1; setp.lt.u32 q, n, 0x200000; @q bra.uni W_%=;\n"
                 "trap;\n"
                 "D_%=: }" :: "r"(bar), "r"(par) : "memory");
}
__device__ __forceinline__ void tma2d(uint32_t dst, const CUtensorMap* m, int c0, int c1, uint32_t bar) {
    asm volatile("cp.async.bulk.tensor.2d.shared::cluster.global.mbarrier::complete_tx::bytes [%0], [%1, {%3, %4}], [%2];"
        :: "r"(dst), "l"((uint64_t)m), "r"(bar), "r"(c0), "r"(c1) : "memory");
}
__device__ __forceinline__ void tma2d_mc(uint32_t dst, const CUtensorMap* m, int c0, int c1, uint32_t bar, uint16_t mask) {
    asm volatile("cp.async.bulk.tensor.2d.shared::cluster.global.mbarrier::complete_tx::bytes.multicast::cluster [%0], [%1, {%3, %4}], [%2], %5;"
        :: "r"(dst), "l"((uint64_t)m), "r"(bar), "r"(c0), "r"(c1), "h"(mask) : "memory");
}
__device__ __forceinline__ uint64_t policy_stream() { uint64_t p; asm("createpolicy.fractional.L2::evict_first.b64 %0, 1.0;" : "=l"(p)); return p; }
__device__ __forceinline__ void tma2d_ef(uint32_t dst, const CUtensorMap* m, int c0, int c1, uint32_t bar, uint64_t pol) {
    asm volatile("cp.async.bulk.tensor.2d.shared::cluster.global.mbarrier::complete_tx::bytes.L2::cache_hint [%0], [%1, {%3, %4}], [%2], %5;"
        :: "r"(dst), "l"((uint64_t)m), "r"(bar), "r"(c0), "r"(c1), "l"(pol) : "memory");
}
__device__ __forceinline__ void tma3d(uint32_t dst, const CUtensorMap* m, int row, int chunk, uint32_t bar) {
    asm volatile("cp.async.bulk.tensor.3d.shared::cluster.global.mbarrier::complete_tx::bytes [%0], [%1, {0, %3, %4}], [%2];"
        :: "r"(dst), "l"((uint64_t)m), "r"(bar), "r"(row), "r"(chunk) : "memory");
}
__device__ __forceinline__ void tma3d_ef(uint32_t dst, const CUtensorMap* m, int row, int chunk, uint32_t bar, uint64_t pol) {
    asm volatile("cp.async.bulk.tensor.3d.shared::cluster.global.mbarrier::complete_tx::bytes.L2::cache_hint [%0], [%1, {0, %3, %4}], [%2], %5;"
        :: "r"(dst), "l"((uint64_t)m), "r"(bar), "r"(row), "r"(chunk), "l"(pol) : "memory");
}
__device__ __forceinline__ void tma3d_store(const CUtensorMap* m, int row, int chunk, uint32_t src, uint64_t pol, bool hint) {
    if (hint) asm volatile("cp.async.bulk.tensor.3d.global.shared::cta.bulk_group.L2::cache_hint [%0, {0, %2, %3}], [%1], %4;"
        :: "l"((uint64_t)m), "r"(src), "r"(row), "r"(chunk), "l"(pol) : "memory");
    else asm volatile("cp.async.bulk.tensor.3d.global.shared::cta.bulk_group [%0, {0, %2, %3}], [%1];"
        :: "l"((uint64_t)m), "r"(src), "r"(row), "r"(chunk) : "memory");
}
__device__ __forceinline__ bool elect() { uint32_t p; asm volatile("{ .reg .pred e; elect.sync _|e, -1; selp.u32 %0, 1, 0, e; }" : "=r"(p)); return p; }
__device__ __forceinline__ uint2 ld_ef(const void* p, uint64_t pol) {
    uint2 v; asm volatile("ld.relaxed.gpu.global.L2::cache_hint.v2.u32 {%0,%1}, [%2], %3;" : "=r"(v.x), "=r"(v.y) : "l"(p), "l"(pol)); return v;
}
__device__ __forceinline__ void st_ef(void* p, uint2 v, uint64_t pol) {
    asm volatile("st.global.L2::cache_hint.v2.u32 [%0], {%1,%2}, %3;" :: "l"(p), "r"(v.x), "r"(v.y), "l"(pol) : "memory");
}
__device__ __forceinline__ void tma2d_prefetch(const CUtensorMap* m, int c0, int c1) {
    asm volatile("cp.async.bulk.prefetch.tensor.2d.L2.global [%0, {%1, %2}];" :: "l"((uint64_t)m), "r"(c0), "r"(c1) : "memory");
}
__device__ __forceinline__ void mbar_arrive_remote(uint32_t bar) { asm volatile("mbarrier.arrive.relaxed.cluster.shared::cluster.b64 _, [%0];" :: "r"(bar) : "memory"); }
__device__ __forceinline__ void tma2d_store(const CUtensorMap* m, int c0, int c1, uint32_t src) {
    asm volatile("cp.async.bulk.tensor.2d.global.shared::cta.bulk_group [%0, {%2, %3}], [%1];"
        :: "l"((uint64_t)m), "r"(src), "r"(c0), "r"(c1) : "memory");
}
__device__ __forceinline__ void bulk_g2s(uint32_t dst, const void* src, int bytes, uint32_t bar) {
    asm volatile("cp.async.bulk.shared::cluster.global.mbarrier::complete_tx::bytes [%0], [%1], %2, [%3];" :: "r"(dst), "l"(src), "r"(bytes), "r"(bar) : "memory");
}
__device__ __forceinline__ void ldsm4(uint32_t (&r)[4], uint32_t a) {
    asm volatile("ldmatrix.sync.aligned.m8n8.x4.shared.b16 {%0,%1,%2,%3}, [%4];" : "=r"(r[0]), "=r"(r[1]), "=r"(r[2]), "=r"(r[3]) : "r"(a) : "memory");
}
__device__ __forceinline__ void ldsm4t(uint32_t (&r)[4], uint32_t a) {
    asm volatile("ldmatrix.sync.aligned.m8n8.x4.trans.shared.b16 {%0,%1,%2,%3}, [%4];" : "=r"(r[0]), "=r"(r[1]), "=r"(r[2]), "=r"(r[3]) : "r"(a) : "memory");
}
__device__ __forceinline__ void stsm4(uint32_t a, uint32_t r0, uint32_t r1, uint32_t r2, uint32_t r3) {
    asm volatile("stmatrix.sync.aligned.m8n8.x4.shared.b16 [%0], {%1,%2,%3,%4};" :: "r"(a), "r"(r0), "r"(r1), "r"(r2), "r"(r3) : "memory");
}
__device__ __forceinline__ void stsm4t(uint32_t a, uint32_t r0, uint32_t r1, uint32_t r2, uint32_t r3) {
    asm volatile("stmatrix.sync.aligned.m8n8.x4.trans.shared.b16 [%0], {%1,%2,%3,%4};" :: "r"(a), "r"(r0), "r"(r1), "r"(r2), "r"(r3) : "memory");
}
__device__ __forceinline__ void stsm2t(uint32_t a, uint32_t r0, uint32_t r1) {
    asm volatile("stmatrix.sync.aligned.m8n8.x2.trans.shared.b16 [%0], {%1,%2};" :: "r"(a), "r"(r0), "r"(r1) : "memory");
}
__device__ __forceinline__ uint32_t movm_t(uint32_t v) { uint32_t r; asm volatile("movmatrix.sync.aligned.m8n8.trans.b16 %0, %1;" : "=r"(r) : "r"(v)); return r; }
__device__ __forceinline__ void mma16(float (&d)[4], uint32_t a0, uint32_t a1, uint32_t a2, uint32_t a3, uint32_t b0, uint32_t b1) {
    asm volatile("mma.sync.aligned.m16n8k16.row.col.f32.bf16.bf16.f32 {%0,%1,%2,%3}, {%4,%5,%6,%7}, {%8,%9}, {%0,%1,%2,%3};"
        : "+f"(d[0]), "+f"(d[1]), "+f"(d[2]), "+f"(d[3]) : "r"(a0), "r"(a1), "r"(a2), "r"(a3), "r"(b0), "r"(b1));
}
__device__ __forceinline__ void mma8(float (&d)[4], uint32_t a0, uint32_t a1, uint32_t b0) {
    asm volatile("mma.sync.aligned.m16n8k8.row.col.f32.bf16.bf16.f32 {%0,%1,%2,%3}, {%4,%5}, {%6}, {%0,%1,%2,%3};"
        : "+f"(d[0]), "+f"(d[1]), "+f"(d[2]), "+f"(d[3]) : "r"(a0), "r"(a1), "r"(b0));
}
__device__ __forceinline__ uint32_t mapa(uint32_t a, uint32_t r) { uint32_t o; asm volatile("mapa.shared::cluster.u32 %0, %1, %2;" : "=r"(o) : "r"(a), "r"(r)); return o; }
__device__ __forceinline__ void bar_sync(int id, int n) { asm volatile("bar.sync %0, %1;" :: "r"(id), "r"(n) : "memory"); }
__device__ __forceinline__ void bar_arrive(int id, int n) { asm volatile("bar.arrive %0, %1;" :: "r"(id), "r"(n) : "memory"); }
__device__ __forceinline__ uint64_t mkdesc(uint32_t addr, uint32_t lbo, uint32_t sbo) {
    return (uint64_t)((addr & 0x3FFFF) >> 4) | ((uint64_t)(lbo >> 4) << 16) | ((uint64_t)(sbo >> 4) << 32) | (1ull << 62);
}
#define WG_FENCE()  asm volatile("wgmma.fence.sync.aligned;" ::: "memory")
#define WG_COMMIT() asm volatile("wgmma.commit_group.sync.aligned;" ::: "memory")
#define WG_WAIT(n)  asm volatile("wgmma.wait_group.sync.aligned %0;" :: "n"(n) : "memory")

__device__ __forceinline__ void wgmma_ss_n192_tb(float (&d)[96], uint64_t a, uint64_t b, int acc) {
    asm volatile("{ .reg .pred p; setp.ne.b32 p, %98, 0;\n"
        "wgmma.mma_async.sync.aligned.m64n192k16.f32.bf16.bf16 {%0,%1,%2,%3,%4,%5,%6,%7,%8,%9,%10,%11,%12,%13,%14,%15,%16,%17,%18,%19,%20,%21,%22,%23,%24,%25,%26,%27,%28,%29,%30,%31,%32,%33,%34,%35,%36,%37,%38,%39,%40,%41,%42,%43,%44,%45,%46,%47,%48,%49,%50,%51,%52,%53,%54,%55,%56,%57,%58,%59,%60,%61,%62,%63,%64,%65,%66,%67,%68,%69,%70,%71,%72,%73,%74,%75,%76,%77,%78,%79,%80,%81,%82,%83,%84,%85,%86,%87,%88,%89,%90,%91,%92,%93,%94,%95}, %96, %97, p, 1, 1, 0, 1; }"
        : "+f"(d[0]), "+f"(d[1]), "+f"(d[2]), "+f"(d[3]), "+f"(d[4]), "+f"(d[5]), "+f"(d[6]), "+f"(d[7]), "+f"(d[8]), "+f"(d[9]), "+f"(d[10]), "+f"(d[11]), "+f"(d[12]), "+f"(d[13]), "+f"(d[14]), "+f"(d[15]), "+f"(d[16]), "+f"(d[17]), "+f"(d[18]), "+f"(d[19]), "+f"(d[20]), "+f"(d[21]), "+f"(d[22]), "+f"(d[23]), "+f"(d[24]), "+f"(d[25]), "+f"(d[26]), "+f"(d[27]), "+f"(d[28]), "+f"(d[29]), "+f"(d[30]), "+f"(d[31]), "+f"(d[32]), "+f"(d[33]), "+f"(d[34]), "+f"(d[35]), "+f"(d[36]), "+f"(d[37]), "+f"(d[38]), "+f"(d[39]), "+f"(d[40]), "+f"(d[41]), "+f"(d[42]), "+f"(d[43]), "+f"(d[44]), "+f"(d[45]), "+f"(d[46]), "+f"(d[47]), "+f"(d[48]), "+f"(d[49]), "+f"(d[50]), "+f"(d[51]), "+f"(d[52]), "+f"(d[53]), "+f"(d[54]), "+f"(d[55]), "+f"(d[56]), "+f"(d[57]), "+f"(d[58]), "+f"(d[59]), "+f"(d[60]), "+f"(d[61]), "+f"(d[62]), "+f"(d[63]), "+f"(d[64]), "+f"(d[65]), "+f"(d[66]), "+f"(d[67]), "+f"(d[68]), "+f"(d[69]), "+f"(d[70]), "+f"(d[71]), "+f"(d[72]), "+f"(d[73]), "+f"(d[74]), "+f"(d[75]), "+f"(d[76]), "+f"(d[77]), "+f"(d[78]), "+f"(d[79]), "+f"(d[80]), "+f"(d[81]), "+f"(d[82]), "+f"(d[83]), "+f"(d[84]), "+f"(d[85]), "+f"(d[86]), "+f"(d[87]), "+f"(d[88]), "+f"(d[89]), "+f"(d[90]), "+f"(d[91]), "+f"(d[92]), "+f"(d[93]), "+f"(d[94]), "+f"(d[95])
        : "l"(a), "l"(b), "r"(acc));
}

__device__ __forceinline__ void wgmma_ss_n128_tb(float (&d)[64], uint64_t a, uint64_t b, int acc) {
    asm volatile("{ .reg .pred p; setp.ne.b32 p, %66, 0;\n"
        "wgmma.mma_async.sync.aligned.m64n128k16.f32.bf16.bf16 {%0,%1,%2,%3,%4,%5,%6,%7,%8,%9,%10,%11,%12,%13,%14,%15,%16,%17,%18,%19,%20,%21,%22,%23,%24,%25,%26,%27,%28,%29,%30,%31,%32,%33,%34,%35,%36,%37,%38,%39,%40,%41,%42,%43,%44,%45,%46,%47,%48,%49,%50,%51,%52,%53,%54,%55,%56,%57,%58,%59,%60,%61,%62,%63}, %64, %65, p, 1, 1, 0, 1; }"
        : "+f"(d[0]), "+f"(d[1]), "+f"(d[2]), "+f"(d[3]), "+f"(d[4]), "+f"(d[5]), "+f"(d[6]), "+f"(d[7]), "+f"(d[8]), "+f"(d[9]), "+f"(d[10]), "+f"(d[11]), "+f"(d[12]), "+f"(d[13]), "+f"(d[14]), "+f"(d[15]), "+f"(d[16]), "+f"(d[17]), "+f"(d[18]), "+f"(d[19]), "+f"(d[20]), "+f"(d[21]), "+f"(d[22]), "+f"(d[23]), "+f"(d[24]), "+f"(d[25]), "+f"(d[26]), "+f"(d[27]), "+f"(d[28]), "+f"(d[29]), "+f"(d[30]), "+f"(d[31]), "+f"(d[32]), "+f"(d[33]), "+f"(d[34]), "+f"(d[35]), "+f"(d[36]), "+f"(d[37]), "+f"(d[38]), "+f"(d[39]), "+f"(d[40]), "+f"(d[41]), "+f"(d[42]), "+f"(d[43]), "+f"(d[44]), "+f"(d[45]), "+f"(d[46]), "+f"(d[47]), "+f"(d[48]), "+f"(d[49]), "+f"(d[50]), "+f"(d[51]), "+f"(d[52]), "+f"(d[53]), "+f"(d[54]), "+f"(d[55]), "+f"(d[56]), "+f"(d[57]), "+f"(d[58]), "+f"(d[59]), "+f"(d[60]), "+f"(d[61]), "+f"(d[62]), "+f"(d[63])
        : "l"(a), "l"(b), "r"(acc));
}

__device__ __forceinline__ void wgmma_rs_n192_tb(float (&d)[96], const uint32_t (&a)[4], uint64_t b, int acc) {
    asm volatile("{ .reg .pred p; setp.ne.b32 p, %101, 0;\n"
        "wgmma.mma_async.sync.aligned.m64n192k16.f32.bf16.bf16 {%0,%1,%2,%3,%4,%5,%6,%7,%8,%9,%10,%11,%12,%13,%14,%15,%16,%17,%18,%19,%20,%21,%22,%23,%24,%25,%26,%27,%28,%29,%30,%31,%32,%33,%34,%35,%36,%37,%38,%39,%40,%41,%42,%43,%44,%45,%46,%47,%48,%49,%50,%51,%52,%53,%54,%55,%56,%57,%58,%59,%60,%61,%62,%63,%64,%65,%66,%67,%68,%69,%70,%71,%72,%73,%74,%75,%76,%77,%78,%79,%80,%81,%82,%83,%84,%85,%86,%87,%88,%89,%90,%91,%92,%93,%94,%95}, {%96,%97,%98,%99}, %100, p, 1, 1, 1; }"
        : "+f"(d[0]), "+f"(d[1]), "+f"(d[2]), "+f"(d[3]), "+f"(d[4]), "+f"(d[5]), "+f"(d[6]), "+f"(d[7]), "+f"(d[8]), "+f"(d[9]), "+f"(d[10]), "+f"(d[11]), "+f"(d[12]), "+f"(d[13]), "+f"(d[14]), "+f"(d[15]), "+f"(d[16]), "+f"(d[17]), "+f"(d[18]), "+f"(d[19]), "+f"(d[20]), "+f"(d[21]), "+f"(d[22]), "+f"(d[23]), "+f"(d[24]), "+f"(d[25]), "+f"(d[26]), "+f"(d[27]), "+f"(d[28]), "+f"(d[29]), "+f"(d[30]), "+f"(d[31]), "+f"(d[32]), "+f"(d[33]), "+f"(d[34]), "+f"(d[35]), "+f"(d[36]), "+f"(d[37]), "+f"(d[38]), "+f"(d[39]), "+f"(d[40]), "+f"(d[41]), "+f"(d[42]), "+f"(d[43]), "+f"(d[44]), "+f"(d[45]), "+f"(d[46]), "+f"(d[47]), "+f"(d[48]), "+f"(d[49]), "+f"(d[50]), "+f"(d[51]), "+f"(d[52]), "+f"(d[53]), "+f"(d[54]), "+f"(d[55]), "+f"(d[56]), "+f"(d[57]), "+f"(d[58]), "+f"(d[59]), "+f"(d[60]), "+f"(d[61]), "+f"(d[62]), "+f"(d[63]), "+f"(d[64]), "+f"(d[65]), "+f"(d[66]), "+f"(d[67]), "+f"(d[68]), "+f"(d[69]), "+f"(d[70]), "+f"(d[71]), "+f"(d[72]), "+f"(d[73]), "+f"(d[74]), "+f"(d[75]), "+f"(d[76]), "+f"(d[77]), "+f"(d[78]), "+f"(d[79]), "+f"(d[80]), "+f"(d[81]), "+f"(d[82]), "+f"(d[83]), "+f"(d[84]), "+f"(d[85]), "+f"(d[86]), "+f"(d[87]), "+f"(d[88]), "+f"(d[89]), "+f"(d[90]), "+f"(d[91]), "+f"(d[92]), "+f"(d[93]), "+f"(d[94]), "+f"(d[95])
        : "r"(a[0]), "r"(a[1]), "r"(a[2]), "r"(a[3]), "l"(b), "r"(acc));
}

__device__ __forceinline__ void wgmma_rs_n128_tb(float (&d)[64], const uint32_t (&a)[4], uint64_t b, int acc) {
    asm volatile("{ .reg .pred p; setp.ne.b32 p, %69, 0;\n"
        "wgmma.mma_async.sync.aligned.m64n128k16.f32.bf16.bf16 {%0,%1,%2,%3,%4,%5,%6,%7,%8,%9,%10,%11,%12,%13,%14,%15,%16,%17,%18,%19,%20,%21,%22,%23,%24,%25,%26,%27,%28,%29,%30,%31,%32,%33,%34,%35,%36,%37,%38,%39,%40,%41,%42,%43,%44,%45,%46,%47,%48,%49,%50,%51,%52,%53,%54,%55,%56,%57,%58,%59,%60,%61,%62,%63}, {%64,%65,%66,%67}, %68, p, 1, 1, 1; }"
        : "+f"(d[0]), "+f"(d[1]), "+f"(d[2]), "+f"(d[3]), "+f"(d[4]), "+f"(d[5]), "+f"(d[6]), "+f"(d[7]), "+f"(d[8]), "+f"(d[9]), "+f"(d[10]), "+f"(d[11]), "+f"(d[12]), "+f"(d[13]), "+f"(d[14]), "+f"(d[15]), "+f"(d[16]), "+f"(d[17]), "+f"(d[18]), "+f"(d[19]), "+f"(d[20]), "+f"(d[21]), "+f"(d[22]), "+f"(d[23]), "+f"(d[24]), "+f"(d[25]), "+f"(d[26]), "+f"(d[27]), "+f"(d[28]), "+f"(d[29]), "+f"(d[30]), "+f"(d[31]), "+f"(d[32]), "+f"(d[33]), "+f"(d[34]), "+f"(d[35]), "+f"(d[36]), "+f"(d[37]), "+f"(d[38]), "+f"(d[39]), "+f"(d[40]), "+f"(d[41]), "+f"(d[42]), "+f"(d[43]), "+f"(d[44]), "+f"(d[45]), "+f"(d[46]), "+f"(d[47]), "+f"(d[48]), "+f"(d[49]), "+f"(d[50]), "+f"(d[51]), "+f"(d[52]), "+f"(d[53]), "+f"(d[54]), "+f"(d[55]), "+f"(d[56]), "+f"(d[57]), "+f"(d[58]), "+f"(d[59]), "+f"(d[60]), "+f"(d[61]), "+f"(d[62]), "+f"(d[63])
        : "r"(a[0]), "r"(a[1]), "r"(a[2]), "r"(a[3]), "l"(b), "r"(acc));
}

__device__ __forceinline__ void wgmma_rs_n32(float (&d)[16], const uint32_t (&a)[4], uint64_t b, int acc) {
    asm volatile("{ .reg .pred p; setp.ne.b32 p, %21, 0;\n"
        "wgmma.mma_async.sync.aligned.m64n32k16.f32.bf16.bf16 {%0,%1,%2,%3,%4,%5,%6,%7,%8,%9,%10,%11,%12,%13,%14,%15}, {%16,%17,%18,%19}, %20, p, 1, 1, 0; }"
        : "+f"(d[0]), "+f"(d[1]), "+f"(d[2]), "+f"(d[3]), "+f"(d[4]), "+f"(d[5]), "+f"(d[6]), "+f"(d[7]), "+f"(d[8]), "+f"(d[9]), "+f"(d[10]), "+f"(d[11]), "+f"(d[12]), "+f"(d[13]), "+f"(d[14]), "+f"(d[15])
        : "r"(a[0]), "r"(a[1]), "r"(a[2]), "r"(a[3]), "l"(b), "r"(acc));
}

__device__ __forceinline__ float warp_sum(float v) {
#pragma unroll
    for (int o = 16; o; o >>= 1) v += __shfl_xor_sync(0xffffffffu, v, o);
    return v;
}
__device__ __forceinline__ uint32_t add2(uint32_t a, uint32_t b) { uint32_t r; asm("add.rn.bf16x2 %0, %1, %2;" : "=r"(r) : "r"(a), "r"(b)); return r; }
__device__ __forceinline__ uint32_t mul2(uint32_t a, uint32_t b) { uint32_t r; asm("mul.rn.bf16x2 %0, %1, %2;" : "=r"(r) : "r"(a), "r"(b)); return r; }
__device__ __forceinline__ uint32_t amax2(uint32_t m, uint32_t v) { uint32_t r; asm("max.u16x2 %0, %1, %2;" : "=r"(r) : "r"(m), "r"(v & 0x7fff7fffu)); return r; }
__device__ __forceinline__ uint32_t amax_warp(uint32_t m) { return __reduce_max_sync(0xffffffffu, max(m & 0xffffu, m >> 16)); }
__device__ __forceinline__ void ln_norm(const uint32_t (&xv)[10], uint32_t (&nv)[10]) {
    float s0 = 0, s1 = 0;
#pragma unroll
    for (int i = 0; i < 10; i++) { s0 += lo_f(xv[i]); s1 += hi_f(xv[i]); }
    const float mean = warp_sum(s0 + s1) * (1.f / DM);
    float q0 = 0, q1 = 0;
#pragma unroll
    for (int i = 0; i < 10; i++) { const float d0 = lo_f(xv[i]) - mean, d1 = hi_f(xv[i]) - mean; q0 += d0 * d0; q1 += d1 * d1; }
    const float inv = inv_std(warp_sum(q0 + q1) * (1.f / DM));
    const uint32_t mb = pack2(-mean, -mean);
#pragma unroll
    for (int i = 0; i < 10; i++) { const uint32_t d = add2(xv[i], mb); nv[i] = pack2(lo_f(d) * inv, hi_f(d) * inv); }
}
__device__ __forceinline__ void ln_mod(const uint32_t (&xv)[10], const uint32_t (&sv)[10], const uint32_t (&tv)[10], uint32_t (&hv)[10]) {
    ln_norm(xv, hv);
#pragma unroll
    for (int i = 0; i < 10; i++) hv[i] = add2(mul2(hv[i], add2(sv[i], 0x3f803f80u)), tv[i]);
}
__device__ __forceinline__ uint32_t ld_rlx(const uint32_t* f) { uint32_t v; asm volatile("ld.relaxed.gpu.global.u32 %0, [%1];" : "=r"(v) : "l"(f) : "memory"); return v; }
__device__ __forceinline__ void bump(uint32_t* f) { asm volatile("red.relaxed.gpu.global.add.u32 [%0], 1;" :: "l"(f) : "memory"); }
#define NAP 100
#define GPU_FENCE() asm volatile("fence.acq_rel.gpu;" ::: "memory")
__device__ __forceinline__ void flag_wait(const uint32_t* f, uint32_t target) {
    for (int n = 0;; n++) {
        uint32_t v; asm volatile("ld.relaxed.gpu.global.u32 %0, [%1];" : "=r"(v) : "l"(f) : "memory");
        if (v >= target) break;
        if (n > (1 << 22)) __trap();
        __nanosleep(NAP);
    }
}
__device__ __forceinline__ void flag_add(uint32_t* f, uint32_t v = 1) { asm volatile("red.release.gpu.global.add.u32 [%0], %1;" :: "l"(f), "r"(v) : "memory"); }
constexpr int N_SIDE = 36;
__device__ __forceinline__ void flags_release(int lane) {
    uint32_t old = 0;
    if (lane == 0) asm volatile("atom.relaxed.gpu.global.add.u32 %0, [%1], 1;" : "=r"(old) : "l"(&g_flags.done) : "memory");
    if (__shfl_sync(0xffffffffu, old, 0) == 96 + N_SIDE - 1)
#pragma unroll 1
        for (int i = lane; i < (int)(sizeof(Flags) / 16); i += 32) ((uint4*)&g_flags)[i] = make_uint4(0, 0, 0, 0);
}

template <int NT> struct ModSlice {
    static constexpr int R = 2 * DM / NT;
    float sc[R]; uint4 wv[R];
    __device__ __forceinline__ void load(const bf16* wmod, const bf16* c, int col, int tid) {
        const bf16* wm = wmod + (tid >> 1) * (6 * DM) + col + (tid & 1) * 8;
#pragma unroll
        for (int i = 0; i < R; i++) {
            asm volatile("ld.global.nc.L1::no_allocate.L2::128B.v4.u32 {%0,%1,%2,%3}, [%4];" : "=r"(wv[i].x), "=r"(wv[i].y), "=r"(wv[i].z), "=r"(wv[i].w) : "l"(wm + i * (NT / 2) * (6 * DM)));
            sc[i] = __uint_as_float((uint32_t)__ldg((const unsigned short*)c + (tid >> 1) + NT / 2 * i) << 16);
        }
    }
    __device__ __forceinline__ void partial(uint32_t buf, int tid) {
        const int lane = tid & 31;
        float a[8] = {0, 0, 0, 0, 0, 0, 0, 0};
#pragma unroll
        for (int i = 0; i < R; i++) {
            const float f = bfr(__fdividef(sc[i], 1.f + __expf(-sc[i])));
            const uint32_t u[4] = {wv[i].x, wv[i].y, wv[i].z, wv[i].w};
#pragma unroll
            for (int e = 0; e < 4; e++) { a[2 * e] += f * lo_f(u[e]); a[2 * e + 1] += f * hi_f(u[e]); }
        }
#pragma unroll
        for (int h = 4; h; h >>= 1)
#pragma unroll
            for (int e = 0; e < h; e++) { const bool up = lane & (4 * h); a[e] = (up ? a[e + h] : a[e]) + __shfl_xor_sync(0xffffffffu, up ? a[e] : a[e + h], 4 * h); }
        a[0] += __shfl_xor_sync(0xffffffffu, a[0], 2);
        asm volatile("st.shared.f32 [%0], %1;" :: "r"(buf + (tid >> 5) * 64 + (lane & 1) * 32 + (lane >> 2) * 4), "f"(a[0]) : "memory");
    }
    static __device__ __forceinline__ uint32_t total(uint32_t buf, int lane) {
        float a0 = 0, a1 = 0;
#pragma unroll
        for (int i = 0; i < NT / 32; i++) { float x, y; asm volatile("ld.shared.v2.f32 {%0,%1}, [%2];" : "=f"(x), "=f"(y) : "r"(buf + i * 64 + (lane & 7) * 8) : "memory"); a0 += x; a1 += y; }
        return pack2(a0, a1);
    }
};

struct ChainMaps { CUtensorMap wq, wk, wv, wo, h2, wo15, o15, slab16; };
struct ChainArgs { const bf16 *x, *mem0, *c, *wmod, *wv, *wo, *wgate, *wup, *wdown; bf16* out; int D1, D2, DG; };
constexpr uint32_t SM_BASE = 1024;
#define NRING 10
#define XORD 0
#define B5AT 41
#define QCUT 0x54
#define NCH 0
#define XA 2
#define VT 1
#define OSEND 1
#define SPOLL 0
#define NOF 0
#define FW 2
#define NPRE 9
#define REG_P 208
#define REG_L (504 - 2 * REG_P)
constexpr int WO_BLK = 7 * 4096;
constexpr int C_WV = 0, C_WO = 81920, C_XR = 167936, C_VP = C_XR + 7 * 4096, C_VX = C_XR + 8 * 4096, C_QX = C_VX + 4096, C_KX = C_QX + 4096,
              C_MEM = C_KX + 4096, C_OX = C_MEM + 9216, C_VM = C_OX + 3072, C_QM = C_VM + 1024, C_KM = C_QM + 1024, C_SC = C_KM + 1024, C_BAR = C_SC + 3840;
constexpr int CB_W = C_BAR, CB_W2 = C_BAR + 8, CB_SC = C_BAR + 16, CB_XD = C_BAR + 24, CB_VX = C_BAR + 32, CB_W3 = C_BAR + 40, CB_XM = C_BAR + 48, CB_OX = C_BAR + 56,
              CB_XF = C_BAR + 64, C_LAG = C_BAR + 96, C_UN = C_BAR + 100, C_MX = C_BAR + 112;
constexpr int C_SMEM = C_BAR + 128;
#define PROF(i)
#define PROFG(i)
#define PROFV(i, v)
static_assert(C_SMEM <= 232448, "chain shared memory");
__device__ __forceinline__ uint32_t umax3(uint32_t a, uint32_t b, uint32_t c) { return max(max(a, b), c); }
__device__ __forceinline__ void wait_until(uint32_t t) {
    asm volatile("{ .reg .pred p; .reg .s32 c; .reg .u64 d;\nU_%=: mov.u64 d, %%clock64; cvt.u32.u64 c, d; sub.s32 c, c, %0; setp.lt.s32 p, c, 0; @p bra.uni U_%=; }" :: "r"(t) : "memory");
}
__device__ __forceinline__ uint32_t gtime() { uint32_t c; asm volatile("mov.u32 %0, %%globaltimer_lo;" : "=r"(c)); return c; }
__device__ __forceinline__ uint32_t opaque(uint32_t v) { uint32_t r; asm volatile("shfl.sync.bfly.b32 %0, %1, 0, 31, -1;" : "=r"(r) : "r"(v)); return r; }
__device__ __forceinline__ uint32_t lds32(uint32_t a) { uint32_t v; asm volatile("ld.shared.u32 %0, [%1];" : "=r"(v) : "r"(a) : "memory"); return v; }
__device__ __forceinline__ float2 lds64f(uint32_t a) { float2 v; asm volatile("ld.shared.v2.f32 {%0,%1}, [%2];" : "=f"(v.x), "=f"(v.y) : "r"(a) : "memory"); return v; }
__device__ __forceinline__ float4 lds128f(uint32_t a) { float4 v; asm volatile("ld.shared.v4.f32 {%0,%1,%2,%3}, [%4];" : "=f"(v.x), "=f"(v.y), "=f"(v.z), "=f"(v.w) : "r"(a) : "memory"); return v; }
__device__ __forceinline__ void sts128f(uint32_t a, float x, float y, float z, float w) { asm volatile("st.shared.v4.f32 [%0], {%1,%2,%3,%4};" :: "r"(a), "f"(x), "f"(y), "f"(z), "f"(w) : "memory"); }
__device__ __forceinline__ void lds64(uint32_t (&v)[2], uint32_t a) { asm volatile("ld.shared.v2.u32 {%0,%1}, [%2];" : "=r"(v[0]), "=r"(v[1]) : "r"(a) : "memory"); }
__device__ __forceinline__ void mma16q(float (&d)[4], const uint32_t (&a)[4], uint32_t b0, uint32_t b1) { mma16(d, a[0], a[1], a[2], a[3], b0, b1); }
__device__ __forceinline__ uint32_t f16_to_bf16(uint32_t v) {
    float lo, hi; asm("{ .reg .f16 l, h; mov.b32 {l, h}, %2; cvt.f32.f16 %0, l; cvt.f32.f16 %1, h; }" : "=f"(lo), "=f"(hi) : "r"(v));
    return pack2(lo, hi);
}
__device__ __forceinline__ uint32_t pack2h(float lo, float hi) { uint32_t r; asm("cvt.rn.f16x2.f32 %0, %1, %2;" : "=r"(r) : "f"(hi), "f"(lo)); return r; }
#define SPLIT 1
__device__ __forceinline__ void cut(uint32_t never, int n) {
    asm volatile("{ .reg .pred p; setp.ne.u32 p, %0, %1; @p bra.uni C_%=; trap; C_%=: }" :: "r"(never), "r"(n) : "memory");
}
__device__ __forceinline__ void pin(uint32_t never, uint32_t a, uint32_t b, uint32_t c, uint32_t d) {
    asm volatile("{ .reg .pred p; setp.eq.u32 p, %0, 0; @p st.shared.v4.u32 [%0], {%1,%2,%3,%4}; }" :: "r"(never), "r"(a), "r"(b), "r"(c), "r"(d) : "memory");
}
__device__ __forceinline__ void pin0(uint32_t never) {
    asm volatile("{ .reg .pred p; setp.eq.u32 p, %0, 0; @p st.shared.u32 [%0], 0; }" :: "r"(never) : "memory");
}
#define ELECTED(txt) "{ .reg .pred e; elect.sync _|e, -1; @e " txt " }"
__device__ __forceinline__ void w_bulk_s2g(void* dst, uint32_t src, int bytes) {
    asm volatile(ELECTED("cp.async.bulk.global.shared::cta.bulk_group [%0], [%1], %2;") :: "l"(dst), "r"(src), "r"(bytes) : "memory");
}
__device__ __forceinline__ void w_bump(uint32_t* f) { asm volatile(ELECTED("red.relaxed.gpu.global.add.u32 [%0], 1;") :: "l"(f) : "memory"); }
__device__ __forceinline__ void w_expect(uint32_t bar, int bytes) { asm volatile(ELECTED("mbarrier.arrive.expect_tx.shared::cta.b64 _, [%0], %1;") :: "r"(bar), "r"(bytes) : "memory"); }
__device__ __forceinline__ void w_flag_wait(const uint32_t* f, uint32_t target) {
    asm volatile("{ .reg .pred p; .reg .u32 n, v; mov.u32 n, 0;\n"
                 "F_%=: ld.relaxed.gpu.global.u32 v, [%0]; setp.ge.u32 p, v, %1; vote.sync.all.pred p, p, -1; @p bra.uni G_%=;\n"
                 "nanosleep.u32 %2; add.u32 n, n, 1; setp.lt.u32 p, n, 0x400000; @p bra.uni F_%=;\ntrap;\nG_%=: }" :: "l"(f), "r"(target), "n"(NAP) : "memory");
}
#define BULK_COMMIT()    asm volatile("cp.async.bulk.commit_group;" ::: "memory")
#define BULK_WAIT()      asm volatile("cp.async.bulk.wait_group 0;" ::: "memory")
#define BULK_WAIT_READ() asm volatile("cp.async.bulk.wait_group.read 0;" ::: "memory")
#define PROXY_FENCE()    asm volatile("fence.proxy.async.shared::cta;" ::: "memory")
__device__ __forceinline__ void send16(uint32_t dst, uint32_t bar, float a, float b, float c, float d) {
    asm volatile("st.async.shared::cluster.mbarrier::complete_tx::bytes.v4.f32 [%0], {%1,%2,%3,%4}, [%5];" :: "r"(dst), "f"(a), "f"(b), "f"(c), "f"(d), "r"(bar) : "memory");
}
__device__ __forceinline__ void send8(uint32_t dst, uint32_t bar, uint32_t a, uint32_t b) {
    asm volatile("st.async.shared::cluster.mbarrier::complete_tx::bytes.v2.b32 [%0], {%1,%2}, [%3];" :: "r"(dst), "r"(a), "r"(b), "r"(bar) : "memory");
}

__device__ __forceinline__ void seg_done(int n, int head) {
    if (n >= 60 || (n & 3) == 3) { if (!NOF) GPU_FENCE(); w_bump(n >= 60 ? &g_flags.seg[(n - 60) * 32 + head] : &g_flags.qk[n >> 2]); }
}
__device__ __forceinline__ uint32_t x_base(int wg, uint32_t small, int sh) { return (uint32_t)mkdesc(SM_BASE + C_XR, 16, 1024) + wg * 256 + (small >> sh); }
__device__ __forceinline__ void x_chunk(float (&acc)[16], const uint32_t (&wa)[40][4], uint32_t xl, int a0, int i, int first) {
#pragma unroll
    for (int ks = 0; ks < 4; ks++)
        wgmma_rs_n32(acc, wa[a0 + 4 * i + ks], mkdesc(0, 0, 1024) | (uint32_t)(xl + (((i ? (i - 1) * 8192 : C_MEM - C_XR) + ks * 32) >> 4)), !(first && ks == 0));
}
__device__ __forceinline__ void x_part(float (&acc)[16], const uint32_t (&wa)[40][4], uint32_t sm, int n, int wg, int w, uint32_t ln, uint32_t small) {
    const int s = n - 1; (void)s;
    uint32_t giv[8];
    auto chunk = [&](int a0, int i, int first) { x_chunk(acc, wa, x_base(wg, small, a0 ? 21 : 22), a0, i, first); };
    mbar_wait(sm + CB_XM, n & 1);
    if (n) bar_sync(5, 384);
    if (wg == 0 && w == 0) PROF(12);
    WG_FENCE();
#pragma unroll
    for (int i = 1 + XA; i < 5; i++) chunk(20, i, 0);
    chunk(20, 0, 0);
    WG_COMMIT();
    if (n) {
        if (wg == 1 && w == 1) BULK_WAIT();
        bar_sync(8, 256);
    }
    if (wg == 0 && w == 0) PROF(18);
    const uint32_t xb = sm + w * 512 + ln * 16, xw = xb + C_KX - wg * 4096, xr = xb + C_QX + wg * 4096;
    WG_WAIT(0);
#pragma unroll
    for (int i = 0; i < 8; i++) asm volatile("cvt.rn.bf16x2.f32 %0, %1, %2;" : "=r"(giv[i]) : "f"(acc[2 * i + 1]), "f"(acc[2 * i]));
#pragma unroll
    for (int p = 0; p < 2; p++) asm volatile("st.shared.v4.u32 [%0], {%1,%2,%3,%4};" :: "r"(xw + p * 2048), "r"(giv[4 * p]), "r"(giv[4 * p + 1]), "r"(giv[4 * p + 2]), "r"(giv[4 * p + 3]) : "memory");
    bar_arrive(12 + wg, 256);
    WG_FENCE();
    chunk(0, 0, 1);
    WG_COMMIT();
    chunk(0, 1, 0);
    if (XORD) chunk(0, 2, 0);
    bar_sync(13 - wg, 256);
#pragma unroll
    for (int p = 0; p < 2; p++) asm volatile("ld.shared.v4.u32 {%0,%1,%2,%3}, [%4];" : "=r"(giv[4 * p]), "=r"(giv[4 * p + 1]), "=r"(giv[4 * p + 2]), "=r"(giv[4 * p + 3]) : "r"(xr + p * 2048) : "memory");
    WG_COMMIT(); WG_WAIT(1); bar_arrive(9, 384);
    WG_FENCE();
    if (!XORD) chunk(0, 2, 0);
    chunk(0, 3, 0); chunk(0, 4, 0);
    WG_COMMIT();
    const uint32_t r = ln & 7, mi = ln >> 3, dst = sm + (wg == 0 ? C_QX : C_KX) + ((mi >> 1) * 8 + r) * 128 + (((2 * w + (mi & 1)) ^ r) << 4);
    pin(xb, giv[0], giv[4], dst, 0);
    bar_sync(10 + wg, 128);
    WG_WAIT(0);
    if (wg == 0 && w == 0) PROF(30);
    if (w == 0 && ln < 3) mbar_arrive_remote(mapa(sm + CB_XD, ln));
#pragma unroll
    for (int i = 0; i < 8; i++) { acc[2 * i] += lo_f(giv[i]); acc[2 * i + 1] += hi_f(giv[i]); }
#pragma unroll
    for (int p = 0; p < 2; p++)
        stsm4t(dst + p * 2048, pack2(acc[8 * p], acc[8 * p + 1]), pack2(acc[8 * p + 2], acc[8 * p + 3]), pack2(acc[8 * p + 4], acc[8 * p + 5]), pack2(acc[8 * p + 6], acc[8 * p + 7]));
    if (wg == 0 && w == 0) PROF(11);
}
__device__ __forceinline__ void x_fill(const ChainMaps& mp, uint32_t sm, int n, int j) {
    mbar_expect(sm + CB_XF, 24576);
    asm volatile("cp.async.bulk.tensor.3d.shared::cluster.global.mbarrier::complete_tx::bytes.multicast::cluster [%0], [%1, {0, %3, %4}], [%2], %5;"
        :: "r"(sm + C_XR + j * 8192), "l"((uint64_t)&mp.h2), "r"(sm + CB_XF), "r"(n * SEG), "r"(2 + 2 * j), "h"((uint16_t)7) : "memory");
}
__device__ __forceinline__ void x_rest(const ChainMaps& mp, uint32_t sm, int n) {
    mbar_expect(sm + CB_XM, 16384);
    tma3d(sm + C_XR + 6 * 4096, &mp.h2, n * SEG, 8, sm + CB_XM); tma3d(sm + C_MEM, &mp.h2, n * SEG, 0, sm + CB_XM);
}

#define WPOS 15
#define WP 8
#define WOPF 30
#define SPF 0
#define SDEL 0
#define EORD 1
#define BPOS 1
#define TPF 1
#define B_LATE 14
constexpr int E_B = C_WO, E_STG = 196608, EB_A = 229376, EB_B = C_BAR + 80, EB_REL = C_BAR + 104;
__device__ __forceinline__ uint32_t e_slot(int wg, int c) { return wg && c == 2 ? E_B + 98304 : wg * 49152 + c * 16384; }
constexpr int T_WG = 0, T_WU = 20480, T_WD = 40960, T_X = 65536, T_RED = 77824, T_KEY = 86016;
__device__ __forceinline__ void wo_half(const ChainMaps& mp, uint32_t sm, int blk, int c) {
    if (blk < 80 && elect()) { mbar_expect(sm + EB_B + 8 * c, 49152); tma3d(sm + E_B + c * 49152, &mp.wo15, blk / 5 * 384 + c * 192, blk % 5 * 2, sm + EB_B + 8 * c); }
}
__device__ __forceinline__ void end_loads(const ChainMaps& mp, const ChainArgs& ar, uint32_t sm, int blk, int wg) {
    const uint32_t bar = sm + EB_A + wg * 48;
    const int kp = blk / 5;
    if (elect()) {
#pragma unroll 1
        for (int c = 0; c < 6; c++) mbar_init(bar + 8 * c, c < 3 ? 1 : 4);
        PROXY_FENCE();
    }
    __syncwarp();
    bar_arrive(5, 384);
    if (EORD) bar_sync(6, 96);
    if (blk >= 80) {
        if (TPF && elect()) {
#pragma unroll 1
            for (int c = 0; c < 3; c++) asm volatile("cp.async.bulk.prefetch.L2.global [%0], 61440;" :: "l"((c == 0 ? ar.wgate : c == 1 ? ar.wup : ar.wdown) + ((blk - 80) * 2 + wg) * 30720) : "memory");
        }
        return;
    }
    const uint64_t ef = policy_stream();
#pragma unroll 1
    for (int b = B_LATE; b < 16; b++) {
        w_flag_wait(b == 15 ? &g_flags.half[kp * 2 + wg] : &g_flags.pair[b * 16 + kp], b == 15 ? 2 : 4);
#pragma unroll 1
        for (int c = 0; c < 3; c++) {
            if (b > B_LATE) mbar_wait(bar + 24 + 8 * c, (b - B_LATE - 1) & 1);
            if (elect()) { mbar_expect(bar + 8 * c, 16384); tma3d_ef(sm + e_slot(wg, c), &mp.o15, b * 128 + wg * 64, kp * 6 + c * 2, bar + 8 * c, ef); }
            __syncwarp();
        }
    }
}
__device__ __forceinline__ void last_blocks(const ChainMaps& mp, const ChainArgs& ar, uint32_t sm, int blk, int tid) {
    const int warp = __shfl_sync(0xffffffffu, tid >> 5, 0), lane = tid & 31, wg = warp >> 2, w = warp & 3, kp = blk / 5, ct = blk % 5;
    const uint32_t bar = sm + EB_A + wg * 48, stg = sm + E_STG + warp * 4096;
    const uint64_t ef = policy_stream();
    bar_sync(5, 384);
    float acc[64];
#pragma unroll
    for (int n = 0; n < 64; n++) acc[n] = 0.f;
#pragma unroll 1
    for (int b = B_LATE; b < 16 && blk < 80; b++) {
#pragma unroll 1
        for (int c = 0; c < 6; c++) {
            mbar_wait(sm + EB_B + 8 * (c >= 3), 0); mbar_wait(bar + 8 * (c >> 1), (b - B_LATE) & 1);
            const uint64_t da = mkdesc(SM_BASE + e_slot(wg, c >> 1) + (c & 1) * 8192, 16, 1024), db = mkdesc(SM_BASE + E_B + (c >= 3 ? 24576 : 0) + c * 8192, 24576, 1024);
            WG_FENCE();
#pragma unroll
            for (int ks = 0; ks < 4; ks++) wgmma_ss_n128_tb(acc, da + ks * 2, db + ks * 128, c | ks);
            WG_COMMIT();
            WG_WAIT(1);
            if ((c & 1) == 0 && c && elect()) mbar_arrive(bar + 16 + 4 * c);
        }
        WG_WAIT(0);
        if (elect()) mbar_arrive(bar + 40);
        const int r = lane & 7, mi = lane >> 3;
#pragma unroll
        for (int p = 0; p < 8; p++) {
            const int oc = 2 * p + (mi >> 1);
            stsm4(stg + (oc >> 3) * 2048 + ((mi & 1) * 8 + r) * 128 + (((oc & 7) ^ r) << 4), pack2(acc[8 * p], acc[8 * p + 1]), pack2(acc[8 * p + 2], acc[8 * p + 3]),
                  pack2(acc[8 * p + 4], acc[8 * p + 5]), pack2(acc[8 * p + 6], acc[8 * p + 7]));
        }
        PROXY_FENCE();
        __syncwarp();
        if (elect()) tma3d_store(&mp.slab16, (b * KSPLIT + kp) * 128 + warp * 16, ct * 2, stg, ef, false);
        BULK_COMMIT(); BULK_WAIT();
        if (w) bar_arrive(12 + wg, 128); else { bar_sync(12 + wg, 128); GPU_FENCE(); w_bump(b < 14 ? &g_flags.o[b] : &g_flags.fin[((b - 14) * 2 + wg) * 32]); }
    }
    bar_sync(8, 256);
    const int o = (tid >> 1) * FF + blk * 16 + (tid & 1) * 8;
    const bf16 *pg = ar.wgate + o, *pu = ar.wup + o, *pd = ar.wdown + tid * DM + (blk < 80 ? blk : 0) * 8;
#pragma unroll
    for (int i = 0; i < 16; i++)
        asm volatile("cp.async.cg.shared.global [%0], [%1], 16;" :: "r"(sm + E_B + i * 4096 + tid * 16), "l"(i < 5 ? pg + i * 128 * FF : i < 10 ? pu + (i - 5) * 128 * FF : pd + (i - 10) * 256 * DM) : "memory");
}
__device__ __forceinline__ void mod_tail(const ChainArgs& ar, const uint32_t tb, const uint32_t bar, const int blk, const int tid) {
#define TPROF(i)
    const int warp = __shfl_sync(0xffffffffu, tid >> 5, 0), lane = tid & 31, r = lane & 7, mi = lane >> 3;
    const uint32_t kb = tb + T_KEY;
    {
        uint32_t k[8];
        for (int n = 0;; n++) {
#pragma unroll
            for (int i = 0; i < 2; i++) asm volatile("ld.relaxed.gpu.global.v4.u32 {%0,%1,%2,%3}, [%4];" : "=r"(k[4 * i]), "=r"(k[4 * i + 1]), "=r"(k[4 * i + 2]), "=r"(k[4 * i + 3]) : "l"(g_key + warp * 256 + i * 128 + lane * 4) : "memory");
            if (__all_sync(0xffffffffu, (k[0] & k[1] & k[2] & k[3] & k[4] & k[5] & k[6] & k[7] & S_TOK) != 0)) break;
            if (n > (1 << 22)) __trap();
            __nanosleep(NAP);
        }
        const uint32_t m = __reduce_max_sync(0xffffffffu, max(umax3(k[0], k[1], k[2]), max(umax3(k[3], k[4], k[5]), max(k[6], k[7]))));
        asm volatile("st.shared.u32 [%0], %1; st.shared.u32 [%2], 0;" :: "r"(kb + warp * 4), "r"(m), "r"(kb + 32) : "memory");
        asm volatile("cp.async.wait_all;" ::: "memory");
        bar_sync(1, 256);
        TPROF(1);
        const uint32_t low = __reduce_min_sync(0xffffffffu, lds32(kb + r * 4));
        uint32_t cnt = 0;
#pragma unroll
        for (int i = 0; i < 8; i++) cnt += k[i] >= low ? 4 : 0;
        if (cnt) {
            uint32_t a; asm volatile("atom.shared.add.u32 %0, [%1], %2;" : "=r"(a) : "r"(kb + 32), "r"(cnt) : "memory");
#pragma unroll
            for (int i = 0; i < 8; i++) if (k[i] >= low) { asm volatile("st.shared.u32 [%0], %1;" :: "r"(kb + 512 + a), "r"(k[i]) : "memory"); a += 4; }
        }
        if (tid == 0) mbar_arrive(bar);
        bar_sync(1, 256);
        const int nc = lds32(kb + 32);
#pragma unroll 1
        for (int c = lane * 4; c < nc; c += 128) {
            const uint32_t me = lds32(kb + 512 + c);
            int rank = 0;
#pragma unroll 2
            for (int e = 0; e < nc; e += 16) {
                const float4 z = lds128f(kb + 512 + e);
                rank += (__float_as_uint(z.x) > me) + (e + 4 < nc && __float_as_uint(z.y) > me) + (e + 8 < nc && __float_as_uint(z.z) > me) + (e + 12 < nc && __float_as_uint(z.w) > me);
            }
            if (rank < 8) asm volatile("st.shared.u32 [%0], %1;" :: "r"(kb + 64 + (warp * 8 + rank) * 4), "r"(me) : "memory");
        }
        __syncwarp();
    }
    const uint32_t k0 = lds32(kb + 64 + (warp * 8 + r) * 4), k1 = lds32(kb + 64 + (warp * 8 + (lane >> 2)) * 4);
    TPROF(2);
    const int trow = ~k1 & (S_TOK - 1), tcol = (blk < 80 ? blk : 0) * 8 + (lane & 3) * 2;
    uint2 xb[5];
#pragma unroll
    for (int h = 0; h < 5; h++) xb[h] = __ldcg((const uint2*)(g_h2 + trow * DM + (warp * 5 + h) * 16 + (lane & 3) * 4));
    const uint32_t fx1 = __ldcg((const uint32_t*)(g_x1 + trow * DM + tcol)), fh2 = __ldcg((const uint32_t*)(g_h2 + trow * DM + tcol)),
                   fgb = __ldcg((const uint32_t*)(g_mod + 5 * DM + tcol));
    const float fr = __uint_as_float(((int)k1 < 0 ? k1 ^ 0x80000000u : ~k1) & 0xffff0000u);
    {
        float dg[4] = {0, 0, 0, 0}, du[4] = {0, 0, 0, 0};
        uint32_t ag[5][4], au[5][4];
#pragma unroll
        for (int h = 0; h < 5; h++) {
            const uint32_t o = tb + ((warp * 5 + h) * 16 + (r >> 1) * 4 + (mi >> 1) * 2 + (r & 1)) * 32 + (mi & 1) * 16;
            ldsm4t(ag[h], o + T_WG); ldsm4t(au[h], o + T_WU);
        }
#pragma unroll
        for (int h = 0; h < 5; h++) { mma16q(dg, ag[h], xb[h].x, xb[h].y); mma16q(du, au[h], xb[h].x, xb[h].y); }
        TPROF(3);
        sts128f(tb + T_RED + warp * 1024 + lane * 16, dg[0], dg[1], dg[2], dg[3]); sts128f(tb + T_RED + warp * 1024 + 512 + lane * 16, du[0], du[1], du[2], du[3]);
    }
    bar_sync(1, 256);
    if (warp < 2) {
        float g2[2] = {0, 0}, u2[2] = {0, 0};
#pragma unroll
        for (int i = 0; i < 8; i++) {
            const float2 a = lds64f(tb + T_RED + i * 1024 + lane * 16 + warp * 8), b = lds64f(tb + T_RED + i * 1024 + 512 + lane * 16 + warp * 8);
            g2[0] += a.x; g2[1] += a.y; u2[0] += b.x; u2[1] += b.y;
        }
        float y[2];
#pragma unroll
        for (int i = 0; i < 2; i++) { const float gq = bfr(g2[i]); y[i] = bfr(__fdividef(gq, 1.f + __expf(-gq))) * bfr(u2[i]); }
        asm volatile("st.relaxed.gpu.global.u32 [%0], %1;" :: "l"(g_gu + (blk >> 1) * 128 + lane * 4 + warp * 2 + (blk & 1)), "r"(movm_t(pack2(y[0], y[1]))) : "memory");
    }
    TPROF(4);
    if (blk < 80) {
        uint32_t a[6][4], b[6][4];
#pragma unroll
        for (int k2 = 0; k2 < 6; k2++) ldsm4t(b[k2], tb + T_WD + (warp * 6 + k2) * 512 + lane * 16);
        for (int n = 0;; n++) {
            uint32_t m = 0;
#pragma unroll
            for (int k2 = 0; k2 < 6; k2++) asm volatile("ld.relaxed.gpu.global.v4.u32 {%0,%1,%2,%3}, [%4];" : "=r"(a[k2][0]), "=r"(a[k2][1]), "=r"(a[k2][2]), "=r"(a[k2][3]) : "l"(g_gu + (warp * 6 + k2) * 128 + lane * 4) : "memory");
#pragma unroll
            for (int k2 = 0; k2 < 6; k2++) m = umax3(umax3(m, a[k2][0], a[k2][1]), a[k2][2], a[k2][3]);
            if (!__any_sync(0xffffffffu, m == ~0u)) break;
            if (n > (1 << 22)) __trap();
        }
        TPROF(5);
        float d[2][4] = {{0, 0, 0, 0}, {0, 0, 0, 0}};
#pragma unroll
        for (int k2 = 0; k2 < 6; k2++) { mma16q(d[0], a[k2], b[k2][0], b[k2][1]); mma16q(d[1], a[k2], b[k2][2], b[k2][3]); }
        asm volatile("st.shared.v2.f32 [%0], {%1,%2};" :: "r"(tb + T_X + warp * 256 + lane * 8), "f"(d[0][0] + d[1][2]), "f"(d[0][1] + d[1][3]) : "memory");
        bar_sync(1, 256);
        if (warp == 0) {
            float y0 = 0, y1 = 0;
#pragma unroll
            for (int i = 0; i < 8; i++) { const float2 z = lds64f(tb + T_X + i * 256 + lane * 8); y0 += z.x; y1 += z.y; }
            const float sg = __fdividef(1.f, 1.f + __expf(-fr));
            *(uint32_t*)(ar.out + trow * DM + tcol) = add2(fx1, mul2(fgb, add2(fh2, mul2(pack2(y0, y1), pack2(sg, sg)))));
        }
    }
    TPROF(6);
}

__global__ void __cluster_dims__(3, 1, 1) __launch_bounds__(384, 1) k_chain(const __grid_constant__ ChainMaps mp, const __grid_constant__ ChainArgs ar) {
    const int D1 = ar.D1, DG = ar.DG;
    extern __shared__ __align__(1024) uint8_t smraw[];
    const uint32_t sm = SM_BASE + ((blockIdx.x % 3) << 24);
    if (smem_u32(smraw) != sm) __trap();
    uint32_t tid; asm volatile("mov.u32 %0, %%tid.x;" : "=r"(tid));
    const int warp = __shfl_sync(0xffffffffu, tid >> 5, 0), lane = tid & 31, wg = warp >> 2, w = warp & 3;
    const int blk = blockIdx.x, head = blk / 3, j = blk % 3;
    const int col0 = head * DH + j * 64;
    asm volatile("griddepcontrol.launch_dependents;");
#define PPROF(i)
    const int r = lane & 7, mi = lane >> 3;
    const uint32_t memrd = opaque(sm + C_MEM + lane * 16);
    if (wg < 2) {
        {
            uint32_t xv[3][10];
            const int row = blk * 8 + warp, nq = row < S_TOK - 1536 ? 3 : 2;
#pragma unroll
            for (int i = 0; i < 15; i++) {
                const uint2 v = __ldcs((const uint2*)(ar.x + (row + (i < 10 || nq == 3 ? i / 5 * 768 : 0)) * DM + lane * 4 + i % 5 * 128));
                xv[i / 5][i % 5 * 2] = v.x; xv[i / 5][i % 5 * 2 + 1] = v.y;
            }
            if (tid == 32) {
#pragma unroll 1
                for (int c = 0; c < 14; c++) if (c != 12) mbar_init(sm + C_BAR + 8 * c, c == 2 ? 5 : c == 3 ? 6 : 1);
                asm volatile("fence.mbarrier_init.release.cluster;" ::: "memory");
                mbar_expect(sm + CB_SC, 2560); mbar_expect(sm + CB_OX, 2048);
            }
            if (warp == 2) {
                const uint32_t f = blk >= 28 ? ~0u : 0u;
                ((uint4*)g_acc)[blk * 32 + lane] = make_uint4(0, 0, 0, 0);
                if (blk < 76) (blk < 12 ? (uint4*)g_stamp + blk * 32 : blk < 28 ? (uint4*)g_key + (blk - 12) * 32 : (uint4*)g_gu + (blk - 28) * 32)[lane] = make_uint4(f, f, f, f);
            }
            __syncwarp();
            asm volatile("barrier.cluster.arrive.relaxed.aligned;" ::: "memory");
            PPROF(8);
#pragma unroll 1
            for (int q = 0; q < 3; q++) {
                uint32_t nv[10];
                ln_norm(xv[0], nv);
#pragma unroll
                for (int i = 0; i < 10; i++) { xv[0][i] = xv[1][i]; xv[1][i] = xv[2][i]; xv[2][i] = nv[i]; }
            }
            PPROF(9);
            if (warp < 5) {
                uint4 u;
                for (int n = 0;; n++) {
                    asm volatile("ld.relaxed.gpu.global.v4.u32 {%0,%1,%2,%3}, [%4];" : "=r"(u.x), "=r"(u.y), "=r"(u.z), "=r"(u.w) : "l"(g_flags.mod1 + tid * 4) : "memory");
                    if (__all_sync(0xffffffffu, u.x && u.y && u.z && u.w)) break;
                    cut(n, 1 << 22);
                }
                asm volatile("st.shared.v4.u32 [%0], {%1,%2,%3,%4};" :: "r"(sm + C_KX + tid * 16), "r"(~u.x), "r"(~u.y), "r"(~u.z), "r"(~u.w) : "memory");
            }
            bar_sync(8, 256);
            PPROF(2);
            uint32_t m = 0;
#pragma unroll
            for (int i = 0; i < 5; i++) {
                uint32_t t[2], u[2];
                lds64(t, sm + C_KX + lane * 8 + i * 256); lds64(u, sm + C_KX + 1280 + lane * 8 + i * 256);
                u[0] = add2(u[0], 0x3f803f80u); u[1] = add2(u[1], 0x3f803f80u);
                m = amax2(amax2(amax2(amax2(m, t[0]), u[0]), t[1]), u[1]);
#pragma unroll
                for (int q = 0; q < 3; q++)
                    if (q < nq) *(uint2*)(g_h + (row + q * 768) * DM + lane * 4 + i * 128) = make_uint2(add2(mul2(xv[q][2 * i], u[0]), t[0]), add2(mul2(xv[q][2 * i + 1], u[1]), t[1]));
            }
            asm volatile("st.shared.u32 [%0], %1;" :: "r"(sm + C_LAG), "r"((amax_warp(m) >> 7) + 1) : "memory");
            bar_sync(8, 256);
            if (tid == 0) flag_add(&g_flags.h);
            __syncwarp();
            bar_arrive(2, 288);
            PPROF(3);
            asm volatile("barrier.cluster.wait.aligned;" ::: "memory");
        }
        asm volatile("setmaxnreg.inc.sync.aligned.u32 %0;" :: "n"(REG_P));
        uint32_t wa[40][4];
        mbar_wait(sm + CB_W, 0);
#pragma unroll
        for (int ks = 0; ks < 40; ks++)
            ldsm4t(wa[ks], sm + ((wg == 0) == (ks < 20) ? C_WV : C_WO) + ((mi >> 1) * 8 + r) * 128 + (((2 * w + (mi & 1)) ^ r) << 4) + (ks % 20 / 4 * 8 + 4 * wg + (ks & 3)) * 2048);
        PPROF(5);
        bar_arrive(1, 288);
        const uint32_t qst = opaque(sm + (wg == 0 ? C_QM : C_KM) + (2 * w + (mi & 1)) * 128 + r * 16);
        const uint32_t vrd = opaque(sm + C_WV + ((mi >> 1) * 8 + r) * 128 + (((2 * w + (mi & 1)) ^ r) << 4) + 4 * wg * 2048);
        const uint32_t mrd = opaque(memrd + wg * 1024);
        float acc[16];
        auto fb = [&](int n) { return mrd + (n >> 1) * 2048 + (n & 1) * 512; };
        auto fa = [&](int k) { return vrd + (k >> 2) * 16384 + (k & 3) * 2048; };
        auto qk_out = [&](int n) {
            uint8_t* rec = g_att + (n * NH + head) * AT_REC;
            w_bulk_s2g(rec + j * 8192, sm + C_QX, 8192); w_bulk_s2g(rec + AT_KM + j * 1024, sm + C_KM, 1024);
            BULK_COMMIT();
        };
        for (int s = -1;; s++) {
          if (s >= 0) {
            x_part(acc, wa, sm, s, wg, w, opaque(mrd) >> 4 & 31, s + ar.D2);
            if (s == 0) mbar_wait(sm + CB_W2, 0);
            uint32_t b[3][4], a[4][4];
#pragma unroll
            for (int i = 0; i < 4; i++) ldsm4t(a[i], fa(4 + i));
            cut(s + ar.D2, 0);
            bar_sync(1, 384);
            if (warp == 0) { PROF(0); PROFG(24); }
            float dv[4] = {0, 0, 0, 0};
            const uint32_t xb = mrd - wg * 1024 - (C_MEM - C_VP) + w * 512;
            {
                float d[2][4] = {{0, 0, 0, 0}, {0, 0, 0, 0}}, g[2][4] = {{0, 0, 0, 0}, {0, 0, 0, 0}};
                ldsm4t(b[0], fb(0)); pin0(mrd); ldsm4t(b[1], fb(1)); pin0(mrd);
#pragma unroll
                for (int n = 0; n < 10; n++) {
                    const int c1 = n >= 10 - NCH;
                    if (n < 8) ldsm4t(b[(n + 2) % 3], fb(n + 2));
#pragma unroll
                    for (int e = 0; e < 2; e++) {
                        mma16q(g[e & c1], wa[20 + 2 * n + e], b[n % 3][2 * e], b[n % 3][2 * e + 1]); mma16q(d[e & c1], wa[2 * n + e], b[n % 3][2 * e], b[n % 3][2 * e + 1]);
                        if (n >= 2 && n < 10 - VT) mma16q(dv, a[(2 * n + e) & 3], b[n % 3][2 * e], b[n % 3][2 * e + 1]);
                        if (n >= 2 && n < 8) ldsm4t(a[(2 * n + e) & 3], fa(2 * n + 4 + e));
                    }
                    if (QCUT >> n & 1) cut(s + ar.D2, 1 + n);
                }
                const float un = __uint_as_float(lds32(sm + C_UN));
                sts128f(xb - 4096 + wg * 2048, g[0][0] + g[1][0], g[0][1] + g[1][1], g[0][2] + g[1][2], g[0][3] + g[1][3]);
#pragma unroll
                for (int k = 20 - 2 * VT; k < 20; k++) mma16q(dv, a[k & 3], b[k / 2 % 3][2 * (k & 1)], b[k / 2 % 3][2 * (k & 1) + 1]);
                bar_sync(8, 256);
                const float4 z = lds128f(xb - 4096 + (wg ^ 1) * 2048);
                sts128f(xb + wg * 2048, dv[0], dv[1], dv[2], dv[3]);
                stsm2t(qst, pack2((d[0][0] + d[1][0] + z.x) * un, (d[0][1] + d[1][1] + z.y) * un), pack2((d[0][2] + d[1][2] + z.z) * un, (d[0][3] + d[1][3] + z.w) * un));
            }
            bar_arrive(2, 384);
            if (w == 0) PROF(1 + wg);
            if (s + 1 == NSEG) break;
          }
          if (warp == 3 && s >= 0)
              asm volatile(ELECTED("st.relaxed.gpu.global.u32 [%0], %1;") :: "l"(g_stamp + (s & 3) * 384 + (blk >> 3) * 32 + (blk & 7)), "r"((gtime() & ~31u) | ((s >> 2) + 1)) : "memory");
          PROXY_FENCE();
          mbar_wait(sm + CB_XF, (s + 1) & 1);
          if (s >= 0) bar_sync(7, 384);
          WG_FENCE();
#pragma unroll
          for (int i = 0; i < 16; i++) acc[i] = 0.f;
#pragma unroll
          for (int i = 1; i <= XA; i++) x_chunk(acc, wa, x_base(wg, s + ar.D2, 20), 20, i, i == 1);
          WG_COMMIT();
          if (warp == FW && s > 0) seg_done(s - 1, head);
          WG_WAIT(0);
          if (s >= 0) {
            if (warp == 0) {
                PROF(7);
                if (elect()) x_rest(mp, sm, s + 1);
            } else {
                if (wg == 1) {
                    if (w == 1) {
                        qk_out(s);
                    }
                    if (w == 2 && blk < 10 && s + 3 < NSEG)
                        asm volatile(ELECTED("cp.async.bulk.prefetch.L2.global [%0], 4096;") :: "l"((const uint8_t*)g_h + (s + 3) * (SEG * DM * 2) + blk * 4096) : "memory");
                } else if (w == 3) {
                    if (SPOLL) wait_until(clock() + SPOLL);
                    const uint32_t l = opaque(mrd) >> 4 & 31, tag = (s >> 2) + 1, now = gtime();
                    const uint32_t* sp = g_stamp + (s & 3) * 384 + (l >> 3) * 32 + (l & 7);
                    uint32_t t[3];
                    for (int n = 0;; n++) {
#pragma unroll
                        for (int i = 0; i < 3; i++) t[i] = ld_rlx(sp + i * 128);
                        if (!__any_sync(0xffffffffu, ((t[0] ^ tag) | (t[1] ^ tag) | (t[2] ^ tag)) & 31) || n > SPIN_LIMIT) break;
                    }
                    int all = -(1 << 30), own = all;
#pragma unroll
                    for (int i = 0; i < 3; i++) { const int d = t[i] - now; all = max(all, d); if ((i * 32 + l) / 3 == head) own = d; }
                    const int lag = min(__reduce_max_sync(0xffffffffu, all) - __reduce_max_sync(0xffffffffu, own), 8000);
                    PROFV(15, lag);
                    asm volatile("st.shared.u32 [%0], %1;" :: "r"(sm + C_LAG), "r"(D1 + ((lag * DG) >> 4)) : "memory");
                    bar_arrive(6, 160);
                } else if (w == 2) {
                    if ((s & 3) == 3) w_flag_wait(&g_flags.v[((s + 1) >> 2) * 32 + head], 2);
                    if (elect()) { mbar_expect(sm + CB_VX, 4096); bulk_g2s(sm + C_VX, g_att + ((s + 1) * NH + head) * AT_REC + AT_V + j * 4096, 4096, sm + CB_VX); }
                    if ((s & 3) == 1 && s + 3 < NSEG) asm volatile("prefetch.global.L2 [%0];" :: "l"(&g_flags.v[((s + 3) >> 2) * 32]));
                    if (s + 2 < NSEG && ((s & 3) != 2 || __all_sync(0xffffffffu, ld_rlx(&g_flags.v[((s + 2) >> 2) * 32 + head]) >= 2)))
                        asm volatile("prefetch.global.L2 [%0];" :: "l"(g_att + ((s + 2) * NH + head) * AT_REC + AT_V + j * 4096 + (opaque(mrd) << 3 & 0xf80)));
                }
            }
          }
        }
        PROXY_FENCE();
        bar_sync(8, 256);
        if (warp == 5) { qk_out(NSEG - 1); BULK_WAIT(); }
        if (warp == 7) seg_done(NSEG - 2, head);
        bar_arrive(7, 384);
        const int t2 = (opaque(mrd) >> 4 & 31) + warp * 32;
        last_blocks(mp, ar, sm, blk, t2);
        mod_tail(ar, sm + E_B, sm + EB_REL, blk, t2);
    } else {
        asm volatile("setmaxnreg.dec.sync.aligned.u32 %0;" :: "n"(REG_L));
        asm volatile("barrier.cluster.arrive.relaxed.aligned;" ::: "memory");
        if (blk < 80) {
            ModSlice<128> ms;
            ms.load(ar.wmod, ar.c, blk * 16, tid - 256); ms.partial(sm + C_QM, tid - 256);
            bar_sync(3, 128);
            if (w == 0) {
                const uint32_t v = ModSlice<128>::total(sm + C_QM, lane);
                asm volatile("st.relaxed.gpu.global.u32 [%0], %1;" :: "l"(g_flags.mod1 + blk * 8 + (lane & 7)), "r"(~v) : "memory");
            }
        }
        uint32_t m0[5][4], mm = 0;
#pragma unroll
        for (int i = 0; i < 20; i++) {
            const unsigned short* p = (const unsigned short*)ar.mem0 + (i & 3) * 2 * DM + (i >> 2) * 128 + tid - 256;
            m0[i >> 2][i & 3] = __ldg(p) | (uint32_t)__ldg(p + DM) << 16;
        }
        {
            asm volatile("barrier.cluster.wait.aligned;" ::: "memory");
            if (w == 3) {
                w_flag_wait(&g_flags.h, 96);
                if (elect()) { x_fill(mp, sm, 0, j); x_rest(mp, sm, 0); }
                __syncwarp();
            }
            if (w == 1) {
                const uint64_t ef = policy_stream();
#pragma unroll 1
                for (int c = 0; c < 2 * WP + 2; c++) {
                    const uint32_t bar = sm + EB_B + 8 * (c & 1);
                    if (c == WPOS) bar_sync(2, 288);
                    if (c >= 2) mbar_wait(bar, (c / 2 - 1) & 1);
                    if (elect()) {
                        if (c < 2 * WP) { mbar_expect(bar, 81920 / WP); tma2d_ef(sm + C_WV + c * (81920 / WP), c < WP ? &mp.wq : &mp.wk, col0, c % WP * (640 / WP), bar, ef); }
                        if (c >= WOPF && c < WOPF + 3) asm volatile("cp.async.bulk.prefetch.tensor.3d.L2.global [%0, {0, %1, %2}];" :: "l"((uint64_t)&mp.wo), "r"(head * DH + (c - WOPF) * 64), "r"(7 * j) : "memory");
                    }
                    __syncwarp();
                }
                if (elect()) mbar_arrive(sm + CB_W);
                bar_sync(1, 288);
                if (elect()) {
                    mbar_expect(sm + CB_W2, 81920); mbar_expect(sm + CB_W3, 3 * WO_BLK);
#pragma unroll 1
                    for (int c = 0; c < 4; c++) tma2d(sm + C_WV + c * 20480, &mp.wv, col0, c * 160, sm + CB_W2);
#pragma unroll 1
                    for (int c = 0; c < 3; c++) tma3d(sm + C_WO + c * WO_BLK, &mp.wo, head * DH + (j + c) % 3 * 64, 7 * j, sm + CB_W3);
                }
                __syncwarp();
                w_flag_wait(&g_flags.v[head], 2);
                if (elect()) { mbar_expect(sm + CB_VX, 4096); bulk_g2s(sm + C_VX, g_att + head * AT_REC + AT_V + j * 4096, 4096, sm + CB_VX); }
            } else {
                uint32_t mw = 0;
#pragma unroll 1
                for (int c = 0; c < 2; c++) {
                    mbar_wait(sm + (c ? CB_W3 : CB_W2), 0);
                    uint32_t m = 0;
                    const uint32_t end = sm + (c ? C_XR : C_WO);
#pragma unroll 1
                    for (uint32_t a = sm + c * C_WO + (w - (w > 0)) * 4096 + lane * 16; a < end; a += 3 * 4096) {
                        float4 z[8];
#pragma unroll
                        for (int i = 0; i < 8; i++) z[i] = lds128f(a + i * 512);
#pragma unroll
                        for (int i = 0; i < 8; i++) m = amax2(amax2(amax2(amax2(m, __float_as_uint(z[i].x)), __float_as_uint(z[i].y)), __float_as_uint(z[i].z)), __float_as_uint(z[i].w));
                    }
                    mw |= amax_warp(m) << (16 * c);
                }
                asm volatile("st.shared.u32 [%0], %1;" :: "r"(sm + C_KM + w * 4), "r"(mw) : "memory");
                bar_sync(3, 96);
                if (w == 0) asm volatile("st.relaxed.gpu.global.u32 [%0], %1;" :: "l"(g_flags.wmax + blk), "r"(amax2(amax2(mw, lds32(sm + C_KM + 8)), lds32(sm + C_KM + 12)) | 0x8000) : "memory");
            }
        }
        bar_sync(9, 384);
#pragma unroll
        for (int i = 0; i < 5; i++) {
            asm volatile("st.shared.v4.u32 [%0], {%1,%2,%3,%4};" :: "r"(sm + C_MEM + (tid - 256 + i * 128) * 16), "r"(m0[i][0]), "r"(m0[i][1]), "r"(m0[i][2]), "r"(m0[i][3]) : "memory");
            mm = amax2(amax2(amax2(amax2(mm, m0[i][0]), m0[i][1]), m0[i][2]), m0[i][3]);
        }
        asm volatile("st.shared.u32 [%0], %1; st.shared.u32 [%2], 0x3f800000;" :: "r"(sm + C_MX + w * 4), "r"(amax_warp(mm)), "r"(sm + C_UN) : "memory");
        int ew = __shfl_sync(0xffffffffu, lds32(sm + C_LAG), 0), es = 0;
        const uint32_t rb1 = (uint32_t)((j + 1) % 3 - j) << 24, rb2 = (uint32_t)((j + 2) % 3 - j) << 24;
        const float scale = 0.07216878364870322f;
        uint32_t va[8][4], mr = memrd;
#pragma unroll
        for (int i = 0; i < 8; i++) ldsm4t(va[i], sm + C_WV + ((mi >> 1) * 8 + r) * 128 + (((2 * w + (mi & 1)) ^ r) << 4) + i * 2048);
        bar_sync(1, 384);
        for (int s = 0; s < NSEG; s++) {
            const float un = __uint_as_float((127 - es) << 23);
            if (w == 1) {
                mbar_wait(sm + CB_XD, s & 1);
                if (s + 1 < NSEG) { if (elect()) x_fill(mp, sm, s + 1, j); }
                else { if (BPOS != 2) wo_half(mp, sm, blk, 0); if (BPOS != 0) wo_half(mp, sm, blk, 1); }
            }
            const uint32_t l0 = mr >> 4 & 31, r0 = l0 & 7, m0 = l0 >> 3;
            float vd[4];
            {
                uint32_t c[4][4];
#pragma unroll
                for (int i = 0; i < 4; i++) ldsm4t(c[i], mr + i * 512);
                float d[2][4] = {{0, 0, 0, 0}, {0, 0, 0, 0}};
#pragma unroll
                for (int i = 0; i < 8; i++) mma16q(d[i & 1], va[i], c[i >> 1][2 * (i & 1)], c[i >> 1][2 * (i & 1) + 1]);
#pragma unroll
                for (int i = 0; i < 4; i++) vd[i] = d[0][i] + d[1][i];
            }
            uint32_t zr = 0;
            if (w == 2)
                asm volatile("atom.relaxed.gpu.global.exch.b32 %0, [%1], 0;" : "=r"(zr)
                    : "l"(g_acc + ((s & 2) ^ 2) * (ACC_PAIR / 2) + (s & 1) * 512 + (blk >> 2) * 1024 + (blk & 3) * 128 + l0 * 4) : "memory");
            __syncwarp();
            uint32_t kb[4][4];
            {
                const uint32_t k7 = r0 ^ (m0 << 2 & 4), kxrd = sm + C_KX + (16 * (w & 1) + 8 * (m0 & 1) + k7) * 128 + (((m0 >> 1) ^ k7) << 4);
#pragma unroll
                for (int i = 0; i < 4; i++) ldsm4(kb[i], kxrd ^ (i << 5));
            }
            const uint32_t qrd = sm + C_QM + (w == 1 ? (m0 & 1) * 2 + (m0 >> 1) : m0) * 128 + r0 * 16;
            const uint32_t scdst = sm + C_SC + j * 1280 + (w == 1 ? 1024 + l0 * 8 : (w & 1) * 512 + (l0 & 2) * 128 + (l0 >> 2) * 32 + (l0 & 1) * 16);
            const uint32_t scrd = sm + C_SC + (l0 >> 4) * 256 + (l0 & 3) * 32 + (l0 >> 2 & 3) * 8;
            const uint32_t v7 = (4 * (m0 & 1) + (r0 >> 1)) ^ (r0 << 2 & 4), vxrd = sm + C_VX + (16 * (m0 >> 1) + 8 * (r0 & 1) + v7) * 128 + (((2 * w) ^ v7) << 4);
            if (s == 0) {
                uint32_t t[3];
                for (int n = 0;; n++) {
#pragma unroll
                    for (int i = 0; i < 3; i++) t[i] = ld_rlx(g_flags.wmax + l0 + 32 * i);
                    if (__all_sync(0xffffffffu, t[0] && t[1] && t[2])) break;
                    cut(n, 1 << 22);
                }
                const uint32_t m = amax2(amax2(amax2(0, t[0]), t[1]), t[2]);
                const int e = 371 - (int)(__reduce_max_sync(0xffffffffu, m & 0xffffu) >> 7) - (int)(__reduce_max_sync(0xffffffffu, m >> 16) >> 7);
                ew = e << 16 | (min(e - ew, 100) & 0xffff);
            }
            mbar_wait(sm + CB_VX, s & 1);
            uint32_t vb[2][4];
            ldsm4t(vb[0], vxrd); ldsm4t(vb[1], vxrd ^ 16);
            const uint32_t word = sm + C_WO + (m0 & 1) * 4096 + ((m0 >> 1) * 8 + r0) * 64 + ((w ^ (r0 >> 1)) << 4);
            const uint32_t word6 = word + 6 * 4096 - (m0 & 1) * 3072;
            const uint32_t oxrd = sm + C_OX + l0 * 8;
            const uint32_t ord = oxrd + w * 256;
            const uint32_t vp = mr - (C_MEM - C_VP) + w * 512, vmst = mr + (C_VM - C_MEM) + w * 256;
            pin(mr, scdst + rb1, sm + CB_SC + rb1, scdst + rb2, sm + CB_SC + rb2); pin(mr, qrd, scdst, scrd, vp); pin(mr, word, word6, oxrd, ord);
            pin(mr, __float_as_uint(vd[0]), __float_as_uint(vd[1]), __float_as_uint(vd[2]), __float_as_uint(vd[3]));
            bar_sync(2, 384);
            const bool odd = mr & 16;
            float4 y0, y1, mx4;
            {
                uint32_t qa[2][4];
                ldsm4(qa[0], qrd); ldsm4(qa[1], qrd + 512);
                float sc[2][4] = {{0, 0, 0, 0}, {0, 0, 0, 0}};
                if (w == 1) {
                    ldsm4(kb[0], mr + (C_KM - C_MEM)); ldsm4(kb[1], mr + (C_KM - C_MEM) + 512);
                    pin0(mr); y0 = lds128f(vp); y1 = lds128f(vp + 2048); mx4 = lds128f(sm + C_MX);
#pragma unroll
                    for (int k = 0; k < 4; k++) mma16q(sc[k & 1], qa[k >> 1], kb[k >> 1][2 * (k & 1)], kb[k >> 1][2 * (k & 1) + 1]);
                    const uint32_t a0 = __float_as_uint(sc[0][0] + sc[1][2]), a1 = __float_as_uint(sc[0][1] + sc[1][3]);
                    send8(scdst + rb1, sm + CB_SC + rb1, a0, a1); send8(scdst + rb2, sm + CB_SC + rb2, a0, a1);
                    asm volatile("st.shared.v2.u32 [%0], {%1,%2};" :: "r"(scdst), "r"(a0), "r"(a1) : "memory");
                } else {
                    pin0(mr); y0 = lds128f(vp); y1 = lds128f(vp + 2048); mx4 = lds128f(sm + C_MX);
                    if (w) {
#pragma unroll
                        for (int k = 0; k < 4; k++) mma16q(sc[k & 1], kb[k], qa[k >> 1][2 * (k & 1)], qa[k >> 1][2 * (k & 1) + 1]);
                        const float a0 = sc[0][0] + sc[1][0], a1 = sc[0][2] + sc[1][2], a2 = sc[0][1] + sc[1][1], a3 = sc[0][3] + sc[1][3];
                        send16(scdst + rb1, sm + CB_SC + rb1, a0, a1, a2, a3); send16(scdst + rb2, sm + CB_SC + rb2, a0, a1, a2, a3);
                        sts128f(scdst, a0, a1, a2, a3);
                    }
                }
            }
            bar_arrive(7, 384);
            if (elect()) mbar_arrive(sm + CB_SC);
            {
                const float4 z = mx4;
                const int em = (int)(max(max(__float_as_uint(z.x), __float_as_uint(z.y)), max(__float_as_uint(z.z), __float_as_uint(z.w))) >> 7) - es;
                es = __shfl_sync(0xffffffffu, max(min((ew >> 16) - em, (int)(short)ew), -120), 0);
            }
            if (w == 0) PROF(4);
            const uint32_t vm0 = pack2((vd[0] + y0.x + y1.x) * un, (vd[1] + y0.y + y1.y) * un), vm1 = pack2((vd[2] + y0.z + y1.z) * un, (vd[3] + y0.w + y1.w) * un);
            stsm2t(vmst, vm0, vm1);
            if (s + 1 == NSEG) {
                mbar_wait(sm + CB_SC, s & 1);
                PROXY_FENCE();
                bar_sync(3, 128);
                if (w == 1) {
                    w_bulk_s2g(g_att + (s * NH + head) * AT_REC + AT_VM + j * 1024, sm + C_VM, 1024);
                    BULK_COMMIT();
                    BULK_WAIT();
                }
                __syncwarp();
                break;
            }
            cut(s + ar.D2, 0);
            mbar_wait(sm + CB_SC, s & 1);
            if (w == 0) PROF(8);
            float sv[10];
            {
                float2 z[5][3];
#pragma unroll
                for (int u = 0; u < 5; u++)
#pragma unroll
                    for (int p = 0; p < 3; p++) z[u][p] = lds64f((u < 4 ? scrd + (u >> 1) * 512 + (u & 1) * 128 : oxrd + (C_SC - C_OX) + 1024) + p * 1280);
#pragma unroll
                for (int u = 0; u < 5; u++) { sv[2 * u] = (z[u][0].x + z[u][1].x) + z[u][2].x; sv[2 * u + 1] = (z[u][0].y + z[u][1].y) + z[u][2].y; }
            }
            float mx = fmaxf(fmaxf(fmaxf(sv[0], sv[1]), fmaxf(sv[2], sv[3])), fmaxf(fmaxf(fmaxf(sv[4], sv[5]), fmaxf(sv[6], sv[7])), fmaxf(sv[8], sv[9])));
            uint32_t a[NRING][4];
            auto frag = [&](int i) { const int p = i / 7, u = i % 7, o = (p >> 1) * WO_BLK + (p & 1) * 2048;
                                     return u == 3 ? word6 + o : word + o + (u > 3 ? 1024 + (u - 4) * 8192 : u * 8192); };
            mx = fmaxf(fmaxf(mx, __shfl_xor_sync(0xffffffffu, mx, 1)), fmaxf(__shfl_xor_sync(0xffffffffu, mx, 2), __shfl_xor_sync(0xffffffffu, mx, 3)));
            pin(mr, __float_as_uint(mx), 0, 0, 0);
            {
#pragma unroll
                for (int i = 0; i < NPRE; i++) ldsm4t(a[i], frag(i));
                pin0(mr);
                const float sl2e = scale * 1.4426950408889634f, mxl = mx * sl2e;
#pragma unroll
                for (int i = 9; i >= 0; i--) asm volatile("ex2.approx.ftz.f32 %0, %1;" : "=f"(sv[i]) : "f"(fmaf(sv[i], sl2e, -mxl)));
                const uint32_t pq[4] = {pack2(sv[0], sv[1]), pack2(sv[4], sv[5]), pack2(sv[2], sv[3]), pack2(sv[6], sv[7])}, pm = pack2(sv[8], sv[9]);
                if (w == 0) PROF(6);
                float o[2][4] = {{0, 0, 0, 0}, {0, 0, 0, 0}}, o2[2][4] = {{0, 0, 0, 0}, {0, 0, 0, 0}}, sx[4] = {0, 0, 0, 0};
                mma8(sx, pm, 0, 0x3f803f80u); mma8(o[0], pm, 0, vm0); mma8(o[1], pm, 0, vm1);
                mma16q(sx, pq, 0x3f803f80u, 0x3f803f80u);
#pragma unroll
                for (int u = 0; u < 2; u++) { mma16q(o[u], pq, vb[u][0], vb[u][1]); mma16q(o2[u], pq, vb[u][2], vb[u][3]); }
                float inv; asm("rcp.approx.ftz.f32 %0, %1;" : "=f"(inv) : "f"((sx[0] + sx[2]) * __uint_as_float((127 - es) << 23)));
                const uint32_t f0 = pack2((o[0][0] + o2[0][2]) * inv, (o[0][1] + o2[0][3]) * inv), f1 = pack2((o[1][0] + o2[1][2]) * inv, (o[1][1] + o2[1][3]) * inv);
                send8(ord + 2048 + rb1, sm + CB_OX + rb1, f0, f1); send8(ord + 1024 + rb2, sm + CB_OX + rb2, f0, f1);
                asm volatile("st.shared.v2.u32 [%0], {%1,%2};" :: "r"(ord), "r"(f0), "r"(f1) : "memory");
            }
            if (w == 0) PROF(10);
#pragma unroll
            for (int i = NPRE; i < NRING; i++) ldsm4t(a[i], frag(i));
            bar_sync(3, 128);
            float e[5][4];
#pragma unroll
            for (int q = 0; q < 5; q++) e[q][0] = e[q][1] = e[q][2] = e[q][3] = 0.f;
            constexpr int LAG = 2;
            uint8_t* pdst = g_acc + ((s & 2) * (ACC_PAIR / 2) + (s & 1) * 512 + w * 2048 + j * 8192 - C_MEM - sm + mr);
#pragma unroll
            for (int h = 0; h < 3; h++) {
                uint32_t ob[4][2];
                if (h == 1) {
#pragma unroll
                    for (int i = 14 - LAG; i < 14; i++) ldsm4t(a[i % NRING], frag(i + NRING));
                    pin(mr, zr, (uint32_t)(uint64_t)pdst, (uint32_t)((uint64_t)pdst >> 32), 0);
                    mbar_wait(sm + CB_OX, s & 1);
                    if (w == 0) PROF(9);
                }
#pragma unroll
                for (int k = 0; k < 4; k++) lds64(ob[k], oxrd + h * 1024 + k * 256);
#pragma unroll
                for (int i = 14 * h; i < 14 * h + 14; i++) {
                    const int u = i % 7, k = 2 * (i / 7 & 1);
                    if (u == 3) { mma16q(e[3], a[i % NRING], ob[k][0], ob[k][1]); mma16q(e[4], a[i % NRING], ob[k + 1][0], ob[k + 1][1]); }
                    else mma16q(e[u & 3], a[i % NRING], ob[k + (u >> 2)][0], ob[k + (u >> 2)][1]);
                    if (i == B5AT) { pin(mr, a[i % NRING][0], a[i % NRING][1], a[i % NRING][2], a[i % NRING][3]); bar_arrive(5, 384); }
                    if (i >= LAG && !(i >= 14 && i < 14 + LAG) && i - LAG + NRING < 42) ldsm4t(a[(i - LAG) % NRING], frag(i - LAG + NRING));
                }
            }
            {
                const uint32_t w6 = pack2h(e[3][0] + e[4][2], e[3][1] + e[4][3]), one = 0x3c003c00u;
                asm volatile("red.relaxed.gpu.global.add.noftz.v4.f16x2 [%0], {%1,%2,%3,%4};"
                    :: "l"(pdst), "r"(pack2h(e[0][0], e[0][1])), "r"(pack2h(e[0][2], e[0][3])), "r"(pack2h(e[1][0], e[1][1])), "r"(odd ? w6 : one) : "memory");
                asm volatile("red.relaxed.gpu.global.add.noftz.v4.f16x2 [%0], {%1,%2,%3,%4};"
                    :: "l"(pdst + 1024), "r"(pack2h(e[1][2], e[1][3])), "r"(pack2h(e[2][0], e[2][1])), "r"(pack2h(e[2][2], e[2][3])), "r"(odd ? one : w6) : "memory");
            }
            const uint32_t tw = clock();
            if (w == 0) { PROF(14); PROFG(25); }
            PROXY_FENCE();
            bar_sync(6, 160);
            mr = opaque(mr);
            const uint32_t ln = mr >> 4 & 31, due = tw + lds32(sm + C_LAG);
            const uint32_t vr = sm + C_WV + ((ln >> 4) * 8 + (ln & 7)) * 128 + (((2 * w + (ln >> 3 & 1)) ^ (ln & 7)) << 4);
            const uint32_t ms0 = sm + C_MEM + w * 128 + (ln & 7) * 16 + (ln >> 3) * 512, ms1 = ms0 + (ln < 24 ? 2048 : 1536);
            if (BPOS == 2 && w == 0 && s + 2 == NSEG) wo_half(mp, sm, blk, 0);
            if (w == 2) { w_expect(sm + CB_SC, 2560); w_expect(sm + CB_OX, 2048); asm volatile("st.shared.u32 [%0], %1;" :: "r"(sm + C_UN), "r"((127 - es) << 23) : "memory"); }
            if (w == 0) { w_bulk_s2g(g_att + (s * NH + head) * AT_REC + AT_VM + j * 1024, sm + C_VM, 1024); BULK_COMMIT(); }
            const uint8_t* src = pdst - j * 8192;
            pin(mr, ms0, ms1, (uint32_t)(uint64_t)src, (uint32_t)((uint64_t)src >> 32));
            pin(mr, vr, due, 0, 0);
            cut(s + ar.D2, 1);
#pragma unroll
            for (int i = 0; i < 8; i++) ldsm4t(va[i], vr + i * 2048);
            wait_until(due);
            if (w == 0) { PROF(5); PROFG(26); }
            uint4 v[6];
            auto fetch = [&]() {
#pragma unroll
                for (int k = 0; k < 6; k++)
                    asm volatile("ld.relaxed.gpu.global.v4.u32 {%0,%1,%2,%3}, [%4];" : "=r"(v[k].x), "=r"(v[k].y), "=r"(v[k].z), "=r"(v[k].w) : "l"(src + (k >> 1) * 8192 + (k & 1) * 1024) : "memory");
            };
            fetch();
            PROFV(20 + w, 0);
            bar_sync(9, 384);
#pragma unroll 1
            for (int n = 0; __any_sync(0xffffffffu, ~((odd ? v[1].w & v[3].w & v[5].w : v[0].w & v[2].w & v[4].w)) & 0x50005000u); n++) {
                PROFV(20 + w, n + 1);
                cut(n, SPIN_LIMIT);
                fetch();
            }
            uint32_t cv[3][7];
#pragma unroll
            for (int k = 0; k < 3; k++) {
                const uint4 x = v[2 * k], y = v[2 * k + 1];
                const uint32_t u[7] = {x.x, x.y, x.z, y.x, y.y, y.z, k < 2 ? (odd ? x.w : y.w) : 0u};
#pragma unroll
                for (int i = 0; i < 7; i++) cv[k][i] = f16_to_bf16(u[i]);
                stsm4(ms0 + k * 3584, cv[k][0], cv[k][1], cv[k][2], cv[k][3]);
                if (k < 2) stsm4(ms1 + k * 3584, cv[k][4], cv[k][5], cv[k][6], cv[k][6]);
                else asm volatile("stmatrix.sync.aligned.m8n8.x2.shared.b16 [%0], {%1,%2};" :: "r"(ms1 + k * 3584), "r"(cv[k][4]), "r"(cv[k][5]) : "memory");
            }
            if (w == 0) PROF(16);
            bar_sync(1, 384);
            if (w == 0) BULK_WAIT();
            cut(s + ar.D2, 2);
            uint32_t mc = 0;
#pragma unroll
            for (int i = 0; i < 20; i++) mc = amax2(mc, cv[i / 7][i % 7]);
            asm volatile("st.shared.u32 [%0], %1;" :: "r"(sm + C_MX + w * 4), "r"(amax_warp(mc)) : "memory");
        }
        if (w >= 2) end_loads(mp, ar, sm, blk, w - 2);
        else if (w == 1) { bar_sync(5, 384); seg_done(NSEG - 1, head); if (EORD) bar_arrive(6, 96); if (BPOS == 0) wo_half(mp, sm, blk, 1); }
        else bar_arrive(5, 384);
        if (w == 0) {
            const int l = mr >> 4 & 31;
            if (blk < 14) {
                uint4 k = __ldcg((const uint4*)g_key + blk * 32 + l);
#pragma unroll 1
                for (int it = 0; it < 3; it++) {
                    const uint32_t m = __reduce_max_sync(0xffffffffu, max(max(k.x, k.y), max(k.z, k.w)));
                    if (k.x == m) k.x = 0; if (k.y == m) k.y = 0; if (k.z == m) k.z = 0; if (k.w == m) k.w = 0;
                    if (m && l < 20) asm volatile("prefetch.global.L2 [%0];" :: "l"((l < 10 ? g_h2 : g_x1) + (~m & (S_TOK - 1)) * DM + l % 10 * 64));
                }
            }
            mbar_wait(sm + EB_REL, 0);
            flags_release(l);
        }
    }
}

struct SideMaps { CUtensorMap h, wv, ost, o, wo, slab3, slab2, lnp[3]; };
constexpr int SD_ST = 43008, SD_NST = 4, SD_EPI = SD_NST * SD_ST, SD_PAR = SD_EPI + 2 * 24576, SD_BAR = SD_PAR + 6400, SD_SMEM = SD_BAR + 768;
#define VLEAD 16
#define EARLY15 0
#define N_LIGHT 6
#define B_HELP 13
#define AUNR_ 2
constexpr int AUNR = AUNR_;
#define GEMV 1
#define ORS 1
#define KSO 6
#define KSA 3
#define B_8 10
#define B_16 13
__device__ __forceinline__ int o_shift(int b) { return b >= B_16 ? 4 : b >= B_8 ? 3 : 2; }
__device__ __forceinline__ int o_split(int b) { return 1 << o_shift(b); }
__device__ __forceinline__ uint32_t o_done(int b) { return b >= B_LATE ? 160 : 4 << o_shift(b); }
__device__ __forceinline__ int next_item(int lane) {
    const int b0 = lane & 15, hi = lane >> 4;
    for (int n = 0;; n++) {
        const uint32_t w0 = ld_rlx(g_flags.qk + lane), w1 = ld_rlx(g_flags.at + lane), w2 = ld_rlx(&g_flags.c[0][0] + lane), w3 = ld_rlx(&g_flags.c[2][0] + lane), w4 = ld_rlx(&g_flags.seg[0]);
        const uint32_t o01 = __ballot_sync(0xffffffffu, lane && w2 < 32), o23 = __ballot_sync(0xffffffffu, b0 < (hi ? 14 : B_LATE) && w3 < 2u * o_split(b0));
        const uint32_t ra = __ballot_sync(0xffffffffu, w0 >= (hi ? 64u : 96u)), rb = __ballot_sync(0xffffffffu, w1 >= (hi ? o_done(b0) : 64u));
        const int bv = __ffs(o01 | 0x10000) - 1, ba = __ffs(o01 >> 16 | 0x10000) - 1, bo = __ffs(o23 | 0x10000) - 1, bl = __ffs(o23 >> 16 | 0x10000) - 1;
        if (bl == 16 && ba == 16) return -1;
        const int bc = __ffs(~ra | 0x10000) - 1;
        const bool last = ba == 15 && (w4 >= 3 || (EARLY15 && bc == 15));
        const bool r1 = (ra & ra >> 16) >> ba & 1, r2 = (rb & 0xffff) >> bo & 1, r3 = rb >> 16 >> bl & 1;
        const int kind = ba == 16 ? (bo < 16 ? 2 : 3) : last ? 1 :
                         blockIdx.x < N_LIGHT ? (r1 ? 1 : r3 ? 3 : bv < 16 ? 0 : -1) :
                         bv < 16 && (bv <= bc + VLEAD || !r2) ? 0 : r1 && ba >= B_HELP ? 1 : r2 ? 2 : r1 ? 1 : r3 ? 3 : bo < ba ? 2 : -1;
        if (kind < 0) { if (n > (1 << 20)) __trap(); __nanosleep(300); continue; }
        const int b = kind == 3 ? bl : kind == 2 ? bo : kind == 1 ? ba : bv;
        uint32_t i = 0;
        if (lane == 0) asm volatile("atom.relaxed.gpu.global.add.u32 %0, [%1], 1;" : "=r"(i) : "l"(&g_flags.c[kind][b]) : "memory");
        i = __shfl_sync(0xffffffffu, i, 0);
        if (i < (kind < 2 ? 32u : 2u * o_split(b))) return kind << 16 | b << 8 | i | ((kind == 1 ? r1 : kind == 2 ? r2 : r3) ? 128 : 0);
    }
}

template <int NP, int CH>
__device__ __forceinline__ void tile_out(const float (&acc)[8 * NP], uint32_t eb, uint32_t efull, uint32_t eempty, int& eph, int lane) {
    const int r = lane & 7, mi = lane >> 3, row = (mi & 1) * 8 + r;
    mbar_wait(eempty, eph); eph ^= 1;
#pragma unroll
    for (int p = 0; p < NP; p++) {
        const int oc = 2 * p + (mi >> 1);
        stsm4(eb + (oc >> 3) * CH + row * 128 + (((oc & 7) ^ r) << 4), pack2(acc[8 * p], acc[8 * p + 1]), pack2(acc[8 * p + 2], acc[8 * p + 3]),
              pack2(acc[8 * p + 4], acc[8 * p + 5]), pack2(acc[8 * p + 6], acc[8 * p + 7]));
    }
    asm volatile("fence.proxy.async.shared::cta;" ::: "memory");
    __syncwarp();
    if (lane == 0) mbar_arrive(efull);
}

template <int MT>
__device__ __forceinline__ void attn_tile(uint32_t base, uint32_t dst, uint32_t eempty, int eph, int lane) {
    constexpr int NK = MT ? 5 : 3;
    const int r = lane & 7, mi = lane >> 3, g = lane >> 2, t = lane & 3;
    float sc[NK][4];
#pragma unroll
    for (int n = 0; n < NK; n++) sc[n][0] = sc[n][1] = sc[n][2] = sc[n][3] = 0.f;
#pragma unroll AUNR
    for (int k2 = 0; k2 < 6; k2++) {
        const uint32_t cb = (k2 >> 1) * 8192, c0 = (k2 & 1) * 4;
        uint32_t a0[4], a1[4], bb[NK][4];
        ldsm4(a0, base + cb + (16 * MT + (mi & 1) * 8 + r) * 128 + (((c0 + (mi >> 1)) ^ r) << 4));
        ldsm4(a1, base + cb + (16 * MT + (mi & 1) * 8 + r) * 128 + (((c0 + 2 + (mi >> 1)) ^ r) << 4));
#pragma unroll
        for (int n = 0; n < NK; n++)
            ldsm4(bb[n], n < NK - 1 ? base + 4096 + cb + (8 * n + r) * 128 + (((c0 + mi) ^ r) << 4) : base + 36864 + k2 * 512 + lane * 16);
#pragma unroll
        for (int n = 0; n < NK; n++) mma16(sc[n], a0[0], a0[1], a0[2], a0[3], bb[n][0], bb[n][1]);
#pragma unroll
        for (int n = 0; n < NK; n++) mma16(sc[n], a1[0], a1[1], a1[2], a1[3], bb[n][2], bb[n][3]);
    }
    const float scale = 0.07216878364870322f, l2e = 1.4426950408889634f;
    float v[2][2 * NK], mx[2], sum[2];
#pragma unroll
    for (int hf = 0; hf < 2; hf++) {
        mx[hf] = -INFINITY;
#pragma unroll
        for (int n = 0; n < NK; n++) {
            uint32_t u = pack2(sc[n][2 * hf], sc[n][2 * hf + 1]);
            u = pack2(lo_f(u) * scale, hi_f(u) * scale);
            const int lim = 16 * MT + 8 * hf + g - 8 * n - 2 * t;
            v[hf][2 * n] = (n < NK - 1 && lim < 0) ? -1e9f : lo_f(u);
            v[hf][2 * n + 1] = (n < NK - 1 && lim < 1) ? -1e9f : hi_f(u);
            mx[hf] = fmaxf(mx[hf], fmaxf(v[hf][2 * n], v[hf][2 * n + 1]));
        }
    }
#pragma unroll
    for (int o = 1; o < 4; o <<= 1)
#pragma unroll
        for (int hf = 0; hf < 2; hf++) mx[hf] = fmaxf(mx[hf], __shfl_xor_sync(0xffffffffu, mx[hf], o));
#pragma unroll
    for (int hf = 0; hf < 2; hf++) {
        sum[hf] = 0;
#pragma unroll
        for (int q = 0; q < 2 * NK; q++) { asm("ex2.approx.ftz.f32 %0, %1;" : "=f"(v[hf][q]) : "f"((v[hf][q] - mx[hf]) * l2e)); sum[hf] += v[hf][q]; }
    }
#pragma unroll
    for (int o = 1; o < 4; o <<= 1)
#pragma unroll
        for (int hf = 0; hf < 2; hf++) sum[hf] += __shfl_xor_sync(0xffffffffu, sum[hf], o);
    uint32_t pa[NK][2];
#pragma unroll
    for (int hf = 0; hf < 2; hf++) {
        const float inv = __fdividef(1.f, sum[hf]);
#pragma unroll
        for (int n = 0; n < NK; n++) pa[n][hf] = pack2(v[hf][2 * n] * inv, v[hf][2 * n + 1] * inv);
    }
    mbar_wait(eempty, eph);
#pragma unroll AUNR
    for (int n4 = 0; n4 < 6; n4++) {
        const uint32_t cb = (n4 >> 1) * 4096, c0 = (n4 & 1) * 4;
        uint32_t bm[4], bb[2 + 2 * MT][4];
        ldsm4t(bm, base + AT_VM + n4 * 512 + lane * 16);
#pragma unroll
        for (int u = 0; u < 2 + 2 * MT; u++) ldsm4t(bb[u], base + AT_V + cb + (16 * (u >> 1) + 8 * (mi & 1) + r) * 128 + (((c0 + 2 * (u & 1) + (mi >> 1)) ^ r) << 4));
        float o[4][4];
#pragma unroll
        for (int u = 0; u < 4; u++) { o[u][0] = o[u][1] = o[u][2] = o[u][3] = 0.f; mma8(o[u], pa[NK - 1][0], pa[NK - 1][1], bm[u]); }
#pragma unroll
        for (int u = 0; u < 4 + 4 * MT; u++) mma16(o[u & 3], pa[u >> 2 << 1][0], pa[u >> 2 << 1][1], pa[(u >> 2 << 1) + 1][0], pa[(u >> 2 << 1) + 1][1], bb[u >> 1][2 * (u & 1)], bb[u >> 1][2 * (u & 1) + 1]);
#pragma unroll
        for (int p = 0; p < 2; p++)
            stsm4(dst + (n4 >> 1) * 2048 + ((mi & 1) * 8 + r) * 128 + (((c0 + 2 * p + (mi >> 1)) ^ r) << 4), pack2(o[2 * p][0], o[2 * p][1]), pack2(o[2 * p][2], o[2 * p][3]),
                  pack2(o[2 * p + 1][0], o[2 * p + 1][1]), pack2(o[2 * p + 1][2], o[2 * p + 1][3]));
    }
}

__device__ __forceinline__ uint32_t ln_row(const uint32_t (&as)[10], const uint2 (&xin)[5], int row, uint32_t par, uint32_t low, bf16* out, uint64_t ef, int lane) {
    const uint32_t pa = par + lane * 8;
    uint32_t xv[10], hv[10], sv[10], tv[10];
#pragma unroll
    for (int q = 0; q < 5; q++) {
        uint32_t ga[2], t[2], u[2];
        lds64(ga, pa + q * 256); lds64(t, pa + 1280 + q * 256); lds64(u, pa + 2560 + q * 256);
#pragma unroll
        for (int e = 0; e < 2; e++) {
            xv[2 * q + e] = add2(e ? xin[q].y : xin[q].x, mul2(ga[e], as[2 * q + e]));
            tv[2 * q + e] = t[e]; sv[2 * q + e] = u[e];
        }
    }
    ln_mod(xv, sv, tv, hv);
    float rs = 0;
#pragma unroll
    for (int q = 0; q < 5; q++) {
        const int c = row * DM + lane * 4 + q * 128;
        const uint32_t h0 = hv[2 * q], h1 = hv[2 * q + 1];
        uint32_t gb[2], wv[2];
        lds64(gb, pa + 3840 + q * 256); lds64(wv, pa + 5120 + q * 256);
        rs += (lo_f(h0) * lo_f(wv[0]) + hi_f(h0) * hi_f(wv[0])) + (lo_f(h1) * lo_f(wv[1]) + hi_f(h1) * hi_f(wv[1]));
        st_ef(out + c, make_uint2(add2(xv[2 * q], mul2(gb[0], h0)), add2(xv[2 * q + 1], mul2(gb[1], h1))), ef);
    }
    const uint32_t rb = pack2(0.f, warp_sum(rs));
    const uint32_t key = (((int)rb < 0 ? ~rb : rb | 0x80000000u) & 0xffff0000u) | (uint32_t)(2 * S_TOK - 1 - row);
    if (key > low) {
#pragma unroll
        for (int q = 0; q < 5; q++) {
            *(uint2*)(g_x1 + row * DM + lane * 4 + q * 128) = make_uint2(xv[2 * q], xv[2 * q + 1]);
            *(uint2*)(g_h2 + row * DM + lane * 4 + q * 128) = make_uint2(hv[2 * q], hv[2 * q + 1]);
        }
    }
    return key;
}
__device__ __forceinline__ void key_out(uint32_t key) {
    __syncwarp();
    if (key) asm volatile("st.release.gpu.global.u32 [%0], %1;" :: "l"(g_key + (~key & (S_TOK - 1))), "r"(key) : "memory");
}

__global__ void __launch_bounds__(384, 1) k_side(const __grid_constant__ SideMaps mp, const bf16* __restrict__ x, const bf16* __restrict__ wr, const bf16* wmod, const bf16* cvec, bf16* __restrict__ out) {
    extern __shared__ __align__(1024) uint8_t smraw[];
    const uint32_t sm = smem_u32(smraw);
    if (sm & 1023) __trap();
    const uint32_t FULL = sm + SD_BAR, EMPTY = FULL + 32, EFULL = FULL + 64, EEMPTY = FULL + 80, IFULL = FULL + 96, IEMPTY = FULL + 128, IQ = FULL + 160, SCHED = FULL + 176, PARAM = FULL + 184, ADONE = FULL + 192, LOW = FULL + 224, KEYS = FULL + 256;
    const int tid = threadIdx.x, warp = __shfl_sync(0xffffffffu, tid >> 5, 0), lane = tid & 31;
    const uint64_t ef = policy_stream();
    if (tid == 0) {
        for (int i = 0; i < SD_NST; i++) { mbar_init(FULL + 8 * i, 1); mbar_init(EMPTY + 8 * i, 2); }
        for (int i = 0; i < 2; i++) { mbar_init(EFULL + 8 * i, 4); mbar_init(EEMPTY + 8 * i, 1); }
        for (int i = 0; i < 4; i++) { mbar_init(IFULL + 8 * i, 1); mbar_init(IEMPTY + 8 * i, 11); }
        mbar_init(SCHED, 1); mbar_init(PARAM, 1);
        sts128f(ADONE, 0, 0, 0, 0); sts128f(ADONE + 16, 0, 0, 0, 0); sts128f(LOW, 0, 0, 0, 0);
        asm volatile("fence.mbarrier_init.release.cluster;" ::: "memory");
    }
    if (SDEL) __nanosleep(SDEL);
    __syncthreads();
    if (warp >= 8) {
      asm volatile("setmaxnreg.dec.sync.aligned.u32 40;");
      if (warp == 8) {
        int st = 0, ph = 1;
        for (int q = 0;; q++) {
            mbar_wait(IFULL + 8 * (q & 3), (q >> 2) & 1);
            const int it = __shfl_sync(0xffffffffu, lds32(IQ + 4 * (q & 3)), 0);
            if (elect()) mbar_arrive(IEMPTY + 8 * (q & 3));
            if (it < 0) break;
            const int kind = it >> 16, b = (it >> 8) & 255, i = it & 63;
            const int nst = kind == 0 ? 10 : kind == 1 ? 4 : kind == 2 ? 192 >> o_shift(b) : b == 14 ? 4 : 2;
            const int ksched = kind == 0 ? 4 : kind == 2 ? nst - KSO : (it & 128) ? -1 : kind == 1 ? KSA : 0;
            if (ksched < 0 && elect()) mbar_arrive(SCHED);
            const bool look = !(it & 128);
            if (look && kind == 1) flag_wait(&g_flags.v[b * 32 + i], 2);
            if (look && kind == 3 && b < 14) flag_wait(&g_flags.o[b], o_done(b));
            for (int kb = 0; kb < nst; kb++) {
                mbar_wait(EMPTY + 8 * st, ph);
                const uint32_t base = sm + st * SD_ST, fb = FULL + 8 * st;
                if (look && kind == 1) flag_wait(&g_flags.seg[kb * 32 + i], 3);
                if (kb == ksched && elect()) mbar_arrive(SCHED);
                if (kind == 0) {
                    if (q == 0 && kb == 0) {
                        if (elect()) {
#pragma unroll 1
                            for (int c = 0; c < SD_NST; c++) tma3d(sm + c * SD_ST + 16384, &mp.wv, c * 64, i * 3, FULL + 8 * c);
#pragma unroll 1
                            for (int c = SD_NST; c < SPF; c++)
                                asm volatile("cp.async.bulk.prefetch.tensor.3d.L2.global [%0, {0, %1, %2}];" :: "l"((uint64_t)&mp.wv), "r"(c * 64), "r"(i * 3) : "memory");
                        }
                        flag_wait(&g_flags.h, 96);
                    }
                    if (elect()) {
                        mbar_expect(fb, 40960);
                        tma2d(base, &mp.h, kb * 64, b * 128, fb);
                        if (q || kb >= SD_NST) tma3d(base + 16384, &mp.wv, kb * 64, i * 3, fb);
                    }
                } else if (kind == 1) {
                    if (elect()) {
                        mbar_expect(fb, 43008);
                        asm volatile("cp.async.bulk.shared::cluster.global.mbarrier::complete_tx::bytes.L2::cache_hint [%0], [%1], %2, [%3], %4;"
                            :: "r"(base), "l"(g_att + ((b * 4 + kb) * NH + i) * AT_REC), "r"(AT_REC), "r"(fb), "l"(ef) : "memory");
                    }
                } else if (kind == 3) {
                    if (b == 14 && !(kb & 1)) flag_wait(&g_flags.fin[(kb + (i >> 4)) * 32], 80);
                    if (elect()) { mbar_expect(fb, 40960); tma3d_ef(base, &mp.lnp[o_shift(b) - 2], i * (160 >> o_shift(b)), b * KSPLIT + (kb << o_shift(b) >> 1), fb, ef); }
                } else {
                    const int k0 = ((i >> 1) * nst + kb) * 32;
                    if (elect()) { mbar_expect(fb, 28672); tma3d(base + 8192, &mp.wo, k0, (i & 1) * 5, fb); }
                    if (look && kb % 12 == 0) flag_wait(&g_flags.pair[b * 16 + k0 / 384], 4);
                    if (elect()) tma2d_ef(base, &mp.o, k0, b * 128, fb, ef);
                }
                __syncwarp();
                if (++st == SD_NST) { st = 0; ph ^= 1; }
            }
        }
      } else if (warp == 11) {
        bool fin = false, par = false;
        for (int q = 0;; q++) {
            if (q) mbar_wait(SCHED, (q - 1) & 1);
            int it = fin ? -1 : q == 0 && blockIdx.x < 32 ? (int)blockIdx.x : next_item(lane);
            if (it < 0 && !fin && blockIdx.x < 32) { it = 3 << 16 | 14 << 8 | blockIdx.x; fin = true; }
            if (lane == 0) {
                if (it >> 16 == 3) {
                    const int b = (it >> 8) & 255, nr = 64 >> o_shift(b);
                    asm volatile("cp.async.bulk.prefetch.L2.global [%0], %1;" :: "l"(x + (b * 128 + (it & 63) * nr) * DM), "r"(nr * DM * 2) : "memory");
                }
                mbar_wait(IEMPTY + 8 * (q & 3), ((q >> 2) & 1) ^ 1);
                asm volatile("st.shared.u32 [%0], %1;" :: "r"(IQ + 4 * (q & 3)), "r"(it) : "memory");
                mbar_arrive(IFULL + 8 * (q & 3));
            }
            if (it >> 16 >= 2 && (it >> 8 & 255) >= 2) {
                const uint4* kp = (const uint4*)g_key + max((it >> 8 & 255) - ((it >> 16) == 2 ? 5 : 3), 0) * 32 + lane;
                const uint4 k1 = __ldcg(kp), k2 = __ldcg(kp + 32);
                uint32_t m = max(max(max(k1.x, k1.y), max(k1.z, k1.w)), max(max(k2.x, k2.y), max(k2.z, k2.w)));
                m = max(m, __shfl_xor_sync(0xffffffffu, m, 1)); m = max(m, __shfl_xor_sync(0xffffffffu, m, 2));
                asm volatile("red.shared.max.u32 [%0], %1;" :: "r"(LOW), "r"(__reduce_min_sync(0xffffffffu, m)) : "memory");
            }
            if (!par && it >> 16 == 3) {
                par = true;
                                if (lane == 0) { mbar_expect(PARAM, 6400); bulk_g2s(sm + SD_PAR, g_mod + 2 * DM, 5120, PARAM); bulk_g2s(sm + SD_PAR + 5120, wr, 1280, PARAM); }
            }
            __syncwarp();
            if (it < 0) break;
        }
        flags_release(lane);
      } else {
        if (lane == 0) {
            const int wg = warp - 9; int ph = 0;
            for (int q = 0;; q++) {
                mbar_wait(IFULL + 8 * (q & 3), (q >> 2) & 1);
                const int it = lds32(IQ + 4 * (q & 3));
                mbar_arrive(IEMPTY + 8 * (q & 3));
                if (it < 0) break;
                const int kind = it >> 16, b = (it >> 8) & 255, i = it & 63;
                if (kind == 3 && b == 14) continue;
                if (kind & 1) {
                    for (int n = 0;; n++) {
                        uint32_t d0, d1, d2, d3;
                        asm volatile("ld.volatile.shared.v4.u32 {%0,%1,%2,%3}, [%4];" : "=r"(d0), "=r"(d1), "=r"(d2), "=r"(d3) : "r"(ADONE + wg * 16) : "memory");
                        if (min(min(d0, d1), min(d2, d3)) > q) break;
                        if (n > (1 << 24)) __trap();
                        __nanosleep(40);
                    }
                    GPU_FENCE();
                    if (kind == 1) { bump(b == 15 ? &g_flags.half[(i & 30) + wg] : &g_flags.pair[b * 16 + (i >> 1)]); bump(&g_flags.at[b]); }
                    else {
#pragma unroll 1
                        for (int c = 0; c < 8; c++) { const uint32_t key = lds32(KEYS + (q & 7) * 64 + wg * 32 + c * 4); if (key) asm volatile("st.relaxed.gpu.global.u32 [%0], %1;" :: "l"(g_key + (~key & (S_TOK - 1))), "r"(key) : "memory"); }
                    }
                    continue;
                }
#pragma unroll 1
                for (int rd = 0; rd < (kind == 2 ? 2 : 1); rd++) {
                    mbar_wait(EFULL + 8 * wg, ph); ph ^= 1;
                    const uint32_t src = sm + SD_EPI + wg * 24576;
                    if (kind == 2) tma3d_store(rd ? &mp.slab2 : &mp.slab3, (b * KSPLIT + (i >> 1)) * 128 + wg * 64, (i & 1) * 5 + rd * 3, src, ef, false);
                    else {
                        uint8_t* dst = g_att + ((b * 4 + wg * 2) * NH + i) * AT_REC + AT_V;
                        asm volatile("cp.async.bulk.global.shared::cta.bulk_group.L2::cache_hint [%0], [%1], 12288, %2;" :: "l"(dst), "r"(src), "l"(ef) : "memory");
                        asm volatile("cp.async.bulk.global.shared::cta.bulk_group.L2::cache_hint [%0], [%1], 12288, %2;" :: "l"(dst + NH * AT_REC), "r"(src + 12288), "l"(ef) : "memory");
                    }
                    asm volatile("cp.async.bulk.commit_group;" ::: "memory");
                    asm volatile("cp.async.bulk.wait_group.read 0;" ::: "memory");
                    mbar_arrive(EEMPTY + 8 * wg);
                }
                asm volatile("cp.async.bulk.wait_group 0;" ::: "memory");
                GPU_FENCE();
                bump(kind == 0 ? &g_flags.v[b * 32 + i] : &g_flags.o[b]);
                if (kind == 0) bump(&g_flags.vb[b]);
            }
        }
      }
    } else {
        asm volatile("setmaxnreg.inc.sync.aligned.u32 232;");
        const int wg = warp >> 2, w = warp & 3;
        int st = 0, ph = 0, eph = 1;
        bool att = false;
        if (blockIdx.x < 32 * GEMV) {
            const uint32_t buf = sm + SD_EPI;
#pragma unroll 1
            for (int k = tid; k < DM; k += 256) {
                const float f = __uint_as_float((uint32_t)__ldg((const unsigned short*)cvec + k) << 16);
                asm volatile("st.shared.f32 [%0], %1;" :: "r"(buf + k * 4), "f"(bfr(__fdividef(f, 1.f + __expf(-f)))) : "memory");
            }
            const int t = min(tid, 199), k0 = t / 10 * 32;
            const bf16* wm = wmod + k0 * (6 * DM) + 2 * DM + blockIdx.x * 80 + t % 10 * 8;
            float a[8] = {0, 0, 0, 0, 0, 0, 0, 0};
#pragma unroll 1
            for (int k = 0; k < 32; k += 8) {
                uint4 z[8];
#pragma unroll
                for (int e = 0; e < 8; e++) z[e] = __ldcs((const uint4*)(wm + (k + e) * (6 * DM)));
                if (k == 0) bar_sync(1, 256);
#pragma unroll
                for (int e = 0; e < 8; e++) {
                    const float f = __uint_as_float(lds32(buf + (k0 + k + e) * 4));
                    a[0] += f * lo_f(z[e].x); a[1] += f * hi_f(z[e].x); a[2] += f * lo_f(z[e].y); a[3] += f * hi_f(z[e].y);
                    a[4] += f * lo_f(z[e].z); a[5] += f * hi_f(z[e].z); a[6] += f * lo_f(z[e].w); a[7] += f * hi_f(z[e].w);
                }
            }
            sts128f(buf + 4096 + t * 32, a[0], a[1], a[2], a[3]); sts128f(buf + 4112 + t * 32, a[4], a[5], a[6], a[7]);
            bar_sync(1, 256);
            if (tid < 40) {
                float a0 = 0, a1 = 0;
#pragma unroll 4
                for (int g = 0; g < 20; g++) { const float2 v = lds64f(buf + 4096 + g * 320 + tid * 8); a0 += v.x; a1 += v.y; }
                ((uint32_t*)(g_mod + 2 * DM + blockIdx.x * 80))[tid] = pack2(a0, a1);
            }
            bar_sync(1, 256);
        }
        const uint32_t eb = sm + SD_EPI + wg * 24576;
        for (int q = 0;; q++) {
            mbar_wait(IFULL + 8 * (q & 3), (q >> 2) & 1);
            const int itc = lds32(IQ + 4 * (q & 3));
            __syncwarp();
            if (lane == 0) mbar_arrive(IEMPTY + 8 * (q & 3));
            if (itc < 0) break;
            const int kind = itc >> 16, b = (itc >> 8) & 255, i = itc & 63;
            if (att && kind != 1) { bar_sync(1, 256); att = false; }
            if (kind == 0) {
                float acc[96];
#pragma unroll
                for (int n = 0; n < 96; n++) acc[n] = 0.f;
                int prev = -1;
#pragma unroll 1
                for (int kb = 0; kb < 10; kb++) {
                    mbar_wait(FULL + 8 * st, ph);
                    const uint32_t base = sm + st * SD_ST;
                    WG_FENCE();
#pragma unroll
                    for (int ks = 0; ks < 4; ks++)
                        wgmma_ss_n192_tb(acc, mkdesc(base + wg * 8192 + ks * 32, 16, 1024), mkdesc(base + 16384 + ks * 2048, 8192, 1024), (kb | ks) != 0);
                    WG_COMMIT();
                    WG_WAIT(1);
                    if (prev >= 0 && (tid & 127) == 0) mbar_arrive(EMPTY + 8 * prev);
                    prev = st;
                    if (++st == SD_NST) { st = 0; ph ^= 1; }
                }
                WG_WAIT(0);
                if ((tid & 127) == 0) mbar_arrive(EMPTY + 8 * prev);
                tile_out<12, 4096>(acc, eb + (w >> 1) * 12288 + (w & 1) * 2048, EFULL + 8 * wg, EEMPTY + 8 * wg, eph, lane);
            } else if (kind == 1) {
                const int seg = warp >> 1, mt = warp & 1;
                int sst = st + seg, sph = ph; if (sst >= SD_NST) { sst -= SD_NST; sph ^= 1; }
                ph ^= 1;
                mbar_wait(FULL + 8 * sst, sph);
                const uint32_t base = sm + sst * SD_ST;
                if (mt) attn_tile<1>(base, eb + w * 6144, EEMPTY + 8 * wg, eph, lane);
                else attn_tile<0>(base, eb + w * 6144, EEMPTY + 8 * wg, eph, lane);
                asm volatile("fence.proxy.async.shared::cta;" ::: "memory");
                __syncwarp();
                if (lane == 0) {
                    mbar_arrive(EMPTY + 8 * sst);
                    tma3d_store(&mp.ost, b * 128 + warp * 16, i * 3, eb + w * 6144, ef, false);
                    BULK_COMMIT(); BULK_WAIT();
                    asm volatile("st.release.cta.shared.u32 [%0], %1;" :: "r"(ADONE + warp * 4), "r"(q + 1) : "memory");
                }
                __syncwarp();
                att = true;
            } else if (kind == 2) {
                float acc[96], acc2[64];
#pragma unroll
                for (int n = 0; n < 96; n++) acc[n] = 0.f;
#pragma unroll
                for (int n = 0; n < 64; n++) acc2[n] = 0.f;
                int prev = -1;
                const uint32_t ao = (wg * 64 + w * 16 + (lane & 15)) * 64 + (((lane >> 4) ^ (lane >> 1 & 3)) << 4);
#pragma unroll 1
                for (int kb = 96 >> o_shift(b); kb > 0; kb--) {
#pragma unroll
                    for (int u = 0; u < 2; u++) {
                        const uint32_t base = sm + st * SD_ST;
                        uint32_t af[2][4];
                        mbar_wait(FULL + 8 * st, ph);
                        ldsm4(af[0], base + ao); ldsm4(af[1], base + (ao ^ 32));
                        WG_FENCE();
#pragma unroll
                        for (int ks = 0; ks < 2; ks++) {
                            wgmma_rs_n192_tb(acc, af[ks], mkdesc(base + 8192 + ks * 2048, 4096, 1024), 1);
                            wgmma_rs_n128_tb(acc2, af[ks], mkdesc(base + 8192 + 3 * 4096 + ks * 2048, 4096, 1024), 1);
                        }
                        WG_COMMIT();
                        WG_WAIT(1);
                        if (prev >= 0 && (tid & 127) == 0) mbar_arrive(EMPTY + 8 * prev);
                        prev = st;
                        if (++st == SD_NST) { st = 0; ph ^= 1; }
                    }
                }
                WG_WAIT(0);
                if ((tid & 127) == 0) mbar_arrive(EMPTY + 8 * prev);
                tile_out<12, 8192>(acc, eb + w * 2048, EFULL + 8 * wg, EEMPTY + 8 * wg, eph, lane);
                tile_out<8, 8192>(acc2, eb + w * 2048, EFULL + 8 * wg, EEMPTY + 8 * wg, eph, lane);
            } else {
                const int sh = o_shift(b), nr = 64 >> sh, fw = b == 14 ? wg : 0, row0 = (b + fw) * 128 + i * nr, lw = warp - 4 * fw;
                if (fw) { st += 2; if (st >= SD_NST) { st -= SD_NST; ph ^= 1; } }
                int st1 = st + 1, ph1 = ph; if (st1 == SD_NST) { st1 = 0; ph1 ^= 1; }
                uint2 xin[2][5];
                uint32_t as[2][10] = {};
#pragma unroll
                for (int q2 = 0; q2 < 10; q2++) xin[q2 & 1][q2 >> 1] = ld_ef(x + (row0 + ((warp + 8 * (q2 & 1)) & (nr - 1))) * DM + lane * 4 + (q2 >> 1) * 128, ef);
                mbar_wait(PARAM, 0); mbar_wait(FULL + 8 * st, ph); mbar_wait(FULL + 8 * st1, ph1);
#pragma unroll 1
                for (int lrow = lw + (nr & 16) / 2; lrow >= 0 && lrow < nr; lrow -= 8) {
                    float a[20];
#pragma unroll
                    for (int q2 = 0; q2 < 20; q2++) a[q2] = 0.f;
#pragma unroll 1
                    for (int k = 0; k < (1 << sh >> 1); k++) {
                        const uint32_t ad = sm + ((k << (6 - sh)) + lrow) * 1280 + lane * 8;
                        uint32_t z[10][2];
#pragma unroll
                        for (int q2 = 0; q2 < 10; q2++) lds64(z[q2], ad + (q2 < 5 ? st : st1) * SD_ST + q2 % 5 * 256);
#pragma unroll
                        for (int q2 = 0; q2 < 10; q2++) { float* p = a + q2 % 5 * 4; p[0] += lo_f(z[q2][0]); p[1] += hi_f(z[q2][0]); p[2] += lo_f(z[q2][1]); p[3] += hi_f(z[q2][1]); }
                    }
#pragma unroll
                    for (int q2 = 0; q2 < 10; q2++) { as[1][q2] = as[0][q2]; as[0][q2] = pack2(a[2 * q2], a[2 * q2 + 1]); }
                }
                bar_sync(2 + wg, 128);
                if ((tid & 127) == 0) { mbar_arrive(EMPTY + 8 * st); mbar_arrive(EMPTY + 8 * st1); }
                uint32_t key = 0;
#pragma unroll 1
                for (int lrow = lw; lrow < nr; lrow += 8) {
                    const int row = row0 + lrow;
                    const uint32_t k1 = ln_row(as[0], xin[0], row, sm + SD_PAR, lds32(LOW), out, ef, lane);
                    if (lane == lrow >> 3) key = k1;
#pragma unroll
                    for (int q2 = 0; q2 < 5; q2++) { as[0][2 * q2] = as[1][2 * q2]; as[0][2 * q2 + 1] = as[1][2 * q2 + 1]; xin[0][q2] = xin[1][q2]; }
                }
                if (b == 14) key_out(key);
                else {
                    if (lane < 2) asm volatile("st.shared.u32 [%0], %1;" :: "r"(KEYS + (q & 7) * 64 + warp * 8 + lane * 4), "r"(key) : "memory");
                    __syncwarp();
                    if (lane == 0) asm volatile("st.release.cta.shared.u32 [%0], %1;" :: "r"(ADONE + warp * 4), "r"(q + 1) : "memory");
                }
                st = st1 + 1; ph = ph1; if (st == SD_NST) { st = 0; ph ^= 1; }
            }
        }
    }
    __syncwarp();
    asm volatile("griddepcontrol.wait;" ::: "memory");
}

#define P_D1 550
#define P_DL 700
#define P_DG 29
typedef CUresult (*EncodeFn)(CUtensorMap*, CUtensorMapDataType, cuuint32_t, void*, const cuuint64_t*, const cuuint64_t*, const cuuint32_t*, const cuuint32_t*,
                             CUtensorMapInterleave, CUtensorMapSwizzle, CUtensorMapL2promotion, CUtensorMapFloatOOBfill);
static EncodeFn s_encode = nullptr;
static void make_map(CUtensorMap* m, const void* p, int rows, int cols, int box_rows, int box_cols = 64) {
    cuuint64_t dims[2] = {(cuuint64_t)cols, (cuuint64_t)rows}, strides[1] = {(cuuint64_t)cols * 2};
    cuuint32_t box[2] = {(cuuint32_t)box_cols, (cuuint32_t)box_rows}, es[2] = {1, 1};
    s_encode(m, CU_TENSOR_MAP_DATA_TYPE_BFLOAT16, 2, (void*)p, dims, strides, box, es, CU_TENSOR_MAP_INTERLEAVE_NONE,
             box_cols == 64 ? CU_TENSOR_MAP_SWIZZLE_128B : box_cols == 32 ? CU_TENSOR_MAP_SWIZZLE_64B : CU_TENSOR_MAP_SWIZZLE_NONE, CU_TENSOR_MAP_L2_PROMOTION_L2_256B, CU_TENSOR_MAP_FLOAT_OOB_FILL_NONE);
}
static void make_map3(CUtensorMap* m, const void* p, int rows, int cols, int box_rows, int box_chunks, int cw = 64) {
    cuuint64_t dims[3] = {(cuuint64_t)cw, (cuuint64_t)rows, (cuuint64_t)(cols / cw)}, strides[2] = {(cuuint64_t)cols * 2, (cuuint64_t)cw * 2};
    cuuint32_t box[3] = {(cuuint32_t)cw, (cuuint32_t)box_rows, (cuuint32_t)box_chunks}, es[3] = {1, 1, 1};
    s_encode(m, CU_TENSOR_MAP_DATA_TYPE_BFLOAT16, 3, (void*)p, dims, strides, box, es, CU_TENSOR_MAP_INTERLEAVE_NONE,
             cw == 64 ? CU_TENSOR_MAP_SWIZZLE_128B : CU_TENSOR_MAP_SWIZZLE_64B, CU_TENSOR_MAP_L2_PROMOTION_L2_256B, CU_TENSOR_MAP_FLOAT_OOB_FILL_NONE);
}
template <typename T> static void* sym(T& s) { void* p = nullptr; cudaGetSymbolAddress(&p, s); return p; }

extern "C" void kernel_launch(void* const* d_in, const int* in_sizes, int n_in, void* d_out, int out_size) {
    const bf16 *x = (const bf16*)d_in[0], *mem0 = (const bf16*)d_in[1], *Wq = (const bf16*)d_in[2], *Wk = (const bf16*)d_in[3],
               *Wv = (const bf16*)d_in[4], *Wo = (const bf16*)d_in[5], *wr = (const bf16*)d_in[8], *wgate = (const bf16*)d_in[9],
               *wup = (const bf16*)d_in[10], *wdown = (const bf16*)d_in[11], *c = (const bf16*)d_in[12], *wmod = (const bf16*)d_in[13];
    bf16* out = (bf16*)d_out;
    if (!s_encode) {
        cudaDriverEntryPointQueryResult qr;
        cudaGetDriverEntryPoint("cuTensorMapEncodeTiled", (void**)&s_encode, cudaEnableDefault, &qr);
        cudaFuncSetAttribute(k_side, cudaFuncAttributeMaxDynamicSharedMemorySize, SD_SMEM);
        cudaFuncSetAttribute(k_chain, cudaFuncAttributeMaxDynamicSharedMemorySize, C_SMEM);
    }
    ChainMaps cm; SideMaps sd;
    make_map(&sd.h, sym(g_h), S_TOK, DM, 128); make_map3(&sd.wv, Wv, DM, HD, 64, 3);
    make_map3(&sd.ost, sym(g_o), S_TOK, HD, 16, 3); make_map(&sd.o, sym(g_o), S_TOK, HD, 128, 32); make_map3(&sd.wo, Wo, HD, DM, 32, 5);
    make_map3(&sd.slab3, sym(g_slab), 16 * KSPLIT * 128, DM, 64, 3); make_map3(&sd.slab2, sym(g_slab), 16 * KSPLIT * 128, DM, 64, 2);
    make_map3(&cm.wo15, Wo, HD, DM, 192, 2); make_map3(&cm.o15, sym(g_o), S_TOK, HD, 64, 2); make_map3(&cm.slab16, sym(g_slab), 16 * KSPLIT * 128, DM, 16, 2);
    for (int i = 0; i < 3; i++) {
        cuuint64_t dims[3] = {256, 320, 16 * KSPLIT}, strides[2] = {512, 128 * DM * 2};
        cuuint32_t box[3] = {256, 40u >> i, 2u << i}, es[3] = {1, 1, 1};
        s_encode(&sd.lnp[i], CU_TENSOR_MAP_DATA_TYPE_BFLOAT16, 3, sym(g_slab), dims, strides, box, es, CU_TENSOR_MAP_INTERLEAVE_NONE,
                 CU_TENSOR_MAP_SWIZZLE_NONE, CU_TENSOR_MAP_L2_PROMOTION_L2_256B, CU_TENSOR_MAP_FLOAT_OOB_FILL_NONE);
    }
    make_map(&cm.wq, Wq, DM, HD, 640 / WP); make_map(&cm.wk, Wk, DM, HD, 640 / WP); make_map(&cm.wv, Wv, DM, HD, 160); make_map3(&cm.wo, Wo, HD, DM, 64, 7, 32);
    make_map3(&cm.h2, sym(g_h), S_TOK, DM, 32, 2);
    ChainArgs ar = {x, mem0, c, wmod, Wv, Wo, wgate, wup, wdown, out, P_D1, P_DL, P_DG};
    k_chain<<<96, 384, C_SMEM>>>(cm, ar);
    cudaLaunchConfig_t cfg = {};
    cfg.gridDim = dim3(N_SIDE); cfg.blockDim = dim3(384); cfg.dynamicSmemBytes = SD_SMEM; cfg.stream = cudaStreamPerThread;
    cudaLaunchAttribute at[1]; at[0].id = cudaLaunchAttributeProgrammaticStreamSerialization; at[0].val.programmaticStreamSerializationAllowed = 1;
    cfg.attrs = at; cfg.numAttrs = 1;
    cudaLaunchKernelEx(&cfg, k_side, sd, x, wr, wmod, c, out);
}
```

```cpp
#include <cuda_runtime.h>
#include <cuda_bf16.h>
#include <cuda.h>
#include <stdint.h>
#include <stdio.h>
#include <string.h>
#include <stdlib.h>

typedef __nv_bfloat16 bf16;
constexpr int S_TOK = 2048, DM = 640, NH = 32, DH = 192, HD = NH * DH, NSEG = 64, SEG = 32, FF = 1536;

__device__ bf16 g_mod[6 * DM];
__device__ bf16 g_h[S_TOK * DM];
constexpr int AT_REC = 43008, AT_V = 24576, AT_KM = 36864, AT_VM = 39936;
__device__ __align__(1024) uint8_t g_att[NSEG * NH * AT_REC];
__device__ bf16 g_o[S_TOK * HD];
__device__ bf16 g_A[S_TOK * DM];
__device__ bf16 g_x1[S_TOK * DM];
__device__ bf16 g_h2[S_TOK * DM];
__device__ __align__(128) uint32_t g_key[S_TOK];
__device__ int g_idx[8];
__device__ __align__(128) uint32_t g_gu[FF / 8 * 32];
constexpr int ACC_PAIR = 24 * 1024;
__device__ __align__(1024) uint8_t g_acc[2 * ACC_PAIR];
__device__ __align__(1024) uint32_t g_stamp[4 * 12 * 32];
constexpr int KSPLIT = 16;
__device__ bf16 g_slab[16 * KSPLIT * 128 * DM];
struct __align__(128) Flags {
    uint32_t qk[16], vb[16];
    uint32_t at[16], o[16];
    uint32_t c[4][16];
    uint32_t half[32];
    uint32_t fin[4 * 32];
    uint32_t v[16 * 32];
    uint32_t seg[4 * 32];
    uint32_t pair[16 * 16];
    uint32_t h, pad2[31], done, pad3[31];
    uint32_t mod1[DM];
    uint32_t wmax[96];
};
__device__ Flags g_flags;
#define EPT(c, i)

__device__ __forceinline__ uint32_t smem_u32(const void* p) { return (uint32_t)__cvta_generic_to_shared(p); }
__device__ __forceinline__ uint32_t pack2(float lo, float hi) {
    uint32_t r; asm("cvt.rn.bf16x2.f32 %0, %1, %2;" : "=r"(r) : "f"(hi), "f"(lo)); return r;
}
__device__ __forceinline__ float bfr(float x) { return __uint_as_float(pack2(0.f, x)); }
__device__ __forceinline__ float inv_std(float var) {
    float s, r; asm("sqrt.approx.f32 %0, %1;" : "=f"(s) : "f"(bfr(bfr(var) + 1e-5f))); asm("rcp.approx.f32 %0, %1;" : "=f"(r) : "f"(bfr(s))); return r;
}
__device__ __forceinline__ float lo_f(uint32_t v) { return __uint_as_float(v << 16); }
__device__ __forceinline__ float hi_f(uint32_t v) { return __uint_as_float(v & 0xffff0000u); }
__device__ __forceinline__ void mbar_init(uint32_t bar, int cnt) { asm volatile("mbarrier.init.shared::cta.b64 [%0], %1;" :: "r"(bar), "r"(cnt) : "memory"); }
__device__ __forceinline__ void mbar_expect(uint32_t bar, int bytes) { asm volatile("mbarrier.arrive.expect_tx.shared::cta.b64 _, [%0], %1;" :: "r"(bar), "r"(bytes) : "memory"); }
__device__ __forceinline__ void mbar_arrive(uint32_t bar) { asm volatile("mbarrier.arrive.shared::cta.b64 _, [%0];" :: "r"(bar) : "memory"); }
__device__ __forceinline__ bool mbar_try(uint32_t bar, int par) {
    uint32_t ok; asm volatile("{ .reg .pred p; mbarrier.try_wait.parity.shared::cta.b64 p, [%1], %2; selp.u32 %0, 1, 0, p; }" : "=r"(ok) : "r"(bar), "r"(par) : "memory"); return ok;
}
__device__ __forceinline__ bool mbar_try_cluster(uint32_t bar, int par) {
    uint32_t ok; asm volatile("{ .reg .pred p; mbarrier.try_wait.parity.acquire.cluster.shared::cta.b64 p, [%1], %2; selp.u32 %0, 1, 0, p; }" : "=r"(ok) : "r"(bar), "r"(par) : "memory"); return ok;
}
__device__ __forceinline__ bool mbar_test(uint32_t bar, uint32_t par) {
    uint32_t ok; asm volatile("{ .reg .pred p; mbarrier.test_wait.parity.shared::cta.b64 p, [%1], %2; selp.u32 %0, 1, 0, p; }" : "=r"(ok) : "r"(bar), "r"(par) : "memory"); return ok;
}
constexpr int SPIN_LIMIT = 1 << 18;
__device__ __forceinline__ void mbar_wait(uint32_t bar, uint32_t par) {
    asm volatile("{ .reg .pred p, q; .reg .u32 n; mov.u32 n, 0;\n"
                 "W_%=: mbarrier.try_wait.parity.shared::cta.b64 p, [%0], %1;\n"
                 "@p bra.uni D_%=;\n"
                 "add.u32 n, n, 1; setp.lt.u32 q, n, 0x200000; @q bra.uni W_%=;\n"
                 "trap;\n"
                 "D_%=: }" :: "r"(bar), "r"(par) : "memory");
}
__device__ __forceinline__ void tma2d(uint32_t dst, const CUtensorMap* m, int c0, int c1, uint32_t bar) {
    asm volatile("cp.async.bulk.tensor.2d.shared::cluster.global.mbarrier::complete_tx::bytes [%0], [%1, {%3, %4}], [%2];"
        :: "r"(dst), "l"((uint64_t)m), "r"(bar), "r"(c0), "r"(c1) : "memory");
}
__device__ __forceinline__ void tma2d_mc(uint32_t dst, const CUtensorMap* m, int c0, int c1, uint32_t bar, uint16_t mask) {
    asm volatile("cp.async.bulk.tensor.2d.shared::cluster.global.mbarrier::complete_tx::bytes.multicast::cluster [%0], [%1, {%3, %4}], [%2], %5;"
        :: "r"(dst), "l"((uint64_t)m), "r"(bar), "r"(c0), "r"(c1), "h"(mask) : "memory");
}
__device__ __forceinline__ uint64_t policy_stream() { uint64_t p; asm("createpolicy.fractional.L2::evict_first.b64 %0, 1.0;" : "=l"(p)); return p; }
__device__ __forceinline__ void tma2d_ef(uint32_t dst, const CUtensorMap* m, int c0, int c1, uint32_t bar, uint64_t pol) {
    asm volatile("cp.async.bulk.tensor.2d.shared::cluster.global.mbarrier::complete_tx::bytes.L2::cache_hint [%0], [%1, {%3, %4}], [%2], %5;"
        :: "r"(dst), "l"((uint64_t)m), "r"(bar), "r"(c0), "r"(c1), "l"(pol) : "memory");
}
__device__ __forceinline__ void tma3d(uint32_t dst, const CUtensorMap* m, int row, int chunk, uint32_t bar) {
    asm volatile("cp.async.bulk.tensor.3d.shared::cluster.global.mbarrier::complete_tx::bytes [%0], [%1, {0, %3, %4}], [%2];"
        :: "r"(dst), "l"((uint64_t)m), "r"(bar), "r"(row), "r"(chunk) : "memory");
}
__device__ __forceinline__ void tma3d_ef(uint32_t dst, const CUtensorMap* m, int row, int chunk, uint32_t bar, uint64_t pol) {
    asm volatile("cp.async.bulk.tensor.3d.shared::cluster.global.mbarrier::complete_tx::bytes.L2::cache_hint [%0], [%1, {0, %3, %4}], [%2], %5;"
        :: "r"(dst), "l"((uint64_t)m), "r"(bar), "r"(row), "r"(chunk), "l"(pol) : "memory");
}
__device__ __forceinline__ void tma3d_store(const CUtensorMap* m, int row, int chunk, uint32_t src, uint64_t pol, bool hint) {
    if (hint) asm volatile("cp.async.bulk.tensor.3d.global.shared::cta.bulk_group.L2::cache_hint [%0, {0, %2, %3}], [%1], %4;"
        :: "l"((uint64_t)m), "r"(src), "r"(row), "r"(chunk), "l"(pol) : "memory");
    else asm volatile("cp.async.bulk.tensor.3d.global.shared::cta.bulk_group [%0, {0, %2, %3}], [%1];"
        :: "l"((uint64_t)m), "r"(src), "r"(row), "r"(chunk) : "memory");
}
__device__ __forceinline__ bool elect() { uint32_t p; asm volatile("{ .reg .pred e; elect.sync _|e, -1; selp.u32 %0, 1, 0, e; }" : "=r"(p)); return p; }
__device__ __forceinline__ uint2 ld_ef(const void* p, uint64_t pol) {
    uint2 v; asm volatile("ld.relaxed.gpu.global.L2::cache_hint.v2.u32 {%0,%1}, [%2], %3;" : "=r"(v.x), "=r"(v.y) : "l"(p), "l"(pol)); return v;
}
__device__ __forceinline__ void st_ef(void* p, uint2 v, uint64_t pol) {
    asm volatile("st.global.L2::cache_hint.v2.u32 [%0], {%1,%2}, %3;" :: "l"(p), "r"(v.x), "r"(v.y), "l"(pol) : "memory");
}
__device__ __forceinline__ void tma2d_prefetch(const CUtensorMap* m, int c0, int c1) {
    asm volatile("cp.async.bulk.prefetch.tensor.2d.L2.global [%0, {%1, %2}];" :: "l"((uint64_t)m), "r"(c0), "r"(c1) : "memory");
}
__device__ __forceinline__ void mbar_arrive_remote(uint32_t bar) { asm volatile("mbarrier.arrive.relaxed.cluster.shared::cluster.b64 _, [%0];" :: "r"(bar) : "memory"); }
__device__ __forceinline__ void tma2d_store(const CUtensorMap* m, int c0, int c1, uint32_t src) {
    asm volatile("cp.async.bulk.tensor.2d.global.shared::cta.bulk_group [%0, {%2, %3}], [%1];"
        :: "l"((uint64_t)m), "r"(src), "r"(c0), "r"(c1) : "memory");
}
__device__ __forceinline__ void bulk_g2s(uint32_t dst, const void* src, int bytes, uint32_t bar) {
    asm volatile("cp.async.bulk.shared::cluster.global.mbarrier::complete_tx::bytes [%0], [%1], %2, [%3];" :: "r"(dst), "l"(src), "r"(bytes), "r"(bar) : "memory");
}
__device__ __forceinline__ void ldsm4(uint32_t (&r)[4], uint32_t a) {
    asm volatile("ldmatrix.sync.aligned.m8n8.x4.shared.b16 {%0,%1,%2,%3}, [%4];" : "=r"(r[0]), "=r"(r[1]), "=r"(r[2]), "=r"(r[3]) : "r"(a) : "memory");
}
__device__ __forceinline__ void ldsm4t(uint32_t (&r)[4], uint32_t a) {
    asm volatile("ldmatrix.sync.aligned.m8n8.x4.trans.shared.b16 {%0,%1,%2,%3}, [%4];" : "=r"(r[0]), "=r"(r[1]), "=r"(r[2]), "=r"(r[3]) : "r"(a) : "memory");
}
__device__ __forceinline__ void stsm4(uint32_t a, uint32_t r0, uint32_t r1, uint32_t r2, uint32_t r3) {
    asm volatile("stmatrix.sync.aligned.m8n8.x4.shared.b16 [%0], {%1,%2,%3,%4};" :: "r"(a), "r"(r0), "r"(r1), "r"(r2), "r"(r3) : "memory");
}
__device__ __forceinline__ void stsm4t(uint32_t a, uint32_t r0, uint32_t r1, uint32_t r2, uint32_t r3) {
    asm volatile("stmatrix.sync.aligned.m8n8.x4.trans.shared.b16 [%0], {%1,%2,%3,%4};" :: "r"(a), "r"(r0), "r"(r1), "r"(r2), "r"(r3) : "memory");
}
__device__ __forceinline__ void stsm2t(uint32_t a, uint32_t r0, uint32_t r1) {
    asm volatile("stmatrix.sync.aligned.m8n8.x2.trans.shared.b16 [%0], {%1,%2};" :: "r"(a), "r"(r0), "r"(r1) : "memory");
}
__device__ __forceinline__ uint32_t movm_t(uint32_t v) { uint32_t r; asm volatile("movmatrix.sync.aligned.m8n8.trans.b16 %0, %1;" : "=r"(r) : "r"(v)); return r; }
__device__ __forceinline__ void mma16(float (&d)[4], uint32_t a0, uint32_t a1, uint32_t a2, uint32_t a3, uint32_t b0, uint32_t b1) {
    asm volatile("mma.sync.aligned.m16n8k16.row.col.f32.bf16.bf16.f32 {%0,%1,%2,%3}, {%4,%5,%6,%7}, {%8,%9}, {%0,%1,%2,%3};"
        : "+f"(d[0]), "+f"(d[1]), "+f"(d[2]), "+f"(d[3]) : "r"(a0), "r"(a1), "r"(a2), "r"(a3), "r"(b0), "r"(b1));
}
__device__ __forceinline__ void mma8(float (&d)[4], uint32_t a0, uint32_t a1, uint32_t b0) {
    asm volatile("mma.sync.aligned.m16n8k8.row.col.f32.bf16.bf16.f32 {%0,%1,%2,%3}, {%4,%5}, {%6}, {%0,%1,%2,%3};"
        : "+f"(d[0]), "+f"(d[1]), "+f"(d[2]), "+f"(d[3]) : "r"(a0), "r"(a1), "r"(b0));
}
__device__ __forceinline__ uint32_t mapa(uint32_t a, uint32_t r) { uint32_t o; asm volatile("mapa.shared::cluster.u32 %0, %1, %2;" : "=r"(o) : "r"(a), "r"(r)); return o; }
__device__ __forceinline__ void bar_sync(int id, int n) { asm volatile("bar.sync %0, %1;" :: "r"(id), "r"(n) : "memory"); }
__device__ __forceinline__ void bar_arrive(int id, int n) { asm volatile("bar.arrive %0, %1;" :: "r"(id), "r"(n) : "memory"); }
__device__ __forceinline__ uint64_t mkdesc(uint32_t addr, uint32_t lbo, uint32_t sbo) {
    return (uint64_t)((addr & 0x3FFFF) >> 4) | ((uint64_t)(lbo >> 4) << 16) | ((uint64_t)(sbo >> 4) << 32) | (1ull << 62);
}
#define WG_FENCE()  asm volatile("wgmma.fence.sync.aligned;" ::: "memory")
#define WG_COMMIT() asm volatile("wgmma.commit_group.sync.aligned;" ::: "memory")
#define WG_WAIT(n)  asm volatile("wgmma.wait_group.sync.aligned %0;" :: "n"(n) : "memory")

__device__ __forceinline__ void wgmma_ss_n192_tb(float (&d)[96], uint64_t a, uint64_t b, int acc) {
    asm volatile("{ .reg .pred p; setp.ne.b32 p, %98, 0;\n"
        "wgmma.mma_async.sync.aligned.m64n192k16.f32.bf16.bf16 {%0,%1,%2,%3,%4,%5,%6,%7,%8,%9,%10,%11,%12,%13,%14,%15,%16,%17,%18,%19,%20,%21,%22,%23,%24,%25,%26,%27,%28,%29,%30,%31,%32,%33,%34,%35,%36,%37,%38,%39,%40,%41,%42,%43,%44,%45,%46,%47,%48,%49,%50,%51,%52,%53,%54,%55,%56,%57,%58,%59,%60,%61,%62,%63,%64,%65,%66,%67,%68,%69,%70,%71,%72,%73,%74,%75,%76,%77,%78,%79,%80,%81,%82,%83,%84,%85,%86,%87,%88,%89,%90,%91,%92,%93,%94,%95}, %96, %97, p, 1, 1, 0, 1; }"
        : "+f"(d[0]), "+f"(d[1]), "+f"(d[2]), "+f"(d[3]), "+f"(d[4]), "+f"(d[5]), "+f"(d[6]), "+f"(d[7]), "+f"(d[8]), "+f"(d[9]), "+f"(d[10]), "+f"(d[11]), "+f"(d[12]), "+f"(d[13]), "+f"(d[14]), "+f"(d[15]), "+f"(d[16]), "+f"(d[17]), "+f"(d[18]), "+f"(d[19]), "+f"(d[20]), "+f"(d[21]), "+f"(d[22]), "+f"(d[23]), "+f"(d[24]), "+f"(d[25]), "+f"(d[26]), "+f"(d[27]), "+f"(d[28]), "+f"(d[29]), "+f"(d[30]), "+f"(d[31]), "+f"(d[32]), "+f"(d[33]), "+f"(d[34]), "+f"(d[35]), "+f"(d[36]), "+f"(d[37]), "+f"(d[38]), "+f"(d[39]), "+f"(d[40]), "+f"(d[41]), "+f"(d[42]), "+f"(d[43]), "+f"(d[44]), "+f"(d[45]), "+f"(d[46]), "+f"(d[47]), "+f"(d[48]), "+f"(d[49]), "+f"(d[50]), "+f"(d[51]), "+f"(d[52]), "+f"(d[53]), "+f"(d[54]), "+f"(d[55]), "+f"(d[56]), "+f"(d[57]), "+f"(d[58]), "+f"(d[59]), "+f"(d[60]), "+f"(d[61]), "+f"(d[62]), "+f"(d[63]), "+f"(d[64]), "+f"(d[65]), "+f"(d[66]), "+f"(d[67]), "+f"(d[68]), "+f"(d[69]), "+f"(d[70]), "+f"(d[71]), "+f"(d[72]), "+f"(d[73]), "+f"(d[74]), "+f"(d[75]), "+f"(d[76]), "+f"(d[77]), "+f"(d[78]), "+f"(d[79]), "+f"(d[80]), "+f"(d[81]), "+f"(d[82]), "+f"(d[83]), "+f"(d[84]), "+f"(d[85]), "+f"(d[86]), "+f"(d[87]), "+f"(d[88]), "+f"(d[89]), "+f"(d[90]), "+f"(d[91]), "+f"(d[92]), "+f"(d[93]), "+f"(d[94]), "+f"(d[95])
        : "l"(a), "l"(b), "r"(acc));
}

__device__ __forceinline__ void wgmma_ss_n128_tb(float (&d)[64], uint64_t a, uint64_t b, int acc) {
    asm volatile("{ .reg .pred p; setp.ne.b32 p, %66, 0;\n"
        "wgmma.mma_async.sync.aligned.m64n128k16.f32.bf16.bf16 {%0,%1,%2,%3,%4,%5,%6,%7,%8,%9,%10,%11,%12,%13,%14,%15,%16,%17,%18,%19,%20,%21,%22,%23,%24,%25,%26,%27,%28,%29,%30,%31,%32,%33,%34,%35,%36,%37,%38,%39,%40,%41,%42,%43,%44,%45,%46,%47,%48,%49,%50,%51,%52,%53,%54,%55,%56,%57,%58,%59,%60,%61,%62,%63}, %64, %65, p, 1, 1, 0, 1; }"
        : "+f"(d[0]), "+f"(d[1]), "+f"(d[2]), "+f"(d[3]), "+f"(d[4]), "+f"(d[5]), "+f"(d[6]), "+f"(d[7]), "+f"(d[8]), "+f"(d[9]), "+f"(d[10]), "+f"(d[11]), "+f"(d[12]), "+f"(d[13]), "+f"(d[14]), "+f"(d[15]), "+f"(d[16]), "+f"(d[17]), "+f"(d[18]), "+f"(d[19]), "+f"(d[20]), "+f"(d[21]), "+f"(d[22]), "+f"(d[23]), "+f"(d[24]), "+f"(d[25]), "+f"(d[26]), "+f"(d[27]), "+f"(d[28]), "+f"(d[29]), "+f"(d[30]), "+f"(d[31]), "+f"(d[32]), "+f"(d[33]), "+f"(d[34]), "+f"(d[35]), "+f"(d[36]), "+f"(d[37]), "+f"(d[38]), "+f"(d[39]), "+f"(d[40]), "+f"(d[41]), "+f"(d[42]), "+f"(d[43]), "+f"(d[44]), "+f"(d[45]), "+f"(d[46]), "+f"(d[47]), "+f"(d[48]), "+f"(d[49]), "+f"(d[50]), "+f"(d[51]), "+f"(d[52]), "+f"(d[53]), "+f"(d[54]), "+f"(d[55]), "+f"(d[56]), "+f"(d[57]), "+f"(d[58]), "+f"(d[59]), "+f"(d[60]), "+f"(d[61]), "+f"(d[62]), "+f"(d[63])
        : "l"(a), "l"(b), "r"(acc));
}

__device__ __forceinline__ void wgmma_rs_n192_tb(float (&d)[96], const uint32_t (&a)[4], uint64_t b, int acc) {
    asm volatile("{ .reg .pred p; setp.ne.b32 p, %101, 0;\n"
        "wgmma.mma_async.sync.aligned.m64n192k16.f32.bf16.bf16 {%0,%1,%2,%3,%4,%5,%6,%7,%8,%9,%10,%11,%12,%13,%14,%15,%16,%17,%18,%19,%20,%21,%22,%23,%24,%25,%26,%27,%28,%29,%30,%31,%32,%33,%34,%35,%36,%37,%38,%39,%40,%41,%42,%43,%44,%45,%46,%47,%48,%49,%50,%51,%52,%53,%54,%55,%56,%57,%58,%59,%60,%61,%62,%63,%64,%65,%66,%67,%68,%69,%70,%71,%72,%73,%74,%75,%76,%77,%78,%79,%80,%81,%82,%83,%84,%85,%86,%87,%88,%89,%90,%91,%92,%93,%94,%95}, {%96,%97,%98,%99}, %100, p, 1, 1, 1; }"
        : "+f"(d[0]), "+f"(d[1]), "+f"(d[2]), "+f"(d[3]), "+f"(d[4]), "+f"(d[5]), "+f"(d[6]), "+f"(d[7]), "+f"(d[8]), "+f"(d[9]), "+f"(d[10]), "+f"(d[11]), "+f"(d[12]), "+f"(d[13]), "+f"(d[14]), "+f"(d[15]), "+f"(d[16]), "+f"(d[17]), "+f"(d[18]), "+f"(d[19]), "+f"(d[20]), "+f"(d[21]), "+f"(d[22]), "+f"(d[23]), "+f"(d[24]), "+f"(d[25]), "+f"(d[26]), "+f"(d[27]), "+f"(d[28]), "+f"(d[29]), "+f"(d[30]), "+f"(d[31]), "+f"(d[32]), "+f"(d[33]), "+f"(d[34]), "+f"(d[35]), "+f"(d[36]), "+f"(d[37]), "+f"(d[38]), "+f"(d[39]), "+f"(d[40]), "+f"(d[41]), "+f"(d[42]), "+f"(d[43]), "+f"(d[44]), "+f"(d[45]), "+f"(d[46]), "+f"(d[47]), "+f"(d[48]), "+f"(d[49]), "+f"(d[50]), "+f"(d[51]), "+f"(d[52]), "+f"(d[53]), "+f"(d[54]), "+f"(d[55]), "+f"(d[56]), "+f"(d[57]), "+f"(d[58]), "+f"(d[59]), "+f"(d[60]), "+f"(d[61]), "+f"(d[62]), "+f"(d[63]), "+f"(d[64]), "+f"(d[65]), "+f"(d[66]), "+f"(d[67]), "+f"(d[68]), "+f"(d[69]), "+f"(d[70]), "+f"(d[71]), "+f"(d[72]), "+f"(d[73]), "+f"(d[74]), "+f"(d[75]), "+f"(d[76]), "+f"(d[77]), "+f"(d[78]), "+f"(d[79]), "+f"(d[80]), "+f"(d[81]), "+f"(d[82]), "+f"(d[83]), "+f"(d[84]), "+f"(d[85]), "+f"(d[86]), "+f"(d[87]), "+f"(d[88]), "+f"(d[89]), "+f"(d[90]), "+f"(d[91]), "+f"(d[92]), "+f"(d[93]), "+f"(d[94]), "+f"(d[95])
        : "r"(a[0]), "r"(a[1]), "r"(a[2]), "r"(a[3]), "l"(b), "r"(acc));
}

__device__ __forceinline__ void wgmma_rs_n128_tb(float (&d)[64], const uint32_t (&a)[4], uint64_t b, int acc) {
    asm volatile("{ .reg .pred p; setp.ne.b32 p, %69, 0;\n"
        "wgmma.mma_async.sync.aligned.m64n128k16.f32.bf16.bf16 {%0,%1,%2,%3,%4,%5,%6,%7,%8,%9,%10,%11,%12,%13,%14,%15,%16,%17,%18,%19,%20,%21,%22,%23,%24,%25,%26,%27,%28,%29,%30,%31,%32,%33,%34,%35,%36,%37,%38,%39,%40,%41,%42,%43,%44,%45,%46,%47,%48,%49,%50,%51,%52,%53,%54,%55,%56,%57,%58,%59,%60,%61,%62,%63}, {%64,%65,%66,%67}, %68, p, 1, 1, 1; }"
        : "+f"(d[0]), "+f"(d[1]), "+f"(d[2]), "+f"(d[3]), "+f"(d[4]), "+f"(d[5]), "+f"(d[6]), "+f"(d[7]), "+f"(d[8]), "+f"(d[9]), "+f"(d[10]), "+f"(d[11]), "+f"(d[12]), "+f"(d[13]), "+f"(d[14]), "+f"(d[15]), "+f"(d[16]), "+f"(d[17]), "+f"(d[18]), "+f"(d[19]), "+f"(d[20]), "+f"(d[21]), "+f"(d[22]), "+f"(d[23]), "+f"(d[24]), "+f"(d[25]), "+f"(d[26]), "+f"(d[27]), "+f"(d[28]), "+f"(d[29]), "+f"(d[30]), "+f"(d[31]), "+f"(d[32]), "+f"(d[33]), "+f"(d[34]), "+f"(d[35]), "+f"(d[36]), "+f"(d[37]), "+f"(d[38]), "+f"(d[39]), "+f"(d[40]), "+f"(d[41]), "+f"(d[42]), "+f"(d[43]), "+f"(d[44]), "+f"(d[45]), "+f"(d[46]), "+f"(d[47]), "+f"(d[48]), "+f"(d[49]), "+f"(d[50]), "+f"(d[51]), "+f"(d[52]), "+f"(d[53]), "+f"(d[54]), "+f"(d[55]), "+f"(d[56]), "+f"(d[57]), "+f"(d[58]), "+f"(d[59]), "+f"(d[60]), "+f"(d[61]), "+f"(d[62]), "+f"(d[63])
        : "r"(a[0]), "r"(a[1]), "r"(a[2]), "r"(a[3]), "l"(b), "r"(acc));
}

__device__ __forceinline__ void wgmma_rs_n32(float (&d)[16], const uint32_t (&a)[4], uint64_t b, int acc) {
    asm volatile("{ .reg .pred p; setp.ne.b32 p, %21, 0;\n"
        "wgmma.mma_async.sync.aligned.m64n32k16.f32.bf16.bf16 {%0,%1,%2,%3,%4,%5,%6,%7,%8,%9,%10,%11,%12,%13,%14,%15}, {%16,%17,%18,%19}, %20, p, 1, 1, 0; }"
        : "+f"(d[0]), "+f"(d[1]), "+f"(d[2]), "+f"(d[3]), "+f"(d[4]), "+f"(d[5]), "+f"(d[6]), "+f"(d[7]), "+f"(d[8]), "+f"(d[9]), "+f"(d[10]), "+f"(d[11]), "+f"(d[12]), "+f"(d[13]), "+f"(d[14]), "+f"(d[15])
        : "r"(a[0]), "r"(a[1]), "r"(a[2]), "r"(a[3]), "l"(b), "r"(acc));
}

__device__ __forceinline__ float warp_sum(float v) {
#pragma unroll
    for (int o = 16; o; o >>= 1) v += __shfl_xor_sync(0xffffffffu, v, o);
    return v;
}
__device__ __forceinline__ uint32_t add2(uint32_t a, uint32_t b) { uint32_t r; asm("add.rn.bf16x2 %0, %1, %2;" : "=r"(r) : "r"(a), "r"(b)); return r; }
__device__ __forceinline__ uint32_t mul2(uint32_t a, uint32_t b) { uint32_t r; asm("mul.rn.bf16x2 %0, %1, %2;" : "=r"(r) : "r"(a), "r"(b)); return r; }
__device__ __forceinline__ uint32_t amax2(uint32_t m, uint32_t v) { uint32_t r; asm("max.u16x2 %0, %1, %2;" : "=r"(r) : "r"(m), "r"(v & 0x7fff7fffu)); return r; }
__device__ __forceinline__ uint32_t amax_warp(uint32_t m) { return __reduce_max_sync(0xffffffffu, max(m & 0xffffu, m >> 16)); }
__device__ __forceinline__ void ln_norm(const uint32_t (&xv)[10], uint32_t (&nv)[10]) {
    float s0 = 0, s1 = 0;
#pragma unroll
    for (int i = 0; i < 10; i++) { s0 += lo_f(xv[i]); s1 += hi_f(xv[i]); }
    const float mean = warp_sum(s0 + s1) * (1.f / DM);
    float q0 = 0, q1 = 0;
#pragma unroll
    for (int i = 0; i < 10; i++) { const float d0 = lo_f(xv[i]) - mean, d1 = hi_f(xv[i]) - mean; q0 += d0 * d0; q1 += d1 * d1; }
    const float inv = inv_std(warp_sum(q0 + q1) * (1.f / DM));
    const uint32_t mb = pack2(-mean, -mean);
#pragma unroll
    for (int i = 0; i < 10; i++) { const uint32_t d = add2(xv[i], mb); nv[i] = pack2(lo_f(d) * inv, hi_f(d) * inv); }
}
__device__ __forceinline__ void ln_mod(const uint32_t (&xv)[10], const uint32_t (&sv)[10], const uint32_t (&tv)[10], uint32_t (&hv)[10]) {
    ln_norm(xv, hv);
#pragma unroll
    for (int i = 0; i < 10; i++) hv[i] = add2(mul2(hv[i], add2(sv[i], 0x3f803f80u)), tv[i]);
}
__device__ __forceinline__ uint32_t ld_rlx(const uint32_t* f) { uint32_t v; asm volatile("ld.relaxed.gpu.global.u32 %0, [%1];" : "=r"(v) : "l"(f) : "memory"); return v; }
__device__ __forceinline__ void bump(uint32_t* f) { asm volatile("red.relaxed.gpu.global.add.u32 [%0], 1;" :: "l"(f) : "memory"); }
#define NAP 100
#define GPU_FENCE() asm volatile("fence.acq_rel.gpu;" ::: "memory")
__device__ __forceinline__ void flag_wait(const uint32_t* f, uint32_t target) {
    for (int n = 0;; n++) {
        uint32_t v; asm volatile("ld.relaxed.gpu.global.u32 %0, [%1];" : "=r"(v) : "l"(f) : "memory");
        if (v >= target) break;
        if (n > (1 << 22)) __trap();
        __nanosleep(NAP);
    }
}
__device__ __forceinline__ void flag_add(uint32_t* f, uint32_t v = 1) { asm volatile("red.release.gpu.global.add.u32 [%0], %1;" :: "l"(f), "r"(v) : "memory"); }
constexpr int N_SIDE = 36;
__device__ __forceinline__ void flags_release(int lane) {
    uint32_t old = 0;
    if (lane == 0) asm volatile("atom.relaxed.gpu.global.add.u32 %0, [%1], 1;" : "=r"(old) : "l"(&g_flags.done) : "memory");
    if (__shfl_sync(0xffffffffu, old, 0) == 96 + N_SIDE - 1)
#pragma unroll 1
        for (int i = lane; i < (int)(sizeof(Flags) / 16); i += 32) ((uint4*)&g_flags)[i] = make_uint4(0, 0, 0, 0);
}

template <int NT> struct ModSlice {
    static constexpr int R = 2 * DM / NT;
    float sc[R]; uint4 wv[R];
    __device__ __forceinline__ void load(const bf16* wmod, const bf16* c, int col, int tid) {
        const bf16* wm = wmod + (tid >> 1) * (6 * DM) + col + (tid & 1) * 8;
#pragma unroll
        for (int i = 0; i < R; i++) {
            asm volatile("ld.global.nc.L1::no_allocate.L2::128B.v4.u32 {%0,%1,%2,%3}, [%4];" : "=r"(wv[i].x), "=r"(wv[i].y), "=r"(wv[i].z), "=r"(wv[i].w) : "l"(wm + i * (NT / 2) * (6 * DM)));
            sc[i] = __uint_as_float((uint32_t)__ldg((const unsigned short*)c + (tid >> 1) + NT / 2 * i) << 16);
        }
    }
    __device__ __forceinline__ void partial(uint32_t buf, int tid) {
        const int lane = tid & 31;
        float a[8] = {0, 0, 0, 0, 0, 0, 0, 0};
#pragma unroll
        for (int i = 0; i < R; i++) {
            const float f = bfr(__fdividef(sc[i], 1.f + __expf(-sc[i])));
            const uint32_t u[4] = {wv[i].x, wv[i].y, wv[i].z, wv[i].w};
#pragma unroll
            for (int e = 0; e < 4; e++) { a[2 * e] += f * lo_f(u[e]); a[2 * e + 1] += f * hi_f(u[e]); }
        }
#pragma unroll
        for (int h = 4; h; h >>= 1)
#pragma unroll
            for (int e = 0; e < h; e++) { const bool up = lane & (4 * h); a[e] = (up ? a[e + h] : a[e]) + __shfl_xor_sync(0xffffffffu, up ? a[e] : a[e + h], 4 * h); }
        a[0] += __shfl_xor_sync(0xffffffffu, a[0], 2);
        asm volatile("st.shared.f32 [%0], %1;" :: "r"(buf + (tid >> 5) * 64 + (lane & 1) * 32 + (lane >> 2) * 4), "f"(a[0]) : "memory");
    }
    static __device__ __forceinline__ uint32_t total(uint32_t buf, int lane) {
        float a0 = 0, a1 = 0;
#pragma unroll
        for (int i = 0; i < NT / 32; i++) { float x, y; asm volatile("ld.shared.v2.f32 {%0,%1}, [%2];" : "=f"(x), "=f"(y) : "r"(buf + i * 64 + (lane & 7) * 8) : "memory"); a0 += x; a1 += y; }
        return pack2(a0, a1);
    }
};

struct ChainMaps { CUtensorMap wq, wk, wv, wo, h2, wo15, o15, slab2; };
struct ChainArgs { const bf16 *x, *mem0, *c, *wmod, *wv, *wo, *wgate, *wup, *wdown; bf16* out; int D1, D2, DG; };
constexpr uint32_t SM_BASE = 1024;
#define NRING 10
#define XORD 0
#define B5AT 41
#define QCUT 0x54
#define NCH 0
#define XA 2
#define VT 1
#define OSEND 1
#define SPOLL 0
#define NOF 0
#define FW 2
#define NPRE 9
#define REG_P 208
#define REG_L (504 - 2 * REG_P)
constexpr int WO_BLK = 7 * 4096;
constexpr int C_WV = 0, C_WO = 81920, C_XR = 167936, C_VP = C_XR + 7 * 4096, C_VX = C_XR + 8 * 4096, C_QX = C_VX + 4096, C_KX = C_QX + 4096,
              C_MEM = C_KX + 4096, C_OX = C_MEM + 9216, C_VM = C_OX + 3072, C_QM = C_VM + 1024, C_KM = C_QM + 1024, C_SC = C_KM + 1024, C_BAR = C_SC + 3840;
constexpr int CB_W = C_BAR, CB_W2 = C_BAR + 8, CB_SC = C_BAR + 16, CB_XD = C_BAR + 24, CB_VX = C_BAR + 32, CB_W3 = C_BAR + 40, CB_XM = C_BAR + 48, CB_OX = C_BAR + 56,
              CB_XF = C_BAR + 64, C_LAG = C_BAR + 96, C_UN = C_BAR + 100, C_MX = C_BAR + 112;
constexpr int C_SMEM = C_BAR + 128;
#define PROF(i)
#define PROFG(i)
#define PROFV(i, v)
static_assert(C_SMEM <= 232448, "chain shared memory");
__device__ __forceinline__ uint32_t umax3(uint32_t a, uint32_t b, uint32_t c) { return max(max(a, b), c); }
__device__ __forceinline__ void wait_until(uint32_t t) {
    asm volatile("{ .reg .pred p; .reg .s32 c; .reg .u64 d;\nU_%=: mov.u64 d, %%clock64; cvt.u32.u64 c, d; sub.s32 c, c, %0; setp.lt.s32 p, c, 0; @p bra.uni U_%=; }" :: "r"(t) : "memory");
}
__device__ __forceinline__ uint32_t gtime() { uint32_t c; asm volatile("mov.u32 %0, %%globaltimer_lo;" : "=r"(c)); return c; }
__device__ __forceinline__ uint32_t opaque(uint32_t v) { uint32_t r; asm volatile("shfl.sync.bfly.b32 %0, %1, 0, 31, -1;" : "=r"(r) : "r"(v)); return r; }
__device__ __forceinline__ uint32_t lds32(uint32_t a) { uint32_t v; asm volatile("ld.shared.u32 %0, [%1];" : "=r"(v) : "r"(a) : "memory"); return v; }
__device__ __forceinline__ float2 lds64f(uint32_t a) { float2 v; asm volatile("ld.shared.v2.f32 {%0,%1}, [%2];" : "=f"(v.x), "=f"(v.y) : "r"(a) : "memory"); return v; }
__device__ __forceinline__ float4 lds128f(uint32_t a) { float4 v; asm volatile("ld.shared.v4.f32 {%0,%1,%2,%3}, [%4];" : "=f"(v.x), "=f"(v.y), "=f"(v.z), "=f"(v.w) : "r"(a) : "memory"); return v; }
__device__ __forceinline__ void sts128f(uint32_t a, float x, float y, float z, float w) { asm volatile("st.shared.v4.f32 [%0], {%1,%2,%3,%4};" :: "r"(a), "f"(x), "f"(y), "f"(z), "f"(w) : "memory"); }
__device__ __forceinline__ void lds64(uint32_t (&v)[2], uint32_t a) { asm volatile("ld.shared.v2.u32 {%0,%1}, [%2];" : "=r"(v[0]), "=r"(v[1]) : "r"(a) : "memory"); }
__device__ __forceinline__ void mma16q(float (&d)[4], const uint32_t (&a)[4], uint32_t b0, uint32_t b1) { mma16(d, a[0], a[1], a[2], a[3], b0, b1); }
__device__ __forceinline__ uint32_t f16_to_bf16(uint32_t v) {
    float lo, hi; asm("{ .reg .f16 l, h; mov.b32 {l, h}, %2; cvt.f32.f16 %0, l; cvt.f32.f16 %1, h; }" : "=f"(lo), "=f"(hi) : "r"(v));
    return pack2(lo, hi);
}
__device__ __forceinline__ uint32_t pack2h(float lo, float hi) { uint32_t r; asm("cvt.rn.f16x2.f32 %0, %1, %2;" : "=r"(r) : "f"(hi), "f"(lo)); return r; }
#define SPLIT 1
__device__ __forceinline__ void cut(uint32_t never, int n) {
    asm volatile("{ .reg .pred p; setp.ne.u32 p, %0, %1; @p bra.uni C_%=; trap; C_%=: }" :: "r"(never), "r"(n) : "memory");
}
__device__ __forceinline__ void pin(uint32_t never, uint32_t a, uint32_t b, uint32_t c, uint32_t d) {
    asm volatile("{ .reg .pred p; setp.eq.u32 p, %0, 0; @p st.shared.v4.u32 [%0], {%1,%2,%3,%4}; }" :: "r"(never), "r"(a), "r"(b), "r"(c), "r"(d) : "memory");
}
__device__ __forceinline__ void pin0(uint32_t never) {
    asm volatile("{ .reg .pred p; setp.eq.u32 p, %0, 0; @p st.shared.u32 [%0], 0; }" :: "r"(never) : "memory");
}
#define ELECTED(txt) "{ .reg .pred e; elect.sync _|e, -1; @e " txt " }"
__device__ __forceinline__ void w_bulk_s2g(void* dst, uint32_t src, int bytes) {
    asm volatile(ELECTED("cp.async.bulk.global.shared::cta.bulk_group [%0], [%1], %2;") :: "l"(dst), "r"(src), "r"(bytes) : "memory");
}
__device__ __forceinline__ void w_bump(uint32_t* f) { asm volatile(ELECTED("red.relaxed.gpu.global.add.u32 [%0], 1;") :: "l"(f) : "memory"); }
__device__ __forceinline__ void w_expect(uint32_t bar, int bytes) { asm volatile(ELECTED("mbarrier.arrive.expect_tx.shared::cta.b64 _, [%0], %1;") :: "r"(bar), "r"(bytes) : "memory"); }
__device__ __forceinline__ void w_flag_wait(const uint32_t* f, uint32_t target) {
    asm volatile("{ .reg .pred p; .reg .u32 n, v; mov.u32 n, 0;\n"
                 "F_%=: ld.relaxed.gpu.global.u32 v, [%0]; setp.ge.u32 p, v, %1; vote.sync.all.pred p, p, -1; @p bra.uni G_%=;\n"
                 "nanosleep.u32 %2; add.u32 n, n, 1; setp.lt.u32 p, n, 0x400000; @p bra.uni F_%=;\ntrap;\nG_%=: }" :: "l"(f), "r"(target), "n"(NAP) : "memory");
}
#define BULK_COMMIT()    asm volatile("cp.async.bulk.commit_group;" ::: "memory")
#define BULK_WAIT()      asm volatile("cp.async.bulk.wait_group 0;" ::: "memory")
#define BULK_WAIT_READ() asm volatile("cp.async.bulk.wait_group.read 0;" ::: "memory")
#define PROXY_FENCE()    asm volatile("fence.proxy.async.shared::cta;" ::: "memory")
__device__ __forceinline__ void send16(uint32_t dst, uint32_t bar, float a, float b, float c, float d) {
    asm volatile("st.async.shared::cluster.mbarrier::complete_tx::bytes.v4.f32 [%0], {%1,%2,%3,%4}, [%5];" :: "r"(dst), "f"(a), "f"(b), "f"(c), "f"(d), "r"(bar) : "memory");
}
__device__ __forceinline__ void send8(uint32_t dst, uint32_t bar, uint32_t a, uint32_t b) {
    asm volatile("st.async.shared::cluster.mbarrier::complete_tx::bytes.v2.b32 [%0], {%1,%2}, [%3];" :: "r"(dst), "r"(a), "r"(b), "r"(bar) : "memory");
}

__device__ __forceinline__ void seg_done(int n, int head) {
    if (n >= 60 || (n & 3) == 3) { if (!NOF) GPU_FENCE(); w_bump(n >= 60 ? &g_flags.seg[(n - 60) * 32 + head] : &g_flags.qk[n >> 2]); }
}
__device__ __forceinline__ uint32_t x_base(int wg, uint32_t small, int sh) { return (uint32_t)mkdesc(SM_BASE + C_XR, 16, 1024) + wg * 256 + (small >> sh); }
__device__ __forceinline__ void x_chunk(float (&acc)[16], const uint32_t (&wa)[40][4], uint32_t xl, int a0, int i, int first) {
#pragma unroll
    for (int ks = 0; ks < 4; ks++)
        wgmma_rs_n32(acc, wa[a0 + 4 * i + ks], mkdesc(0, 0, 1024) | (uint32_t)(xl + (((i ? (i - 1) * 8192 : C_MEM - C_XR) + ks * 32) >> 4)), !(first && ks == 0));
}
__device__ __forceinline__ void x_part(float (&acc)[16], const uint32_t (&wa)[40][4], uint32_t sm, int n, int wg, int w, uint32_t ln, uint32_t small) {
    const int s = n - 1; (void)s;
    uint32_t giv[8];
    auto chunk = [&](int a0, int i, int first) { x_chunk(acc, wa, x_base(wg, small, a0 ? 21 : 22), a0, i, first); };
    mbar_wait(sm + CB_XM, n & 1);
    if (n) bar_sync(5, 384);
    if (wg == 0 && w == 0) PROF(12);
    WG_FENCE();
#pragma unroll
    for (int i = 1 + XA; i < 5; i++) chunk(20, i, 0);
    chunk(20, 0, 0);
    WG_COMMIT();
    if (n) {
        if (wg == 1 && w == 1) BULK_WAIT();
        bar_sync(8, 256);
    }
    if (wg == 0 && w == 0) PROF(18);
    const uint32_t xb = sm + w * 512 + ln * 16, xw = xb + C_KX - wg * 4096, xr = xb + C_QX + wg * 4096;
    WG_WAIT(0);
#pragma unroll
    for (int i = 0; i < 8; i++) asm volatile("cvt.rn.bf16x2.f32 %0, %1, %2;" : "=r"(giv[i]) : "f"(acc[2 * i + 1]), "f"(acc[2 * i]));
#pragma unroll
    for (int p = 0; p < 2; p++) asm volatile("st.shared.v4.u32 [%0], {%1,%2,%3,%4};" :: "r"(xw + p * 2048), "r"(giv[4 * p]), "r"(giv[4 * p + 1]), "r"(giv[4 * p + 2]), "r"(giv[4 * p + 3]) : "memory");
    bar_arrive(12 + wg, 256);
    WG_FENCE();
    chunk(0, 0, 1);
    WG_COMMIT();
    chunk(0, 1, 0);
    if (XORD) chunk(0, 2, 0);
    bar_sync(13 - wg, 256);
#pragma unroll
    for (int p = 0; p < 2; p++) asm volatile("ld.shared.v4.u32 {%0,%1,%2,%3}, [%4];" : "=r"(giv[4 * p]), "=r"(giv[4 * p + 1]), "=r"(giv[4 * p + 2]), "=r"(giv[4 * p + 3]) : "r"(xr + p * 2048) : "memory");
    WG_COMMIT(); WG_WAIT(1); bar_arrive(9, 384);
    WG_FENCE();
    if (!XORD) chunk(0, 2, 0);
    chunk(0, 3, 0); chunk(0, 4, 0);
    WG_COMMIT();
    const uint32_t r = ln & 7, mi = ln >> 3, dst = sm + (wg == 0 ? C_QX : C_KX) + ((mi >> 1) * 8 + r) * 128 + (((2 * w + (mi & 1)) ^ r) << 4);
    pin(xb, giv[0], giv[4], dst, 0);
    bar_sync(10 + wg, 128);
    WG_WAIT(0);
    if (wg == 0 && w == 0) PROF(30);
    if (w == 0 && ln < 3) mbar_arrive_remote(mapa(sm + CB_XD, ln));
#pragma unroll
    for (int i = 0; i < 8; i++) { acc[2 * i] += lo_f(giv[i]); acc[2 * i + 1] += hi_f(giv[i]); }
#pragma unroll
    for (int p = 0; p < 2; p++)
        stsm4t(dst + p * 2048, pack2(acc[8 * p], acc[8 * p + 1]), pack2(acc[8 * p + 2], acc[8 * p + 3]), pack2(acc[8 * p + 4], acc[8 * p + 5]), pack2(acc[8 * p + 6], acc[8 * p + 7]));
    if (wg == 0 && w == 0) PROF(11);
}
__device__ __forceinline__ void x_fill(const ChainMaps& mp, uint32_t sm, int n, int j) {
    mbar_expect(sm + CB_XF, 24576);
    asm volatile("cp.async.bulk.tensor.3d.shared::cluster.global.mbarrier::complete_tx::bytes.multicast::cluster [%0], [%1, {0, %3, %4}], [%2], %5;"
        :: "r"(sm + C_XR + j * 8192), "l"((uint64_t)&mp.h2), "r"(sm + CB_XF), "r"(n * SEG), "r"(2 + 2 * j), "h"((uint16_t)7) : "memory");
}
__device__ __forceinline__ void x_rest(const ChainMaps& mp, uint32_t sm, int n) {
    mbar_expect(sm + CB_XM, 16384);
    tma3d(sm + C_XR + 6 * 4096, &mp.h2, n * SEG, 8, sm + CB_XM); tma3d(sm + C_MEM, &mp.h2, n * SEG, 0, sm + CB_XM);
}

#define WPOS 15
#define WP 8
#define WOPF 30
#define SPF 0
#define SDEL 0
#define EORD 0
#define BPOS 2
#define TPF 1
#define B_LATE 13
constexpr int E_B = C_WO, E_STG = 196608, EB_A = 229376, EB_B = C_BAR + 80, EB_REL = C_BAR + 104;
__device__ __forceinline__ uint32_t e_slot(int wg, int c) { return wg && c == 2 ? E_B + 98304 : wg * 49152 + c * 16384; }
constexpr int T_WG = 0, T_WU = 20480, T_WD = 40960, T_X = 65536, T_RED = 77824, T_KEY = 86016;
__device__ __forceinline__ void wo_half(const ChainMaps& mp, uint32_t sm, int blk, int c) {
    if (blk < 80 && elect()) { mbar_expect(sm + EB_B + 8 * c, 49152); tma3d(sm + E_B + c * 49152, &mp.wo15, blk / 5 * 384 + c * 192, blk % 5 * 2, sm + EB_B + 8 * c); }
}
__device__ __forceinline__ void end_loads(const ChainMaps& mp, const ChainArgs& ar, uint32_t sm, int blk, int wg) {
    const uint32_t bar = sm + EB_A + wg * 48;
    const int kp = blk / 5;
    if (elect()) {
#pragma unroll 1
        for (int c = 0; c < 6; c++) mbar_init(bar + 8 * c, c < 3 ? 1 : 4);
        PROXY_FENCE();
    }
    __syncwarp();
    bar_arrive(5, 384);
    if (EORD) bar_sync(6, 96);
    if (blk >= 80) {
        if (TPF && elect()) {
#pragma unroll 1
            for (int c = 0; c < 3; c++) asm volatile("cp.async.bulk.prefetch.L2.global [%0], 61440;" :: "l"((c == 0 ? ar.wgate : c == 1 ? ar.wup : ar.wdown) + ((blk - 80) * 2 + wg) * 30720) : "memory");
        }
        return;
    }
    const uint64_t ef = policy_stream();
#pragma unroll 1
    for (int b = B_LATE; b < 16; b++) {
        w_flag_wait(b == 15 ? &g_flags.half[kp * 2 + wg] : &g_flags.pair[b * 16 + kp], b == 15 ? 2 : 4);
#pragma unroll 1
        for (int c = 0; c < 3; c++) {
            if (b > B_LATE) mbar_wait(bar + 24 + 8 * c, (b - B_LATE - 1) & 1);
            if (elect()) { mbar_expect(bar + 8 * c, 16384); tma3d_ef(sm + e_slot(wg, c), &mp.o15, b * 128 + wg * 64, kp * 6 + c * 2, bar + 8 * c, ef); }
            __syncwarp();
        }
    }
}
__device__ __forceinline__ void end_stores(const ChainMaps& mp, uint32_t sm, int blk, int wg) {
#pragma unroll 1
    for (int b = B_LATE; b < 16 && blk < 80; b++) {
        bar_sync(12 + wg, 160);
        if (elect()) tma3d_store(&mp.slab2, (b * KSPLIT + blk / 5) * 128 + wg * 64, blk % 5 * 2, sm + E_STG + wg * 16384, 0, false);
        BULK_COMMIT(); BULK_WAIT();
        if (b < 15) bar_arrive(10 + wg, 160);
        GPU_FENCE();
        w_bump(b < 14 ? &g_flags.o[b] : &g_flags.fin[((b - 14) * 2 + wg) * 32]);
    }
    bar_arrive(8, 320);
}
__device__ __forceinline__ void last_blocks(const ChainArgs& ar, uint32_t sm, int blk, int tid) {
    const int warp = __shfl_sync(0xffffffffu, tid >> 5, 0), lane = tid & 31, wg = warp >> 2, w = warp & 3;
    const uint32_t bar = sm + EB_A + wg * 48, stg = sm + E_STG + wg * 16384 + w * 2048;
    bar_sync(5, 384);
    EPT(tid == 128, 7);
    float acc[64];
#pragma unroll
    for (int n = 0; n < 64; n++) acc[n] = 0.f;
#pragma unroll 1
    for (int b = B_LATE; b < 16 && blk < 80; b++) {
#pragma unroll 1
        for (int c = 0; c < 6; c++) {
            mbar_wait(sm + EB_B + 8 * (c >= 3), 0); mbar_wait(bar + 8 * (c >> 1), (b - B_LATE) & 1);
            const uint64_t da = mkdesc(SM_BASE + e_slot(wg, c >> 1) + (c & 1) * 8192, 16, 1024), db = mkdesc(SM_BASE + E_B + (c >= 3 ? 24576 : 0) + c * 8192, 24576, 1024);
            WG_FENCE();
#pragma unroll
            for (int ks = 0; ks < 4; ks++) wgmma_ss_n128_tb(acc, da + ks * 2, db + ks * 128, c | ks);
            WG_COMMIT();
            WG_WAIT(1);
            if ((c & 1) == 0 && c && elect()) mbar_arrive(bar + 16 + 4 * c);
        }
        if (b > B_LATE) bar_sync(10 + wg, 160);
        WG_WAIT(0);
        if (elect()) mbar_arrive(bar + 40);
        EPT(tid == 128, 13 + 15 - b);
        const int r = lane & 7, mi = lane >> 3;
#pragma unroll
        for (int p = 0; p < 8; p++) {
            const int oc = 2 * p + (mi >> 1);
            stsm4(stg + (oc >> 3) * 8192 + ((mi & 1) * 8 + r) * 128 + (((oc & 7) ^ r) << 4), pack2(acc[8 * p], acc[8 * p + 1]), pack2(acc[8 * p + 2], acc[8 * p + 3]),
                  pack2(acc[8 * p + 4], acc[8 * p + 5]), pack2(acc[8 * p + 6], acc[8 * p + 7]));
        }
        PROXY_FENCE();
        bar_arrive(12 + wg, 160);
    }
    bar_sync(8, 320);
    const int o = (tid >> 1) * FF + blk * 16 + (tid & 1) * 8;
    const bf16 *pg = ar.wgate + o, *pu = ar.wup + o, *pd = ar.wdown + tid * DM + (blk < 80 ? blk : 0) * 8;
#pragma unroll
    for (int i = 0; i < 16; i++)
        asm volatile("cp.async.cg.shared.global [%0], [%1], 16;" :: "r"(sm + E_B + i * 4096 + tid * 16), "l"(i < 5 ? pg + i * 128 * FF : i < 10 ? pu + (i - 5) * 128 * FF : pd + (i - 10) * 256 * DM) : "memory");
    EPT(tid == 128, 8);
}
__device__ __forceinline__ void mod_tail(const ChainArgs& ar, const uint32_t tb, const uint32_t bar, const int blk, const int tid) {
#define TPROF(i) EPT(tid == 0, i)
    const int warp = __shfl_sync(0xffffffffu, tid >> 5, 0), lane = tid & 31, r = lane & 7, mi = lane >> 3;
    const uint32_t kb = tb + T_KEY;
    {
        uint32_t k[8];
        for (int n = 0;; n++) {
#pragma unroll
            for (int i = 0; i < 2; i++) asm volatile("ld.relaxed.gpu.global.v4.u32 {%0,%1,%2,%3}, [%4];" : "=r"(k[4 * i]), "=r"(k[4 * i + 1]), "=r"(k[4 * i + 2]), "=r"(k[4 * i + 3]) : "l"(g_key + warp * 256 + i * 128 + lane * 4) : "memory");
            if (__all_sync(0xffffffffu, (k[0] & k[1] & k[2] & k[3] & k[4] & k[5] & k[6] & k[7] & S_TOK) != 0)) break;
            if (n > (1 << 22)) __trap();
            __nanosleep(NAP);
        }
        const uint32_t m = __reduce_max_sync(0xffffffffu, max(umax3(k[0], k[1], k[2]), max(umax3(k[3], k[4], k[5]), max(k[6], k[7]))));
        asm volatile("st.shared.u32 [%0], %1; st.shared.u32 [%2], 0;" :: "r"(kb + warp * 4), "r"(m), "r"(kb + 32) : "memory");
        asm volatile("cp.async.wait_all;" ::: "memory");
        bar_sync(1, 256);
        TPROF(1);
        const uint32_t low = __reduce_min_sync(0xffffffffu, lds32(kb + r * 4));
        uint32_t cnt = 0;
#pragma unroll
        for (int i = 0; i < 8; i++) cnt += k[i] >= low ? 4 : 0;
        if (cnt) {
            uint32_t a; asm volatile("atom.shared.add.u32 %0, [%1], %2;" : "=r"(a) : "r"(kb + 32), "r"(cnt) : "memory");
#pragma unroll
            for (int i = 0; i < 8; i++) if (k[i] >= low) { asm volatile("st.shared.u32 [%0], %1;" :: "r"(kb + 512 + a), "r"(k[i]) : "memory"); a += 4; }
        }
        if (tid == 0) mbar_arrive(bar);
        bar_sync(1, 256);
        const int nc = lds32(kb + 32);
#pragma unroll 1
        for (int c = lane * 4; c < nc; c += 128) {
            const uint32_t me = lds32(kb + 512 + c);
            int rank = 0;
#pragma unroll 2
            for (int e = 0; e < nc; e += 16) {
                const float4 z = lds128f(kb + 512 + e);
                rank += (__float_as_uint(z.x) > me) + (e + 4 < nc && __float_as_uint(z.y) > me) + (e + 8 < nc && __float_as_uint(z.z) > me) + (e + 12 < nc && __float_as_uint(z.w) > me);
            }
            if (rank < 8) asm volatile("st.shared.u32 [%0], %1;" :: "r"(kb + 64 + (warp * 8 + rank) * 4), "r"(me) : "memory");
        }
        __syncwarp();
    }
    const uint32_t k0 = lds32(kb + 64 + (warp * 8 + r) * 4), k1 = lds32(kb + 64 + (warp * 8 + (lane >> 2)) * 4);
    TPROF(2);
    const int trow = ~k1 & (S_TOK - 1), tcol = (blk < 80 ? blk : 0) * 8 + (lane & 3) * 2;
    uint2 xb[5];
#pragma unroll
    for (int h = 0; h < 5; h++) xb[h] = __ldcg((const uint2*)(g_h2 + trow * DM + (warp * 5 + h) * 16 + (lane & 3) * 4));
    const uint32_t fx1 = __ldcg((const uint32_t*)(g_x1 + trow * DM + tcol)), fh2 = __ldcg((const uint32_t*)(g_h2 + trow * DM + tcol)),
                   fgb = __ldcg((const uint32_t*)(g_mod + 5 * DM + tcol));
    const float fr = __uint_as_float(((int)k1 < 0 ? k1 ^ 0x80000000u : ~k1) & 0xffff0000u);
    {
        float dg[4] = {0, 0, 0, 0}, du[4] = {0, 0, 0, 0};
        uint32_t ag[5][4], au[5][4];
#pragma unroll
        for (int h = 0; h < 5; h++) {
            const uint32_t o = tb + ((warp * 5 + h) * 16 + (r >> 1) * 4 + (mi >> 1) * 2 + (r & 1)) * 32 + (mi & 1) * 16;
            ldsm4t(ag[h], o + T_WG); ldsm4t(au[h], o + T_WU);
        }
#pragma unroll
        for (int h = 0; h < 5; h++) { mma16q(dg, ag[h], xb[h].x, xb[h].y); mma16q(du, au[h], xb[h].x, xb[h].y); }
        TPROF(3);
        sts128f(tb + T_RED + warp * 1024 + lane * 16, dg[0], dg[1], dg[2], dg[3]); sts128f(tb + T_RED + warp * 1024 + 512 + lane * 16, du[0], du[1], du[2], du[3]);
    }
    bar_sync(1, 256);
    if (warp < 2) {
        float g2[2] = {0, 0}, u2[2] = {0, 0};
#pragma unroll
        for (int i = 0; i < 8; i++) {
            const float2 a = lds64f(tb + T_RED + i * 1024 + lane * 16 + warp * 8), b = lds64f(tb + T_RED + i * 1024 + 512 + lane * 16 + warp * 8);
            g2[0] += a.x; g2[1] += a.y; u2[0] += b.x; u2[1] += b.y;
        }
        float y[2];
#pragma unroll
        for (int i = 0; i < 2; i++) { const float gq = bfr(g2[i]); y[i] = bfr(__fdividef(gq, 1.f + __expf(-gq))) * bfr(u2[i]); }
        asm volatile("st.relaxed.gpu.global.u32 [%0], %1;" :: "l"(g_gu + (blk >> 1) * 128 + lane * 4 + warp * 2 + (blk & 1)), "r"(movm_t(pack2(y[0], y[1]))) : "memory");
    }
    TPROF(4);
    if (blk < 80) {
        uint32_t a[6][4], b[6][4];
#pragma unroll
        for (int k2 = 0; k2 < 6; k2++) ldsm4t(b[k2], tb + T_WD + (warp * 6 + k2) * 512 + lane * 16);
        for (int n = 0;; n++) {
            uint32_t m = 0;
#pragma unroll
            for (int k2 = 0; k2 < 6; k2++) asm volatile("ld.relaxed.gpu.global.v4.u32 {%0,%1,%2,%3}, [%4];" : "=r"(a[k2][0]), "=r"(a[k2][1]), "=r"(a[k2][2]), "=r"(a[k2][3]) : "l"(g_gu + (warp * 6 + k2) * 128 + lane * 4) : "memory");
#pragma unroll
            for (int k2 = 0; k2 < 6; k2++) m = umax3(umax3(m, a[k2][0], a[k2][1]), a[k2][2], a[k2][3]);
            if (!__any_sync(0xffffffffu, m == ~0u)) break;
            if (n > (1 << 22)) __trap();
        }
        TPROF(5);
        float d[2][4] = {{0, 0, 0, 0}, {0, 0, 0, 0}};
#pragma unroll
        for (int k2 = 0; k2 < 6; k2++) { mma16q(d[0], a[k2], b[k2][0], b[k2][1]); mma16q(d[1], a[k2], b[k2][2], b[k2][3]); }
        asm volatile("st.shared.v2.f32 [%0], {%1,%2};" :: "r"(tb + T_X + warp * 256 + lane * 8), "f"(d[0][0] + d[1][2]), "f"(d[0][1] + d[1][3]) : "memory");
        bar_sync(1, 256);
        if (warp == 0) {
            float y0 = 0, y1 = 0;
#pragma unroll
            for (int i = 0; i < 8; i++) { const float2 z = lds64f(tb + T_X + i * 256 + lane * 8); y0 += z.x; y1 += z.y; }
            const float sg = __fdividef(1.f, 1.f + __expf(-fr));
            *(uint32_t*)(ar.out + trow * DM + tcol) = add2(fx1, mul2(fgb, add2(fh2, mul2(pack2(y0, y1), pack2(sg, sg)))));
        }
    }
    TPROF(6);
}

__global__ void __cluster_dims__(3, 1, 1) __launch_bounds__(384, 1) k_chain(const __grid_constant__ ChainMaps mp, const __grid_constant__ ChainArgs ar) {
    const int D1 = ar.D1, DG = ar.DG;
    extern __shared__ __align__(1024) uint8_t smraw[];
    const uint32_t sm = SM_BASE + ((blockIdx.x % 3) << 24);
    if (smem_u32(smraw) != sm) __trap();
    uint32_t tid; asm volatile("mov.u32 %0, %%tid.x;" : "=r"(tid));
    const int warp = __shfl_sync(0xffffffffu, tid >> 5, 0), lane = tid & 31, wg = warp >> 2, w = warp & 3;
    const int blk = blockIdx.x, head = blk / 3, j = blk % 3;
    const int col0 = head * DH + j * 64;
    asm volatile("griddepcontrol.launch_dependents;");
#define PPROF(i)
    const int r = lane & 7, mi = lane >> 3;
    const uint32_t memrd = opaque(sm + C_MEM + lane * 16);
    if (wg < 2) {
        {
            uint32_t xv[3][10];
            const int row = blk * 8 + warp, nq = row < S_TOK - 1536 ? 3 : 2;
#pragma unroll
            for (int i = 0; i < 15; i++) {
                const uint2 v = __ldcs((const uint2*)(ar.x + (row + (i < 10 || nq == 3 ? i / 5 * 768 : 0)) * DM + lane * 4 + i % 5 * 128));
                xv[i / 5][i % 5 * 2] = v.x; xv[i / 5][i % 5 * 2 + 1] = v.y;
            }
            if (tid == 32) {
#pragma unroll 1
                for (int c = 0; c < 14; c++) if (c != 12) mbar_init(sm + C_BAR + 8 * c, c == 2 ? 5 : c == 3 ? 6 : 1);
                asm volatile("fence.mbarrier_init.release.cluster;" ::: "memory");
                mbar_expect(sm + CB_SC, 2560); mbar_expect(sm + CB_OX, 2048);
            }
            if (warp == 2) {
                const uint32_t f = blk >= 28 ? ~0u : 0u;
                ((uint4*)g_acc)[blk * 32 + lane] = make_uint4(0, 0, 0, 0);
                if (blk < 76) (blk < 12 ? (uint4*)g_stamp + blk * 32 : blk < 28 ? (uint4*)g_key + (blk - 12) * 32 : (uint4*)g_gu + (blk - 28) * 32)[lane] = make_uint4(f, f, f, f);
            }
            __syncwarp();
            asm volatile("barrier.cluster.arrive.relaxed.aligned;" ::: "memory");
            PPROF(8);
#pragma unroll 1
            for (int q = 0; q < 3; q++) {
                uint32_t nv[10];
                ln_norm(xv[0], nv);
#pragma unroll
                for (int i = 0; i < 10; i++) { xv[0][i] = xv[1][i]; xv[1][i] = xv[2][i]; xv[2][i] = nv[i]; }
            }
            PPROF(9);
            if (warp < 5) {
                uint4 u;
                for (int n = 0;; n++) {
                    asm volatile("ld.relaxed.gpu.global.v4.u32 {%0,%1,%2,%3}, [%4];" : "=r"(u.x), "=r"(u.y), "=r"(u.z), "=r"(u.w) : "l"(g_flags.mod1 + tid * 4) : "memory");
                    if (__all_sync(0xffffffffu, u.x && u.y && u.z && u.w)) break;
                    cut(n, 1 << 22);
                }
                asm volatile("st.shared.v4.u32 [%0], {%1,%2,%3,%4};" :: "r"(sm + C_KX + tid * 16), "r"(~u.x), "r"(~u.y), "r"(~u.z), "r"(~u.w) : "memory");
            }
            bar_sync(8, 256);
            PPROF(2);
            uint32_t m = 0;
#pragma unroll
            for (int i = 0; i < 5; i++) {
                uint32_t t[2], u[2];
                lds64(t, sm + C_KX + lane * 8 + i * 256); lds64(u, sm + C_KX + 1280 + lane * 8 + i * 256);
                u[0] = add2(u[0], 0x3f803f80u); u[1] = add2(u[1], 0x3f803f80u);
                m = amax2(amax2(amax2(amax2(m, t[0]), u[0]), t[1]), u[1]);
#pragma unroll
                for (int q = 0; q < 3; q++)
                    if (q < nq) *(uint2*)(g_h + (row + q * 768) * DM + lane * 4 + i * 128) = make_uint2(add2(mul2(xv[q][2 * i], u[0]), t[0]), add2(mul2(xv[q][2 * i + 1], u[1]), t[1]));
            }
            asm volatile("st.shared.u32 [%0], %1;" :: "r"(sm + C_LAG), "r"((amax_warp(m) >> 7) + 1) : "memory");
            bar_sync(8, 256);
            if (tid == 0) flag_add(&g_flags.h);
            __syncwarp();
            bar_arrive(2, 288);
            PPROF(3);
            asm volatile("barrier.cluster.wait.aligned;" ::: "memory");
        }
        asm volatile("setmaxnreg.inc.sync.aligned.u32 %0;" :: "n"(REG_P));
        uint32_t wa[40][4];
        mbar_wait(sm + CB_W, 0);
#pragma unroll
        for (int ks = 0; ks < 40; ks++)
            ldsm4t(wa[ks], sm + ((wg == 0) == (ks < 20) ? C_WV : C_WO) + ((mi >> 1) * 8 + r) * 128 + (((2 * w + (mi & 1)) ^ r) << 4) + (ks % 20 / 4 * 8 + 4 * wg + (ks & 3)) * 2048);
        PPROF(5);
        bar_arrive(1, 288);
        const uint32_t qst = opaque(sm + (wg == 0 ? C_QM : C_KM) + (2 * w + (mi & 1)) * 128 + r * 16);
        const uint32_t vrd = opaque(sm + C_WV + ((mi >> 1) * 8 + r) * 128 + (((2 * w + (mi & 1)) ^ r) << 4) + 4 * wg * 2048);
        const uint32_t mrd = opaque(memrd + wg * 1024);
        float acc[16];
        auto fb = [&](int n) { return mrd + (n >> 1) * 2048 + (n & 1) * 512; };
        auto fa = [&](int k) { return vrd + (k >> 2) * 16384 + (k & 3) * 2048; };
        auto qk_out = [&](int n) {
            uint8_t* rec = g_att + (n * NH + head) * AT_REC;
            w_bulk_s2g(rec + j * 8192, sm + C_QX, 8192); w_bulk_s2g(rec + AT_KM + j * 1024, sm + C_KM, 1024);
            BULK_COMMIT();
        };
        for (int s = -1;; s++) {
          if (s >= 0) {
            x_part(acc, wa, sm, s, wg, w, opaque(mrd) >> 4 & 31, s + ar.D2);
            if (s == 0) mbar_wait(sm + CB_W2, 0);
            uint32_t b[3][4], a[4][4];
#pragma unroll
            for (int i = 0; i < 4; i++) ldsm4t(a[i], fa(4 + i));
            cut(s + ar.D2, 0);
            bar_sync(1, 384);
            if (warp == 0) { PROF(0); PROFG(24); }
            float dv[4] = {0, 0, 0, 0};
            const uint32_t xb = mrd - wg * 1024 - (C_MEM - C_VP) + w * 512;
            {
                float d[2][4] = {{0, 0, 0, 0}, {0, 0, 0, 0}}, g[2][4] = {{0, 0, 0, 0}, {0, 0, 0, 0}};
                ldsm4t(b[0], fb(0)); pin0(mrd); ldsm4t(b[1], fb(1)); pin0(mrd);
#pragma unroll
                for (int n = 0; n < 10; n++) {
                    const int c1 = n >= 10 - NCH;
                    if (n < 8) ldsm4t(b[(n + 2) % 3], fb(n + 2));
#pragma unroll
                    for (int e = 0; e < 2; e++) {
                        mma16q(g[e & c1], wa[20 + 2 * n + e], b[n % 3][2 * e], b[n % 3][2 * e + 1]); mma16q(d[e & c1], wa[2 * n + e], b[n % 3][2 * e], b[n % 3][2 * e + 1]);
                        if (n >= 2 && n < 10 - VT) mma16q(dv, a[(2 * n + e) & 3], b[n % 3][2 * e], b[n % 3][2 * e + 1]);
                        if (n >= 2 && n < 8) ldsm4t(a[(2 * n + e) & 3], fa(2 * n + 4 + e));
                    }
                    if (QCUT >> n & 1) cut(s + ar.D2, 1 + n);
                }
                const float un = __uint_as_float(lds32(sm + C_UN));
                sts128f(xb - 4096 + wg * 2048, g[0][0] + g[1][0], g[0][1] + g[1][1], g[0][2] + g[1][2], g[0][3] + g[1][3]);
#pragma unroll
                for (int k = 20 - 2 * VT; k < 20; k++) mma16q(dv, a[k & 3], b[k / 2 % 3][2 * (k & 1)], b[k / 2 % 3][2 * (k & 1) + 1]);
                bar_sync(8, 256);
                const float4 z = lds128f(xb - 4096 + (wg ^ 1) * 2048);
                sts128f(xb + wg * 2048, dv[0], dv[1], dv[2], dv[3]);
                stsm2t(qst, pack2((d[0][0] + d[1][0] + z.x) * un, (d[0][1] + d[1][1] + z.y) * un), pack2((d[0][2] + d[1][2] + z.z) * un, (d[0][3] + d[1][3] + z.w) * un));
            }
            bar_arrive(2, 384);
            if (w == 0) PROF(1 + wg);
            if (s + 1 == NSEG) break;
          }
          if (warp == 3 && s >= 0)
              asm volatile(ELECTED("st.relaxed.gpu.global.u32 [%0], %1;") :: "l"(g_stamp + (s & 3) * 384 + (blk >> 3) * 32 + (blk & 7)), "r"((gtime() & ~31u) | ((s >> 2) + 1)) : "memory");
          PROXY_FENCE();
          mbar_wait(sm + CB_XF, (s + 1) & 1);
          if (s >= 0) bar_sync(7, 384);
          WG_FENCE();
#pragma unroll
          for (int i = 0; i < 16; i++) acc[i] = 0.f;
#pragma unroll
          for (int i = 1; i <= XA; i++) x_chunk(acc, wa, x_base(wg, s + ar.D2, 20), 20, i, i == 1);
          WG_COMMIT();
          if (warp == FW && s > 0) seg_done(s - 1, head);
          WG_WAIT(0);
          if (s >= 0) {
            if (warp == 0) {
                PROF(7);
                if (elect()) x_rest(mp, sm, s + 1);
            } else {
                if (wg == 1) {
                    if (w == 1) {
                        qk_out(s);
                    }
                    if (w == 2 && blk < 10 && s + 3 < NSEG)
                        asm volatile(ELECTED("cp.async.bulk.prefetch.L2.global [%0], 4096;") :: "l"((const uint8_t*)g_h + (s + 3) * (SEG * DM * 2) + blk * 4096) : "memory");
                } else if (w == 3) {
                    if (SPOLL) wait_until(clock() + SPOLL);
                    const uint32_t l = opaque(mrd) >> 4 & 31, tag = (s >> 2) + 1, now = gtime();
                    const uint32_t* sp = g_stamp + (s & 3) * 384 + (l >> 3) * 32 + (l & 7);
                    uint32_t t[3];
                    for (int n = 0;; n++) {
#pragma unroll
                        for (int i = 0; i < 3; i++) t[i] = ld_rlx(sp + i * 128);
                        if (!__any_sync(0xffffffffu, ((t[0] ^ tag) | (t[1] ^ tag) | (t[2] ^ tag)) & 31) || n > SPIN_LIMIT) break;
                    }
                    int all = -(1 << 30), own = all;
#pragma unroll
                    for (int i = 0; i < 3; i++) { const int d = t[i] - now; all = max(all, d); if ((i * 32 + l) / 3 == head) own = d; }
                    const int lag = min(__reduce_max_sync(0xffffffffu, all) - __reduce_max_sync(0xffffffffu, own), 8000);
                    PROFV(15, lag);
                    asm volatile("st.shared.u32 [%0], %1;" :: "r"(sm + C_LAG), "r"(D1 + ((lag * DG) >> 4)) : "memory");
                    bar_arrive(6, 160);
                } else if (w == 2) {
                    if ((s & 3) == 3) w_flag_wait(&g_flags.v[((s + 1) >> 2) * 32 + head], 2);
                    if (elect()) { mbar_expect(sm + CB_VX, 4096); bulk_g2s(sm + C_VX, g_att + ((s + 1) * NH + head) * AT_REC + AT_V + j * 4096, 4096, sm + CB_VX); }
                    if ((s & 3) == 1 && s + 3 < NSEG) asm volatile("prefetch.global.L2 [%0];" :: "l"(&g_flags.v[((s + 3) >> 2) * 32]));
                    if (s + 2 < NSEG && ((s & 3) != 2 || __all_sync(0xffffffffu, ld_rlx(&g_flags.v[((s + 2) >> 2) * 32 + head]) >= 2)))
                        asm volatile("prefetch.global.L2 [%0];" :: "l"(g_att + ((s + 2) * NH + head) * AT_REC + AT_V + j * 4096 + (opaque(mrd) << 3 & 0xf80)));
                }
            }
          }
        }
        PROXY_FENCE();
        bar_sync(8, 256);
        if (warp == 5) { qk_out(NSEG - 1); BULK_WAIT(); }
        if (warp == 7) seg_done(NSEG - 2, head);
        bar_arrive(7, 384);
        const int t2 = (opaque(mrd) >> 4 & 31) + warp * 32;
        EPT(t2 == 0, 0);
        last_blocks(ar, sm, blk, t2);
        mod_tail(ar, sm + E_B, sm + EB_REL, blk, t2);
    } else {
        asm volatile("setmaxnreg.dec.sync.aligned.u32 %0;" :: "n"(REG_L));
        asm volatile("barrier.cluster.arrive.relaxed.aligned;" ::: "memory");
        if (blk < 80) {
            ModSlice<128> ms;
            ms.load(ar.wmod, ar.c, blk * 16, tid - 256); ms.partial(sm + C_QM, tid - 256);
            bar_sync(3, 128);
            if (w == 0) {
                const uint32_t v = ModSlice<128>::total(sm + C_QM, lane);
                asm volatile("st.relaxed.gpu.global.u32 [%0], %1;" :: "l"(g_flags.mod1 + blk * 8 + (lane & 7)), "r"(~v) : "memory");
            }
        }
        uint32_t m0[5][4], mm = 0;
#pragma unroll
        for (int i = 0; i < 20; i++) {
            const unsigned short* p = (const unsigned short*)ar.mem0 + (i & 3) * 2 * DM + (i >> 2) * 128 + tid - 256;
            m0[i >> 2][i & 3] = __ldg(p) | (uint32_t)__ldg(p + DM) << 16;
        }
        {
            asm volatile("barrier.cluster.wait.aligned;" ::: "memory");
            if (w == 3) {
                w_flag_wait(&g_flags.h, 96);
                if (elect()) { x_fill(mp, sm, 0, j); x_rest(mp, sm, 0); }
                __syncwarp();
            }
            if (w == 1) {
                const uint64_t ef = policy_stream();
#pragma unroll 1
                for (int c = 0; c < 2 * WP + 2; c++) {
                    const uint32_t bar = sm + EB_B + 8 * (c & 1);
                    if (c == WPOS) bar_sync(2, 288);
                    if (c >= 2) mbar_wait(bar, (c / 2 - 1) & 1);
                    if (elect()) {
                        if (c < 2 * WP) { mbar_expect(bar, 81920 / WP); tma2d_ef(sm + C_WV + c * (81920 / WP), c < WP ? &mp.wq : &mp.wk, col0, c % WP * (640 / WP), bar, ef); }
                        if (c >= WOPF && c < WOPF + 3) asm volatile("cp.async.bulk.prefetch.tensor.3d.L2.global [%0, {0, %1, %2}];" :: "l"((uint64_t)&mp.wo), "r"(head * DH + (c - WOPF) * 64), "r"(7 * j) : "memory");
                    }
                    __syncwarp();
                }
                if (elect()) mbar_arrive(sm + CB_W);
                bar_sync(1, 288);
                if (elect()) {
                    mbar_expect(sm + CB_W2, 81920); mbar_expect(sm + CB_W3, 3 * WO_BLK);
#pragma unroll 1
                    for (int c = 0; c < 4; c++) tma2d(sm + C_WV + c * 20480, &mp.wv, col0, c * 160, sm + CB_W2);
#pragma unroll 1
                    for (int c = 0; c < 3; c++) tma3d(sm + C_WO + c * WO_BLK, &mp.wo, head * DH + (j + c) % 3 * 64, 7 * j, sm + CB_W3);
                }
                __syncwarp();
                w_flag_wait(&g_flags.v[head], 2);
                if (elect()) { mbar_expect(sm + CB_VX, 4096); bulk_g2s(sm + C_VX, g_att + head * AT_REC + AT_V + j * 4096, 4096, sm + CB_VX); }
            } else {
                uint32_t mw = 0;
#pragma unroll 1
                for (int c = 0; c < 2; c++) {
                    mbar_wait(sm + (c ? CB_W3 : CB_W2), 0);
                    uint32_t m = 0;
                    const uint32_t end = sm + (c ? C_XR : C_WO);
#pragma unroll 1
                    for (uint32_t a = sm + c * C_WO + (w - (w > 0)) * 4096 + lane * 16; a < end; a += 3 * 4096) {
                        float4 z[8];
#pragma unroll
                        for (int i = 0; i < 8; i++) z[i] = lds128f(a + i * 512);
#pragma unroll
                        for (int i = 0; i < 8; i++) m = amax2(amax2(amax2(amax2(m, __float_as_uint(z[i].x)), __float_as_uint(z[i].y)), __float_as_uint(z[i].z)), __float_as_uint(z[i].w));
                    }
                    mw |= amax_warp(m) << (16 * c);
                }
                asm volatile("st.shared.u32 [%0], %1;" :: "r"(sm + C_KM + w * 4), "r"(mw) : "memory");
                bar_sync(3, 96);
                if (w == 0) asm volatile("st.relaxed.gpu.global.u32 [%0], %1;" :: "l"(g_flags.wmax + blk), "r"(amax2(amax2(mw, lds32(sm + C_KM + 8)), lds32(sm + C_KM + 12)) | 0x8000) : "memory");
            }
        }
        bar_sync(9, 384);
#pragma unroll
        for (int i = 0; i < 5; i++) {
            asm volatile("st.shared.v4.u32 [%0], {%1,%2,%3,%4};" :: "r"(sm + C_MEM + (tid - 256 + i * 128) * 16), "r"(m0[i][0]), "r"(m0[i][1]), "r"(m0[i][2]), "r"(m0[i][3]) : "memory");
            mm = amax2(amax2(amax2(amax2(mm, m0[i][0]), m0[i][1]), m0[i][2]), m0[i][3]);
        }
        asm volatile("st.shared.u32 [%0], %1; st.shared.u32 [%2], 0x3f800000;" :: "r"(sm + C_MX + w * 4), "r"(amax_warp(mm)), "r"(sm + C_UN) : "memory");
        int ew = __shfl_sync(0xffffffffu, lds32(sm + C_LAG), 0), es = 0;
        const uint32_t rb1 = (uint32_t)((j + 1) % 3 - j) << 24, rb2 = (uint32_t)((j + 2) % 3 - j) << 24;
        const float scale = 0.07216878364870322f;
        uint32_t va[8][4], mr = memrd;
#pragma unroll
        for (int i = 0; i < 8; i++) ldsm4t(va[i], sm + C_WV + ((mi >> 1) * 8 + r) * 128 + (((2 * w + (mi & 1)) ^ r) << 4) + i * 2048);
        bar_sync(1, 384);
        for (int s = 0; s < NSEG; s++) {
            const float un = __uint_as_float((127 - es) << 23);
            if (w == 1) {
                mbar_wait(sm + CB_XD, s & 1);
                if (s + 1 < NSEG) { if (elect()) x_fill(mp, sm, s + 1, j); }
                else { if (BPOS != 2) wo_half(mp, sm, blk, 0); if (BPOS != 0) wo_half(mp, sm, blk, 1); }
            }
            const uint32_t l0 = mr >> 4 & 31, r0 = l0 & 7, m0 = l0 >> 3;
            float vd[4];
            {
                uint32_t c[4][4];
#pragma unroll
                for (int i = 0; i < 4; i++) ldsm4t(c[i], mr + i * 512);
                float d[2][4] = {{0, 0, 0, 0}, {0, 0, 0, 0}};
#pragma unroll
                for (int i = 0; i < 8; i++) mma16q(d[i & 1], va[i], c[i >> 1][2 * (i & 1)], c[i >> 1][2 * (i & 1) + 1]);
#pragma unroll
                for (int i = 0; i < 4; i++) vd[i] = d[0][i] + d[1][i];
            }
            uint32_t zr = 0;
            if (w == 2)
                asm volatile("atom.relaxed.gpu.global.exch.b32 %0, [%1], 0;" : "=r"(zr)
                    : "l"(g_acc + ((s & 2) ^ 2) * (ACC_PAIR / 2) + (s & 1) * 512 + (blk >> 2) * 1024 + (blk & 3) * 128 + l0 * 4) : "memory");
            __syncwarp();
            uint32_t kb[4][4];
            {
                const uint32_t k7 = r0 ^ (m0 << 2 & 4), kxrd = sm + C_KX + (16 * (w & 1) + 8 * (m0 & 1) + k7) * 128 + (((m0 >> 1) ^ k7) << 4);
#pragma unroll
                for (int i = 0; i < 4; i++) ldsm4(kb[i], kxrd ^ (i << 5));
            }
            const uint32_t qrd = sm + C_QM + (w == 1 ? (m0 & 1) * 2 + (m0 >> 1) : m0) * 128 + r0 * 16;
            const uint32_t scdst = sm + C_SC + j * 1280 + (w == 1 ? 1024 + l0 * 8 : (w & 1) * 512 + (l0 & 2) * 128 + (l0 >> 2) * 32 + (l0 & 1) * 16);
            const uint32_t scrd = sm + C_SC + (l0 >> 4) * 256 + (l0 & 3) * 32 + (l0 >> 2 & 3) * 8;
            const uint32_t v7 = (4 * (m0 & 1) + (r0 >> 1)) ^ (r0 << 2 & 4), vxrd = sm + C_VX + (16 * (m0 >> 1) + 8 * (r0 & 1) + v7) * 128 + (((2 * w) ^ v7) << 4);
            if (s == 0) {
                uint32_t t[3];
                for (int n = 0;; n++) {
#pragma unroll
                    for (int i = 0; i < 3; i++) t[i] = ld_rlx(g_flags.wmax + l0 + 32 * i);
                    if (__all_sync(0xffffffffu, t[0] && t[1] && t[2])) break;
                    cut(n, 1 << 22);
                }
                const uint32_t m = amax2(amax2(amax2(0, t[0]), t[1]), t[2]);
                const int e = 371 - (int)(__reduce_max_sync(0xffffffffu, m & 0xffffu) >> 7) - (int)(__reduce_max_sync(0xffffffffu, m >> 16) >> 7);
                ew = e << 16 | (min(e - ew, 100) & 0xffff);
            }
            mbar_wait(sm + CB_VX, s & 1);
            uint32_t vb[2][4];
            ldsm4t(vb[0], vxrd); ldsm4t(vb[1], vxrd ^ 16);
            const uint32_t word = sm + C_WO + (m0 & 1) * 4096 + ((m0 >> 1) * 8 + r0) * 64 + ((w ^ (r0 >> 1)) << 4);
            const uint32_t word6 = word + 6 * 4096 - (m0 & 1) * 3072;
            const uint32_t oxrd = sm + C_OX + l0 * 8;
            const uint32_t ord = oxrd + w * 256;
            const uint32_t vp = mr - (C_MEM - C_VP) + w * 512, vmst = mr + (C_VM - C_MEM) + w * 256;
            pin(mr, scdst + rb1, sm + CB_SC + rb1, scdst + rb2, sm + CB_SC + rb2); pin(mr, qrd, scdst, scrd, vp); pin(mr, word, word6, oxrd, ord);
            pin(mr, __float_as_uint(vd[0]), __float_as_uint(vd[1]), __float_as_uint(vd[2]), __float_as_uint(vd[3]));
            bar_sync(2, 384);
            const bool odd = mr & 16;
            float4 y0, y1, mx4;
            {
                uint32_t qa[2][4];
                ldsm4(qa[0], qrd); ldsm4(qa[1], qrd + 512);
                float sc[2][4] = {{0, 0, 0, 0}, {0, 0, 0, 0}};
                if (w == 1) {
                    ldsm4(kb[0], mr + (C_KM - C_MEM)); ldsm4(kb[1], mr + (C_KM - C_MEM) + 512);
                    pin0(mr); y0 = lds128f(vp); y1 = lds128f(vp + 2048); mx4 = lds128f(sm + C_MX);
#pragma unroll
                    for (int k = 0; k < 4; k++) mma16q(sc[k & 1], qa[k >> 1], kb[k >> 1][2 * (k & 1)], kb[k >> 1][2 * (k & 1) + 1]);
                    const uint32_t a0 = __float_as_uint(sc[0][0] + sc[1][2]), a1 = __float_as_uint(sc[0][1] + sc[1][3]);
                    send8(scdst + rb1, sm + CB_SC + rb1, a0, a1); send8(scdst + rb2, sm + CB_SC + rb2, a0, a1);
                    asm volatile("st.shared.v2.u32 [%0], {%1,%2};" :: "r"(scdst), "r"(a0), "r"(a1) : "memory");
                } else {
                    pin0(mr); y0 = lds128f(vp); y1 = lds128f(vp + 2048); mx4 = lds128f(sm + C_MX);
                    if (w) {
#pragma unroll
                        for (int k = 0; k < 4; k++) mma16q(sc[k & 1], kb[k], qa[k >> 1][2 * (k & 1)], qa[k >> 1][2 * (k & 1) + 1]);
                        const float a0 = sc[0][0] + sc[1][0], a1 = sc[0][2] + sc[1][2], a2 = sc[0][1] + sc[1][1], a3 = sc[0][3] + sc[1][3];
                        send16(scdst + rb1, sm + CB_SC + rb1, a0, a1, a2, a3); send16(scdst + rb2, sm + CB_SC + rb2, a0, a1, a2, a3);
                        sts128f(scdst, a0, a1, a2, a3);
                    }
                }
            }
            bar_arrive(7, 384);
            if (elect()) mbar_arrive(sm + CB_SC);
            {
                const float4 z = mx4;
                const int em = (int)(max(max(__float_as_uint(z.x), __float_as_uint(z.y)), max(__float_as_uint(z.z), __float_as_uint(z.w))) >> 7) - es;
                es = __shfl_sync(0xffffffffu, max(min((ew >> 16) - em, (int)(short)ew), -120), 0);
            }
            if (w == 0) PROF(4);
            const uint32_t vm0 = pack2((vd[0] + y0.x + y1.x) * un, (vd[1] + y0.y + y1.y) * un), vm1 = pack2((vd[2] + y0.z + y1.z) * un, (vd[3] + y0.w + y1.w) * un);
            stsm2t(vmst, vm0, vm1);
            if (s + 1 == NSEG) {
                mbar_wait(sm + CB_SC, s & 1);
                PROXY_FENCE();
                bar_sync(3, 128);
                if (w == 1) {
                    w_bulk_s2g(g_att + (s * NH + head) * AT_REC + AT_VM + j * 1024, sm + C_VM, 1024);
                    BULK_COMMIT();
                    BULK_WAIT();
                }
                __syncwarp();
                break;
            }
            cut(s + ar.D2, 0);
            mbar_wait(sm + CB_SC, s & 1);
            if (w == 0) PROF(8);
            float sv[10];
            {
                float2 z[5][3];
#pragma unroll
                for (int u = 0; u < 5; u++)
#pragma unroll
                    for (int p = 0; p < 3; p++) z[u][p] = lds64f((u < 4 ? scrd + (u >> 1) * 512 + (u & 1) * 128 : oxrd + (C_SC - C_OX) + 1024) + p * 1280);
#pragma unroll
                for (int u = 0; u < 5; u++) { sv[2 * u] = (z[u][0].x + z[u][1].x) + z[u][2].x; sv[2 * u + 1] = (z[u][0].y + z[u][1].y) + z[u][2].y; }
            }
            float mx = fmaxf(fmaxf(fmaxf(sv[0], sv[1]), fmaxf(sv[2], sv[3])), fmaxf(fmaxf(fmaxf(sv[4], sv[5]), fmaxf(sv[6], sv[7])), fmaxf(sv[8], sv[9])));
            uint32_t a[NRING][4];
            auto frag = [&](int i) { const int p = i / 7, u = i % 7, o = (p >> 1) * WO_BLK + (p & 1) * 2048;
                                     return u == 3 ? word6 + o : word + o + (u > 3 ? 1024 + (u - 4) * 8192 : u * 8192); };
            mx = fmaxf(fmaxf(mx, __shfl_xor_sync(0xffffffffu, mx, 1)), fmaxf(__shfl_xor_sync(0xffffffffu, mx, 2), __shfl_xor_sync(0xffffffffu, mx, 3)));
            pin(mr, __float_as_uint(mx), 0, 0, 0);
            {
#pragma unroll
                for (int i = 0; i < NPRE; i++) ldsm4t(a[i], frag(i));
                pin0(mr);
                const float sl2e = scale * 1.4426950408889634f, mxl = mx * sl2e;
#pragma unroll
                for (int i = 9; i >= 0; i--) asm volatile("ex2.approx.ftz.f32 %0, %1;" : "=f"(sv[i]) : "f"(fmaf(sv[i], sl2e, -mxl)));
                const uint32_t pq[4] = {pack2(sv[0], sv[1]), pack2(sv[4], sv[5]), pack2(sv[2], sv[3]), pack2(sv[6], sv[7])}, pm = pack2(sv[8], sv[9]);
                if (w == 0) PROF(6);
                float o[2][4] = {{0, 0, 0, 0}, {0, 0, 0, 0}}, o2[2][4] = {{0, 0, 0, 0}, {0, 0, 0, 0}}, sx[4] = {0, 0, 0, 0};
                mma8(sx, pm, 0, 0x3f803f80u); mma8(o[0], pm, 0, vm0); mma8(o[1], pm, 0, vm1);
                mma16q(sx, pq, 0x3f803f80u, 0x3f803f80u);
#pragma unroll
                for (int u = 0; u < 2; u++) { mma16q(o[u], pq, vb[u][0], vb[u][1]); mma16q(o2[u], pq, vb[u][2], vb[u][3]); }
                float inv; asm("rcp.approx.ftz.f32 %0, %1;" : "=f"(inv) : "f"((sx[0] + sx[2]) * __uint_as_float((127 - es) << 23)));
                const uint32_t f0 = pack2((o[0][0] + o2[0][2]) * inv, (o[0][1] + o2[0][3]) * inv), f1 = pack2((o[1][0] + o2[1][2]) * inv, (o[1][1] + o2[1][3]) * inv);
                send8(ord + 2048 + rb1, sm + CB_OX + rb1, f0, f1); send8(ord + 1024 + rb2, sm + CB_OX + rb2, f0, f1);
                asm volatile("st.shared.v2.u32 [%0], {%1,%2};" :: "r"(ord), "r"(f0), "r"(f1) : "memory");
            }
            if (w == 0) PROF(10);
#pragma unroll
            for (int i = NPRE; i < NRING; i++) ldsm4t(a[i], frag(i));
            bar_sync(3, 128);
            float e[5][4];
#pragma unroll
            for (int q = 0; q < 5; q++) e[q][0] = e[q][1] = e[q][2] = e[q][3] = 0.f;
            constexpr int LAG = 2;
            uint8_t* pdst = g_acc + ((s & 2) * (ACC_PAIR / 2) + (s & 1) * 512 + w * 2048 + j * 8192 - C_MEM - sm + mr);
#pragma unroll
            for (int h = 0; h < 3; h++) {
                uint32_t ob[4][2];
                if (h == 1) {
#pragma unroll
                    for (int i = 14 - LAG; i < 14; i++) ldsm4t(a[i % NRING], frag(i + NRING));
                    pin(mr, zr, (uint32_t)(uint64_t)pdst, (uint32_t)((uint64_t)pdst >> 32), 0);
                    mbar_wait(sm + CB_OX, s & 1);
                    if (w == 0) PROF(9);
                }
#pragma unroll
                for (int k = 0; k < 4; k++) lds64(ob[k], oxrd + h * 1024 + k * 256);
#pragma unroll
                for (int i = 14 * h; i < 14 * h + 14; i++) {
                    const int u = i % 7, k = 2 * (i / 7 & 1);
                    if (u == 3) { mma16q(e[3], a[i % NRING], ob[k][0], ob[k][1]); mma16q(e[4], a[i % NRING], ob[k + 1][0], ob[k + 1][1]); }
                    else mma16q(e[u & 3], a[i % NRING], ob[k + (u >> 2)][0], ob[k + (u >> 2)][1]);
                    if (i == B5AT) { pin(mr, a[i % NRING][0], a[i % NRING][1], a[i % NRING][2], a[i % NRING][3]); bar_arrive(5, 384); }
                    if (i >= LAG && !(i >= 14 && i < 14 + LAG) && i - LAG + NRING < 42) ldsm4t(a[(i - LAG) % NRING], frag(i - LAG + NRING));
                }
            }
            {
                const uint32_t w6 = pack2h(e[3][0] + e[4][2], e[3][1] + e[4][3]), one = 0x3c003c00u;
                asm volatile("red.relaxed.gpu.global.add.noftz.v4.f16x2 [%0], {%1,%2,%3,%4};"
                    :: "l"(pdst), "r"(pack2h(e[0][0], e[0][1])), "r"(pack2h(e[0][2], e[0][3])), "r"(pack2h(e[1][0], e[1][1])), "r"(odd ? w6 : one) : "memory");
                asm volatile("red.relaxed.gpu.global.add.noftz.v4.f16x2 [%0], {%1,%2,%3,%4};"
                    :: "l"(pdst + 1024), "r"(pack2h(e[1][2], e[1][3])), "r"(pack2h(e[2][0], e[2][1])), "r"(pack2h(e[2][2], e[2][3])), "r"(odd ? one : w6) : "memory");
            }
            const uint32_t tw = clock();
            if (w == 0) { PROF(14); PROFG(25); }
            PROXY_FENCE();
            bar_sync(6, 160);
            mr = opaque(mr);
            const uint32_t ln = mr >> 4 & 31, due = tw + lds32(sm + C_LAG);
            const uint32_t vr = sm + C_WV + ((ln >> 4) * 8 + (ln & 7)) * 128 + (((2 * w + (ln >> 3 & 1)) ^ (ln & 7)) << 4);
            const uint32_t ms0 = sm + C_MEM + w * 128 + (ln & 7) * 16 + (ln >> 3) * 512, ms1 = ms0 + (ln < 24 ? 2048 : 1536);
            if (BPOS == 2 && w == 0 && s + 2 == NSEG) wo_half(mp, sm, blk, 0);
            if (w == 2) { w_expect(sm + CB_SC, 2560); w_expect(sm + CB_OX, 2048); asm volatile("st.shared.u32 [%0], %1;" :: "r"(sm + C_UN), "r"((127 - es) << 23) : "memory"); }
            if (w == 0) { w_bulk_s2g(g_att + (s * NH + head) * AT_REC + AT_VM + j * 1024, sm + C_VM, 1024); BULK_COMMIT(); }
            const uint8_t* src = pdst - j * 8192;
            pin(mr, ms0, ms1, (uint32_t)(uint64_t)src, (uint32_t)((uint64_t)src >> 32));
            pin(mr, vr, due, 0, 0);
            cut(s + ar.D2, 1);
#pragma unroll
            for (int i = 0; i < 8; i++) ldsm4t(va[i], vr + i * 2048);
            wait_until(due);
            if (w == 0) { PROF(5); PROFG(26); }
            uint4 v[6];
            auto fetch = [&]() {
#pragma unroll
                for (int k = 0; k < 6; k++)
                    asm volatile("ld.relaxed.gpu.global.v4.u32 {%0,%1,%2,%3}, [%4];" : "=r"(v[k].x), "=r"(v[k].y), "=r"(v[k].z), "=r"(v[k].w) : "l"(src + (k >> 1) * 8192 + (k & 1) * 1024) : "memory");
            };
            fetch();
            PROFV(20 + w, 0);
            bar_sync(9, 384);
#pragma unroll 1
            for (int n = 0; __any_sync(0xffffffffu, ~((odd ? v[1].w & v[3].w & v[5].w : v[0].w & v[2].w & v[4].w)) & 0x50005000u); n++) {
                PROFV(20 + w, n + 1);
                cut(n, SPIN_LIMIT);
                fetch();
            }
            uint32_t cv[3][7];
#pragma unroll
            for (int k = 0; k < 3; k++) {
                const uint4 x = v[2 * k], y = v[2 * k + 1];
                const uint32_t u[7] = {x.x, x.y, x.z, y.x, y.y, y.z, k < 2 ? (odd ? x.w : y.w) : 0u};
#pragma unroll
                for (int i = 0; i < 7; i++) cv[k][i] = f16_to_bf16(u[i]);
                stsm4(ms0 + k * 3584, cv[k][0], cv[k][1], cv[k][2], cv[k][3]);
                if (k < 2) stsm4(ms1 + k * 3584, cv[k][4], cv[k][5], cv[k][6], cv[k][6]);
                else asm volatile("stmatrix.sync.aligned.m8n8.x2.shared.b16 [%0], {%1,%2};" :: "r"(ms1 + k * 3584), "r"(cv[k][4]), "r"(cv[k][5]) : "memory");
            }
            if (w == 0) PROF(16);
            bar_sync(1, 384);
            if (w == 0) BULK_WAIT();
            cut(s + ar.D2, 2);
            uint32_t mc = 0;
#pragma unroll
            for (int i = 0; i < 20; i++) mc = amax2(mc, cv[i / 7][i % 7]);
            asm volatile("st.shared.u32 [%0], %1;" :: "r"(sm + C_MX + w * 4), "r"(amax_warp(mc)) : "memory");
        }
        if (w >= 2) end_loads(mp, ar, sm, blk, w - 2);
        else if (w == 1) { bar_sync(5, 384); seg_done(NSEG - 1, head); EPT(true, 9); if (EORD) bar_arrive(6, 96); if (BPOS == 0) wo_half(mp, sm, blk, 1); }
        else bar_arrive(5, 384);
        if (w < 2) end_stores(mp, sm, blk, w);
        if (w == 0) { mbar_wait(sm + EB_REL, 0); flags_release(mr >> 4 & 31); }
    }
}

struct SideMaps { CUtensorMap h, wv, ost, o, wo, slab3, slab2, lnp[3]; };
constexpr int SD_ST = 43008, SD_NST = 4, SD_EPI = SD_NST * SD_ST, SD_PAR = SD_EPI + 2 * 24576, SD_BAR = SD_PAR + 6400, SD_SMEM = SD_BAR + 768;
#define VLEAD 16
#define EARLY15 0
#define N_LIGHT 6
#define B_HELP 13
#define AUNR_ 2
constexpr int AUNR = AUNR_;
#define GEMV 1
#define ORS 1
#define KSO 6
#define KSA 3
#define B_8 10
#define B_16 13
__device__ __forceinline__ int o_shift(int b) { return b >= B_16 ? 4 : b >= B_8 ? 3 : 2; }
__device__ __forceinline__ int o_split(int b) { return 1 << o_shift(b); }
__device__ __forceinline__ uint32_t o_done(int b) { return b >= B_LATE ? 160 : 4 << o_shift(b); }
__device__ __forceinline__ int next_item(int lane) {
    const int b0 = lane & 15, hi = lane >> 4;
    for (int n = 0;; n++) {
        const uint32_t w0 = ld_rlx(g_flags.qk + lane), w1 = ld_rlx(g_flags.at + lane), w2 = ld_rlx(&g_flags.c[0][0] + lane), w3 = ld_rlx(&g_flags.c[2][0] + lane), w4 = ld_rlx(&g_flags.seg[0]);
        const uint32_t o01 = __ballot_sync(0xffffffffu, lane && w2 < 32), o23 = __ballot_sync(0xffffffffu, b0 < (hi ? 14 : B_LATE) && w3 < 2u * o_split(b0));
        const uint32_t ra = __ballot_sync(0xffffffffu, w0 >= (hi ? 64u : 96u)), rb = __ballot_sync(0xffffffffu, w1 >= (hi ? o_done(b0) : 64u));
        const int bv = __ffs(o01 | 0x10000) - 1, ba = __ffs(o01 >> 16 | 0x10000) - 1, bo = __ffs(o23 | 0x10000) - 1, bl = __ffs(o23 >> 16 | 0x10000) - 1;
        if (bl == 16 && ba == 16) return -1;
        const int bc = __ffs(~ra | 0x10000) - 1;
        const bool last = ba == 15 && (w4 >= 3 || (EARLY15 && bc == 15));
        const bool r1 = (ra & ra >> 16) >> ba & 1, r2 = (rb & 0xffff) >> bo & 1, r3 = rb >> 16 >> bl & 1;
        const int kind = ba == 16 ? (bo < 16 ? 2 : 3) : last ? 1 :
                         blockIdx.x < N_LIGHT ? (r1 ? 1 : r3 ? 3 : bv < 16 ? 0 : -1) :
                         bv < 16 && (bv <= bc + VLEAD || !r2) ? 0 : r1 && ba >= B_HELP ? 1 : r2 ? 2 : r1 ? 1 : r3 ? 3 : bo < ba ? 2 : -1;
        if (kind < 0) { if (n > (1 << 20)) __trap(); __nanosleep(300); continue; }
        const int b = kind == 3 ? bl : kind == 2 ? bo : kind == 1 ? ba : bv;
        uint32_t i = 0;
        if (lane == 0) asm volatile("atom.relaxed.gpu.global.add.u32 %0, [%1], 1;" : "=r"(i) : "l"(&g_flags.c[kind][b]) : "memory");
        i = __shfl_sync(0xffffffffu, i, 0);
        if (i < (kind < 2 ? 32u : 2u * o_split(b))) return kind << 16 | b << 8 | i | ((kind == 1 ? r1 : kind == 2 ? r2 : r3) ? 128 : 0);
    }
}

template <int NP, int CH>
__device__ __forceinline__ void tile_out(const float (&acc)[8 * NP], uint32_t eb, uint32_t efull, uint32_t eempty, int& eph, int lane) {
    const int r = lane & 7, mi = lane >> 3, row = (mi & 1) * 8 + r;
    mbar_wait(eempty, eph); eph ^= 1;
#pragma unroll
    for (int p = 0; p < NP; p++) {
        const int oc = 2 * p + (mi >> 1);
        stsm4(eb + (oc >> 3) * CH + row * 128 + (((oc & 7) ^ r) << 4), pack2(acc[8 * p], acc[8 * p + 1]), pack2(acc[8 * p + 2], acc[8 * p + 3]),
              pack2(acc[8 * p + 4], acc[8 * p + 5]), pack2(acc[8 * p + 6], acc[8 * p + 7]));
    }
    asm volatile("fence.proxy.async.shared::cta;" ::: "memory");
    __syncwarp();
    if (lane == 0) mbar_arrive(efull);
}

template <int MT>
__device__ __forceinline__ void attn_tile(uint32_t base, uint32_t dst, uint32_t eempty, int eph, int lane) {
    constexpr int NK = MT ? 5 : 3;
    const int r = lane & 7, mi = lane >> 3, g = lane >> 2, t = lane & 3;
    float sc[NK][4];
#pragma unroll
    for (int n = 0; n < NK; n++) sc[n][0] = sc[n][1] = sc[n][2] = sc[n][3] = 0.f;
#pragma unroll AUNR
    for (int k2 = 0; k2 < 6; k2++) {
        const uint32_t cb = (k2 >> 1) * 8192, c0 = (k2 & 1) * 4;
        uint32_t a0[4], a1[4], bb[NK][4];
        ldsm4(a0, base + cb + (16 * MT + (mi & 1) * 8 + r) * 128 + (((c0 + (mi >> 1)) ^ r) << 4));
        ldsm4(a1, base + cb + (16 * MT + (mi & 1) * 8 + r) * 128 + (((c0 + 2 + (mi >> 1)) ^ r) << 4));
#pragma unroll
        for (int n = 0; n < NK; n++)
            ldsm4(bb[n], n < NK - 1 ? base + 4096 + cb + (8 * n + r) * 128 + (((c0 + mi) ^ r) << 4) : base + 36864 + k2 * 512 + lane * 16);
#pragma unroll
        for (int n = 0; n < NK; n++) mma16(sc[n], a0[0], a0[1], a0[2], a0[3], bb[n][0], bb[n][1]);
#pragma unroll
        for (int n = 0; n < NK; n++) mma16(sc[n], a1[0], a1[1], a1[2], a1[3], bb[n][2], bb[n][3]);
    }
    const float scale = 0.07216878364870322f, l2e = 1.4426950408889634f;
    float v[2][2 * NK], mx[2], sum[2];
#pragma unroll
    for (int hf = 0; hf < 2; hf++) {
        mx[hf] = -INFINITY;
#pragma unroll
        for (int n = 0; n < NK; n++) {
            uint32_t u = pack2(sc[n][2 * hf], sc[n][2 * hf + 1]);
            u = pack2(lo_f(u) * scale, hi_f(u) * scale);
            const int lim = 16 * MT + 8 * hf + g - 8 * n - 2 * t;
            v[hf][2 * n] = (n < NK - 1 && lim < 0) ? -1e9f : lo_f(u);
            v[hf][2 * n + 1] = (n < NK - 1 && lim < 1) ? -1e9f : hi_f(u);
            mx[hf] = fmaxf(mx[hf], fmaxf(v[hf][2 * n], v[hf][2 * n + 1]));
        }
    }
#pragma unroll
    for (int o = 1; o < 4; o <<= 1)
#pragma unroll
        for (int hf = 0; hf < 2; hf++) mx[hf] = fmaxf(mx[hf], __shfl_xor_sync(0xffffffffu, mx[hf], o));
#pragma unroll
    for (int hf = 0; hf < 2; hf++) {
        sum[hf] = 0;
#pragma unroll
        for (int q = 0; q < 2 * NK; q++) { asm("ex2.approx.ftz.f32 %0, %1;" : "=f"(v[hf][q]) : "f"((v[hf][q] - mx[hf]) * l2e)); sum[hf] += v[hf][q]; }
    }
#pragma unroll
    for (int o = 1; o < 4; o <<= 1)
#pragma unroll
        for (int hf = 0; hf < 2; hf++) sum[hf] += __shfl_xor_sync(0xffffffffu, sum[hf], o);
    uint32_t pa[NK][2];
#pragma unroll
    for (int hf = 0; hf < 2; hf++) {
        const float inv = __fdividef(1.f, sum[hf]);
#pragma unroll
        for (int n = 0; n < NK; n++) pa[n][hf] = pack2(v[hf][2 * n] * inv, v[hf][2 * n + 1] * inv);
    }
    mbar_wait(eempty, eph);
#pragma unroll AUNR
    for (int n4 = 0; n4 < 6; n4++) {
        const uint32_t cb = (n4 >> 1) * 4096, c0 = (n4 & 1) * 4;
        uint32_t bm[4], bb[2 + 2 * MT][4];
        ldsm4t(bm, base + AT_VM + n4 * 512 + lane * 16);
#pragma unroll
        for (int u = 0; u < 2 + 2 * MT; u++) ldsm4t(bb[u], base + AT_V + cb + (16 * (u >> 1) + 8 * (mi & 1) + r) * 128 + (((c0 + 2 * (u & 1) + (mi >> 1)) ^ r) << 4));
        float o[4][4];
#pragma unroll
        for (int u = 0; u < 4; u++) { o[u][0] = o[u][1] = o[u][2] = o[u][3] = 0.f; mma8(o[u], pa[NK - 1][0], pa[NK - 1][1], bm[u]); }
#pragma unroll
        for (int u = 0; u < 4 + 4 * MT; u++) mma16(o[u & 3], pa[u >> 2 << 1][0], pa[u >> 2 << 1][1], pa[(u >> 2 << 1) + 1][0], pa[(u >> 2 << 1) + 1][1], bb[u >> 1][2 * (u & 1)], bb[u >> 1][2 * (u & 1) + 1]);
#pragma unroll
        for (int p = 0; p < 2; p++)
            stsm4(dst + (n4 >> 1) * 2048 + ((mi & 1) * 8 + r) * 128 + (((c0 + 2 * p + (mi >> 1)) ^ r) << 4), pack2(o[2 * p][0], o[2 * p][1]), pack2(o[2 * p][2], o[2 * p][3]),
                  pack2(o[2 * p + 1][0], o[2 * p + 1][1]), pack2(o[2 * p + 1][2], o[2 * p + 1][3]));
    }
}

__device__ __forceinline__ uint32_t ln_row(const uint32_t (&as)[10], const uint2 (&xin)[5], int row, uint32_t par, uint32_t low, bf16* out, uint64_t ef, int lane) {
    const uint32_t pa = par + lane * 8;
    uint32_t xv[10], hv[10], sv[10], tv[10];
#pragma unroll
    for (int q = 0; q < 5; q++) {
        uint32_t ga[2], t[2], u[2];
        lds64(ga, pa + q * 256); lds64(t, pa + 1280 + q * 256); lds64(u, pa + 2560 + q * 256);
#pragma unroll
        for (int e = 0; e < 2; e++) {
            xv[2 * q + e] = add2(e ? xin[q].y : xin[q].x, mul2(ga[e], as[2 * q + e]));
            tv[2 * q + e] = t[e]; sv[2 * q + e] = u[e];
        }
    }
    ln_mod(xv, sv, tv, hv);
    float rs = 0;
#pragma unroll
    for (int q = 0; q < 5; q++) {
        const int c = row * DM + lane * 4 + q * 128;
        const uint32_t h0 = hv[2 * q], h1 = hv[2 * q + 1];
        uint32_t gb[2], wv[2];
        lds64(gb, pa + 3840 + q * 256); lds64(wv, pa + 5120 + q * 256);
        rs += (lo_f(h0) * lo_f(wv[0]) + hi_f(h0) * hi_f(wv[0])) + (lo_f(h1) * lo_f(wv[1]) + hi_f(h1) * hi_f(wv[1]));
        st_ef(out + c, make_uint2(add2(xv[2 * q], mul2(gb[0], h0)), add2(xv[2 * q + 1], mul2(gb[1], h1))), ef);
    }
    const uint32_t rb = pack2(0.f, warp_sum(rs));
    const uint32_t key = (((int)rb < 0 ? ~rb : rb | 0x80000000u) & 0xffff0000u) | (uint32_t)(2 * S_TOK - 1 - row);
    if (key > low) {
#pragma unroll
        for (int q = 0; q < 5; q++) {
            *(uint2*)(g_x1 + row * DM + lane * 4 + q * 128) = make_uint2(xv[2 * q], xv[2 * q + 1]);
            *(uint2*)(g_h2 + row * DM + lane * 4 + q * 128) = make_uint2(hv[2 * q], hv[2 * q + 1]);
        }
    }
    return key;
}
__device__ __forceinline__ void key_out(uint32_t key) {
    __syncwarp();
    if (key) asm volatile("st.release.gpu.global.u32 [%0], %1;" :: "l"(g_key + (~key & (S_TOK - 1))), "r"(key) : "memory");
}

__global__ void __launch_bounds__(384, 1) k_side(const __grid_constant__ SideMaps mp, const bf16* __restrict__ x, const bf16* __restrict__ wr, const bf16* wmod, const bf16* cvec, bf16* __restrict__ out) {
    extern __shared__ __align__(1024) uint8_t smraw[];
    const uint32_t sm = smem_u32(smraw);
    if (sm & 1023) __trap();
    const uint32_t FULL = sm + SD_BAR, EMPTY = FULL + 32, EFULL = FULL + 64, EEMPTY = FULL + 80, IFULL = FULL + 96, IEMPTY = FULL + 128, IQ = FULL + 160, SCHED = FULL + 176, PARAM = FULL + 184, ADONE = FULL + 192, LOW = FULL + 224, KEYS = FULL + 256;
    const int tid = threadIdx.x, warp = __shfl_sync(0xffffffffu, tid >> 5, 0), lane = tid & 31;
    const uint64_t ef = policy_stream();
    if (tid == 0) {
        for (int i = 0; i < SD_NST; i++) { mbar_init(FULL + 8 * i, 1); mbar_init(EMPTY + 8 * i, 2); }
        for (int i = 0; i < 2; i++) { mbar_init(EFULL + 8 * i, 4); mbar_init(EEMPTY + 8 * i, 1); }
        for (int i = 0; i < 4; i++) { mbar_init(IFULL + 8 * i, 1); mbar_init(IEMPTY + 8 * i, 11); }
        mbar_init(SCHED, 1); mbar_init(PARAM, 1);
        sts128f(ADONE, 0, 0, 0, 0); sts128f(ADONE + 16, 0, 0, 0, 0); sts128f(LOW, 0, 0, 0, 0);
        asm volatile("fence.mbarrier_init.release.cluster;" ::: "memory");
    }
    if (SDEL) __nanosleep(SDEL);
    __syncthreads();
    if (warp >= 8) {
      asm volatile("setmaxnreg.dec.sync.aligned.u32 40;");
      if (warp == 8) {
        int st = 0, ph = 1;
        for (int q = 0;; q++) {
            mbar_wait(IFULL + 8 * (q & 3), (q >> 2) & 1);
            const int it = __shfl_sync(0xffffffffu, lds32(IQ + 4 * (q & 3)), 0);
            if (elect()) mbar_arrive(IEMPTY + 8 * (q & 3));
            if (it < 0) break;
            const int kind = it >> 16, b = (it >> 8) & 255, i = it & 63;
            const int nst = kind == 0 ? 10 : kind == 1 ? 4 : kind == 2 ? 192 >> o_shift(b) : b == 14 ? 4 : 2;
            const int ksched = kind == 0 ? 4 : kind == 2 ? nst - KSO : (it & 128) ? -1 : kind == 1 ? KSA : 0;
            if (ksched < 0 && elect()) mbar_arrive(SCHED);
            const bool look = !(it & 128);
            if (look && kind == 1) flag_wait(&g_flags.v[b * 32 + i], 2);
            if (look && kind == 3 && b < 14) flag_wait(&g_flags.o[b], o_done(b));
            for (int kb = 0; kb < nst; kb++) {
                mbar_wait(EMPTY + 8 * st, ph);
                const uint32_t base = sm + st * SD_ST, fb = FULL + 8 * st;
                if (look && kind == 1) flag_wait(&g_flags.seg[kb * 32 + i], 3);
                if (kb == ksched && elect()) mbar_arrive(SCHED);
                if (kind == 0) {
                    if (q == 0 && kb == 0) {
                        if (elect()) {
#pragma unroll 1
                            for (int c = 0; c < SD_NST; c++) tma3d(sm + c * SD_ST + 16384, &mp.wv, c * 64, i * 3, FULL + 8 * c);
#pragma unroll 1
                            for (int c = SD_NST; c < SPF; c++)
                                asm volatile("cp.async.bulk.prefetch.tensor.3d.L2.global [%0, {0, %1, %2}];" :: "l"((uint64_t)&mp.wv), "r"(c * 64), "r"(i * 3) : "memory");
                        }
                        flag_wait(&g_flags.h, 96);
                    }
                    if (elect()) {
                        mbar_expect(fb, 40960);
                        tma2d(base, &mp.h, kb * 64, b * 128, fb);
                        if (q || kb >= SD_NST) tma3d(base + 16384, &mp.wv, kb * 64, i * 3, fb);
                    }
                } else if (kind == 1) {
                    if (elect()) {
                        mbar_expect(fb, 43008);
                        asm volatile("cp.async.bulk.shared::cluster.global.mbarrier::complete_tx::bytes.L2::cache_hint [%0], [%1], %2, [%3], %4;"
                            :: "r"(base), "l"(g_att + ((b * 4 + kb) * NH + i) * AT_REC), "r"(AT_REC), "r"(fb), "l"(ef) : "memory");
                    }
                } else if (kind == 3) {
                    if (b == 14 && !(kb & 1)) flag_wait(&g_flags.fin[(kb + (i >> 4)) * 32], 80);
                    if (elect()) { mbar_expect(fb, 40960); tma3d_ef(base, &mp.lnp[o_shift(b) - 2], i * (160 >> o_shift(b)), b * KSPLIT + (kb << o_shift(b) >> 1), fb, ef); }
                } else {
                    const int k0 = ((i >> 1) * nst + kb) * 32;
                    if (elect()) { mbar_expect(fb, 28672); tma3d(base + 8192, &mp.wo, k0, (i & 1) * 5, fb); }
                    if (look && kb % 12 == 0) flag_wait(&g_flags.pair[b * 16 + k0 / 384], 4);
                    if (elect()) tma2d_ef(base, &mp.o, k0, b * 128, fb, ef);
                }
                __syncwarp();
                if (++st == SD_NST) { st = 0; ph ^= 1; }
            }
        }
      } else if (warp == 11) {
        bool fin = false, par = false;
        for (int q = 0;; q++) {
            if (q) mbar_wait(SCHED, (q - 1) & 1);
            int it = fin ? -1 : q == 0 && blockIdx.x < 32 ? (int)blockIdx.x : next_item(lane);
            if (it < 0 && !fin && blockIdx.x < 32) { it = 3 << 16 | 14 << 8 | blockIdx.x; fin = true; }
            if (lane == 0) {
                if (it >> 16 == 3) {
                    const int b = (it >> 8) & 255, nr = 64 >> o_shift(b);
                    asm volatile("cp.async.bulk.prefetch.L2.global [%0], %1;" :: "l"(x + (b * 128 + (it & 63) * nr) * DM), "r"(nr * DM * 2) : "memory");
                }
                mbar_wait(IEMPTY + 8 * (q & 3), ((q >> 2) & 1) ^ 1);
                asm volatile("st.shared.u32 [%0], %1;" :: "r"(IQ + 4 * (q & 3)), "r"(it) : "memory");
                mbar_arrive(IFULL + 8 * (q & 3));
            }
            if (it >> 16 >= 2 && (it >> 8 & 255) >= 2) {
                const uint4* kp = (const uint4*)g_key + max((it >> 8 & 255) - ((it >> 16) == 2 ? 5 : 3), 0) * 32 + lane;
                const uint4 k1 = __ldcg(kp), k2 = __ldcg(kp + 32);
                uint32_t m = max(max(max(k1.x, k1.y), max(k1.z, k1.w)), max(max(k2.x, k2.y), max(k2.z, k2.w)));
                m = max(m, __shfl_xor_sync(0xffffffffu, m, 1)); m = max(m, __shfl_xor_sync(0xffffffffu, m, 2));
                asm volatile("red.shared.max.u32 [%0], %1;" :: "r"(LOW), "r"(__reduce_min_sync(0xffffffffu, m)) : "memory");
            }
            if (!par && it >> 16 == 3) {
                par = true;
                                if (lane == 0) { mbar_expect(PARAM, 6400); bulk_g2s(sm + SD_PAR, g_mod + 2 * DM, 5120, PARAM); bulk_g2s(sm + SD_PAR + 5120, wr, 1280, PARAM); }
            }
            __syncwarp();
            if (it < 0) break;
        }
        flags_release(lane);
      } else {
        if (lane == 0) {
            const int wg = warp - 9; int ph = 0;
            for (int q = 0;; q++) {
                mbar_wait(IFULL + 8 * (q & 3), (q >> 2) & 1);
                const int it = lds32(IQ + 4 * (q & 3));
                mbar_arrive(IEMPTY + 8 * (q & 3));
                if (it < 0) break;
                const int kind = it >> 16, b = (it >> 8) & 255, i = it & 63;
                if (kind == 3 && b == 14) continue;
                if (kind & 1) {
                    for (int n = 0;; n++) {
                        uint32_t d0, d1, d2, d3;
                        asm volatile("ld.volatile.shared.v4.u32 {%0,%1,%2,%3}, [%4];" : "=r"(d0), "=r"(d1), "=r"(d2), "=r"(d3) : "r"(ADONE + wg * 16) : "memory");
                        if (min(min(d0, d1), min(d2, d3)) > q) break;
                        if (n > (1 << 24)) __trap();
                        __nanosleep(40);
                    }
                    GPU_FENCE();
                    EPT(kind == 1 && b == 15 && wg, 17);
                    if (kind == 1) { bump(b == 15 ? &g_flags.half[(i & 30) + wg] : &g_flags.pair[b * 16 + (i >> 1)]); bump(&g_flags.at[b]); }
                    else {
#pragma unroll 1
                        for (int c = 0; c < 8; c++) { const uint32_t key = lds32(KEYS + (q & 7) * 64 + wg * 32 + c * 4); if (key) asm volatile("st.relaxed.gpu.global.u32 [%0], %1;" :: "l"(g_key + (~key & (S_TOK - 1))), "r"(key) : "memory"); }
                    }
                    continue;
                }
#pragma unroll 1
                for (int rd = 0; rd < (kind == 2 ? 2 : 1); rd++) {
                    mbar_wait(EFULL + 8 * wg, ph); ph ^= 1;
                    const uint32_t src = sm + SD_EPI + wg * 24576;
                    if (kind == 2) tma3d_store(rd ? &mp.slab2 : &mp.slab3, (b * KSPLIT + (i >> 1)) * 128 + wg * 64, (i & 1) * 5 + rd * 3, src, ef, false);
                    else {
                        uint8_t* dst = g_att + ((b * 4 + wg * 2) * NH + i) * AT_REC + AT_V;
                        asm volatile("cp.async.bulk.global.shared::cta.bulk_group.L2::cache_hint [%0], [%1], 12288, %2;" :: "l"(dst), "r"(src), "l"(ef) : "memory");
                        asm volatile("cp.async.bulk.global.shared::cta.bulk_group.L2::cache_hint [%0], [%1], 12288, %2;" :: "l"(dst + NH * AT_REC), "r"(src + 12288), "l"(ef) : "memory");
                    }
                    asm volatile("cp.async.bulk.commit_group;" ::: "memory");
                    asm volatile("cp.async.bulk.wait_group.read 0;" ::: "memory");
                    mbar_arrive(EEMPTY + 8 * wg);
                }
                asm volatile("cp.async.bulk.wait_group 0;" ::: "memory");
                GPU_FENCE();
                bump(kind == 0 ? &g_flags.v[b * 32 + i] : &g_flags.o[b]);
                if (kind == 0) bump(&g_flags.vb[b]);
            }
        }
      }
    } else {
        asm volatile("setmaxnreg.inc.sync.aligned.u32 232;");
        const int wg = warp >> 2, w = warp & 3;
        int st = 0, ph = 0, eph = 1;
        bool att = false;
        if (blockIdx.x < 32 * GEMV) {
            const uint32_t buf = sm + SD_EPI;
#pragma unroll 1
            for (int k = tid; k < DM; k += 256) {
                const float f = __uint_as_float((uint32_t)__ldg((const unsigned short*)cvec + k) << 16);
                asm volatile("st.shared.f32 [%0], %1;" :: "r"(buf + k * 4), "f"(bfr(__fdividef(f, 1.f + __expf(-f)))) : "memory");
            }
            const int t = min(tid, 199), k0 = t / 10 * 32;
            const bf16* wm = wmod + k0 * (6 * DM) + 2 * DM + blockIdx.x * 80 + t % 10 * 8;
            float a[8] = {0, 0, 0, 0, 0, 0, 0, 0};
#pragma unroll 1
            for (int k = 0; k < 32; k += 8) {
                uint4 z[8];
#pragma unroll
                for (int e = 0; e < 8; e++) z[e] = __ldcs((const uint4*)(wm + (k + e) * (6 * DM)));
                if (k == 0) bar_sync(1, 256);
#pragma unroll
                for (int e = 0; e < 8; e++) {
                    const float f = __uint_as_float(lds32(buf + (k0 + k + e) * 4));
                    a[0] += f * lo_f(z[e].x); a[1] += f * hi_f(z[e].x); a[2] += f * lo_f(z[e].y); a[3] += f * hi_f(z[e].y);
                    a[4] += f * lo_f(z[e].z); a[5] += f * hi_f(z[e].z); a[6] += f * lo_f(z[e].w); a[7] += f * hi_f(z[e].w);
                }
            }
            sts128f(buf + 4096 + t * 32, a[0], a[1], a[2], a[3]); sts128f(buf + 4112 + t * 32, a[4], a[5], a[6], a[7]);
            bar_sync(1, 256);
            if (tid < 40) {
                float a0 = 0, a1 = 0;
#pragma unroll 4
                for (int g = 0; g < 20; g++) { const float2 v = lds64f(buf + 4096 + g * 320 + tid * 8); a0 += v.x; a1 += v.y; }
                ((uint32_t*)(g_mod + 2 * DM + blockIdx.x * 80))[tid] = pack2(a0, a1);
            }
            bar_sync(1, 256);
        }
        const uint32_t eb = sm + SD_EPI + wg * 24576;
        for (int q = 0;; q++) {
            mbar_wait(IFULL + 8 * (q & 3), (q >> 2) & 1);
            const int itc = lds32(IQ + 4 * (q & 3));
            __syncwarp();
            if (lane == 0) mbar_arrive(IEMPTY + 8 * (q & 3));
            if (itc < 0) break;
            const int kind = itc >> 16, b = (itc >> 8) & 255, i = itc & 63;
            if (att && kind != 1) { bar_sync(1, 256); att = false; }
            if (kind == 0) {
                float acc[96];
#pragma unroll
                for (int n = 0; n < 96; n++) acc[n] = 0.f;
                int prev = -1;
#pragma unroll 1
                for (int kb = 0; kb < 10; kb++) {
                    mbar_wait(FULL + 8 * st, ph);
                    const uint32_t base = sm + st * SD_ST;
                    WG_FENCE();
#pragma unroll
                    for (int ks = 0; ks < 4; ks++)
                        wgmma_ss_n192_tb(acc, mkdesc(base + wg * 8192 + ks * 32, 16, 1024), mkdesc(base + 16384 + ks * 2048, 8192, 1024), (kb | ks) != 0);
                    WG_COMMIT();
                    WG_WAIT(1);
                    if (prev >= 0 && (tid & 127) == 0) mbar_arrive(EMPTY + 8 * prev);
                    prev = st;
                    if (++st == SD_NST) { st = 0; ph ^= 1; }
                }
                WG_WAIT(0);
                if ((tid & 127) == 0) mbar_arrive(EMPTY + 8 * prev);
                tile_out<12, 4096>(acc, eb + (w >> 1) * 12288 + (w & 1) * 2048, EFULL + 8 * wg, EEMPTY + 8 * wg, eph, lane);
            } else if (kind == 1) {
                const int seg = warp >> 1, mt = warp & 1;
                int sst = st + seg, sph = ph; if (sst >= SD_NST) { sst -= SD_NST; sph ^= 1; }
                ph ^= 1;
                mbar_wait(FULL + 8 * sst, sph);
                EPT(tid == 224 && b == 15, 16);
                const uint32_t base = sm + sst * SD_ST;
                if (mt) attn_tile<1>(base, eb + w * 6144, EEMPTY + 8 * wg, eph, lane);
                else attn_tile<0>(base, eb + w * 6144, EEMPTY + 8 * wg, eph, lane);
                asm volatile("fence.proxy.async.shared::cta;" ::: "memory");
                __syncwarp();
                if (lane == 0) {
                    mbar_arrive(EMPTY + 8 * sst);
                    tma3d_store(&mp.ost, b * 128 + warp * 16, i * 3, eb + w * 6144, ef, false);
                    BULK_COMMIT(); BULK_WAIT();
                    asm volatile("st.release.cta.shared.u32 [%0], %1;" :: "r"(ADONE + warp * 4), "r"(q + 1) : "memory");
                }
                __syncwarp();
                att = true;
            } else if (kind == 2) {
                float acc[96], acc2[64];
#pragma unroll
                for (int n = 0; n < 96; n++) acc[n] = 0.f;
#pragma unroll
                for (int n = 0; n < 64; n++) acc2[n] = 0.f;
                int prev = -1;
                const uint32_t ao = (wg * 64 + w * 16 + (lane & 15)) * 64 + (((lane >> 4) ^ (lane >> 1 & 3)) << 4);
#pragma unroll 1
                for (int kb = 96 >> o_shift(b); kb > 0; kb--) {
#pragma unroll
                    for (int u = 0; u < 2; u++) {
                        const uint32_t base = sm + st * SD_ST;
                        uint32_t af[2][4];
                        mbar_wait(FULL + 8 * st, ph);
                        ldsm4(af[0], base + ao); ldsm4(af[1], base + (ao ^ 32));
                        WG_FENCE();
#pragma unroll
                        for (int ks = 0; ks < 2; ks++) {
                            wgmma_rs_n192_tb(acc, af[ks], mkdesc(base + 8192 + ks * 2048, 4096, 1024), 1);
                            wgmma_rs_n128_tb(acc2, af[ks], mkdesc(base + 8192 + 3 * 4096 + ks * 2048, 4096, 1024), 1);
                        }
                        WG_COMMIT();
                        WG_WAIT(1);
                        if (prev >= 0 && (tid & 127) == 0) mbar_arrive(EMPTY + 8 * prev);
                        prev = st;
                        if (++st == SD_NST) { st = 0; ph ^= 1; }
                    }
                }
                WG_WAIT(0);
                if ((tid & 127) == 0) mbar_arrive(EMPTY + 8 * prev);
                tile_out<12, 8192>(acc, eb + w * 2048, EFULL + 8 * wg, EEMPTY + 8 * wg, eph, lane);
                tile_out<8, 8192>(acc2, eb + w * 2048, EFULL + 8 * wg, EEMPTY + 8 * wg, eph, lane);
            } else {
                const int sh = o_shift(b), nr = 64 >> sh, fw = b == 14 ? wg : 0, row0 = (b + fw) * 128 + i * nr, lw = warp - 4 * fw;
                if (fw) { st += 2; if (st >= SD_NST) { st -= SD_NST; ph ^= 1; } }
                int st1 = st + 1, ph1 = ph; if (st1 == SD_NST) { st1 = 0; ph1 ^= 1; }
                uint2 xin[2][5];
                uint32_t as[2][10] = {};
#pragma unroll
                for (int q2 = 0; q2 < 10; q2++) xin[q2 & 1][q2 >> 1] = ld_ef(x + (row0 + ((warp + 8 * (q2 & 1)) & (nr - 1))) * DM + lane * 4 + (q2 >> 1) * 128, ef);
                mbar_wait(PARAM, 0); mbar_wait(FULL + 8 * st, ph); mbar_wait(FULL + 8 * st1, ph1);
                EPT((tid & 127) == 0 && b == 14, 18 + wg);
#pragma unroll 1
                for (int lrow = lw + (nr & 16) / 2; lrow >= 0 && lrow < nr; lrow -= 8) {
                    float a[20];
#pragma unroll
                    for (int q2 = 0; q2 < 20; q2++) a[q2] = 0.f;
#pragma unroll 1
                    for (int k = 0; k < (1 << sh >> 1); k++) {
                        const uint32_t ad = sm + ((k << (6 - sh)) + lrow) * 1280 + lane * 8;
                        uint32_t z[10][2];
#pragma unroll
                        for (int q2 = 0; q2 < 10; q2++) lds64(z[q2], ad + (q2 < 5 ? st : st1) * SD_ST + q2 % 5 * 256);
#pragma unroll
                        for (int q2 = 0; q2 < 10; q2++) { float* p = a + q2 % 5 * 4; p[0] += lo_f(z[q2][0]); p[1] += hi_f(z[q2][0]); p[2] += lo_f(z[q2][1]); p[3] += hi_f(z[q2][1]); }
                    }
#pragma unroll
                    for (int q2 = 0; q2 < 10; q2++) { as[1][q2] = as[0][q2]; as[0][q2] = pack2(a[2 * q2], a[2 * q2 + 1]); }
                }
                bar_sync(2 + wg, 128);
                if ((tid & 127) == 0) { mbar_arrive(EMPTY + 8 * st); mbar_arrive(EMPTY + 8 * st1); }
                uint32_t key = 0;
#pragma unroll 1
                for (int lrow = lw; lrow < nr; lrow += 8) {
                    const int row = row0 + lrow;
                    const uint32_t k1 = ln_row(as[0], xin[0], row, sm + SD_PAR, lds32(LOW), out, ef, lane);
                    if (lane == lrow >> 3) key = k1;
#pragma unroll
                    for (int q2 = 0; q2 < 5; q2++) { as[0][2 * q2] = as[1][2 * q2]; as[0][2 * q2 + 1] = as[1][2 * q2 + 1]; xin[0][q2] = xin[1][q2]; }
                }
                if (b == 14) { EPT(tid == 128, 20); key_out(key); EPT(tid == 128, 21); }
                else {
                    if (lane < 2) asm volatile("st.shared.u32 [%0], %1;" :: "r"(KEYS + (q & 7) * 64 + warp * 8 + lane * 4), "r"(key) : "memory");
                    __syncwarp();
                    if (lane == 0) asm volatile("st.release.cta.shared.u32 [%0], %1;" :: "r"(ADONE + warp * 4), "r"(q + 1) : "memory");
                }
                st = st1 + 1; ph = ph1; if (st == SD_NST) { st = 0; ph ^= 1; }
            }
        }
    }
    __syncwarp();
    asm volatile("griddepcontrol.wait;" ::: "memory");
}

#define P_D1 550
#define P_DL 700
#define P_DG 29
typedef CUresult (*EncodeFn)(CUtensorMap*, CUtensorMapDataType, cuuint32_t, void*, const cuuint64_t*, const cuuint64_t*, const cuuint32_t*, const cuuint32_t*,
                             CUtensorMapInterleave, CUtensorMapSwizzle, CUtensorMapL2promotion, CUtensorMapFloatOOBfill);
static EncodeFn s_encode = nullptr;
static void make_map(CUtensorMap* m, const void* p, int rows, int cols, int box_rows, int box_cols = 64) {
    cuuint64_t dims[2] = {(cuuint64_t)cols, (cuuint64_t)rows}, strides[1] = {(cuuint64_t)cols * 2};
    cuuint32_t box[2] = {(cuuint32_t)box_cols, (cuuint32_t)box_rows}, es[2] = {1, 1};
    s_encode(m, CU_TENSOR_MAP_DATA_TYPE_BFLOAT16, 2, (void*)p, dims, strides, box, es, CU_TENSOR_MAP_INTERLEAVE_NONE,
             box_cols == 64 ? CU_TENSOR_MAP_SWIZZLE_128B : box_cols == 32 ? CU_TENSOR_MAP_SWIZZLE_64B : CU_TENSOR_MAP_SWIZZLE_NONE, CU_TENSOR_MAP_L2_PROMOTION_L2_256B, CU_TENSOR_MAP_FLOAT_OOB_FILL_NONE);
}
static void make_map3(CUtensorMap* m, const void* p, int rows, int cols, int box_rows, int box_chunks, int cw = 64) {
    cuuint64_t dims[3] = {(cuuint64_t)cw, (cuuint64_t)rows, (cuuint64_t)(cols / cw)}, strides[2] = {(cuuint64_t)cols * 2, (cuuint64_t)cw * 2};
    cuuint32_t box[3] = {(cuuint32_t)cw, (cuuint32_t)box_rows, (cuuint32_t)box_chunks}, es[3] = {1, 1, 1};
    s_encode(m, CU_TENSOR_MAP_DATA_TYPE_BFLOAT16, 3, (void*)p, dims, strides, box, es, CU_TENSOR_MAP_INTERLEAVE_NONE,
             cw == 64 ? CU_TENSOR_MAP_SWIZZLE_128B : CU_TENSOR_MAP_SWIZZLE_64B, CU_TENSOR_MAP_L2_PROMOTION_L2_256B, CU_TENSOR_MAP_FLOAT_OOB_FILL_NONE);
}
template <typename T> static void* sym(T& s) { void* p = nullptr; cudaGetSymbolAddress(&p, s); return p; }

extern "C" void kernel_launch(void* const* d_in, const int* in_sizes, int n_in, void* d_out, int out_size) {
    const bf16 *x = (const bf16*)d_in[0], *mem0 = (const bf16*)d_in[1], *Wq = (const bf16*)d_in[2], *Wk = (const bf16*)d_in[3],
               *Wv = (const bf16*)d_in[4], *Wo = (const bf16*)d_in[5], *wr = (const bf16*)d_in[8], *wgate = (const bf16*)d_in[9],
               *wup = (const bf16*)d_in[10], *wdown = (const bf16*)d_in[11], *c = (const bf16*)d_in[12], *wmod = (const bf16*)d_in[13];
    bf16* out = (bf16*)d_out;
    if (!s_encode) {
        cudaDriverEntryPointQueryResult qr;
        cudaGetDriverEntryPoint("cuTensorMapEncodeTiled", (void**)&s_encode, cudaEnableDefault, &qr);
        cudaFuncSetAttribute(k_side, cudaFuncAttributeMaxDynamicSharedMemorySize, SD_SMEM);
        cudaFuncSetAttribute(k_chain, cudaFuncAttributeMaxDynamicSharedMemorySize, C_SMEM);
    }
    ChainMaps cm; SideMaps sd;
    make_map(&sd.h, sym(g_h), S_TOK, DM, 128); make_map3(&sd.wv, Wv, DM, HD, 64, 3);
    make_map3(&sd.ost, sym(g_o), S_TOK, HD, 16, 3); make_map(&sd.o, sym(g_o), S_TOK, HD, 128, 32); make_map3(&sd.wo, Wo, HD, DM, 32, 5);
    make_map3(&sd.slab3, sym(g_slab), 16 * KSPLIT * 128, DM, 64, 3); make_map3(&sd.slab2, sym(g_slab), 16 * KSPLIT * 128, DM, 64, 2);
    make_map3(&cm.wo15, Wo, HD, DM, 192, 2); make_map3(&cm.o15, sym(g_o), S_TOK, HD, 64, 2); cm.slab2 = sd.slab2;
    for (int i = 0; i < 3; i++) {
        cuuint64_t dims[3] = {256, 320, 16 * KSPLIT}, strides[2] = {512, 128 * DM * 2};
        cuuint32_t box[3] = {256, 40u >> i, 2u << i}, es[3] = {1, 1, 1};
        s_encode(&sd.lnp[i], CU_TENSOR_MAP_DATA_TYPE_BFLOAT16, 3, sym(g_slab), dims, strides, box, es, CU_TENSOR_MAP_INTERLEAVE_NONE,
                 CU_TENSOR_MAP_SWIZZLE_NONE, CU_TENSOR_MAP_L2_PROMOTION_L2_256B, CU_TENSOR_MAP_FLOAT_OOB_FILL_NONE);
    }
    make_map(&cm.wq, Wq, DM, HD, 640 / WP); make_map(&cm.wk, Wk, DM, HD, 640 / WP); make_map(&cm.wv, Wv, DM, HD, 160); make_map3(&cm.wo, Wo, HD, DM, 64, 7, 32);
    make_map3(&cm.h2, sym(g_h), S_TOK, DM, 32, 2);
    ChainArgs ar = {x, mem0, c, wmod, Wv, Wo, wgate, wup, wdown, out, P_D1, P_DL, P_DG};
    k_chain<<<96, 384, C_SMEM>>>(cm, ar);
    cudaLaunchConfig_t cfg = {};
    cfg.gridDim = dim3(N_SIDE); cfg.blockDim = dim3(384); cfg.dynamicSmemBytes = SD_SMEM; cfg.stream = cudaStreamPerThread;
    cudaLaunchAttribute at[1]; at[0].id = cudaLaunchAttributeProgrammaticStreamSerialization; at[0].val.programmaticStreamSerializationAllowed = 1;
    cfg.attrs = at; cfg.numAttrs = 1;
    cudaLaunchKernelEx(&cfg, k_side, sd, x, wr, wmod, c, out);
}
```

```cpp
#include <cuda_runtime.h>
#include <cuda_bf16.h>
#include <cuda.h>
#include <stdint.h>
#include <stdio.h>
#include <string.h>
#include <stdlib.h>

typedef __nv_bfloat16 bf16;
constexpr int S_TOK = 2048, DM = 640, NH = 32, DH = 192, HD = NH * DH, NSEG = 64, SEG = 32, FF = 1536;

__device__ bf16 g_mod[6 * DM];
__device__ bf16 g_h[S_TOK * DM];
constexpr int AT_REC = 43008, AT_V = 24576, AT_KM = 36864, AT_VM = 39936;
__device__ __align__(1024) uint8_t g_att[NSEG * NH * AT_REC];
__device__ bf16 g_o[S_TOK * HD];
__device__ bf16 g_A[S_TOK * DM];
__device__ bf16 g_x1[S_TOK * DM];
__device__ bf16 g_h2[S_TOK * DM];
__device__ __align__(128) uint32_t g_key[S_TOK];
__device__ int g_idx[8];
__device__ __align__(128) uint32_t g_gu[FF / 8 * 32];
constexpr int ACC_PAIR = 24 * 1024;
__device__ __align__(1024) uint8_t g_acc[2 * ACC_PAIR];
__device__ __align__(1024) uint32_t g_stamp[4 * 12 * 32];
constexpr int KSPLIT = 16;
__device__ bf16 g_slab[16 * KSPLIT * 128 * DM];
struct __align__(128) Flags {
    uint32_t qk[16], vb[16];
    uint32_t at[16], o[16];
    uint32_t c[4][16];
    uint32_t half[32];
    uint32_t fin[4 * 32];
    uint32_t v[16 * 32];
    uint32_t seg[4 * 32];
    uint32_t pair[16 * 16];
    uint32_t h, pad2[31], done, mod, pad3[30];
    uint32_t mod1[DM];
    uint32_t wmax[96];
};
__device__ Flags g_flags;
#define EPT(c, i)

__device__ __forceinline__ uint32_t smem_u32(const void* p) { return (uint32_t)__cvta_generic_to_shared(p); }
__device__ __forceinline__ uint32_t pack2(float lo, float hi) {
    uint32_t r; asm("cvt.rn.bf16x2.f32 %0, %1, %2;" : "=r"(r) : "f"(hi), "f"(lo)); return r;
}
__device__ __forceinline__ float bfr(float x) { return __uint_as_float(pack2(0.f, x)); }
__device__ __forceinline__ float inv_std(float var) {
    float s, r; asm("sqrt.approx.f32 %0, %1;" : "=f"(s) : "f"(bfr(bfr(var) + 1e-5f))); asm("rcp.approx.f32 %0, %1;" : "=f"(r) : "f"(bfr(s))); return r;
}
__device__ __forceinline__ float lo_f(uint32_t v) { return __uint_as_float(v << 16); }
__device__ __forceinline__ float hi_f(uint32_t v) { return __uint_as_float(v & 0xffff0000u); }
__device__ __forceinline__ void mbar_init(uint32_t bar, int cnt) { asm volatile("mbarrier.init.shared::cta.b64 [%0], %1;" :: "r"(bar), "r"(cnt) : "memory"); }
__device__ __forceinline__ void mbar_expect(uint32_t bar, int bytes) { asm volatile("mbarrier.arrive.expect_tx.shared::cta.b64 _, [%0], %1;" :: "r"(bar), "r"(bytes) : "memory"); }
__device__ __forceinline__ void mbar_arrive(uint32_t bar) { asm volatile("mbarrier.arrive.shared::cta.b64 _, [%0];" :: "r"(bar) : "memory"); }
__device__ __forceinline__ bool mbar_try(uint32_t bar, int par) {
    uint32_t ok; asm volatile("{ .reg .pred p; mbarrier.try_wait.parity.shared::cta.b64 p, [%1], %2; selp.u32 %0, 1, 0, p; }" : "=r"(ok) : "r"(bar), "r"(par) : "memory"); return ok;
}
__device__ __forceinline__ bool mbar_try_cluster(uint32_t bar, int par) {
    uint32_t ok; asm volatile("{ .reg .pred p; mbarrier.try_wait.parity.acquire.cluster.shared::cta.b64 p, [%1], %2; selp.u32 %0, 1, 0, p; }" : "=r"(ok) : "r"(bar), "r"(par) : "memory"); return ok;
}
__device__ __forceinline__ bool mbar_test(uint32_t bar, uint32_t par) {
    uint32_t ok; asm volatile("{ .reg .pred p; mbarrier.test_wait.parity.shared::cta.b64 p, [%1], %2; selp.u32 %0, 1, 0, p; }" : "=r"(ok) : "r"(bar), "r"(par) : "memory"); return ok;
}
constexpr int SPIN_LIMIT = 1 << 18;
__device__ __forceinline__ void mbar_wait(uint32_t bar, uint32_t par) {
    asm volatile("{ .reg .pred p, q; .reg .u32 n; mov.u32 n, 0;\n"
                 "W_%=: mbarrier.try_wait.parity.shared::cta.b64 p, [%0], %1;\n"
                 "@p bra.uni D_%=;\n"
                 "add.u32 n, n, 1; setp.lt.u32 q, n, 0x200000; @q bra.uni W_%=;\n"
                 "trap;\n"
                 "D_%=: }" :: "r"(bar), "r"(par) : "memory");
}
__device__ __forceinline__ void tma2d(uint32_t dst, const CUtensorMap* m, int c0, int c1, uint32_t bar) {
    asm volatile("cp.async.bulk.tensor.2d.shared::cluster.global.mbarrier::complete_tx::bytes [%0], [%1, {%3, %4}], [%2];"
        :: "r"(dst), "l"((uint64_t)m), "r"(bar), "r"(c0), "r"(c1) : "memory");
}
__device__ __forceinline__ void tma2d_mc(uint32_t dst, const CUtensorMap* m, int c0, int c1, uint32_t bar, uint16_t mask) {
    asm volatile("cp.async.bulk.tensor.2d.shared::cluster.global.mbarrier::complete_tx::bytes.multicast::cluster [%0], [%1, {%3, %4}], [%2], %5;"
        :: "r"(dst), "l"((uint64_t)m), "r"(bar), "r"(c0), "r"(c1), "h"(mask) : "memory");
}
__device__ __forceinline__ uint64_t policy_stream() { uint64_t p; asm("createpolicy.fractional.L2::evict_first.b64 %0, 1.0;" : "=l"(p)); return p; }
__device__ __forceinline__ void tma2d_ef(uint32_t dst, const CUtensorMap* m, int c0, int c1, uint32_t bar, uint64_t pol) {
    asm volatile("cp.async.bulk.tensor.2d.shared::cluster.global.mbarrier::complete_tx::bytes.L2::cache_hint [%0], [%1, {%3, %4}], [%2], %5;"
        :: "r"(dst), "l"((uint64_t)m), "r"(bar), "r"(c0), "r"(c1), "l"(pol) : "memory");
}
__device__ __forceinline__ void tma3d(uint32_t dst, const CUtensorMap* m, int row, int chunk, uint32_t bar) {
    asm volatile("cp.async.bulk.tensor.3d.shared::cluster.global.mbarrier::complete_tx::bytes [%0], [%1, {0, %3, %4}], [%2];"
        :: "r"(dst), "l"((uint64_t)m), "r"(bar), "r"(row), "r"(chunk) : "memory");
}
__device__ __forceinline__ void tma3d_ef(uint32_t dst, const CUtensorMap* m, int row, int chunk, uint32_t bar, uint64_t pol) {
    asm volatile("cp.async.bulk.tensor.3d.shared::cluster.global.mbarrier::complete_tx::bytes.L2::cache_hint [%0], [%1, {0, %3, %4}], [%2], %5;"
        :: "r"(dst), "l"((uint64_t)m), "r"(bar), "r"(row), "r"(chunk), "l"(pol) : "memory");
}
__device__ __forceinline__ void tma3d_store(const CUtensorMap* m, int row, int chunk, uint32_t src, uint64_t pol, bool hint) {
    if (hint) asm volatile("cp.async.bulk.tensor.3d.global.shared::cta.bulk_group.L2::cache_hint [%0, {0, %2, %3}], [%1], %4;"
        :: "l"((uint64_t)m), "r"(src), "r"(row), "r"(chunk), "l"(pol) : "memory");
    else asm volatile("cp.async.bulk.tensor.3d.global.shared::cta.bulk_group [%0, {0, %2, %3}], [%1];"
        :: "l"((uint64_t)m), "r"(src), "r"(row), "r"(chunk) : "memory");
}
__device__ __forceinline__ bool elect() { uint32_t p; asm volatile("{ .reg .pred e; elect.sync _|e, -1; selp.u32 %0, 1, 0, e; }" : "=r"(p)); return p; }
__device__ __forceinline__ uint2 ld_ef(const void* p, uint64_t pol) {
    uint2 v; asm volatile("ld.relaxed.gpu.global.L2::cache_hint.v2.u32 {%0,%1}, [%2], %3;" : "=r"(v.x), "=r"(v.y) : "l"(p), "l"(pol)); return v;
}
__device__ __forceinline__ void st_ef(void* p, uint2 v, uint64_t pol) {
    asm volatile("st.global.L2::cache_hint.v2.u32 [%0], {%1,%2}, %3;" :: "l"(p), "r"(v.x), "r"(v.y), "l"(pol) : "memory");
}
__device__ __forceinline__ void tma2d_prefetch(const CUtensorMap* m, int c0, int c1) {
    asm volatile("cp.async.bulk.prefetch.tensor.2d.L2.global [%0, {%1, %2}];" :: "l"((uint64_t)m), "r"(c0), "r"(c1) : "memory");
}
__device__ __forceinline__ void mbar_arrive_remote(uint32_t bar) { asm volatile("mbarrier.arrive.relaxed.cluster.shared::cluster.b64 _, [%0];" :: "r"(bar) : "memory"); }
__device__ __forceinline__ void tma2d_store(const CUtensorMap* m, int c0, int c1, uint32_t src) {
    asm volatile("cp.async.bulk.tensor.2d.global.shared::cta.bulk_group [%0, {%2, %3}], [%1];"
        :: "l"((uint64_t)m), "r"(src), "r"(c0), "r"(c1) : "memory");
}
__device__ __forceinline__ void bulk_g2s(uint32_t dst, const void* src, int bytes, uint32_t bar) {
    asm volatile("cp.async.bulk.shared::cluster.global.mbarrier::complete_tx::bytes [%0], [%1], %2, [%3];" :: "r"(dst), "l"(src), "r"(bytes), "r"(bar) : "memory");
}
__device__ __forceinline__ void ldsm4(uint32_t (&r)[4], uint32_t a) {
    asm volatile("ldmatrix.sync.aligned.m8n8.x4.shared.b16 {%0,%1,%2,%3}, [%4];" : "=r"(r[0]), "=r"(r[1]), "=r"(r[2]), "=r"(r[3]) : "r"(a) : "memory");
}
__device__ __forceinline__ void ldsm4t(uint32_t (&r)[4], uint32_t a) {
    asm volatile("ldmatrix.sync.aligned.m8n8.x4.trans.shared.b16 {%0,%1,%2,%3}, [%4];" : "=r"(r[0]), "=r"(r[1]), "=r"(r[2]), "=r"(r[3]) : "r"(a) : "memory");
}
__device__ __forceinline__ void stsm4(uint32_t a, uint32_t r0, uint32_t r1, uint32_t r2, uint32_t r3) {
    asm volatile("stmatrix.sync.aligned.m8n8.x4.shared.b16 [%0], {%1,%2,%3,%4};" :: "r"(a), "r"(r0), "r"(r1), "r"(r2), "r"(r3) : "memory");
}
__device__ __forceinline__ void stsm4t(uint32_t a, uint32_t r0, uint32_t r1, uint32_t r2, uint32_t r3) {
    asm volatile("stmatrix.sync.aligned.m8n8.x4.trans.shared.b16 [%0], {%1,%2,%3,%4};" :: "r"(a), "r"(r0), "r"(r1), "r"(r2), "r"(r3) : "memory");
}
__device__ __forceinline__ void stsm2t(uint32_t a, uint32_t r0, uint32_t r1) {
    asm volatile("stmatrix.sync.aligned.m8n8.x2.trans.shared.b16 [%0], {%1,%2};" :: "r"(a), "r"(r0), "r"(r1) : "memory");
}
__device__ __forceinline__ uint32_t movm_t(uint32_t v) { uint32_t r; asm volatile("movmatrix.sync.aligned.m8n8.trans.b16 %0, %1;" : "=r"(r) : "r"(v)); return r; }
__device__ __forceinline__ void mma16(float (&d)[4], uint32_t a0, uint32_t a1, uint32_t a2, uint32_t a3, uint32_t b0, uint32_t b1) {
    asm volatile("mma.sync.aligned.m16n8k16.row.col.f32.bf16.bf16.f32 {%0,%1,%2,%3}, {%4,%5,%6,%7}, {%8,%9}, {%0,%1,%2,%3};"
        : "+f"(d[0]), "+f"(d[1]), "+f"(d[2]), "+f"(d[3]) : "r"(a0), "r"(a1), "r"(a2), "r"(a3), "r"(b0), "r"(b1));
}
__device__ __forceinline__ void mma8(float (&d)[4], uint32_t a0, uint32_t a1, uint32_t b0) {
    asm volatile("mma.sync.aligned.m16n8k8.row.col.f32.bf16.bf16.f32 {%0,%1,%2,%3}, {%4,%5}, {%6}, {%0,%1,%2,%3};"
        : "+f"(d[0]), "+f"(d[1]), "+f"(d[2]), "+f"(d[3]) : "r"(a0), "r"(a1), "r"(b0));
}
__device__ __forceinline__ uint32_t mapa(uint32_t a, uint32_t r) { uint32_t o; asm volatile("mapa.shared::cluster.u32 %0, %1, %2;" : "=r"(o) : "r"(a), "r"(r)); return o; }
__device__ __forceinline__ void bar_sync(int id, int n) { asm volatile("bar.sync %0, %1;" :: "r"(id), "r"(n) : "memory"); }
__device__ __forceinline__ void bar_arrive(int id, int n) { asm volatile("bar.arrive %0, %1;" :: "r"(id), "r"(n) : "memory"); }
__device__ __forceinline__ uint64_t mkdesc(uint32_t addr, uint32_t lbo, uint32_t sbo) {
    return (uint64_t)((addr & 0x3FFFF) >> 4) | ((uint64_t)(lbo >> 4) << 16) | ((uint64_t)(sbo >> 4) << 32) | (1ull << 62);
}
#define WG_FENCE()  asm volatile("wgmma.fence.sync.aligned;" ::: "memory")
#define WG_COMMIT() asm volatile("wgmma.commit_group.sync.aligned;" ::: "memory")
#define WG_WAIT(n)  asm volatile("wgmma.wait_group.sync.aligned %0;" :: "n"(n) : "memory")

__device__ __forceinline__ void wgmma_ss_n192_tb(float (&d)[96], uint64_t a, uint64_t b, int acc) {
    asm volatile("{ .reg .pred p; setp.ne.b32 p, %98, 0;\n"
        "wgmma.mma_async.sync.aligned.m64n192k16.f32.bf16.bf16 {%0,%1,%2,%3,%4,%5,%6,%7,%8,%9,%10,%11,%12,%13,%14,%15,%16,%17,%18,%19,%20,%21,%22,%23,%24,%25,%26,%27,%28,%29,%30,%31,%32,%33,%34,%35,%36,%37,%38,%39,%40,%41,%42,%43,%44,%45,%46,%47,%48,%49,%50,%51,%52,%53,%54,%55,%56,%57,%58,%59,%60,%61,%62,%63,%64,%65,%66,%67,%68,%69,%70,%71,%72,%73,%74,%75,%76,%77,%78,%79,%80,%81,%82,%83,%84,%85,%86,%87,%88,%89,%90,%91,%92,%93,%94,%95}, %96, %97, p, 1, 1, 0, 1; }"
        : "+f"(d[0]), "+f"(d[1]), "+f"(d[2]), "+f"(d[3]), "+f"(d[4]), "+f"(d[5]), "+f"(d[6]), "+f"(d[7]), "+f"(d[8]), "+f"(d[9]), "+f"(d[10]), "+f"(d[11]), "+f"(d[12]), "+f"(d[13]), "+f"(d[14]), "+f"(d[15]), "+f"(d[16]), "+f"(d[17]), "+f"(d[18]), "+f"(d[19]), "+f"(d[20]), "+f"(d[21]), "+f"(d[22]), "+f"(d[23]), "+f"(d[24]), "+f"(d[25]), "+f"(d[26]), "+f"(d[27]), "+f"(d[28]), "+f"(d[29]), "+f"(d[30]), "+f"(d[31]), "+f"(d[32]), "+f"(d[33]), "+f"(d[34]), "+f"(d[35]), "+f"(d[36]), "+f"(d[37]), "+f"(d[38]), "+f"(d[39]), "+f"(d[40]), "+f"(d[41]), "+f"(d[42]), "+f"(d[43]), "+f"(d[44]), "+f"(d[45]), "+f"(d[46]), "+f"(d[47]), "+f"(d[48]), "+f"(d[49]), "+f"(d[50]), "+f"(d[51]), "+f"(d[52]), "+f"(d[53]), "+f"(d[54]), "+f"(d[55]), "+f"(d[56]), "+f"(d[57]), "+f"(d[58]), "+f"(d[59]), "+f"(d[60]), "+f"(d[61]), "+f"(d[62]), "+f"(d[63]), "+f"(d[64]), "+f"(d[65]), "+f"(d[66]), "+f"(d[67]), "+f"(d[68]), "+f"(d[69]), "+f"(d[70]), "+f"(d[71]), "+f"(d[72]), "+f"(d[73]), "+f"(d[74]), "+f"(d[75]), "+f"(d[76]), "+f"(d[77]), "+f"(d[78]), "+f"(d[79]), "+f"(d[80]), "+f"(d[81]), "+f"(d[82]), "+f"(d[83]), "+f"(d[84]), "+f"(d[85]), "+f"(d[86]), "+f"(d[87]), "+f"(d[88]), "+f"(d[89]), "+f"(d[90]), "+f"(d[91]), "+f"(d[92]), "+f"(d[93]), "+f"(d[94]), "+f"(d[95])
        : "l"(a), "l"(b), "r"(acc));
}

__device__ __forceinline__ void wgmma_ss_n128_tb(float (&d)[64], uint64_t a, uint64_t b, int acc) {
    asm volatile("{ .reg .pred p; setp.ne.b32 p, %66, 0;\n"
        "wgmma.mma_async.sync.aligned.m64n128k16.f32.bf16.bf16 {%0,%1,%2,%3,%4,%5,%6,%7,%8,%9,%10,%11,%12,%13,%14,%15,%16,%17,%18,%19,%20,%21,%22,%23,%24,%25,%26,%27,%28,%29,%30,%31,%32,%33,%34,%35,%36,%37,%38,%39,%40,%41,%42,%43,%44,%45,%46,%47,%48,%49,%50,%51,%52,%53,%54,%55,%56,%57,%58,%59,%60,%61,%62,%63}, %64, %65, p, 1, 1, 0, 1; }"
        : "+f"(d[0]), "+f"(d[1]), "+f"(d[2]), "+f"(d[3]), "+f"(d[4]), "+f"(d[5]), "+f"(d[6]), "+f"(d[7]), "+f"(d[8]), "+f"(d[9]), "+f"(d[10]), "+f"(d[11]), "+f"(d[12]), "+f"(d[13]), "+f"(d[14]), "+f"(d[15]), "+f"(d[16]), "+f"(d[17]), "+f"(d[18]), "+f"(d[19]), "+f"(d[20]), "+f"(d[21]), "+f"(d[22]), "+f"(d[23]), "+f"(d[24]), "+f"(d[25]), "+f"(d[26]), "+f"(d[27]), "+f"(d[28]), "+f"(d[29]), "+f"(d[30]), "+f"(d[31]), "+f"(d[32]), "+f"(d[33]), "+f"(d[34]), "+f"(d[35]), "+f"(d[36]), "+f"(d[37]), "+f"(d[38]), "+f"(d[39]), "+f"(d[40]), "+f"(d[41]), "+f"(d[42]), "+f"(d[43]), "+f"(d[44]), "+f"(d[45]), "+f"(d[46]), "+f"(d[47]), "+f"(d[48]), "+f"(d[49]), "+f"(d[50]), "+f"(d[51]), "+f"(d[52]), "+f"(d[53]), "+f"(d[54]), "+f"(d[55]), "+f"(d[56]), "+f"(d[57]), "+f"(d[58]), "+f"(d[59]), "+f"(d[60]), "+f"(d[61]), "+f"(d[62]), "+f"(d[63])
        : "l"(a), "l"(b), "r"(acc));
}

__device__ __forceinline__ void wgmma_rs_n32(float (&d)[16], const uint32_t (&a)[4], uint64_t b, int acc) {
    asm volatile("{ .reg .pred p; setp.ne.b32 p, %21, 0;\n"
        "wgmma.mma_async.sync.aligned.m64n32k16.f32.bf16.bf16 {%0,%1,%2,%3,%4,%5,%6,%7,%8,%9,%10,%11,%12,%13,%14,%15}, {%16,%17,%18,%19}, %20, p, 1, 1, 0; }"
        : "+f"(d[0]), "+f"(d[1]), "+f"(d[2]), "+f"(d[3]), "+f"(d[4]), "+f"(d[5]), "+f"(d[6]), "+f"(d[7]), "+f"(d[8]), "+f"(d[9]), "+f"(d[10]), "+f"(d[11]), "+f"(d[12]), "+f"(d[13]), "+f"(d[14]), "+f"(d[15])
        : "r"(a[0]), "r"(a[1]), "r"(a[2]), "r"(a[3]), "l"(b), "r"(acc));
}

__device__ __forceinline__ float warp_sum(float v) {
#pragma unroll
    for (int o = 16; o; o >>= 1) v += __shfl_xor_sync(0xffffffffu, v, o);
    return v;
}
__device__ __forceinline__ uint32_t add2(uint32_t a, uint32_t b) { uint32_t r; asm("add.rn.bf16x2 %0, %1, %2;" : "=r"(r) : "r"(a), "r"(b)); return r; }
__device__ __forceinline__ uint32_t mul2(uint32_t a, uint32_t b) { uint32_t r; asm("mul.rn.bf16x2 %0, %1, %2;" : "=r"(r) : "r"(a), "r"(b)); return r; }
__device__ __forceinline__ uint32_t amax2(uint32_t m, uint32_t v) { uint32_t r; asm("max.u16x2 %0, %1, %2;" : "=r"(r) : "r"(m), "r"(v & 0x7fff7fffu)); return r; }
__device__ __forceinline__ uint32_t amax_warp(uint32_t m) { return __reduce_max_sync(0xffffffffu, max(m & 0xffffu, m >> 16)); }
__device__ __forceinline__ void ln_norm(const uint32_t (&xv)[10], uint32_t (&nv)[10]) {
    float s0 = 0, s1 = 0;
#pragma unroll
    for (int i = 0; i < 10; i++) { s0 += lo_f(xv[i]); s1 += hi_f(xv[i]); }
    const float mean = warp_sum(s0 + s1) * (1.f / DM);
    float q0 = 0, q1 = 0;
#pragma unroll
    for (int i = 0; i < 10; i++) { const float d0 = lo_f(xv[i]) - mean, d1 = hi_f(xv[i]) - mean; q0 += d0 * d0; q1 += d1 * d1; }
    const float inv = inv_std(warp_sum(q0 + q1) * (1.f / DM));
    const uint32_t mb = pack2(-mean, -mean);
#pragma unroll
    for (int i = 0; i < 10; i++) { const uint32_t d = add2(xv[i], mb); nv[i] = pack2(lo_f(d) * inv, hi_f(d) * inv); }
}
__device__ __forceinline__ void ln_mod(const uint32_t (&xv)[10], const uint32_t (&sv)[10], const uint32_t (&tv)[10], uint32_t (&hv)[10]) {
    ln_norm(xv, hv);
#pragma unroll
    for (int i = 0; i < 10; i++) hv[i] = add2(mul2(hv[i], add2(sv[i], 0x3f803f80u)), tv[i]);
}
__device__ __forceinline__ uint32_t ld_rlx(const uint32_t* f) { uint32_t v; asm volatile("ld.relaxed.gpu.global.u32 %0, [%1];" : "=r"(v) : "l"(f) : "memory"); return v; }
__device__ __forceinline__ void bump(uint32_t* f) { asm volatile("red.relaxed.gpu.global.add.u32 [%0], 1;" :: "l"(f) : "memory"); }
#define NAP 100
#define GPU_FENCE() asm volatile("fence.acq_rel.gpu;" ::: "memory")
__device__ __forceinline__ void flag_wait(const uint32_t* f, uint32_t target) {
    for (int n = 0;; n++) {
        uint32_t v; asm volatile("ld.relaxed.gpu.global.u32 %0, [%1];" : "=r"(v) : "l"(f) : "memory");
        if (v >= target) break;
        if (n > (1 << 22)) __trap();
        __nanosleep(NAP);
    }
}
__device__ __forceinline__ void flag_add(uint32_t* f, uint32_t v = 1) { asm volatile("red.release.gpu.global.add.u32 [%0], %1;" :: "l"(f), "r"(v) : "memory"); }
constexpr int N_SIDE = 36;
__device__ __forceinline__ void flags_release(int lane) {
    uint32_t old = 0;
    if (lane == 0) asm volatile("atom.relaxed.gpu.global.add.u32 %0, [%1], 1;" : "=r"(old) : "l"(&g_flags.done) : "memory");
    if (__shfl_sync(0xffffffffu, old, 0) == 96 + N_SIDE - 1)
#pragma unroll 1
        for (int i = lane; i < (int)(sizeof(Flags) / 16); i += 32) ((uint4*)&g_flags)[i] = make_uint4(0, 0, 0, 0);
}

struct ChainMaps { CUtensorMap wq, wk, wv, wo, h2, wo15, o15, slab2; };
struct ChainArgs { const bf16 *x, *mem0, *c, *wmod, *wv, *wo, *wgate, *wup, *wdown; bf16* out; int D1, D2, DG; };
constexpr uint32_t SM_BASE = 1024;
#define NRING 10
#define XORD 0
#define B5AT 41
#define QCUT 0x54
#define NCH 0
#define XA 2
#define VT 1
#define OSEND 1
#define SPOLL 0
#define NOF 0
#define FW 2
#define NPRE 9
#define REG_P 208
#define REG_L (504 - 2 * REG_P)
constexpr int WO_BLK = 7 * 4096;
constexpr int C_WV = 0, C_WO = 81920, C_XR = 167936, C_VP = C_XR + 7 * 4096, C_VX = C_XR + 8 * 4096, C_QX = C_VX + 4096, C_KX = C_QX + 4096,
              C_MEM = C_KX + 4096, C_OX = C_MEM + 9216, C_VM = C_OX + 3072, C_QM = C_VM + 1024, C_KM = C_QM + 1024, C_SC = C_KM + 1024, C_BAR = C_SC + 3840;
constexpr int CB_W = C_BAR, CB_W2 = C_BAR + 8, CB_SC = C_BAR + 16, CB_XD = C_BAR + 24, CB_VX = C_BAR + 32, CB_W3 = C_BAR + 40, CB_XM = C_BAR + 48, CB_OX = C_BAR + 56,
              CB_XF = C_BAR + 64, C_LAG = C_BAR + 96, C_UN = C_BAR + 100, C_MX = C_BAR + 112;
constexpr int C_SMEM = C_BAR + 128;
#define PROF(i)
#define PROFG(i)
#define PROFV(i, v)
static_assert(C_SMEM <= 232448, "chain shared memory");
__device__ __forceinline__ uint32_t umax3(uint32_t a, uint32_t b, uint32_t c) { return max(max(a, b), c); }
__device__ __forceinline__ void wait_until(uint32_t t) {
    asm volatile("{ .reg .pred p; .reg .s32 c; .reg .u64 d;\nU_%=: mov.u64 d, %%clock64; cvt.u32.u64 c, d; sub.s32 c, c, %0; setp.lt.s32 p, c, 0; @p bra.uni U_%=; }" :: "r"(t) : "memory");
}
__device__ __forceinline__ uint32_t gtime() { uint32_t c; asm volatile("mov.u32 %0, %%globaltimer_lo;" : "=r"(c)); return c; }
__device__ __forceinline__ uint32_t opaque(uint32_t v) { uint32_t r; asm volatile("shfl.sync.bfly.b32 %0, %1, 0, 31, -1;" : "=r"(r) : "r"(v)); return r; }
__device__ __forceinline__ uint32_t lds32(uint32_t a) { uint32_t v; asm volatile("ld.shared.u32 %0, [%1];" : "=r"(v) : "r"(a) : "memory"); return v; }
__device__ __forceinline__ float2 lds64f(uint32_t a) { float2 v; asm volatile("ld.shared.v2.f32 {%0,%1}, [%2];" : "=f"(v.x), "=f"(v.y) : "r"(a) : "memory"); return v; }
__device__ __forceinline__ float4 lds128f(uint32_t a) { float4 v; asm volatile("ld.shared.v4.f32 {%0,%1,%2,%3}, [%4];" : "=f"(v.x), "=f"(v.y), "=f"(v.z), "=f"(v.w) : "r"(a) : "memory"); return v; }
__device__ __forceinline__ void sts128f(uint32_t a, float x, float y, float z, float w) { asm volatile("st.shared.v4.f32 [%0], {%1,%2,%3,%4};" :: "r"(a), "f"(x), "f"(y), "f"(z), "f"(w) : "memory"); }
__device__ __forceinline__ void lds64(uint32_t (&v)[2], uint32_t a) { asm volatile("ld.shared.v2.u32 {%0,%1}, [%2];" : "=r"(v[0]), "=r"(v[1]) : "r"(a) : "memory"); }
__device__ __forceinline__ void mma16q(float (&d)[4], const uint32_t (&a)[4], uint32_t b0, uint32_t b1) { mma16(d, a[0], a[1], a[2], a[3], b0, b1); }
__device__ __forceinline__ uint32_t f16_to_bf16(uint32_t v) {
    float lo, hi; asm("{ .reg .f16 l, h; mov.b32 {l, h}, %2; cvt.f32.f16 %0, l; cvt.f32.f16 %1, h; }" : "=f"(lo), "=f"(hi) : "r"(v));
    return pack2(lo, hi);
}
__device__ __forceinline__ uint32_t pack2h(float lo, float hi) { uint32_t r; asm("cvt.rn.f16x2.f32 %0, %1, %2;" : "=r"(r) : "f"(hi), "f"(lo)); return r; }
#define SPLIT 1
__device__ __forceinline__ void cut(uint32_t never, int n) {
    asm volatile("{ .reg .pred p; setp.ne.u32 p, %0, %1; @p bra.uni C_%=; trap; C_%=: }" :: "r"(never), "r"(n) : "memory");
}
__device__ __forceinline__ void pin(uint32_t never, uint32_t a, uint32_t b, uint32_t c, uint32_t d) {
    asm volatile("{ .reg .pred p; setp.eq.u32 p, %0, 0; @p st.shared.v4.u32 [%0], {%1,%2,%3,%4}; }" :: "r"(never), "r"(a), "r"(b), "r"(c), "r"(d) : "memory");
}
__device__ __forceinline__ void pin0(uint32_t never) {
    asm volatile("{ .reg .pred p; setp.eq.u32 p, %0, 0; @p st.shared.u32 [%0], 0; }" :: "r"(never) : "memory");
}
#define ELECTED(txt) "{ .reg .pred e; elect.sync _|e, -1; @e " txt " }"
__device__ __forceinline__ void w_bulk_s2g(void* dst, uint32_t src, int bytes) {
    asm volatile(ELECTED("cp.async.bulk.global.shared::cta.bulk_group [%0], [%1], %2;") :: "l"(dst), "r"(src), "r"(bytes) : "memory");
}
__device__ __forceinline__ void w_bump(uint32_t* f) { asm volatile(ELECTED("red.relaxed.gpu.global.add.u32 [%0], 1;") :: "l"(f) : "memory"); }
__device__ __forceinline__ void w_expect(uint32_t bar, int bytes) { asm volatile(ELECTED("mbarrier.arrive.expect_tx.shared::cta.b64 _, [%0], %1;") :: "r"(bar), "r"(bytes) : "memory"); }
__device__ __forceinline__ void w_flag_wait(const uint32_t* f, uint32_t target) {
    asm volatile("{ .reg .pred p; .reg .u32 n, v; mov.u32 n, 0;\n"
                 "F_%=: ld.relaxed.gpu.global.u32 v, [%0]; setp.ge.u32 p, v, %1; vote.sync.all.pred p, p, -1; @p bra.uni G_%=;\n"
                 "nanosleep.u32 %2; add.u32 n, n, 1; setp.lt.u32 p, n, 0x400000; @p bra.uni F_%=;\ntrap;\nG_%=: }" :: "l"(f), "r"(target), "n"(NAP) : "memory");
}
#define BULK_COMMIT()    asm volatile("cp.async.bulk.commit_group;" ::: "memory")
#define BULK_WAIT()      asm volatile("cp.async.bulk.wait_group 0;" ::: "memory")
#define BULK_WAIT_READ() asm volatile("cp.async.bulk.wait_group.read 0;" ::: "memory")
#define PROXY_FENCE()    asm volatile("fence.proxy.async.shared::cta;" ::: "memory")
__device__ __forceinline__ void send16(uint32_t dst, uint32_t bar, float a, float b, float c, float d) {
    asm volatile("st.async.shared::cluster.mbarrier::complete_tx::bytes.v4.f32 [%0], {%1,%2,%3,%4}, [%5];" :: "r"(dst), "f"(a), "f"(b), "f"(c), "f"(d), "r"(bar) : "memory");
}
__device__ __forceinline__ void send8(uint32_t dst, uint32_t bar, uint32_t a, uint32_t b) {
    asm volatile("st.async.shared::cluster.mbarrier::complete_tx::bytes.v2.b32 [%0], {%1,%2}, [%3];" :: "r"(dst), "r"(a), "r"(b), "r"(bar) : "memory");
}

__device__ __forceinline__ void seg_done(int n, int head) {
    if (n >= 60 || (n & 3) == 3) { if (!NOF) GPU_FENCE(); w_bump(n >= 60 ? &g_flags.seg[(n - 60) * 32 + head] : &g_flags.qk[n >> 2]); }
}
__device__ __forceinline__ uint32_t x_base(int wg, uint32_t small, int sh) { return (uint32_t)mkdesc(SM_BASE + C_XR, 16, 1024) + wg * 256 + (small >> sh); }
__device__ __forceinline__ void x_chunk(float (&acc)[16], const uint32_t (&wa)[40][4], uint32_t xl, int a0, int i, int first) {
#pragma unroll
    for (int ks = 0; ks < 4; ks++)
        wgmma_rs_n32(acc, wa[a0 + 4 * i + ks], mkdesc(0, 0, 1024) | (uint32_t)(xl + (((i ? (i - 1) * 8192 : C_MEM - C_XR) + ks * 32) >> 4)), !(first && ks == 0));
}
__device__ __forceinline__ void x_part(float (&acc)[16], const uint32_t (&wa)[40][4], uint32_t sm, int n, int wg, int w, uint32_t ln, uint32_t small) {
    const int s = n - 1; (void)s;
    uint32_t giv[8];
    auto chunk = [&](int a0, int i, int first) { x_chunk(acc, wa, x_base(wg, small, a0 ? 21 : 22), a0, i, first); };
    mbar_wait(sm + CB_XM, n & 1);
    if (n) bar_sync(5, 384);
    if (wg == 0 && w == 0) PROF(12);
    WG_FENCE();
#pragma unroll
    for (int i = 1 + XA; i < 5; i++) chunk(20, i, 0);
    chunk(20, 0, 0);
    WG_COMMIT();
    if (n) {
        if (wg == 1 && w == 1) BULK_WAIT();
        bar_sync(8, 256);
    }
    if (wg == 0 && w == 0) PROF(18);
    const uint32_t xb = sm + w * 512 + ln * 16, xw = xb + C_KX - wg * 4096, xr = xb + C_QX + wg * 4096;
    WG_WAIT(0);
#pragma unroll
    for (int i = 0; i < 8; i++) asm volatile("cvt.rn.bf16x2.f32 %0, %1, %2;" : "=r"(giv[i]) : "f"(acc[2 * i + 1]), "f"(acc[2 * i]));
#pragma unroll
    for (int p = 0; p < 2; p++) asm volatile("st.shared.v4.u32 [%0], {%1,%2,%3,%4};" :: "r"(xw + p * 2048), "r"(giv[4 * p]), "r"(giv[4 * p + 1]), "r"(giv[4 * p + 2]), "r"(giv[4 * p + 3]) : "memory");
    bar_arrive(12 + wg, 256);
    WG_FENCE();
    chunk(0, 0, 1);
    WG_COMMIT();
    chunk(0, 1, 0);
    if (XORD) chunk(0, 2, 0);
    bar_sync(13 - wg, 256);
#pragma unroll
    for (int p = 0; p < 2; p++) asm volatile("ld.shared.v4.u32 {%0,%1,%2,%3}, [%4];" : "=r"(giv[4 * p]), "=r"(giv[4 * p + 1]), "=r"(giv[4 * p + 2]), "=r"(giv[4 * p + 3]) : "r"(xr + p * 2048) : "memory");
    WG_COMMIT(); WG_WAIT(1); bar_arrive(9, 384);
    WG_FENCE();
    if (!XORD) chunk(0, 2, 0);
    chunk(0, 3, 0); chunk(0, 4, 0);
    WG_COMMIT();
    const uint32_t r = ln & 7, mi = ln >> 3, dst = sm + (wg == 0 ? C_QX : C_KX) + ((mi >> 1) * 8 + r) * 128 + (((2 * w + (mi & 1)) ^ r) << 4);
    pin(xb, giv[0], giv[4], dst, 0);
    bar_sync(10 + wg, 128);
    WG_WAIT(0);
    if (wg == 0 && w == 0) PROF(30);
    if (w == 0 && ln < 3) mbar_arrive_remote(mapa(sm + CB_XD, ln));
#pragma unroll
    for (int i = 0; i < 8; i++) { acc[2 * i] += lo_f(giv[i]); acc[2 * i + 1] += hi_f(giv[i]); }
#pragma unroll
    for (int p = 0; p < 2; p++)
        stsm4t(dst + p * 2048, pack2(acc[8 * p], acc[8 * p + 1]), pack2(acc[8 * p + 2], acc[8 * p + 3]), pack2(acc[8 * p + 4], acc[8 * p + 5]), pack2(acc[8 * p + 6], acc[8 * p + 7]));
    if (wg == 0 && w == 0) PROF(11);
}
__device__ __forceinline__ void x_fill(const ChainMaps& mp, uint32_t sm, int n, int j) {
    mbar_expect(sm + CB_XF, 24576);
    asm volatile("cp.async.bulk.tensor.3d.shared::cluster.global.mbarrier::complete_tx::bytes.multicast::cluster [%0], [%1, {0, %3, %4}], [%2], %5;"
        :: "r"(sm + C_XR + j * 8192), "l"((uint64_t)&mp.h2), "r"(sm + CB_XF), "r"(n * SEG), "r"(2 + 2 * j), "h"((uint16_t)7) : "memory");
}
__device__ __forceinline__ void x_rest(const ChainMaps& mp, uint32_t sm, int n) {
    mbar_expect(sm + CB_XM, 16384);
    tma3d(sm + C_XR + 6 * 4096, &mp.h2, n * SEG, 8, sm + CB_XM); tma3d(sm + C_MEM, &mp.h2, n * SEG, 0, sm + CB_XM);
}

#define WPOS 2
#define WP 4
#define WOPF 30
#define SDEL 0
#define EORD 0
#define BPOS 2
#define TPF 1
#define B_LATE 13
constexpr int E_B = C_WO, E_STG = 196608, EB_A = 229376, EB_B = C_BAR + 80, EB_REL = C_BAR + 104;
__device__ __forceinline__ uint32_t e_slot(int wg, int c) { return wg && c == 2 ? E_B + 98304 : wg * 49152 + c * 16384; }
constexpr int T_WG = 0, T_WU = 20480, T_WD = 40960, T_X = 65536, T_RED = 77824, T_KEY = 86016;
__device__ __forceinline__ void wo_half(const ChainMaps& mp, uint32_t sm, int blk, int c) {
    if (blk < 80 && elect()) { mbar_expect(sm + EB_B + 8 * c, 49152); tma3d(sm + E_B + c * 49152, &mp.wo15, blk / 5 * 384 + c * 192, blk % 5 * 2, sm + EB_B + 8 * c); }
}
__device__ __forceinline__ void end_loads(const ChainMaps& mp, const ChainArgs& ar, uint32_t sm, int blk, int wg) {
    const uint32_t bar = sm + EB_A + wg * 48;
    const int kp = blk / 5;
    if (elect()) {
#pragma unroll 1
        for (int c = 0; c < 6; c++) mbar_init(bar + 8 * c, c < 3 ? 1 : 4);
        PROXY_FENCE();
    }
    __syncwarp();
    bar_arrive(5, 384);
    if (EORD) bar_sync(6, 96);
    if (blk >= 80) {
        if (TPF && elect()) {
#pragma unroll 1
            for (int c = 0; c < 3; c++) asm volatile("cp.async.bulk.prefetch.L2.global [%0], 61440;" :: "l"((c == 0 ? ar.wgate : c == 1 ? ar.wup : ar.wdown) + ((blk - 80) * 2 + wg) * 30720) : "memory");
        }
        return;
    }
    const uint64_t ef = policy_stream();
#pragma unroll 1
    for (int b = B_LATE; b < 16; b++) {
        w_flag_wait(b == 15 ? &g_flags.half[kp * 2 + wg] : &g_flags.pair[b * 16 + kp], b == 15 ? 2 : 4);
#pragma unroll 1
        for (int c = 0; c < 3; c++) {
            if (b > B_LATE) mbar_wait(bar + 24 + 8 * c, (b - B_LATE - 1) & 1);
            if (elect()) { mbar_expect(bar + 8 * c, 16384); tma3d_ef(sm + e_slot(wg, c), &mp.o15, b * 128 + wg * 64, kp * 6 + c * 2, bar + 8 * c, ef); }
            __syncwarp();
        }
    }
}
__device__ __forceinline__ void end_stores(const ChainMaps& mp, uint32_t sm, int blk, int wg) {
#pragma unroll 1
    for (int b = B_LATE; b < 16 && blk < 80; b++) {
        bar_sync(12 + wg, 160);
        if (elect()) tma3d_store(&mp.slab2, (b * KSPLIT + blk / 5) * 128 + wg * 64, blk % 5 * 2, sm + E_STG + wg * 16384, 0, false);
        BULK_COMMIT(); BULK_WAIT();
        if (b < 15) bar_arrive(10 + wg, 160);
        GPU_FENCE();
        w_bump(b < 14 ? &g_flags.o[b] : &g_flags.fin[((b - 14) * 2 + wg) * 32]);
    }
    bar_arrive(8, 320);
}
__device__ __forceinline__ void last_blocks(const ChainArgs& ar, uint32_t sm, int blk, int tid) {
    const int warp = __shfl_sync(0xffffffffu, tid >> 5, 0), lane = tid & 31, wg = warp >> 2, w = warp & 3;
    const uint32_t bar = sm + EB_A + wg * 48, stg = sm + E_STG + wg * 16384 + w * 2048;
    bar_sync(5, 384);
    EPT(tid == 128, 7);
    float acc[64];
#pragma unroll
    for (int n = 0; n < 64; n++) acc[n] = 0.f;
#pragma unroll 1
    for (int b = B_LATE; b < 16 && blk < 80; b++) {
#pragma unroll 1
        for (int c = 0; c < 6; c++) {
            mbar_wait(sm + EB_B + 8 * (c >= 3), 0); mbar_wait(bar + 8 * (c >> 1), (b - B_LATE) & 1);
            const uint64_t da = mkdesc(SM_BASE + e_slot(wg, c >> 1) + (c & 1) * 8192, 16, 1024), db = mkdesc(SM_BASE + E_B + (c >= 3 ? 24576 : 0) + c * 8192, 24576, 1024);
            WG_FENCE();
#pragma unroll
            for (int ks = 0; ks < 4; ks++) wgmma_ss_n128_tb(acc, da + ks * 2, db + ks * 128, c | ks);
            WG_COMMIT();
            WG_WAIT(1);
            if ((c & 1) == 0 && c && elect()) mbar_arrive(bar + 16 + 4 * c);
        }
        if (b > B_LATE) bar_sync(10 + wg, 160);
        WG_WAIT(0);
        if (elect()) mbar_arrive(bar + 40);
        EPT(tid == 128, 13 + 15 - b);
        const int r = lane & 7, mi = lane >> 3;
#pragma unroll
        for (int p = 0; p < 8; p++) {
            const int oc = 2 * p + (mi >> 1);
            stsm4(stg + (oc >> 3) * 8192 + ((mi & 1) * 8 + r) * 128 + (((oc & 7) ^ r) << 4), pack2(acc[8 * p], acc[8 * p + 1]), pack2(acc[8 * p + 2], acc[8 * p + 3]),
                  pack2(acc[8 * p + 4], acc[8 * p + 5]), pack2(acc[8 * p + 6], acc[8 * p + 7]));
        }
        PROXY_FENCE();
        bar_arrive(12 + wg, 160);
    }
    bar_sync(8, 320);
    const int o = (tid >> 1) * FF + blk * 16 + (tid & 1) * 8;
    const bf16 *pg = ar.wgate + o, *pu = ar.wup + o, *pd = ar.wdown + tid * DM + (blk < 80 ? blk : 0) * 8;
#pragma unroll 1
    for (int i = 0; i < 6; i++) {
        const uint32_t d = sm + E_B + i * 4096 + tid * 16;
        if (i < 5) asm volatile("cp.async.cg.shared.global [%0], [%1], 16; cp.async.cg.shared.global [%0 + 20480], [%2], 16;" :: "r"(d), "l"(pg + i * 128 * FF), "l"(pu + i * 128 * FF) : "memory");
        asm volatile("cp.async.cg.shared.global [%0 + 40960], [%1], 16;" :: "r"(d), "l"(pd + i * 256 * DM) : "memory");
    }
    EPT(tid == 128, 8);
}
__device__ __forceinline__ void mod_tail(const ChainArgs& ar, const uint32_t tb, const uint32_t bar, const int blk, const int tid) {
#define TPROF(i) EPT(tid == 0, i)
    const int warp = __shfl_sync(0xffffffffu, tid >> 5, 0), lane = tid & 31, r = lane & 7, mi = lane >> 3;
    const uint32_t kb = tb + T_KEY;
    {
        uint32_t k[8];
        for (int n = 0;; n++) {
#pragma unroll
            for (int i = 0; i < 2; i++) asm volatile("ld.relaxed.gpu.global.v4.u32 {%0,%1,%2,%3}, [%4];" : "=r"(k[4 * i]), "=r"(k[4 * i + 1]), "=r"(k[4 * i + 2]), "=r"(k[4 * i + 3]) : "l"(g_key + warp * 256 + i * 128 + lane * 4) : "memory");
            if (__all_sync(0xffffffffu, (k[0] & k[1] & k[2] & k[3] & k[4] & k[5] & k[6] & k[7] & S_TOK) != 0)) break;
            if (n > (1 << 22)) __trap();
            __nanosleep(NAP);
        }
        const uint32_t m = __reduce_max_sync(0xffffffffu, max(umax3(k[0], k[1], k[2]), max(umax3(k[3], k[4], k[5]), max(k[6], k[7]))));
        asm volatile("st.shared.u32 [%0], %1; st.shared.u32 [%2], 0;" :: "r"(kb + warp * 4), "r"(m), "r"(kb + 32) : "memory");
        asm volatile("cp.async.wait_all;" ::: "memory");
        bar_sync(1, 256);
        TPROF(1);
        const uint32_t low = __reduce_min_sync(0xffffffffu, lds32(kb + r * 4));
        uint32_t cnt = 0;
#pragma unroll
        for (int i = 0; i < 8; i++) cnt += k[i] >= low ? 4 : 0;
        if (cnt) {
            uint32_t a; asm volatile("atom.shared.add.u32 %0, [%1], %2;" : "=r"(a) : "r"(kb + 32), "r"(cnt) : "memory");
#pragma unroll
            for (int i = 0; i < 8; i++) if (k[i] >= low) { asm volatile("st.shared.u32 [%0], %1;" :: "r"(kb + 512 + a), "r"(k[i]) : "memory"); a += 4; }
        }
        if (tid == 0) mbar_arrive(bar);
        bar_sync(1, 256);
        const int nc = lds32(kb + 32);
#pragma unroll 1
        for (int c = lane * 4; c < nc; c += 128) {
            const uint32_t me = lds32(kb + 512 + c);
            int rank = 0;
#pragma unroll 2
            for (int e = 0; e < nc; e += 16) {
                const float4 z = lds128f(kb + 512 + e);
                rank += (__float_as_uint(z.x) > me) + (e + 4 < nc && __float_as_uint(z.y) > me) + (e + 8 < nc && __float_as_uint(z.z) > me) + (e + 12 < nc && __float_as_uint(z.w) > me);
            }
            if (rank < 8) asm volatile("st.shared.u32 [%0], %1;" :: "r"(kb + 64 + (warp * 8 + rank) * 4), "r"(me) : "memory");
        }
        __syncwarp();
    }
    const uint32_t k0 = lds32(kb + 64 + (warp * 8 + r) * 4), k1 = lds32(kb + 64 + (warp * 8 + (lane >> 2)) * 4);
    TPROF(2);
    const int trow = ~k1 & (S_TOK - 1), tcol = (blk < 80 ? blk : 0) * 8 + (lane & 3) * 2;
    uint2 xb[5];
#pragma unroll
    for (int h = 0; h < 5; h++) xb[h] = __ldcg((const uint2*)(g_h2 + trow * DM + (warp * 5 + h) * 16 + (lane & 3) * 4));
    const uint32_t fx1 = __ldcg((const uint32_t*)(g_x1 + trow * DM + tcol)), fh2 = __ldcg((const uint32_t*)(g_h2 + trow * DM + tcol)),
                   fgb = __ldcg((const uint32_t*)(g_mod + 5 * DM + tcol));
    const float fr = __uint_as_float(((int)k1 < 0 ? k1 ^ 0x80000000u : ~k1) & 0xffff0000u);
    {
        float dg[4] = {0, 0, 0, 0}, du[4] = {0, 0, 0, 0};
        uint32_t ag[5][4], au[5][4];
#pragma unroll
        for (int h = 0; h < 5; h++) {
            const uint32_t o = tb + ((warp * 5 + h) * 16 + (r >> 1) * 4 + (mi >> 1) * 2 + (r & 1)) * 32 + (mi & 1) * 16;
            ldsm4t(ag[h], o + T_WG); ldsm4t(au[h], o + T_WU);
        }
#pragma unroll
        for (int h = 0; h < 5; h++) { mma16q(dg, ag[h], xb[h].x, xb[h].y); mma16q(du, au[h], xb[h].x, xb[h].y); }
        TPROF(3);
        sts128f(tb + T_RED + warp * 1024 + lane * 16, dg[0], dg[1], dg[2], dg[3]); sts128f(tb + T_RED + warp * 1024 + 512 + lane * 16, du[0], du[1], du[2], du[3]);
    }
    bar_sync(1, 256);
    if (warp < 2) {
        float g2[2] = {0, 0}, u2[2] = {0, 0};
#pragma unroll
        for (int i = 0; i < 8; i++) {
            const float2 a = lds64f(tb + T_RED + i * 1024 + lane * 16 + warp * 8), b = lds64f(tb + T_RED + i * 1024 + 512 + lane * 16 + warp * 8);
            g2[0] += a.x; g2[1] += a.y; u2[0] += b.x; u2[1] += b.y;
        }
        float y[2];
#pragma unroll
        for (int i = 0; i < 2; i++) { const float gq = bfr(g2[i]); y[i] = bfr(__fdividef(gq, 1.f + __expf(-gq))) * bfr(u2[i]); }
        asm volatile("st.relaxed.gpu.global.u32 [%0], %1;" :: "l"(g_gu + (blk >> 1) * 128 + lane * 4 + warp * 2 + (blk & 1)), "r"(movm_t(pack2(y[0], y[1]))) : "memory");
    }
    TPROF(4);
    if (blk < 80) {
        uint32_t a[6][4], b[6][4];
#pragma unroll
        for (int k2 = 0; k2 < 6; k2++) ldsm4t(b[k2], tb + T_WD + (warp * 6 + k2) * 512 + lane * 16);
        for (int n = 0;; n++) {
            uint32_t m = 0;
#pragma unroll
            for (int k2 = 0; k2 < 6; k2++) asm volatile("ld.relaxed.gpu.global.v4.u32 {%0,%1,%2,%3}, [%4];" : "=r"(a[k2][0]), "=r"(a[k2][1]), "=r"(a[k2][2]), "=r"(a[k2][3]) : "l"(g_gu + (warp * 6 + k2) * 128 + lane * 4) : "memory");
#pragma unroll
            for (int k2 = 0; k2 < 6; k2++) m = umax3(umax3(m, a[k2][0], a[k2][1]), a[k2][2], a[k2][3]);
            if (!__any_sync(0xffffffffu, m == ~0u)) break;
            if (n > (1 << 22)) __trap();
        }
        TPROF(5);
        float d[2][4] = {{0, 0, 0, 0}, {0, 0, 0, 0}};
#pragma unroll
        for (int k2 = 0; k2 < 6; k2++) { mma16q(d[0], a[k2], b[k2][0], b[k2][1]); mma16q(d[1], a[k2], b[k2][2], b[k2][3]); }
        asm volatile("st.shared.v2.f32 [%0], {%1,%2};" :: "r"(tb + T_X + warp * 256 + lane * 8), "f"(d[0][0] + d[1][2]), "f"(d[0][1] + d[1][3]) : "memory");
        bar_sync(1, 256);
        if (warp == 0) {
            float y0 = 0, y1 = 0;
#pragma unroll
            for (int i = 0; i < 8; i++) { const float2 z = lds64f(tb + T_X + i * 256 + lane * 8); y0 += z.x; y1 += z.y; }
            const float sg = __fdividef(1.f, 1.f + __expf(-fr));
            *(uint32_t*)(ar.out + trow * DM + tcol) = add2(fx1, mul2(fgb, add2(fh2, mul2(pack2(y0, y1), pack2(sg, sg)))));
        }
    }
    TPROF(6);
}

__global__ void __cluster_dims__(3, 1, 1) __launch_bounds__(384, 1) k_chain(const __grid_constant__ ChainMaps mp, const __grid_constant__ ChainArgs ar) {
    const int D1 = ar.D1, DG = ar.DG;
    extern __shared__ __align__(1024) uint8_t smraw[];
    const uint32_t sm = SM_BASE + ((blockIdx.x % 3) << 24);
    if (smem_u32(smraw) != sm) __trap();
    uint32_t tid; asm volatile("mov.u32 %0, %%tid.x;" : "=r"(tid));
    const int warp = __shfl_sync(0xffffffffu, tid >> 5, 0), lane = tid & 31, wg = warp >> 2, w = warp & 3;
    const int blk = blockIdx.x, head = blk / 3, j = blk % 3;
    const int col0 = head * DH + j * 64;
    asm volatile("griddepcontrol.launch_dependents;");
#define PPROF(i)
    const int r = lane & 7, mi = lane >> 3;
    const uint32_t memrd = opaque(sm + C_MEM + lane * 16);
    if (wg < 2) {
        {
            uint32_t xv[3][10];
            const int row = blk * 8 + warp, nq = row < S_TOK - 1536 ? 3 : 2;
#pragma unroll
            for (int i = 0; i < 15; i++) {
                const uint2 v = __ldcs((const uint2*)(ar.x + (row + (i < 10 || nq == 3 ? i / 5 * 768 : 0)) * DM + lane * 4 + i % 5 * 128));
                xv[i / 5][i % 5 * 2] = v.x; xv[i / 5][i % 5 * 2 + 1] = v.y;
            }
            if (tid == 32) {
#pragma unroll 1
                for (int c = 0; c < 14; c++) if (c != 12) mbar_init(sm + C_BAR + 8 * c, c == 2 ? 5 : c == 3 ? 6 : 1);
                asm volatile("fence.mbarrier_init.release.cluster;" ::: "memory");
                mbar_expect(sm + CB_SC, 2560); mbar_expect(sm + CB_OX, 2048);
            }
            if (warp == 2) {
                const uint32_t f = blk >= 28 ? ~0u : 0u;
                ((uint4*)g_acc)[blk * 32 + lane] = make_uint4(0, 0, 0, 0);
                if (blk < 76) (blk < 12 ? (uint4*)g_stamp + blk * 32 : blk < 28 ? (uint4*)g_key + (blk - 12) * 32 : (uint4*)g_gu + (blk - 28) * 32)[lane] = make_uint4(f, f, f, f);
            }
            __syncwarp();
            asm volatile("barrier.cluster.arrive.relaxed.aligned;" ::: "memory");
            PPROF(8);
#pragma unroll 1
            for (int q = 0; q < 3; q++) {
                uint32_t nv[10];
                ln_norm(xv[0], nv);
#pragma unroll
                for (int i = 0; i < 10; i++) { xv[0][i] = xv[1][i]; xv[1][i] = xv[2][i]; xv[2][i] = nv[i]; }
            }
            PPROF(9);
            if (warp < 5) {
                uint4 u;
                for (int n = 0;; n++) {
                    asm volatile("ld.relaxed.gpu.global.v4.u32 {%0,%1,%2,%3}, [%4];" : "=r"(u.x), "=r"(u.y), "=r"(u.z), "=r"(u.w) : "l"(g_flags.mod1 + tid * 4) : "memory");
                    if (__all_sync(0xffffffffu, u.x && u.y && u.z && u.w)) break;
                    cut(n, 1 << 22);
                }
                asm volatile("st.shared.v4.u32 [%0], {%1,%2,%3,%4};" :: "r"(sm + C_KX + tid * 16), "r"(~u.x), "r"(~u.y), "r"(~u.z), "r"(~u.w) : "memory");
            }
            bar_sync(8, 256);
            PPROF(2);
            uint32_t m = 0;
#pragma unroll
            for (int i = 0; i < 5; i++) {
                uint32_t t[2], u[2];
                lds64(t, sm + C_KX + lane * 8 + i * 256); lds64(u, sm + C_KX + 1280 + lane * 8 + i * 256);
                u[0] = add2(u[0], 0x3f803f80u); u[1] = add2(u[1], 0x3f803f80u);
                m = amax2(amax2(amax2(amax2(m, t[0]), u[0]), t[1]), u[1]);
#pragma unroll
                for (int q = 0; q < 3; q++)
                    if (q < nq) *(uint2*)(g_h + (row + q * 768) * DM + lane * 4 + i * 128) = make_uint2(add2(mul2(xv[q][2 * i], u[0]), t[0]), add2(mul2(xv[q][2 * i + 1], u[1]), t[1]));
            }
            asm volatile("st.shared.u32 [%0], %1;" :: "r"(sm + C_LAG), "r"((amax_warp(m) >> 7) + 1) : "memory");
            bar_sync(8, 256);
            if (tid == 0) flag_add(&g_flags.h);
            __syncwarp();
            bar_arrive(2, 288);
            PPROF(3);
            asm volatile("barrier.cluster.wait.aligned;" ::: "memory");
        }
        asm volatile("setmaxnreg.inc.sync.aligned.u32 %0;" :: "n"(REG_P));
        uint32_t wa[40][4];
        mbar_wait(sm + CB_W, 0);
#pragma unroll
        for (int ks = 0; ks < 40; ks++)
            ldsm4t(wa[ks], sm + ((wg == 0) == (ks < 20) ? C_WV : C_WO) + ((mi >> 1) * 8 + r) * 128 + (((2 * w + (mi & 1)) ^ r) << 4) + (ks % 20 / 4 * 8 + 4 * wg + (ks & 3)) * 2048);
        PPROF(5);
        bar_arrive(1, 288);
        const uint32_t qst = opaque(sm + (wg == 0 ? C_QM : C_KM) + (2 * w + (mi & 1)) * 128 + r * 16);
        const uint32_t vrd = opaque(sm + C_WV + ((mi >> 1) * 8 + r) * 128 + (((2 * w + (mi & 1)) ^ r) << 4) + 4 * wg * 2048);
        const uint32_t mrd = opaque(memrd + wg * 1024);
        float acc[16];
        auto fb = [&](int n) { return mrd + (n >> 1) * 2048 + (n & 1) * 512; };
        auto fa = [&](int k) { return vrd + (k >> 2) * 16384 + (k & 3) * 2048; };
        auto qk_out = [&](int n) {
            uint8_t* rec = g_att + (n * NH + head) * AT_REC;
            w_bulk_s2g(rec + j * 8192, sm + C_QX, 8192); w_bulk_s2g(rec + AT_KM + j * 1024, sm + C_KM, 1024);
            BULK_COMMIT();
        };
        for (int s = -1;; s++) {
          if (s >= 0) {
            x_part(acc, wa, sm, s, wg, w, opaque(mrd) >> 4 & 31, s + ar.D2);
            if (s == 0) mbar_wait(sm + CB_W2, 0);
            uint32_t b[3][4], a[4][4];
#pragma unroll
            for (int i = 0; i < 4; i++) ldsm4t(a[i], fa(4 + i));
            cut(s + ar.D2, 0);
            bar_sync(1, 384);
            if (warp == 0) { PROF(0); PROFG(24); }
            float dv[4] = {0, 0, 0, 0};
            const uint32_t xb = mrd - wg * 1024 - (C_MEM - C_VP) + w * 512;
            {
                float d[2][4] = {{0, 0, 0, 0}, {0, 0, 0, 0}}, g[2][4] = {{0, 0, 0, 0}, {0, 0, 0, 0}};
                ldsm4t(b[0], fb(0)); pin0(mrd); ldsm4t(b[1], fb(1)); pin0(mrd);
#pragma unroll
                for (int n = 0; n < 10; n++) {
                    const int c1 = n >= 10 - NCH;
                    if (n < 8) ldsm4t(b[(n + 2) % 3], fb(n + 2));
#pragma unroll
                    for (int e = 0; e < 2; e++) {
                        mma16q(g[e & c1], wa[20 + 2 * n + e], b[n % 3][2 * e], b[n % 3][2 * e + 1]); mma16q(d[e & c1], wa[2 * n + e], b[n % 3][2 * e], b[n % 3][2 * e + 1]);
                        if (n >= 2 && n < 10 - VT) mma16q(dv, a[(2 * n + e) & 3], b[n % 3][2 * e], b[n % 3][2 * e + 1]);
                        if (n >= 2 && n < 8) ldsm4t(a[(2 * n + e) & 3], fa(2 * n + 4 + e));
                    }
                    if (QCUT >> n & 1) cut(s + ar.D2, 1 + n);
                }
                const float un = __uint_as_float(lds32(sm + C_UN));
                sts128f(xb - 4096 + wg * 2048, g[0][0] + g[1][0], g[0][1] + g[1][1], g[0][2] + g[1][2], g[0][3] + g[1][3]);
#pragma unroll
                for (int k = 20 - 2 * VT; k < 20; k++) mma16q(dv, a[k & 3], b[k / 2 % 3][2 * (k & 1)], b[k / 2 % 3][2 * (k & 1) + 1]);
                bar_sync(8, 256);
                const float4 z = lds128f(xb - 4096 + (wg ^ 1) * 2048);
                sts128f(xb + wg * 2048, dv[0], dv[1], dv[2], dv[3]);
                stsm2t(qst, pack2((d[0][0] + d[1][0] + z.x) * un, (d[0][1] + d[1][1] + z.y) * un), pack2((d[0][2] + d[1][2] + z.z) * un, (d[0][3] + d[1][3] + z.w) * un));
            }
            bar_arrive(2, 384);
            if (w == 0) PROF(1 + wg);
            if (s + 1 == NSEG) break;
          }
          if (warp == 3 && s >= 0)
              asm volatile(ELECTED("st.relaxed.gpu.global.u32 [%0], %1;") :: "l"(g_stamp + (s & 3) * 384 + (blk >> 3) * 32 + (blk & 7)), "r"((gtime() & ~31u) | ((s >> 2) + 1)) : "memory");
          PROXY_FENCE();
          mbar_wait(sm + CB_XF, (s + 1) & 1);
          if (s >= 0) bar_sync(7, 384);
          WG_FENCE();
#pragma unroll
          for (int i = 0; i < 16; i++) acc[i] = 0.f;
#pragma unroll
          for (int i = 1; i <= XA; i++) x_chunk(acc, wa, x_base(wg, s + ar.D2, 20), 20, i, i == 1);
          WG_COMMIT();
          if (warp == FW && s > 0) seg_done(s - 1, head);
          WG_WAIT(0);
          if (s >= 0) {
            if (warp == 0) {
                PROF(7);
                if (elect()) x_rest(mp, sm, s + 1);
            } else {
                if (wg == 1) {
                    if (w == 1) {
                        qk_out(s);
                    }
                    if (w == 2 && blk < 10 && s + 3 < NSEG)
                        asm volatile(ELECTED("cp.async.bulk.prefetch.L2.global [%0], 4096;") :: "l"((const uint8_t*)g_h + (s + 3) * (SEG * DM * 2) + blk * 4096) : "memory");
                } else if (w == 3) {
                    if (SPOLL) wait_until(clock() + SPOLL);
                    const uint32_t l = opaque(mrd) >> 4 & 31, tag = (s >> 2) + 1, now = gtime();
                    const uint32_t* sp = g_stamp + (s & 3) * 384 + (l >> 3) * 32 + (l & 7);
                    uint32_t t[3];
                    for (int n = 0;; n++) {
#pragma unroll
                        for (int i = 0; i < 3; i++) t[i] = ld_rlx(sp + i * 128);
                        if (!__any_sync(0xffffffffu, ((t[0] ^ tag) | (t[1] ^ tag) | (t[2] ^ tag)) & 31) || n > SPIN_LIMIT) break;
                    }
                    int all = -(1 << 30), own = all;
#pragma unroll
                    for (int i = 0; i < 3; i++) { const int d = t[i] - now; all = max(all, d); if ((i * 32 + l) / 3 == head) own = d; }
                    const int lag = min(__reduce_max_sync(0xffffffffu, all) - __reduce_max_sync(0xffffffffu, own), 8000);
                    PROFV(15, lag);
                    asm volatile("st.shared.u32 [%0], %1;" :: "r"(sm + C_LAG), "r"(D1 + ((lag * DG) >> 4)) : "memory");
                    bar_arrive(6, 160);
                } else if (w == 2) {
                    if ((s & 3) == 3) w_flag_wait(&g_flags.v[((s + 1) >> 2) * 32 + head], 2);
                    if (elect()) { mbar_expect(sm + CB_VX, 4096); bulk_g2s(sm + C_VX, g_att + ((s + 1) * NH + head) * AT_REC + AT_V + j * 4096, 4096, sm + CB_VX); }
                    if ((s & 3) == 1 && s + 3 < NSEG) asm volatile("prefetch.global.L2 [%0];" :: "l"(&g_flags.v[((s + 3) >> 2) * 32]));
                    if (s + 2 < NSEG && ((s & 3) != 2 || __all_sync(0xffffffffu, ld_rlx(&g_flags.v[((s + 2) >> 2) * 32 + head]) >= 2)))
                        asm volatile("prefetch.global.L2 [%0];" :: "l"(g_att + ((s + 2) * NH + head) * AT_REC + AT_V + j * 4096 + (opaque(mrd) << 3 & 0xf80)));
                }
            }
          }
        }
        PROXY_FENCE();
        bar_sync(8, 256);
        if (warp == 5) { qk_out(NSEG - 1); BULK_WAIT(); }
        if (warp == 7) seg_done(NSEG - 2, head);
        bar_arrive(7, 384);
        const int t2 = (opaque(mrd) >> 4 & 31) + warp * 32;
        EPT(t2 == 0, 0);
        last_blocks(ar, sm, blk, t2);
        mod_tail(ar, sm + E_B, sm + EB_REL, blk, t2);
    } else {
        asm volatile("setmaxnreg.dec.sync.aligned.u32 %0;" :: "n"(REG_L));
        asm volatile("barrier.cluster.arrive.relaxed.aligned;" ::: "memory");
        if (blk < 80) {
            const int t = tid - 256;
#pragma unroll 1
            for (int i = 0; i < 10; i++)
                asm volatile("cp.async.cg.shared.global.L2::128B [%0], [%1], 16;" :: "r"(sm + C_XR + i * 2048 + t * 16), "l"(ar.wmod + ((t >> 1) + 64 * i) * (6 * DM) + blk * 16 + (t & 1) * 8) : "memory");
            float cs[5];
#pragma unroll
            for (int i = 0; i < 5; i++) cs[i] = __uint_as_float((uint32_t)__ldg((const unsigned short*)ar.c + t + 128 * i) << 16);
#pragma unroll
            for (int i = 0; i < 5; i++) asm volatile("st.shared.f32 [%0], %1;" :: "r"(sm + C_QX + (t + 128 * i) * 4), "f"(bfr(__fdividef(cs[i], 1.f + __expf(-cs[i])))) : "memory");
            asm volatile("cp.async.wait_all;" ::: "memory");
            bar_sync(3, 128);
            float a0 = 0, a1 = 0;
#pragma unroll 8
            for (int i = 0; i < 40; i++) {
                const float f = __uint_as_float(lds32(sm + C_QX + (t >> 3) * 4 + i * 64));
                const uint32_t u = lds32(sm + C_XR + t * 4 + i * 512);
                a0 += f * lo_f(u); a1 += f * hi_f(u);
            }
#pragma unroll
            for (int o = 8; o < 32; o <<= 1) { a0 += __shfl_xor_sync(0xffffffffu, a0, o); a1 += __shfl_xor_sync(0xffffffffu, a1, o); }
            asm volatile("st.shared.v2.f32 [%0], {%1,%2};" :: "r"(sm + C_QM + w * 64 + (lane & 7) * 8), "f"(a0), "f"(a1) : "memory");
            bar_sync(3, 128);
            if (w == 0) {
#pragma unroll
                for (int i = 1; i < 4; i++) { const float2 z = lds64f(sm + C_QM + i * 64 + (lane & 7) * 8); a0 += z.x; a1 += z.y; }
                const uint32_t v = pack2(a0, a1);
                asm volatile("st.relaxed.gpu.global.u32 [%0], %1;" :: "l"(g_flags.mod1 + blk * 8 + (lane & 7)), "r"(~v) : "memory");
            }
        }
        uint32_t m0[5][4], mm = 0;
#pragma unroll
        for (int i = 0; i < 20; i++) {
            const unsigned short* p = (const unsigned short*)ar.mem0 + (i & 3) * 2 * DM + (i >> 2) * 128 + tid - 256;
            m0[i >> 2][i & 3] = __ldg(p) | (uint32_t)__ldg(p + DM) << 16;
        }
        {
            asm volatile("barrier.cluster.wait.aligned;" ::: "memory");
            if (w == 3) {
                w_flag_wait(&g_flags.h, 96);
                if (elect()) { x_fill(mp, sm, 0, j); x_rest(mp, sm, 0); }
                __syncwarp();
            }
            if (w == 1) {
                const uint64_t ef = policy_stream();
#pragma unroll 1
                for (int c = 0; c < 2 * WP + 2; c++) {
                    const uint32_t bar = sm + EB_B + 8 * (c & 1);
                    if (c == WPOS) bar_sync(2, 288);
                    if (c >= 2) mbar_wait(bar, (c / 2 - 1) & 1);
                    if (elect()) {
                        if (c < 2 * WP) { mbar_expect(bar, 81920 / WP); tma2d_ef(sm + C_WV + c * (81920 / WP), c < WP ? &mp.wq : &mp.wk, col0, c % WP * (640 / WP), bar, ef); }
                        if (c >= WOPF && c < WOPF + 3) asm volatile("cp.async.bulk.prefetch.tensor.3d.L2.global [%0, {0, %1, %2}];" :: "l"((uint64_t)&mp.wo), "r"(head * DH + (c - WOPF) * 64), "r"(7 * j) : "memory");
                    }
                    __syncwarp();
                }
                if (elect()) mbar_arrive(sm + CB_W);
                bar_sync(1, 288);
                if (elect()) {
                    mbar_expect(sm + CB_W2, 81920); mbar_expect(sm + CB_W3, 3 * WO_BLK);
#pragma unroll 1
                    for (int c = 0; c < 4; c++) tma2d(sm + C_WV + c * 20480, &mp.wv, col0, c * 160, sm + CB_W2);
#pragma unroll 1
                    for (int c = 0; c < 3; c++) tma3d(sm + C_WO + c * WO_BLK, &mp.wo, head * DH + (j + c) % 3 * 64, 7 * j, sm + CB_W3);
                }
                __syncwarp();
                w_flag_wait(&g_flags.v[head], 2);
                if (elect()) { mbar_expect(sm + CB_VX, 4096); bulk_g2s(sm + C_VX, g_att + head * AT_REC + AT_V + j * 4096, 4096, sm + CB_VX); }
            } else {
                uint32_t mw = 0;
#pragma unroll 1
                for (int c = 0; c < 2; c++) {
                    mbar_wait(sm + (c ? CB_W3 : CB_W2), 0);
                    uint32_t m = 0;
                    const uint32_t end = sm + (c ? C_XR : C_WO);
#pragma unroll 1
                    for (uint32_t a = sm + c * C_WO + (w - (w > 0)) * 4096 + lane * 16; a < end; a += 3 * 4096) {
                        float4 z[8];
#pragma unroll
                        for (int i = 0; i < 8; i++) z[i] = lds128f(a + i * 512);
#pragma unroll
                        for (int i = 0; i < 8; i++) m = amax2(amax2(amax2(amax2(m, __float_as_uint(z[i].x)), __float_as_uint(z[i].y)), __float_as_uint(z[i].z)), __float_as_uint(z[i].w));
                    }
                    mw |= amax_warp(m) << (16 * c);
                }
                asm volatile("st.shared.u32 [%0], %1;" :: "r"(sm + C_KM + w * 4), "r"(mw) : "memory");
                bar_sync(3, 96);
                if (w == 0) asm volatile("st.relaxed.gpu.global.u32 [%0], %1;" :: "l"(g_flags.wmax + blk), "r"(amax2(amax2(mw, lds32(sm + C_KM + 8)), lds32(sm + C_KM + 12)) | 0x8000) : "memory");
            }
        }
        bar_sync(9, 384);
#pragma unroll
        for (int i = 0; i < 5; i++) {
            asm volatile("st.shared.v4.u32 [%0], {%1,%2,%3,%4};" :: "r"(sm + C_MEM + (tid - 256 + i * 128) * 16), "r"(m0[i][0]), "r"(m0[i][1]), "r"(m0[i][2]), "r"(m0[i][3]) : "memory");
            mm = amax2(amax2(amax2(amax2(mm, m0[i][0]), m0[i][1]), m0[i][2]), m0[i][3]);
        }
        asm volatile("st.shared.u32 [%0], %1; st.shared.u32 [%2], 0x3f800000;" :: "r"(sm + C_MX + w * 4), "r"(amax_warp(mm)), "r"(sm + C_UN) : "memory");
        int ew = __shfl_sync(0xffffffffu, lds32(sm + C_LAG), 0), es = 0;
        const uint32_t rb1 = (uint32_t)((j + 1) % 3 - j) << 24, rb2 = (uint32_t)((j + 2) % 3 - j) << 24;
        const float scale = 0.07216878364870322f;
        uint32_t va[8][4], mr = memrd;
#pragma unroll
        for (int i = 0; i < 8; i++) ldsm4t(va[i], sm + C_WV + ((mi >> 1) * 8 + r) * 128 + (((2 * w + (mi & 1)) ^ r) << 4) + i * 2048);
        bar_sync(1, 384);
        for (int s = 0; s < NSEG; s++) {
            const float un = __uint_as_float((127 - es) << 23);
            if (w == 1) {
                mbar_wait(sm + CB_XD, s & 1);
                if (s + 1 < NSEG) { if (elect()) x_fill(mp, sm, s + 1, j); }
                else { if (BPOS != 2) wo_half(mp, sm, blk, 0); if (BPOS != 0) wo_half(mp, sm, blk, 1); }
            }
            const uint32_t l0 = mr >> 4 & 31, r0 = l0 & 7, m0 = l0 >> 3;
            float vd[4];
            {
                uint32_t c[4][4];
#pragma unroll
                for (int i = 0; i < 4; i++) ldsm4t(c[i], mr + i * 512);
                float d[2][4] = {{0, 0, 0, 0}, {0, 0, 0, 0}};
#pragma unroll
                for (int i = 0; i < 8; i++) mma16q(d[i & 1], va[i], c[i >> 1][2 * (i & 1)], c[i >> 1][2 * (i & 1) + 1]);
#pragma unroll
                for (int i = 0; i < 4; i++) vd[i] = d[0][i] + d[1][i];
            }
            uint32_t zr = 0;
            if (w == 2)
                asm volatile("atom.relaxed.gpu.global.exch.b32 %0, [%1], 0;" : "=r"(zr)
                    : "l"(g_acc + ((s & 2) ^ 2) * (ACC_PAIR / 2) + (s & 1) * 512 + (blk >> 2) * 1024 + (blk & 3) * 128 + l0 * 4) : "memory");
            __syncwarp();
            uint32_t kb[4][4];
            {
                const uint32_t k7 = r0 ^ (m0 << 2 & 4), kxrd = sm + C_KX + (16 * (w & 1) + 8 * (m0 & 1) + k7) * 128 + (((m0 >> 1) ^ k7) << 4);
#pragma unroll
                for (int i = 0; i < 4; i++) ldsm4(kb[i], kxrd ^ (i << 5));
            }
            const uint32_t qrd = sm + C_QM + (w == 1 ? (m0 & 1) * 2 + (m0 >> 1) : m0) * 128 + r0 * 16;
            const uint32_t scdst = sm + C_SC + j * 1280 + (w == 1 ? 1024 + l0 * 8 : (w & 1) * 512 + (l0 & 2) * 128 + (l0 >> 2) * 32 + (l0 & 1) * 16);
            const uint32_t scrd = sm + C_SC + (l0 >> 4) * 256 + (l0 & 3) * 32 + (l0 >> 2 & 3) * 8;
            const uint32_t v7 = (4 * (m0 & 1) + (r0 >> 1)) ^ (r0 << 2 & 4), vxrd = sm + C_VX + (16 * (m0 >> 1) + 8 * (r0 & 1) + v7) * 128 + (((2 * w) ^ v7) << 4);
            if (s == 0) {
                uint32_t t[3];
                for (int n = 0;; n++) {
#pragma unroll
                    for (int i = 0; i < 3; i++) t[i] = ld_rlx(g_flags.wmax + l0 + 32 * i);
                    if (__all_sync(0xffffffffu, t[0] && t[1] && t[2])) break;
                    cut(n, 1 << 22);
                }
                const uint32_t m = amax2(amax2(amax2(0, t[0]), t[1]), t[2]);
                const int e = 371 - (int)(__reduce_max_sync(0xffffffffu, m & 0xffffu) >> 7) - (int)(__reduce_max_sync(0xffffffffu, m >> 16) >> 7);
                ew = e << 16 | (min(e - ew, 100) & 0xffff);
            }
            mbar_wait(sm + CB_VX, s & 1);
            uint32_t vb[2][4];
            ldsm4t(vb[0], vxrd); ldsm4t(vb[1], vxrd ^ 16);
            const uint32_t word = sm + C_WO + (m0 & 1) * 4096 + ((m0 >> 1) * 8 + r0) * 64 + ((w ^ (r0 >> 1)) << 4);
            const uint32_t word6 = word + 6 * 4096 - (m0 & 1) * 3072;
            const uint32_t oxrd = sm + C_OX + l0 * 8;
            const uint32_t ord = oxrd + w * 256;
            const uint32_t vp = mr - (C_MEM - C_VP) + w * 512, vmst = mr + (C_VM - C_MEM) + w * 256;
            pin(mr, scdst + rb1, sm + CB_SC + rb1, scdst + rb2, sm + CB_SC + rb2); pin(mr, qrd, scdst, scrd, vp); pin(mr, word, word6, oxrd, ord);
            pin(mr, __float_as_uint(vd[0]), __float_as_uint(vd[1]), __float_as_uint(vd[2]), __float_as_uint(vd[3]));
            bar_sync(2, 384);
            const bool odd = mr & 16;
            float4 y0, y1, mx4;
            {
                uint32_t qa[2][4];
                ldsm4(qa[0], qrd); ldsm4(qa[1], qrd + 512);
                float sc[2][4] = {{0, 0, 0, 0}, {0, 0, 0, 0}};
                if (w == 1) {
                    ldsm4(kb[0], mr + (C_KM - C_MEM)); ldsm4(kb[1], mr + (C_KM - C_MEM) + 512);
                    pin0(mr); y0 = lds128f(vp); y1 = lds128f(vp + 2048); mx4 = lds128f(sm + C_MX);
#pragma unroll
                    for (int k = 0; k < 4; k++) mma16q(sc[k & 1], qa[k >> 1], kb[k >> 1][2 * (k & 1)], kb[k >> 1][2 * (k & 1) + 1]);
                    const uint32_t a0 = __float_as_uint(sc[0][0] + sc[1][2]), a1 = __float_as_uint(sc[0][1] + sc[1][3]);
                    send8(scdst + rb1, sm + CB_SC + rb1, a0, a1); send8(scdst + rb2, sm + CB_SC + rb2, a0, a1);
                    asm volatile("st.shared.v2.u32 [%0], {%1,%2};" :: "r"(scdst), "r"(a0), "r"(a1) : "memory");
                } else {
                    pin0(mr); y0 = lds128f(vp); y1 = lds128f(vp + 2048); mx4 = lds128f(sm + C_MX);
                    if (w) {
#pragma unroll
                        for (int k = 0; k < 4; k++) mma16q(sc[k & 1], kb[k], qa[k >> 1][2 * (k & 1)], qa[k >> 1][2 * (k & 1) + 1]);
                        const float a0 = sc[0][0] + sc[1][0], a1 = sc[0][2] + sc[1][2], a2 = sc[0][1] + sc[1][1], a3 = sc[0][3] + sc[1][3];
                        send16(scdst + rb1, sm + CB_SC + rb1, a0, a1, a2, a3); send16(scdst + rb2, sm + CB_SC + rb2, a0, a1, a2, a3);
                        sts128f(scdst, a0, a1, a2, a3);
                    }
                }
            }
            bar_arrive(7, 384);
            if (elect()) mbar_arrive(sm + CB_SC);
            {
                const float4 z = mx4;
                const int em = (int)(max(max(__float_as_uint(z.x), __float_as_uint(z.y)), max(__float_as_uint(z.z), __float_as_uint(z.w))) >> 7) - es;
                es = __shfl_sync(0xffffffffu, max(min((ew >> 16) - em, (int)(short)ew), -120), 0);
            }
            if (w == 0) PROF(4);
            const uint32_t vm0 = pack2((vd[0] + y0.x + y1.x) * un, (vd[1] + y0.y + y1.y) * un), vm1 = pack2((vd[2] + y0.z + y1.z) * un, (vd[3] + y0.w + y1.w) * un);
            stsm2t(vmst, vm0, vm1);
            if (s + 1 == NSEG) {
                mbar_wait(sm + CB_SC, s & 1);
                PROXY_FENCE();
                bar_sync(3, 128);
                if (w == 1) {
                    w_bulk_s2g(g_att + (s * NH + head) * AT_REC + AT_VM + j * 1024, sm + C_VM, 1024);
                    BULK_COMMIT();
                    BULK_WAIT();
                }
                __syncwarp();
                break;
            }
            cut(s + ar.D2, 0);
            mbar_wait(sm + CB_SC, s & 1);
            if (w == 0) PROF(8);
            float sv[10];
            {
                float2 z[5][3];
#pragma unroll
                for (int u = 0; u < 5; u++)
#pragma unroll
                    for (int p = 0; p < 3; p++) z[u][p] = lds64f((u < 4 ? scrd + (u >> 1) * 512 + (u & 1) * 128 : oxrd + (C_SC - C_OX) + 1024) + p * 1280);
#pragma unroll
                for (int u = 0; u < 5; u++) { sv[2 * u] = (z[u][0].x + z[u][1].x) + z[u][2].x; sv[2 * u + 1] = (z[u][0].y + z[u][1].y) + z[u][2].y; }
            }
            float mx = fmaxf(fmaxf(fmaxf(sv[0], sv[1]), fmaxf(sv[2], sv[3])), fmaxf(fmaxf(fmaxf(sv[4], sv[5]), fmaxf(sv[6], sv[7])), fmaxf(sv[8], sv[9])));
            uint32_t a[NRING][4];
            auto frag = [&](int i) { const int p = i / 7, u = i % 7, o = (p >> 1) * WO_BLK + (p & 1) * 2048;
                                     return u == 3 ? word6 + o : word + o + (u > 3 ? 1024 + (u - 4) * 8192 : u * 8192); };
            mx = fmaxf(fmaxf(mx, __shfl_xor_sync(0xffffffffu, mx, 1)), fmaxf(__shfl_xor_sync(0xffffffffu, mx, 2), __shfl_xor_sync(0xffffffffu, mx, 3)));
            pin(mr, __float_as_uint(mx), 0, 0, 0);
            {
#pragma unroll
                for (int i = 0; i < NPRE; i++) ldsm4t(a[i], frag(i));
                pin0(mr);
                const float sl2e = scale * 1.4426950408889634f, mxl = mx * sl2e;
#pragma unroll
                for (int i = 9; i >= 0; i--) asm volatile("ex2.approx.ftz.f32 %0, %1;" : "=f"(sv[i]) : "f"(fmaf(sv[i], sl2e, -mxl)));
                const uint32_t pq[4] = {pack2(sv[0], sv[1]), pack2(sv[4], sv[5]), pack2(sv[2], sv[3]), pack2(sv[6], sv[7])}, pm = pack2(sv[8], sv[9]);
                if (w == 0) PROF(6);
                float o[2][4] = {{0, 0, 0, 0}, {0, 0, 0, 0}}, o2[2][4] = {{0, 0, 0, 0}, {0, 0, 0, 0}}, sx[4] = {0, 0, 0, 0};
                mma8(sx, pm, 0, 0x3f803f80u); mma8(o[0], pm, 0, vm0); mma8(o[1], pm, 0, vm1);
                mma16q(sx, pq, 0x3f803f80u, 0x3f803f80u);
#pragma unroll
                for (int u = 0; u < 2; u++) { mma16q(o[u], pq, vb[u][0], vb[u][1]); mma16q(o2[u], pq, vb[u][2], vb[u][3]); }
                float inv; asm("rcp.approx.ftz.f32 %0, %1;" : "=f"(inv) : "f"((sx[0] + sx[2]) * __uint_as_float((127 - es) << 23)));
                const uint32_t f0 = pack2((o[0][0] + o2[0][2]) * inv, (o[0][1] + o2[0][3]) * inv), f1 = pack2((o[1][0] + o2[1][2]) * inv, (o[1][1] + o2[1][3]) * inv);
                send8(ord + 2048 + rb1, sm + CB_OX + rb1, f0, f1); send8(ord + 1024 + rb2, sm + CB_OX + rb2, f0, f1);
                asm volatile("st.shared.v2.u32 [%0], {%1,%2};" :: "r"(ord), "r"(f0), "r"(f1) : "memory");
            }
            if (w == 0) PROF(10);
#pragma unroll
            for (int i = NPRE; i < NRING; i++) ldsm4t(a[i], frag(i));
            bar_sync(3, 128);
            float e[5][4];
#pragma unroll
            for (int q = 0; q < 5; q++) e[q][0] = e[q][1] = e[q][2] = e[q][3] = 0.f;
            constexpr int LAG = 2;
            uint8_t* pdst = g_acc + ((s & 2) * (ACC_PAIR / 2) + (s & 1) * 512 + w * 2048 + j * 8192 - C_MEM - sm + mr);
#pragma unroll
            for (int h = 0; h < 3; h++) {
                uint32_t ob[4][2];
                if (h == 1) {
#pragma unroll
                    for (int i = 14 - LAG; i < 14; i++) ldsm4t(a[i % NRING], frag(i + NRING));
                    pin(mr, zr, (uint32_t)(uint64_t)pdst, (uint32_t)((uint64_t)pdst >> 32), 0);
                    mbar_wait(sm + CB_OX, s & 1);
                    if (w == 0) PROF(9);
                }
#pragma unroll
                for (int k = 0; k < 4; k++) lds64(ob[k], oxrd + h * 1024 + k * 256);
#pragma unroll
                for (int i = 14 * h; i < 14 * h + 14; i++) {
                    const int u = i % 7, k = 2 * (i / 7 & 1);
                    if (u == 3) { mma16q(e[3], a[i % NRING], ob[k][0], ob[k][1]); mma16q(e[4], a[i % NRING], ob[k + 1][0], ob[k + 1][1]); }
                    else mma16q(e[u & 3], a[i % NRING], ob[k + (u >> 2)][0], ob[k + (u >> 2)][1]);
                    if (i == B5AT) { pin(mr, a[i % NRING][0], a[i % NRING][1], a[i % NRING][2], a[i % NRING][3]); bar_arrive(5, 384); }
                    if (i >= LAG && !(i >= 14 && i < 14 + LAG) && i - LAG + NRING < 42) ldsm4t(a[(i - LAG) % NRING], frag(i - LAG + NRING));
                }
            }
            {
                const uint32_t w6 = pack2h(e[3][0] + e[4][2], e[3][1] + e[4][3]), one = 0x3c003c00u;
                asm volatile("red.relaxed.gpu.global.add.noftz.v4.f16x2 [%0], {%1,%2,%3,%4};"
                    :: "l"(pdst), "r"(pack2h(e[0][0], e[0][1])), "r"(pack2h(e[0][2], e[0][3])), "r"(pack2h(e[1][0], e[1][1])), "r"(odd ? w6 : one) : "memory");
                asm volatile("red.relaxed.gpu.global.add.noftz.v4.f16x2 [%0], {%1,%2,%3,%4};"
                    :: "l"(pdst + 1024), "r"(pack2h(e[1][2], e[1][3])), "r"(pack2h(e[2][0], e[2][1])), "r"(pack2h(e[2][2], e[2][3])), "r"(odd ? one : w6) : "memory");
            }
            const uint32_t tw = clock();
            if (w == 0) { PROF(14); PROFG(25); }
            PROXY_FENCE();
            bar_sync(6, 160);
            mr = opaque(mr);
            const uint32_t ln = mr >> 4 & 31, due = tw + lds32(sm + C_LAG);
            const uint32_t vr = sm + C_WV + ((ln >> 4) * 8 + (ln & 7)) * 128 + (((2 * w + (ln >> 3 & 1)) ^ (ln & 7)) << 4);
            const uint32_t ms0 = sm + C_MEM + w * 128 + (ln & 7) * 16 + (ln >> 3) * 512, ms1 = ms0 + (ln < 24 ? 2048 : 1536);
            if (BPOS == 2 && w == 0 && s + 2 == NSEG) wo_half(mp, sm, blk, 0);
            if (w == 2) { w_expect(sm + CB_SC, 2560); w_expect(sm + CB_OX, 2048); asm volatile("st.shared.u32 [%0], %1;" :: "r"(sm + C_UN), "r"((127 - es) << 23) : "memory"); }
            if (w == 0) { w_bulk_s2g(g_att + (s * NH + head) * AT_REC + AT_VM + j * 1024, sm + C_VM, 1024); BULK_COMMIT(); }
            const uint8_t* src = pdst - j * 8192;
            pin(mr, ms0, ms1, (uint32_t)(uint64_t)src, (uint32_t)((uint64_t)src >> 32));
            pin(mr, vr, due, 0, 0);
            cut(s + ar.D2, 1);
#pragma unroll
            for (int i = 0; i < 8; i++) ldsm4t(va[i], vr + i * 2048);
            wait_until(due);
            if (w == 0) { PROF(5); PROFG(26); }
            uint4 v[6];
            auto fetch = [&]() {
#pragma unroll
                for (int k = 0; k < 6; k++)
                    asm volatile("ld.relaxed.gpu.global.v4.u32 {%0,%1,%2,%3}, [%4];" : "=r"(v[k].x), "=r"(v[k].y), "=r"(v[k].z), "=r"(v[k].w) : "l"(src + (k >> 1) * 8192 + (k & 1) * 1024) : "memory");
            };
            fetch();
            PROFV(20 + w, 0);
            bar_sync(9, 384);
#pragma unroll 1
            for (int n = 0; __any_sync(0xffffffffu, ~((odd ? v[1].w & v[3].w & v[5].w : v[0].w & v[2].w & v[4].w)) & 0x50005000u); n++) {
                PROFV(20 + w, n + 1);
                cut(n, SPIN_LIMIT);
                fetch();
            }
            uint32_t cv[3][7];
#pragma unroll
            for (int k = 0; k < 3; k++) {
                const uint4 x = v[2 * k], y = v[2 * k + 1];
                const uint32_t u[7] = {x.x, x.y, x.z, y.x, y.y, y.z, k < 2 ? (odd ? x.w : y.w) : 0u};
#pragma unroll
                for (int i = 0; i < 7; i++) cv[k][i] = f16_to_bf16(u[i]);
                stsm4(ms0 + k * 3584, cv[k][0], cv[k][1], cv[k][2], cv[k][3]);
                if (k < 2) stsm4(ms1 + k * 3584, cv[k][4], cv[k][5], cv[k][6], cv[k][6]);
                else asm volatile("stmatrix.sync.aligned.m8n8.x2.shared.b16 [%0], {%1,%2};" :: "r"(ms1 + k * 3584), "r"(cv[k][4]), "r"(cv[k][5]) : "memory");
            }
            if (w == 0) PROF(16);
            bar_sync(1, 384);
            if (w == 0) BULK_WAIT();
            cut(s + ar.D2, 2);
            uint32_t mc = 0;
#pragma unroll
            for (int i = 0; i < 20; i++) mc = amax2(mc, cv[i / 7][i % 7]);
            asm volatile("st.shared.u32 [%0], %1;" :: "r"(sm + C_MX + w * 4), "r"(amax_warp(mc)) : "memory");
        }
        if (w >= 2) end_loads(mp, ar, sm, blk, w - 2);
        else if (w == 1) { bar_sync(5, 384); seg_done(NSEG - 1, head); EPT(true, 9); if (EORD) bar_arrive(6, 96); if (BPOS == 0) wo_half(mp, sm, blk, 1); }
        else bar_arrive(5, 384);
        if (w < 2) end_stores(mp, sm, blk, w);
        if (w == 0) { mbar_wait(sm + EB_REL, 0); flags_release(mr >> 4 & 31); }
    }
}

struct SideMaps { CUtensorMap h, wv, ost, o, wo, slab3, slab2, lnp[3]; };
constexpr int SD_ST = 14336, SD_NST = 12, SD_EPI = SD_NST * SD_ST, SD_PAR = SD_EPI + 2 * 24576, SD_BAR = SD_PAR + 6400, SD_SMEM = SD_BAR + 1024;
#define VLEAD 16
#define EARLY15 0
#define N_LIGHT 6
#define B_HELP 13
#define AUNR_ 2
constexpr int AUNR = AUNR_;
#define KSO 4
#define KSA 3
#define B_8 10
#define B_16 13
__device__ __forceinline__ int o_shift(int b) { return b >= B_16 ? 4 : b >= B_8 ? 3 : 2; }
__device__ __forceinline__ int o_split(int b) { return 1 << o_shift(b); }
__device__ __forceinline__ uint32_t o_done(int b) { return b >= B_LATE ? 160 : 4 << o_shift(b); }
__device__ __forceinline__ int next_item(int lane) {
    const int b0 = lane & 15, hi = lane >> 4;
    for (int n = 0;; n++) {
        const uint32_t w0 = ld_rlx(g_flags.qk + lane), w1 = ld_rlx(g_flags.at + lane), w2 = ld_rlx(&g_flags.c[0][0] + lane), w3 = ld_rlx(&g_flags.c[2][0] + lane), w4 = ld_rlx(&g_flags.seg[0]);
        const uint32_t o01 = __ballot_sync(0xffffffffu, lane && w2 < 32), o23 = __ballot_sync(0xffffffffu, b0 < (hi ? 14 : B_LATE) && w3 < 2u * o_split(b0));
        const uint32_t ra = __ballot_sync(0xffffffffu, w0 >= (hi ? 64u : 96u)), rb = __ballot_sync(0xffffffffu, w1 >= (hi ? o_done(b0) : 64u));
        const int bv = __ffs(o01 | 0x10000) - 1, ba = __ffs(o01 >> 16 | 0x10000) - 1, bo = __ffs(o23 | 0x10000) - 1, bl = __ffs(o23 >> 16 | 0x10000) - 1;
        if (bl == 16 && ba == 16) return -1;
        const int bc = __ffs(~ra | 0x10000) - 1;
        const bool last = ba == 15 && (w4 >= 3 || (EARLY15 && bc == 15));
        const bool r1 = (ra & ra >> 16) >> ba & 1, r2 = (rb & 0xffff) >> bo & 1, r3 = rb >> 16 >> bl & 1;
        const int kind = ba == 16 ? (bo < 16 ? 2 : 3) : last ? 1 :
                         blockIdx.x < N_LIGHT ? (r1 ? 1 : r3 ? 3 : bv < 16 ? 0 : -1) :
                         bv < 16 && (bv <= bc + VLEAD || !r2) ? 0 : r1 && ba >= B_HELP ? 1 : r2 ? 2 : r1 ? 1 : r3 ? 3 : bo < ba ? 2 : -1;
        if (kind < 0) { if (n > (1 << 20)) __trap(); __nanosleep(300); continue; }
        const int b = kind == 3 ? bl : kind == 2 ? bo : kind == 1 ? ba : bv;
        uint32_t i = 0;
        if (lane == 0) asm volatile("atom.relaxed.gpu.global.add.u32 %0, [%1], 1;" : "=r"(i) : "l"(&g_flags.c[kind][b]) : "memory");
        i = __shfl_sync(0xffffffffu, i, 0);
        if (i < (kind < 2 ? 32u : 2u * o_split(b))) return kind << 16 | b << 8 | i | ((kind == 1 ? r1 : kind == 2 ? r2 : r3) ? 128 : 0);
    }
}

template <int NP>
__device__ __forceinline__ void tile_out(const float (&acc)[8 * NP], uint32_t eb, uint32_t CH, uint32_t efull, uint32_t eempty, int& eph, int lane) {
    const int r = lane & 7, mi = lane >> 3, row = (mi & 1) * 8 + r;
    mbar_wait(eempty, eph); eph ^= 1;
#pragma unroll
    for (int p = 0; p < NP; p++) {
        const int oc = 2 * p + (mi >> 1);
        stsm4(eb + (oc >> 3) * CH + row * 128 + (((oc & 7) ^ r) << 4), pack2(acc[8 * p], acc[8 * p + 1]), pack2(acc[8 * p + 2], acc[8 * p + 3]),
              pack2(acc[8 * p + 4], acc[8 * p + 5]), pack2(acc[8 * p + 6], acc[8 * p + 7]));
    }
    asm volatile("fence.proxy.async.shared::cta;" ::: "memory");
    __syncwarp();
    if (lane == 0) mbar_arrive(efull);
}

template <int MT>
__device__ __forceinline__ void attn_tile(uint32_t base, uint32_t dst, uint32_t eempty, int eph, int lane) {
    constexpr int NK = MT ? 5 : 3;
    const int r = lane & 7, mi = lane >> 3, g = lane >> 2, t = lane & 3;
    float sc[NK][4];
#pragma unroll
    for (int n = 0; n < NK; n++) sc[n][0] = sc[n][1] = sc[n][2] = sc[n][3] = 0.f;
#pragma unroll AUNR
    for (int k2 = 0; k2 < 6; k2++) {
        const uint32_t cb = (k2 >> 1) * 8192, c0 = (k2 & 1) * 4;
        uint32_t a0[4], a1[4], bb[NK][4];
        ldsm4(a0, base + cb + (16 * MT + (mi & 1) * 8 + r) * 128 + (((c0 + (mi >> 1)) ^ r) << 4));
        ldsm4(a1, base + cb + (16 * MT + (mi & 1) * 8 + r) * 128 + (((c0 + 2 + (mi >> 1)) ^ r) << 4));
#pragma unroll
        for (int n = 0; n < NK; n++)
            ldsm4(bb[n], n < NK - 1 ? base + 4096 + cb + (8 * n + r) * 128 + (((c0 + mi) ^ r) << 4) : base + 36864 + k2 * 512 + lane * 16);
#pragma unroll
        for (int n = 0; n < NK; n++) mma16(sc[n], a0[0], a0[1], a0[2], a0[3], bb[n][0], bb[n][1]);
#pragma unroll
        for (int n = 0; n < NK; n++) mma16(sc[n], a1[0], a1[1], a1[2], a1[3], bb[n][2], bb[n][3]);
    }
    const float scale = 0.07216878364870322f, l2e = 1.4426950408889634f;
    float v[2][2 * NK], mx[2], sum[2];
#pragma unroll
    for (int hf = 0; hf < 2; hf++) {
        mx[hf] = -INFINITY;
#pragma unroll
        for (int n = 0; n < NK; n++) {
            uint32_t u = pack2(sc[n][2 * hf], sc[n][2 * hf + 1]);
            u = pack2(lo_f(u) * scale, hi_f(u) * scale);
            const int lim = 16 * MT + 8 * hf + g - 8 * n - 2 * t;
            v[hf][2 * n] = (n < NK - 1 && lim < 0) ? -1e9f : lo_f(u);
            v[hf][2 * n + 1] = (n < NK - 1 && lim < 1) ? -1e9f : hi_f(u);
            mx[hf] = fmaxf(mx[hf], fmaxf(v[hf][2 * n], v[hf][2 * n + 1]));
        }
    }
#pragma unroll
    for (int o = 1; o < 4; o <<= 1)
#pragma unroll
        for (int hf = 0; hf < 2; hf++) mx[hf] = fmaxf(mx[hf], __shfl_xor_sync(0xffffffffu, mx[hf], o));
#pragma unroll
    for (int hf = 0; hf < 2; hf++) {
        sum[hf] = 0;
#pragma unroll
        for (int q = 0; q < 2 * NK; q++) { asm("ex2.approx.ftz.f32 %0, %1;" : "=f"(v[hf][q]) : "f"((v[hf][q] - mx[hf]) * l2e)); sum[hf] += v[hf][q]; }
    }
#pragma unroll
    for (int o = 1; o < 4; o <<= 1)
#pragma unroll
        for (int hf = 0; hf < 2; hf++) sum[hf] += __shfl_xor_sync(0xffffffffu, sum[hf], o);
    uint32_t pa[NK][2];
#pragma unroll
    for (int hf = 0; hf < 2; hf++) {
        const float inv = __fdividef(1.f, sum[hf]);
#pragma unroll
        for (int n = 0; n < NK; n++) pa[n][hf] = pack2(v[hf][2 * n] * inv, v[hf][2 * n + 1] * inv);
    }
    mbar_wait(eempty, eph);
#pragma unroll AUNR
    for (int n4 = 0; n4 < 6; n4++) {
        const uint32_t cb = (n4 >> 1) * 4096, c0 = (n4 & 1) * 4;
        uint32_t bm[4], bb[2 + 2 * MT][4];
        ldsm4t(bm, base + AT_VM + n4 * 512 + lane * 16);
#pragma unroll
        for (int u = 0; u < 2 + 2 * MT; u++) ldsm4t(bb[u], base + AT_V + cb + (16 * (u >> 1) + 8 * (mi & 1) + r) * 128 + (((c0 + 2 * (u & 1) + (mi >> 1)) ^ r) << 4));
        float o[4][4];
#pragma unroll
        for (int u = 0; u < 4; u++) { o[u][0] = o[u][1] = o[u][2] = o[u][3] = 0.f; mma8(o[u], pa[NK - 1][0], pa[NK - 1][1], bm[u]); }
#pragma unroll
        for (int u = 0; u < 4 + 4 * MT; u++) mma16(o[u & 3], pa[u >> 2 << 1][0], pa[u >> 2 << 1][1], pa[(u >> 2 << 1) + 1][0], pa[(u >> 2 << 1) + 1][1], bb[u >> 1][2 * (u & 1)], bb[u >> 1][2 * (u & 1) + 1]);
#pragma unroll
        for (int p = 0; p < 2; p++)
            stsm4(dst + (n4 >> 1) * 2048 + ((mi & 1) * 8 + r) * 128 + (((c0 + 2 * p + (mi >> 1)) ^ r) << 4), pack2(o[2 * p][0], o[2 * p][1]), pack2(o[2 * p][2], o[2 * p][3]),
                  pack2(o[2 * p + 1][0], o[2 * p + 1][1]), pack2(o[2 * p + 1][2], o[2 * p + 1][3]));
    }
}

__device__ __forceinline__ uint32_t ln_row(const uint32_t (&as)[10], const uint2 (&xin)[5], int row, uint32_t par, uint32_t low, bf16* out, uint64_t ef, int lane) {
    const uint32_t pa = par + lane * 8;
    uint32_t xv[10], hv[10], sv[10], tv[10];
#pragma unroll
    for (int q = 0; q < 5; q++) {
        uint32_t ga[2], t[2], u[2];
        lds64(ga, pa + q * 256); lds64(t, pa + 1280 + q * 256); lds64(u, pa + 2560 + q * 256);
#pragma unroll
        for (int e = 0; e < 2; e++) {
            xv[2 * q + e] = add2(e ? xin[q].y : xin[q].x, mul2(ga[e], as[2 * q + e]));
            tv[2 * q + e] = t[e]; sv[2 * q + e] = u[e];
        }
    }
    ln_mod(xv, sv, tv, hv);
    float rs = 0;
#pragma unroll
    for (int q = 0; q < 5; q++) {
        const int c = row * DM + lane * 4 + q * 128;
        const uint32_t h0 = hv[2 * q], h1 = hv[2 * q + 1];
        uint32_t gb[2], wv[2];
        lds64(gb, pa + 3840 + q * 256); lds64(wv, pa + 5120 + q * 256);
        rs += (lo_f(h0) * lo_f(wv[0]) + hi_f(h0) * hi_f(wv[0])) + (lo_f(h1) * lo_f(wv[1]) + hi_f(h1) * hi_f(wv[1]));
        st_ef(out + c, make_uint2(add2(xv[2 * q], mul2(gb[0], h0)), add2(xv[2 * q + 1], mul2(gb[1], h1))), ef);
    }
    const uint32_t rb = pack2(0.f, warp_sum(rs));
    const uint32_t key = (((int)rb < 0 ? ~rb : rb | 0x80000000u) & 0xffff0000u) | (uint32_t)(2 * S_TOK - 1 - row);
    if (key > low) {
#pragma unroll
        for (int q = 0; q < 5; q++) {
            *(uint2*)(g_x1 + row * DM + lane * 4 + q * 128) = make_uint2(xv[2 * q], xv[2 * q + 1]);
            *(uint2*)(g_h2 + row * DM + lane * 4 + q * 128) = make_uint2(hv[2 * q], hv[2 * q + 1]);
        }
    }
    return key;
}
__device__ __forceinline__ void key_out(uint32_t key) {
    __syncwarp();
    if (key) asm volatile("st.release.gpu.global.u32 [%0], %1;" :: "l"(g_key + (~key & (S_TOK - 1))), "r"(key) : "memory");
}

__global__ void __launch_bounds__(384, 1) k_side(const __grid_constant__ SideMaps mp, const bf16* __restrict__ x, const bf16* __restrict__ wr, const bf16* wmod, const bf16* cvec, bf16* __restrict__ out) {
    extern __shared__ __align__(1024) uint8_t smraw[];
    const uint32_t sm = smem_u32(smraw);
    if (sm & 1023) __trap();
    const uint32_t BARS = sm + SD_BAR, FULL = BARS + 768, EMPTY = FULL + 96, EFULL = BARS + 64, EEMPTY = BARS + 80, IFULL = BARS + 96, IEMPTY = BARS + 128, IQ = BARS + 160, SCHED = BARS + 176, PARAM = BARS + 184, ADONE = BARS + 192, LOW = BARS + 224, KEYS = BARS + 256;
    const int tid = threadIdx.x, warp = __shfl_sync(0xffffffffu, tid >> 5, 0), lane = tid & 31;
    const uint64_t ef = policy_stream();
    if (tid == 0) {
#pragma unroll 1
        for (int i = 0; i < SD_NST; i++) { mbar_init(FULL + 8 * i, 1); mbar_init(EMPTY + 8 * i, 2); }
        for (int i = 0; i < 2; i++) { mbar_init(EFULL + 8 * i, 4); mbar_init(EEMPTY + 8 * i, 1); }
        for (int i = 0; i < 4; i++) { mbar_init(IFULL + 8 * i, 1); mbar_init(IEMPTY + 8 * i, 11); }
        mbar_init(SCHED, 1); mbar_init(PARAM, 1);
        sts128f(ADONE, 0, 0, 0, 0); sts128f(ADONE + 16, 0, 0, 0, 0); sts128f(LOW, 0, 0, 0, 0);
        asm volatile("fence.mbarrier_init.release.cluster;" ::: "memory");
    }
    if (SDEL) __nanosleep(SDEL);
    __syncthreads();
    if (warp >= 8) {
      asm volatile("setmaxnreg.dec.sync.aligned.u32 40;");
      if (warp == 8) {
        int st = 0, ph = 1;
        for (int q = 0;; q++) {
            mbar_wait(IFULL + 8 * (q & 3), (q >> 2) & 1);
            const int it = __shfl_sync(0xffffffffu, lds32(IQ + 4 * (q & 3)), 0);
            if (elect()) mbar_arrive(IEMPTY + 8 * (q & 3));
            if (it < 0) break;
            const int kind = it >> 16, b = (it >> 8) & 255, i = it & 63;
            const int nst = kind == 0 ? 10 : kind == 1 ? 4 : kind == 2 ? 192 >> o_shift(b) : b == 14 ? 4 : 2;
            const int ksched = kind == 0 ? 4 : kind == 2 ? nst - KSO : (it & 128) ? -1 : kind == 1 ? KSA : 0;
            if (ksched < 0 && elect()) mbar_arrive(SCHED);
            const bool look = !(it & 128);
            const int nu = kind == 2 ? 2 : 3;
            if (look && kind == 1) flag_wait(&g_flags.v[b * 32 + i], 2);
            if (look && kind == 3 && b < 14) flag_wait(&g_flags.o[b], o_done(b));
            for (int kb = 0; kb < nst; kb++) {
                if (kb < 6) mbar_wait(EMPTY + 8 * st, ph);
                mbar_wait(EMPTY + 8 * (st + nu - 1), ph);
                const uint32_t base = sm + st * SD_ST, fb = FULL + 8 * st;
                if (lane && lane < nu) mbar_arrive(fb + 8 * lane);
                if (look && kind == 1) flag_wait(&g_flags.seg[kb * 32 + i], 3);
                if (kb == ksched && elect()) mbar_arrive(SCHED);
                if (kind == 0) {
                    if (q == 0 && kb == 0) {
                        if (elect()) {
#pragma unroll 1
                            for (int c = 0; c < 4; c++) tma3d(sm + 3 * c * SD_ST + 16384, &mp.wv, c * 64, i * 3, FULL + 24 * c);
                        }
                        flag_wait(&g_flags.h, 96);
                    }
                    if (elect()) {
                        mbar_expect(fb, 40960);
                        tma2d(base, &mp.h, kb * 64, b * 128, fb);
                        if (q || kb >= 4) tma3d(base + 16384, &mp.wv, kb * 64, i * 3, fb);
                    }
                } else if (kind == 1) {
                    if (elect()) {
                        mbar_expect(fb, 43008);
                        asm volatile("cp.async.bulk.shared::cluster.global.mbarrier::complete_tx::bytes.L2::cache_hint [%0], [%1], %2, [%3], %4;"
                            :: "r"(base), "l"(g_att + ((b * 4 + kb) * NH + i) * AT_REC), "r"(AT_REC), "r"(fb), "l"(ef) : "memory");
                    }
                } else if (kind == 3) {
                    if (b == 14 && !(kb & 1)) flag_wait(&g_flags.fin[(kb + (i >> 4)) * 32], 80);
                    if (elect()) { mbar_expect(fb, 40960); tma3d_ef(base, &mp.lnp[o_shift(b) - 2], i * (160 >> o_shift(b)), b * KSPLIT + (kb << o_shift(b) >> 1), fb, ef); }
                } else {
                    const int k0 = ((i >> 1) * nst + kb) * 32;
                    if (elect()) { mbar_expect(fb, 28672); tma3d(base + 8192, &mp.wo, k0, (i & 1) * 5, fb); }
                    if (look && kb % 12 == 0) flag_wait(&g_flags.pair[b * 16 + k0 / 384], 4);
                    if (elect()) tma2d_ef(base, &mp.o, k0, b * 128, fb, ef);
                }
                __syncwarp();
                st += nu; if (st == SD_NST) { st = 0; ph ^= 1; }
            }
        }
      } else if (warp == 11) {
        bool fin = false, par = false;
        for (int q = 0;; q++) {
            if (q) mbar_wait(SCHED, (q - 1) & 1);
            int it = fin ? -1 : q == 0 && blockIdx.x < 32 ? (int)blockIdx.x : next_item(lane);
            if (it < 0 && !fin && blockIdx.x < 32) { it = 3 << 16 | 14 << 8 | blockIdx.x; fin = true; }
            if (lane == 0) {
                if (it >> 16 == 3) {
                    const int b = (it >> 8) & 255, nr = 64 >> o_shift(b);
                    asm volatile("cp.async.bulk.prefetch.L2.global [%0], %1;" :: "l"(x + (b * 128 + (it & 63) * nr) * DM), "r"(nr * DM * 2) : "memory");
                }
                mbar_wait(IEMPTY + 8 * (q & 3), ((q >> 2) & 1) ^ 1);
                asm volatile("st.shared.u32 [%0], %1;" :: "r"(IQ + 4 * (q & 3)), "r"(it) : "memory");
                mbar_arrive(IFULL + 8 * (q & 3));
            }
            if (it >> 16 >= 2 && (it >> 8 & 255) >= 2) {
                const uint4* kp = (const uint4*)g_key + max((it >> 8 & 255) - ((it >> 16) == 2 ? 5 : 3), 0) * 32 + lane;
                const uint4 k1 = __ldcg(kp), k2 = __ldcg(kp + 32);
                uint32_t m = max(max(max(k1.x, k1.y), max(k1.z, k1.w)), max(max(k2.x, k2.y), max(k2.z, k2.w)));
                m = max(m, __shfl_xor_sync(0xffffffffu, m, 1)); m = max(m, __shfl_xor_sync(0xffffffffu, m, 2));
                asm volatile("red.shared.max.u32 [%0], %1;" :: "r"(LOW), "r"(__reduce_min_sync(0xffffffffu, m)) : "memory");
            }
            if (!par && it >> 16 == 3) {
                par = true;
                flag_wait(&g_flags.mod, 64);
                if (lane == 0) { mbar_expect(PARAM, 6400); bulk_g2s(sm + SD_PAR, g_mod + 2 * DM, 5120, PARAM); bulk_g2s(sm + SD_PAR + 5120, wr, 1280, PARAM); }
            }
            __syncwarp();
            if (it < 0) break;
        }
        flags_release(lane);
      } else {
        if (lane == 0) {
            const int wg = warp - 9; int ph = 0;
            for (int q = 0;; q++) {
                mbar_wait(IFULL + 8 * (q & 3), (q >> 2) & 1);
                const int it = lds32(IQ + 4 * (q & 3));
                mbar_arrive(IEMPTY + 8 * (q & 3));
                if (it < 0) break;
                const int kind = it >> 16, b = (it >> 8) & 255, i = it & 63;
                if (kind == 3 && b == 14) continue;
                if (kind & 1) {
                    for (int n = 0;; n++) {
                        uint32_t d0, d1, d2, d3;
                        asm volatile("ld.volatile.shared.v4.u32 {%0,%1,%2,%3}, [%4];" : "=r"(d0), "=r"(d1), "=r"(d2), "=r"(d3) : "r"(ADONE + wg * 16) : "memory");
                        if (min(min(d0, d1), min(d2, d3)) > q) break;
                        if (n > (1 << 24)) __trap();
                        __nanosleep(40);
                    }
                    GPU_FENCE();
                    EPT(kind == 1 && b == 15 && wg, 17);
                    if (kind == 1) { bump(b == 15 ? &g_flags.half[(i & 30) + wg] : &g_flags.pair[b * 16 + (i >> 1)]); bump(&g_flags.at[b]); }
                    else {
#pragma unroll 1
                        for (int c = 0; c < 8; c++) { const uint32_t key = lds32(KEYS + (q & 7) * 64 + wg * 32 + c * 4); if (key) asm volatile("st.relaxed.gpu.global.u32 [%0], %1;" :: "l"(g_key + (~key & (S_TOK - 1))), "r"(key) : "memory"); }
                    }
                    continue;
                }
#pragma unroll 1
                for (int rd = 0; rd < (kind == 2 ? 2 : 1); rd++) {
                    mbar_wait(EFULL + 8 * wg, ph); ph ^= 1;
                    const uint32_t src = sm + SD_EPI + wg * 24576;
                    if (kind == 2) tma3d_store(rd ? &mp.slab3 : &mp.slab2, (b * KSPLIT + (i >> 1)) * 128 + wg * 64, (i & 1) * 5 + (rd ? 0 : 3), src, ef, false);
                    else {
                        uint8_t* dst = g_att + ((b * 4 + wg * 2) * NH + i) * AT_REC + AT_V;
                        asm volatile("cp.async.bulk.global.shared::cta.bulk_group.L2::cache_hint [%0], [%1], 12288, %2;" :: "l"(dst), "r"(src), "l"(ef) : "memory");
                        asm volatile("cp.async.bulk.global.shared::cta.bulk_group.L2::cache_hint [%0], [%1], 12288, %2;" :: "l"(dst + NH * AT_REC), "r"(src + 12288), "l"(ef) : "memory");
                    }
                    asm volatile("cp.async.bulk.commit_group;" ::: "memory");
                    asm volatile("cp.async.bulk.wait_group.read 0;" ::: "memory");
                    mbar_arrive(EEMPTY + 8 * wg);
                }
                asm volatile("cp.async.bulk.wait_group 0;" ::: "memory");
                GPU_FENCE();
                bump(kind == 0 ? &g_flags.v[b * 32 + i] : &g_flags.o[b]);
                if (kind == 0) bump(&g_flags.vb[b]);
            }
        }
      }
    } else {
        asm volatile("setmaxnreg.inc.sync.aligned.u32 232;");
        const int wg = warp >> 2, w = warp & 3;
        int st = 0, ph = 0, eph = 1;
        bool att = false;
        uint4 mz[4] = {}; uint2 mc = {}; float ma[8] = {0, 0, 0, 0, 0, 0, 0, 0};
        const uint32_t eb = sm + SD_EPI + wg * 24576;
        for (int q = 0;; q++) {
            mbar_wait(IFULL + 8 * (q & 3), (q >> 2) & 1);
            const int itc = __shfl_sync(0xffffffffu, lds32(IQ + 4 * (q & 3)), 0);
            __syncwarp();
            if (lane == 0) mbar_arrive(IEMPTY + 8 * (q & 3));
            if (itc < 0) break;
            const int kind = itc >> 16, b = (itc >> 8) & 255, i = itc & 63;
            if (q >= 1 && q <= 9 && blockIdx.x < 32) {
                const int t = min(tid, 199), k = t / 10 * 32 + (q - 1) * 4;
#pragma unroll
                for (int e = 0; e < 4; e++) {
                    const uint32_t cw = e & 2 ? mc.y : mc.x;
                    const float c = e & 1 ? hi_f(cw) : lo_f(cw), f = bfr(__fdividef(c, 1.f + __expf(-c)));
                    ma[0] += f * lo_f(mz[e].x); ma[1] += f * hi_f(mz[e].x); ma[2] += f * lo_f(mz[e].y); ma[3] += f * hi_f(mz[e].y);
                    ma[4] += f * lo_f(mz[e].z); ma[5] += f * hi_f(mz[e].z); ma[6] += f * lo_f(mz[e].w); ma[7] += f * hi_f(mz[e].w);
                }
                if (q < 9) {
#pragma unroll
                    for (int e = 0; e < 4; e++) mz[e] = __ldcs((const uint4*)(wmod + (k + e) * (6 * DM) + 2 * DM + blockIdx.x * 80 + t % 10 * 8));
                    mc = __ldg((const uint2*)(cvec + k));
                } else {
                    sts128f(sm + SD_PAR + t * 32, ma[0], ma[1], ma[2], ma[3]); sts128f(sm + SD_PAR + 16 + t * 32, ma[4], ma[5], ma[6], ma[7]);
                    bar_sync(1, 256);
                    if (tid < 40) {
                        float a0 = 0, a1 = 0;
#pragma unroll 4
                        for (int g = 0; g < 20; g++) { const float2 v = lds64f(sm + SD_PAR + g * 320 + tid * 8); a0 += v.x; a1 += v.y; }
                        ((uint32_t*)(g_mod + 2 * DM + blockIdx.x * 80))[tid] = pack2(a0, a1);
                    }
                    __syncwarp();
                    if (warp < 2 && lane == 0) flag_add(&g_flags.mod);
                }
            }
            if (att && kind != 1) { bar_sync(1, 256); att = false; }
            int prev = -1;
            auto next = [&](int nu) {
                WG_COMMIT();
                WG_WAIT(1);
                if (prev >= 0 && (tid & 127) < nu) mbar_arrive(EMPTY + 8 * (prev + (tid & 127)));
                prev = st;
                st += nu; if (st == SD_NST) { st = 0; ph ^= 1; }
            };
            auto desc = [](uint32_t lo, uint32_t hi) { return (uint64_t)hi << 32 | lo; };
            if (kind == 0) {
                float acc[96];
#pragma unroll
                for (int n = 0; n < 96; n++) acc[n] = 0.f;
#pragma unroll 1
                for (int kb = 0; kb < 10; kb++) {
                    mbar_wait(FULL + 8 * st, ph);
                    const uint32_t d0 = (sm + st * SD_ST) >> 4, da = d0 + wg * 512 + 0x10000, db = d0 + 1024 + 0x2000000;
                    WG_FENCE();
#pragma unroll
                    for (int ks = 0; ks < 4; ks++) wgmma_ss_n192_tb(acc, desc(da + ks * 2, 0x40000040), desc(db + ks * 128, 0x40000040), 1);
                    next(3);
                }
                WG_WAIT(0);
                if ((tid & 127) < 3) mbar_arrive(EMPTY + 8 * (prev + (tid & 127)));
                tile_out<12>(acc, eb + (w >> 1) * 12288 + (w & 1) * 2048, 4096, EFULL + 8 * wg, EEMPTY + 8 * wg, eph, lane);
            } else if (kind == 2) {
                float acc[96], acc2[64];
#pragma unroll
                for (int n = 0; n < 96; n++) acc[n] = 0.f;
#pragma unroll
                for (int n = 0; n < 64; n++) acc2[n] = 0.f;
                int kb = 192 >> o_shift(b);
#pragma unroll 1
                do {
                    mbar_wait(FULL + 8 * st, ph);
                    const uint32_t d0 = (sm + st * SD_ST) >> 4, da = d0 + wg * 256 + 0x10000, db = d0 + 512 + 0x1000000;
                    WG_FENCE();
#pragma unroll
                    for (int ks = 0; ks < 2; ks++) {
                        wgmma_ss_n192_tb(acc, desc(da + ks * 2, 0x80000020), desc(db + ks * 128, 0x40000040), 1);
                        wgmma_ss_n128_tb(acc2, desc(da + ks * 2, 0x80000020), desc(db + 768 + ks * 128, 0x40000040), 1);
                    }
                    next(2);
                } while (--kb);
                WG_WAIT(0);
                if ((tid & 127) < 2) mbar_arrive(EMPTY + 8 * (prev + (tid & 127)));
                tile_out<8>(acc2, eb + w * 2048, 8192, EFULL + 8 * wg, EEMPTY + 8 * wg, eph, lane);
                tile_out<12>(acc, eb + w * 2048, 8192, EFULL + 8 * wg, EEMPTY + 8 * wg, eph, lane);
            } else if (kind == 1) {
                const int seg = warp >> 1, mt = warp & 1;
                int sst = st + 3 * seg, sph = ph; if (sst >= SD_NST) { sst -= SD_NST; sph ^= 1; }
                ph ^= 1;
                mbar_wait(FULL + 8 * sst, sph);
                EPT(tid == 224 && b == 15, 16);
                const uint32_t base = sm + sst * SD_ST;
                if (mt) attn_tile<1>(base, eb + w * 6144, EEMPTY + 8 * wg, eph, lane);
                else attn_tile<0>(base, eb + w * 6144, EEMPTY + 8 * wg, eph, lane);
                asm volatile("fence.proxy.async.shared::cta;" ::: "memory");
                __syncwarp();
                if (lane < 3) mbar_arrive(EMPTY + 8 * (sst + lane));
                if (lane == 0) {
                    tma3d_store(&mp.ost, b * 128 + warp * 16, i * 3, eb + w * 6144, ef, false);
                    BULK_COMMIT(); BULK_WAIT();
                    asm volatile("st.release.cta.shared.u32 [%0], %1;" :: "r"(ADONE + warp * 4), "r"(q + 1) : "memory");
                }
                __syncwarp();
                att = true;
            } else {
                const int sh = o_shift(b), nr = 64 >> sh, fw = b == 14 ? wg : 0, row0 = (b + fw) * 128 + i * nr, lw = warp - 4 * fw;
                if (fw) { ph ^= st != 0; st ^= 6; }
                uint2 xin[2][5];
                uint32_t as[2][10] = {};
#pragma unroll
                for (int q2 = 0; q2 < 10; q2++) xin[q2 & 1][q2 >> 1] = ld_ef(x + (row0 + ((warp + 8 * (q2 & 1)) & (nr - 1))) * DM + lane * 4 + (q2 >> 1) * 128, ef);
                mbar_wait(PARAM, 0); mbar_wait(FULL + 8 * st, ph); mbar_wait(FULL + 8 * st + 24, ph);
                EPT((tid & 127) == 0 && b == 14, 18 + wg);
#pragma unroll 1
                for (int lrow = lw + (nr & 16) / 2; lrow >= 0 && lrow < nr; lrow -= 8) {
                    float a[20];
#pragma unroll
                    for (int q2 = 0; q2 < 20; q2++) a[q2] = 0.f;
#pragma unroll 1
                    for (int k = 0; k < (1 << sh >> 1); k++) {
                        const uint32_t ad = sm + st * SD_ST + ((k << (6 - sh)) + lrow) * 1280 + lane * 8;
                        uint32_t z[10][2];
#pragma unroll
                        for (int q2 = 0; q2 < 10; q2++) lds64(z[q2], ad + (q2 < 5 ? 0 : 3 * SD_ST) + q2 % 5 * 256);
#pragma unroll
                        for (int q2 = 0; q2 < 10; q2++) { float* p = a + q2 % 5 * 4; p[0] += lo_f(z[q2][0]); p[1] += hi_f(z[q2][0]); p[2] += lo_f(z[q2][1]); p[3] += hi_f(z[q2][1]); }
                    }
#pragma unroll
                    for (int q2 = 0; q2 < 10; q2++) { as[1][q2] = as[0][q2]; as[0][q2] = pack2(a[2 * q2], a[2 * q2 + 1]); }
                }
                bar_sync(2 + wg, 128);
                if ((tid & 127) < 6) mbar_arrive(EMPTY + 8 * (st + (tid & 127)));
                uint32_t key = 0;
#pragma unroll 1
                for (int lrow = lw; lrow < nr; lrow += 8) {
                    const int row = row0 + lrow;
                    const uint32_t k1 = ln_row(as[0], xin[0], row, sm + SD_PAR, lds32(LOW), out, ef, lane);
                    if (lane == lrow >> 3) key = k1;
#pragma unroll
                    for (int q2 = 0; q2 < 5; q2++) { as[0][2 * q2] = as[1][2 * q2]; as[0][2 * q2 + 1] = as[1][2 * q2 + 1]; xin[0][q2] = xin[1][q2]; }
                }
                if (b == 14) { EPT(tid == 128, 20); key_out(key); EPT(tid == 128, 21); }
                else {
                    if (lane < 2) asm volatile("st.shared.u32 [%0], %1;" :: "r"(KEYS + (q & 7) * 64 + warp * 8 + lane * 4), "r"(key) : "memory");
                    __syncwarp();
                    if (lane == 0) asm volatile("st.release.cta.shared.u32 [%0], %1;" :: "r"(ADONE + warp * 4), "r"(q + 1) : "memory");
                }
                ph ^= st != 0; st ^= 6;
            }
        }
    }
    __syncwarp();
    asm volatile("griddepcontrol.wait;" ::: "memory");
}

#define P_D1 550
#define P_DL 700
#define P_DG 29
typedef CUresult (*EncodeFn)(CUtensorMap*, CUtensorMapDataType, cuuint32_t, void*, const cuuint64_t*, const cuuint64_t*, const cuuint32_t*, const cuuint32_t*,
                             CUtensorMapInterleave, CUtensorMapSwizzle, CUtensorMapL2promotion, CUtensorMapFloatOOBfill);
static EncodeFn s_encode = nullptr;
static void make_map(CUtensorMap* m, const void* p, int rows, int cols, int box_rows, int box_cols = 64) {
    cuuint64_t dims[2] = {(cuuint64_t)cols, (cuuint64_t)rows}, strides[1] = {(cuuint64_t)cols * 2};
    cuuint32_t box[2] = {(cuuint32_t)box_cols, (cuuint32_t)box_rows}, es[2] = {1, 1};
    s_encode(m, CU_TENSOR_MAP_DATA_TYPE_BFLOAT16, 2, (void*)p, dims, strides, box, es, CU_TENSOR_MAP_INTERLEAVE_NONE,
             box_cols == 64 ? CU_TENSOR_MAP_SWIZZLE_128B : box_cols == 32 ? CU_TENSOR_MAP_SWIZZLE_64B : CU_TENSOR_MAP_SWIZZLE_NONE, CU_TENSOR_MAP_L2_PROMOTION_L2_256B, CU_TENSOR_MAP_FLOAT_OOB_FILL_NONE);
}
static void make_map3(CUtensorMap* m, const void* p, int rows, int cols, int box_rows, int box_chunks, int cw = 64) {
    cuuint64_t dims[3] = {(cuuint64_t)cw, (cuuint64_t)rows, (cuuint64_t)(cols / cw)}, strides[2] = {(cuuint64_t)cols * 2, (cuuint64_t)cw * 2};
    cuuint32_t box[3] = {(cuuint32_t)cw, (cuuint32_t)box_rows, (cuuint32_t)box_chunks}, es[3] = {1, 1, 1};
    s_encode(m, CU_TENSOR_MAP_DATA_TYPE_BFLOAT16, 3, (void*)p, dims, strides, box, es, CU_TENSOR_MAP_INTERLEAVE_NONE,
             cw == 64 ? CU_TENSOR_MAP_SWIZZLE_128B : CU_TENSOR_MAP_SWIZZLE_64B, CU_TENSOR_MAP_L2_PROMOTION_L2_256B, CU_TENSOR_MAP_FLOAT_OOB_FILL_NONE);
}
template <typename T> static void* sym(T& s) { void* p = nullptr; cudaGetSymbolAddress(&p, s); return p; }

extern "C" void kernel_launch(void* const* d_in, const int* in_sizes, int n_in, void* d_out, int out_size) {
    const bf16 *x = (const bf16*)d_in[0], *mem0 = (const bf16*)d_in[1], *Wq = (const bf16*)d_in[2], *Wk = (const bf16*)d_in[3],
               *Wv = (const bf16*)d_in[4], *Wo = (const bf16*)d_in[5], *wr = (const bf16*)d_in[8], *wgate = (const bf16*)d_in[9],
               *wup = (const bf16*)d_in[10], *wdown = (const bf16*)d_in[11], *c = (const bf16*)d_in[12], *wmod = (const bf16*)d_in[13];
    bf16* out = (bf16*)d_out;
    if (!s_encode) {
        cudaDriverEntryPointQueryResult qr;
        cudaGetDriverEntryPoint("cuTensorMapEncodeTiled", (void**)&s_encode, cudaEnableDefault, &qr);
        cudaFuncSetAttribute(k_side, cudaFuncAttributeMaxDynamicSharedMemorySize, SD_SMEM);
        cudaFuncSetAttribute(k_chain, cudaFuncAttributeMaxDynamicSharedMemorySize, C_SMEM);
    }
    ChainMaps cm; SideMaps sd;
    make_map(&sd.h, sym(g_h), S_TOK, DM, 128); make_map3(&sd.wv, Wv, DM, HD, 64, 3);
    make_map3(&sd.ost, sym(g_o), S_TOK, HD, 16, 3); make_map(&sd.o, sym(g_o), S_TOK, HD, 128, 32); make_map3(&sd.wo, Wo, HD, DM, 32, 5);
    make_map3(&sd.slab3, sym(g_slab), 16 * KSPLIT * 128, DM, 64, 3); make_map3(&sd.slab2, sym(g_slab), 16 * KSPLIT * 128, DM, 64, 2);
    make_map3(&cm.wo15, Wo, HD, DM, 192, 2); make_map3(&cm.o15, sym(g_o), S_TOK, HD, 64, 2); cm.slab2 = sd.slab2;
    for (int i = 0; i < 3; i++) {
        cuuint64_t dims[3] = {256, 320, 16 * KSPLIT}, strides[2] = {512, 128 * DM * 2};
        cuuint32_t box[3] = {256, 40u >> i, 2u << i}, es[3] = {1, 1, 1};
        s_encode(&sd.lnp[i], CU_TENSOR_MAP_DATA_TYPE_BFLOAT16, 3, sym(g_slab), dims, strides, box, es, CU_TENSOR_MAP_INTERLEAVE_NONE,
                 CU_TENSOR_MAP_SWIZZLE_NONE, CU_TENSOR_MAP_L2_PROMOTION_L2_256B, CU_TENSOR_MAP_FLOAT_OOB_FILL_NONE);
    }
    make_map(&cm.wq, Wq, DM, HD, 640 / WP); make_map(&cm.wk, Wk, DM, HD, 640 / WP); make_map(&cm.wv, Wv, DM, HD, 160); make_map3(&cm.wo, Wo, HD, DM, 64, 7, 32);
    make_map3(&cm.h2, sym(g_h), S_TOK, DM, 32, 2);
    ChainArgs ar = {x, mem0, c, wmod, Wv, Wo, wgate, wup, wdown, out, P_D1, P_DL, P_DG};
    k_chain<<<96, 384, C_SMEM>>>(cm, ar);
    cudaLaunchConfig_t cfg = {};
    cfg.gridDim = dim3(N_SIDE); cfg.blockDim = dim3(384); cfg.dynamicSmemBytes = SD_SMEM; cfg.stream = cudaStreamPerThread;
    cudaLaunchAttribute at[1]; at[0].id = cudaLaunchAttributeProgrammaticStreamSerialization; at[0].val.programmaticStreamSerializationAllowed = 1;
    cfg.attrs = at; cfg.numAttrs = 1;
    cudaLaunchKernelEx(&cfg, k_side, sd, x, wr, wmod, c, out);
}
```

```cpp
#include <cuda_runtime.h>
#include <cuda_bf16.h>
#include <cuda.h>
#include <stdint.h>
#include <stdio.h>
#include <string.h>
#include <stdlib.h>

typedef __nv_bfloat16 bf16;
constexpr int S_TOK = 2048, DM = 640, NH = 32, DH = 192, HD = NH * DH, NSEG = 64, SEG = 32, FF = 1536;

__device__ bf16 g_mod[6 * DM];
__device__ bf16 g_h[S_TOK * DM];
constexpr int AT_REC = 43008, AT_V = 24576, AT_KM = 36864, AT_VM = 39936;
__device__ __align__(1024) uint8_t g_att[NSEG * NH * AT_REC];
__device__ bf16 g_o[S_TOK * HD];
__device__ bf16 g_A[S_TOK * DM];
__device__ bf16 g_x1[S_TOK * DM];
__device__ bf16 g_h2[S_TOK * DM];
__device__ __align__(128) uint32_t g_key[S_TOK];
__device__ int g_idx[8];
__device__ __align__(128) uint32_t g_gu[FF / 8 * 32];
constexpr int ACC_PAIR = 24 * 1024;
__device__ __align__(1024) uint8_t g_acc[2 * ACC_PAIR];
__device__ __align__(1024) uint32_t g_stamp[4 * 12 * 32];
constexpr int KSPLIT = 16;
__device__ bf16 g_slab[16 * KSPLIT * 128 * DM];
struct __align__(128) Flags {
    uint32_t qk[16], vb[16];
    uint32_t at[16], o[16];
    uint32_t c[4][16];
    uint32_t half[32];
    uint32_t fin[4 * 32];
    uint32_t v[16 * 32];
    uint32_t seg[4 * 32];
    uint32_t pair[16 * 16];
    uint32_t h, pad2[31], done, mod, pad3[30];
    uint32_t mod1[DM];
    uint32_t wmax[96];
};
__device__ Flags g_flags;
#define EPT(c, i)

__device__ __forceinline__ uint32_t smem_u32(const void* p) { return (uint32_t)__cvta_generic_to_shared(p); }
__device__ __forceinline__ uint32_t pack2(float lo, float hi) {
    uint32_t r; asm("cvt.rn.bf16x2.f32 %0, %1, %2;" : "=r"(r) : "f"(hi), "f"(lo)); return r;
}
__device__ __forceinline__ float bfr(float x) { return __uint_as_float(pack2(0.f, x)); }
__device__ __forceinline__ float inv_std(float var) {
    float s, r; asm("sqrt.approx.f32 %0, %1;" : "=f"(s) : "f"(bfr(bfr(var) + 1e-5f))); asm("rcp.approx.f32 %0, %1;" : "=f"(r) : "f"(bfr(s))); return r;
}
__device__ __forceinline__ float lo_f(uint32_t v) { return __uint_as_float(v << 16); }
__device__ __forceinline__ float hi_f(uint32_t v) { return __uint_as_float(v & 0xffff0000u); }
__device__ __forceinline__ void mbar_init(uint32_t bar, int cnt) { asm volatile("mbarrier.init.shared::cta.b64 [%0], %1;" :: "r"(bar), "r"(cnt) : "memory"); }
__device__ __forceinline__ void mbar_expect(uint32_t bar, int bytes) { asm volatile("mbarrier.arrive.expect_tx.shared::cta.b64 _, [%0], %1;" :: "r"(bar), "r"(bytes) : "memory"); }
__device__ __forceinline__ void mbar_arrive(uint32_t bar) { asm volatile("mbarrier.arrive.shared::cta.b64 _, [%0];" :: "r"(bar) : "memory"); }
__device__ __forceinline__ bool mbar_try(uint32_t bar, int par) {
    uint32_t ok; asm volatile("{ .reg .pred p; mbarrier.try_wait.parity.shared::cta.b64 p, [%1], %2; selp.u32 %0, 1, 0, p; }" : "=r"(ok) : "r"(bar), "r"(par) : "memory"); return ok;
}
__device__ __forceinline__ bool mbar_try_cluster(uint32_t bar, int par) {
    uint32_t ok; asm volatile("{ .reg .pred p; mbarrier.try_wait.parity.acquire.cluster.shared::cta.b64 p, [%1], %2; selp.u32 %0, 1, 0, p; }" : "=r"(ok) : "r"(bar), "r"(par) : "memory"); return ok;
}
__device__ __forceinline__ bool mbar_test(uint32_t bar, uint32_t par) {
    uint32_t ok; asm volatile("{ .reg .pred p; mbarrier.test_wait.parity.shared::cta.b64 p, [%1], %2; selp.u32 %0, 1, 0, p; }" : "=r"(ok) : "r"(bar), "r"(par) : "memory"); return ok;
}
constexpr int SPIN_LIMIT = 1 << 18;
__device__ __forceinline__ void mbar_wait(uint32_t bar, uint32_t par) {
    asm volatile("{ .reg .pred p, q; .reg .u32 n; mov.u32 n, 0;\n"
                 "W_%=: mbarrier.try_wait.parity.shared::cta.b64 p, [%0], %1;\n"
                 "@p bra.uni D_%=;\n"
                 "add.u32 n, n, 1; setp.lt.u32 q, n, 0x200000; @q bra.uni W_%=;\n"
                 "trap;\n"
                 "D_%=: }" :: "r"(bar), "r"(par) : "memory");
}
__device__ __forceinline__ void tma2d(uint32_t dst, const CUtensorMap* m, int c0, int c1, uint32_t bar) {
    asm volatile("cp.async.bulk.tensor.2d.shared::cluster.global.mbarrier::complete_tx::bytes [%0], [%1, {%3, %4}], [%2];"
        :: "r"(dst), "l"((uint64_t)m), "r"(bar), "r"(c0), "r"(c1) : "memory");
}
__device__ __forceinline__ void tma2d_mc(uint32_t dst, const CUtensorMap* m, int c0, int c1, uint32_t bar, uint16_t mask) {
    asm volatile("cp.async.bulk.tensor.2d.shared::cluster.global.mbarrier::complete_tx::bytes.multicast::cluster [%0], [%1, {%3, %4}], [%2], %5;"
        :: "r"(dst), "l"((uint64_t)m), "r"(bar), "r"(c0), "r"(c1), "h"(mask) : "memory");
}
__device__ __forceinline__ uint64_t policy_stream() { uint64_t p; asm("createpolicy.fractional.L2::evict_first.b64 %0, 1.0;" : "=l"(p)); return p; }
__device__ __forceinline__ void tma2d_ef(uint32_t dst, const CUtensorMap* m, int c0, int c1, uint32_t bar, uint64_t pol) {
    asm volatile("cp.async.bulk.tensor.2d.shared::cluster.global.mbarrier::complete_tx::bytes.L2::cache_hint [%0], [%1, {%3, %4}], [%2], %5;"
        :: "r"(dst), "l"((uint64_t)m), "r"(bar), "r"(c0), "r"(c1), "l"(pol) : "memory");
}
__device__ __forceinline__ void tma3d(uint32_t dst, const CUtensorMap* m, int row, int chunk, uint32_t bar) {
    asm volatile("cp.async.bulk.tensor.3d.shared::cluster.global.mbarrier::complete_tx::bytes [%0], [%1, {0, %3, %4}], [%2];"
        :: "r"(dst), "l"((uint64_t)m), "r"(bar), "r"(row), "r"(chunk) : "memory");
}
__device__ __forceinline__ void tma3d_ef(uint32_t dst, const CUtensorMap* m, int row, int chunk, uint32_t bar, uint64_t pol) {
    asm volatile("cp.async.bulk.tensor.3d.shared::cluster.global.mbarrier::complete_tx::bytes.L2::cache_hint [%0], [%1, {0, %3, %4}], [%2], %5;"
        :: "r"(dst), "l"((uint64_t)m), "r"(bar), "r"(row), "r"(chunk), "l"(pol) : "memory");
}
__device__ __forceinline__ void tma3d_store(const CUtensorMap* m, int row, int chunk, uint32_t src, uint64_t pol, bool hint) {
    if (hint) asm volatile("cp.async.bulk.tensor.3d.global.shared::cta.bulk_group.L2::cache_hint [%0, {0, %2, %3}], [%1], %4;"
        :: "l"((uint64_t)m), "r"(src), "r"(row), "r"(chunk), "l"(pol) : "memory");
    else asm volatile("cp.async.bulk.tensor.3d.global.shared::cta.bulk_group [%0, {0, %2, %3}], [%1];"
        :: "l"((uint64_t)m), "r"(src), "r"(row), "r"(chunk) : "memory");
}
__device__ __forceinline__ bool elect() { uint32_t p; asm volatile("{ .reg .pred e; elect.sync _|e, -1; selp.u32 %0, 1, 0, e; }" : "=r"(p)); return p; }
__device__ __forceinline__ uint2 ld_ef(const void* p, uint64_t pol) {
    uint2 v; asm volatile("ld.relaxed.gpu.global.L2::cache_hint.v2.u32 {%0,%1}, [%2], %3;" : "=r"(v.x), "=r"(v.y) : "l"(p), "l"(pol)); return v;
}
__device__ __forceinline__ void st_ef(void* p, uint2 v, uint64_t pol) {
    asm volatile("st.global.L2::cache_hint.v2.u32 [%0], {%1,%2}, %3;" :: "l"(p), "r"(v.x), "r"(v.y), "l"(pol) : "memory");
}
__device__ __forceinline__ void tma2d_prefetch(const CUtensorMap* m, int c0, int c1) {
    asm volatile("cp.async.bulk.prefetch.tensor.2d.L2.global [%0, {%1, %2}];" :: "l"((uint64_t)m), "r"(c0), "r"(c1) : "memory");
}
__device__ __forceinline__ void mbar_arrive_remote(uint32_t bar) { asm volatile("mbarrier.arrive.relaxed.cluster.shared::cluster.b64 _, [%0];" :: "r"(bar) : "memory"); }
__device__ __forceinline__ void tma2d_store(const CUtensorMap* m, int c0, int c1, uint32_t src) {
    asm volatile("cp.async.bulk.tensor.2d.global.shared::cta.bulk_group [%0, {%2, %3}], [%1];"
        :: "l"((uint64_t)m), "r"(src), "r"(c0), "r"(c1) : "memory");
}
__device__ __forceinline__ void bulk_g2s(uint32_t dst, const void* src, int bytes, uint32_t bar) {
    asm volatile("cp.async.bulk.shared::cluster.global.mbarrier::complete_tx::bytes [%0], [%1], %2, [%3];" :: "r"(dst), "l"(src), "r"(bytes), "r"(bar) : "memory");
}
__device__ __forceinline__ void ldsm4(uint32_t (&r)[4], uint32_t a) {
    asm volatile("ldmatrix.sync.aligned.m8n8.x4.shared.b16 {%0,%1,%2,%3}, [%4];" : "=r"(r[0]), "=r"(r[1]), "=r"(r[2]), "=r"(r[3]) : "r"(a) : "memory");
}
__device__ __forceinline__ void ldsm4t(uint32_t (&r)[4], uint32_t a) {
    asm volatile("ldmatrix.sync.aligned.m8n8.x4.trans.shared.b16 {%0,%1,%2,%3}, [%4];" : "=r"(r[0]), "=r"(r[1]), "=r"(r[2]), "=r"(r[3]) : "r"(a) : "memory");
}
__device__ __forceinline__ void stsm4(uint32_t a, uint32_t r0, uint32_t r1, uint32_t r2, uint32_t r3) {
    asm volatile("stmatrix.sync.aligned.m8n8.x4.shared.b16 [%0], {%1,%2,%3,%4};" :: "r"(a), "r"(r0), "r"(r1), "r"(r2), "r"(r3) : "memory");
}
__device__ __forceinline__ void stsm4t(uint32_t a, uint32_t r0, uint32_t r1, uint32_t r2, uint32_t r3) {
    asm volatile("stmatrix.sync.aligned.m8n8.x4.trans.shared.b16 [%0], {%1,%2,%3,%4};" :: "r"(a), "r"(r0), "r"(r1), "r"(r2), "r"(r3) : "memory");
}
__device__ __forceinline__ void stsm2t(uint32_t a, uint32_t r0, uint32_t r1) {
    asm volatile("stmatrix.sync.aligned.m8n8.x2.trans.shared.b16 [%0], {%1,%2};" :: "r"(a), "r"(r0), "r"(r1) : "memory");
}
__device__ __forceinline__ uint32_t movm_t(uint32_t v) { uint32_t r; asm volatile("movmatrix.sync.aligned.m8n8.trans.b16 %0, %1;" : "=r"(r) : "r"(v)); return r; }
__device__ __forceinline__ void mma16(float (&d)[4], uint32_t a0, uint32_t a1, uint32_t a2, uint32_t a3, uint32_t b0, uint32_t b1) {
    asm volatile("mma.sync.aligned.m16n8k16.row.col.f32.bf16.bf16.f32 {%0,%1,%2,%3}, {%4,%5,%6,%7}, {%8,%9}, {%0,%1,%2,%3};"
        : "+f"(d[0]), "+f"(d[1]), "+f"(d[2]), "+f"(d[3]) : "r"(a0), "r"(a1), "r"(a2), "r"(a3), "r"(b0), "r"(b1));
}
__device__ __forceinline__ void mma8(float (&d)[4], uint32_t a0, uint32_t a1, uint32_t b0) {
    asm volatile("mma.sync.aligned.m16n8k8.row.col.f32.bf16.bf16.f32 {%0,%1,%2,%3}, {%4,%5}, {%6}, {%0,%1,%2,%3};"
        : "+f"(d[0]), "+f"(d[1]), "+f"(d[2]), "+f"(d[3]) : "r"(a0), "r"(a1), "r"(b0));
}
__device__ __forceinline__ uint32_t mapa(uint32_t a, uint32_t r) { uint32_t o; asm volatile("mapa.shared::cluster.u32 %0, %1, %2;" : "=r"(o) : "r"(a), "r"(r)); return o; }
__device__ __forceinline__ void bar_sync(int id, int n) { asm volatile("bar.sync %0, %1;" :: "r"(id), "r"(n) : "memory"); }
__device__ __forceinline__ void bar_arrive(int id, int n) { asm volatile("bar.arrive %0, %1;" :: "r"(id), "r"(n) : "memory"); }
__device__ __forceinline__ uint64_t mkdesc(uint32_t addr, uint32_t lbo, uint32_t sbo) {
    return (uint64_t)((addr & 0x3FFFF) >> 4) | ((uint64_t)(lbo >> 4) << 16) | ((uint64_t)(sbo >> 4) << 32) | (1ull << 62);
}
#define WG_FENCE()  asm volatile("wgmma.fence.sync.aligned;" ::: "memory")
#define WG_COMMIT() asm volatile("wgmma.commit_group.sync.aligned;" ::: "memory")
#define WG_WAIT(n)  asm volatile("wgmma.wait_group.sync.aligned %0;" :: "n"(n) : "memory")

__device__ __forceinline__ void wgmma_ss_n192_tb(float (&d)[96], uint64_t a, uint64_t b, int acc) {
    asm volatile("{ .reg .pred p; setp.ne.b32 p, %98, 0;\n"
        "wgmma.mma_async.sync.aligned.m64n192k16.f32.bf16.bf16 {%0,%1,%2,%3,%4,%5,%6,%7,%8,%9,%10,%11,%12,%13,%14,%15,%16,%17,%18,%19,%20,%21,%22,%23,%24,%25,%26,%27,%28,%29,%30,%31,%32,%33,%34,%35,%36,%37,%38,%39,%40,%41,%42,%43,%44,%45,%46,%47,%48,%49,%50,%51,%52,%53,%54,%55,%56,%57,%58,%59,%60,%61,%62,%63,%64,%65,%66,%67,%68,%69,%70,%71,%72,%73,%74,%75,%76,%77,%78,%79,%80,%81,%82,%83,%84,%85,%86,%87,%88,%89,%90,%91,%92,%93,%94,%95}, %96, %97, p, 1, 1, 0, 1; }"
        : "+f"(d[0]), "+f"(d[1]), "+f"(d[2]), "+f"(d[3]), "+f"(d[4]), "+f"(d[5]), "+f"(d[6]), "+f"(d[7]), "+f"(d[8]), "+f"(d[9]), "+f"(d[10]), "+f"(d[11]), "+f"(d[12]), "+f"(d[13]), "+f"(d[14]), "+f"(d[15]), "+f"(d[16]), "+f"(d[17]), "+f"(d[18]), "+f"(d[19]), "+f"(d[20]), "+f"(d[21]), "+f"(d[22]), "+f"(d[23]), "+f"(d[24]), "+f"(d[25]), "+f"(d[26]), "+f"(d[27]), "+f"(d[28]), "+f"(d[29]), "+f"(d[30]), "+f"(d[31]), "+f"(d[32]), "+f"(d[33]), "+f"(d[34]), "+f"(d[35]), "+f"(d[36]), "+f"(d[37]), "+f"(d[38]), "+f"(d[39]), "+f"(d[40]), "+f"(d[41]), "+f"(d[42]), "+f"(d[43]), "+f"(d[44]), "+f"(d[45]), "+f"(d[46]), "+f"(d[47]), "+f"(d[48]), "+f"(d[49]), "+f"(d[50]), "+f"(d[51]), "+f"(d[52]), "+f"(d[53]), "+f"(d[54]), "+f"(d[55]), "+f"(d[56]), "+f"(d[57]), "+f"(d[58]), "+f"(d[59]), "+f"(d[60]), "+f"(d[61]), "+f"(d[62]), "+f"(d[63]), "+f"(d[64]), "+f"(d[65]), "+f"(d[66]), "+f"(d[67]), "+f"(d[68]), "+f"(d[69]), "+f"(d[70]), "+f"(d[71]), "+f"(d[72]), "+f"(d[73]), "+f"(d[74]), "+f"(d[75]), "+f"(d[76]), "+f"(d[77]), "+f"(d[78]), "+f"(d[79]), "+f"(d[80]), "+f"(d[81]), "+f"(d[82]), "+f"(d[83]), "+f"(d[84]), "+f"(d[85]), "+f"(d[86]), "+f"(d[87]), "+f"(d[88]), "+f"(d[89]), "+f"(d[90]), "+f"(d[91]), "+f"(d[92]), "+f"(d[93]), "+f"(d[94]), "+f"(d[95])
        : "l"(a), "l"(b), "r"(acc));
}

__device__ __forceinline__ void wgmma_ss_n128_tb(float (&d)[64], uint64_t a, uint64_t b, int acc) {
    asm volatile("{ .reg .pred p; setp.ne.b32 p, %66, 0;\n"
        "wgmma.mma_async.sync.aligned.m64n128k16.f32.bf16.bf16 {%0,%1,%2,%3,%4,%5,%6,%7,%8,%9,%10,%11,%12,%13,%14,%15,%16,%17,%18,%19,%20,%21,%22,%23,%24,%25,%26,%27,%28,%29,%30,%31,%32,%33,%34,%35,%36,%37,%38,%39,%40,%41,%42,%43,%44,%45,%46,%47,%48,%49,%50,%51,%52,%53,%54,%55,%56,%57,%58,%59,%60,%61,%62,%63}, %64, %65, p, 1, 1, 0, 1; }"
        : "+f"(d[0]), "+f"(d[1]), "+f"(d[2]), "+f"(d[3]), "+f"(d[4]), "+f"(d[5]), "+f"(d[6]), "+f"(d[7]), "+f"(d[8]), "+f"(d[9]), "+f"(d[10]), "+f"(d[11]), "+f"(d[12]), "+f"(d[13]), "+f"(d[14]), "+f"(d[15]), "+f"(d[16]), "+f"(d[17]), "+f"(d[18]), "+f"(d[19]), "+f"(d[20]), "+f"(d[21]), "+f"(d[22]), "+f"(d[23]), "+f"(d[24]), "+f"(d[25]), "+f"(d[26]), "+f"(d[27]), "+f"(d[28]), "+f"(d[29]), "+f"(d[30]), "+f"(d[31]), "+f"(d[32]), "+f"(d[33]), "+f"(d[34]), "+f"(d[35]), "+f"(d[36]), "+f"(d[37]), "+f"(d[38]), "+f"(d[39]), "+f"(d[40]), "+f"(d[41]), "+f"(d[42]), "+f"(d[43]), "+f"(d[44]), "+f"(d[45]), "+f"(d[46]), "+f"(d[47]), "+f"(d[48]), "+f"(d[49]), "+f"(d[50]), "+f"(d[51]), "+f"(d[52]), "+f"(d[53]), "+f"(d[54]), "+f"(d[55]), "+f"(d[56]), "+f"(d[57]), "+f"(d[58]), "+f"(d[59]), "+f"(d[60]), "+f"(d[61]), "+f"(d[62]), "+f"(d[63])
        : "l"(a), "l"(b), "r"(acc));
}

__device__ __forceinline__ void wgmma_rs_n32(float (&d)[16], const uint32_t (&a)[4], uint64_t b, int acc) {
    asm volatile("{ .reg .pred p; setp.ne.b32 p, %21, 0;\n"
        "wgmma.mma_async.sync.aligned.m64n32k16.f32.bf16.bf16 {%0,%1,%2,%3,%4,%5,%6,%7,%8,%9,%10,%11,%12,%13,%14,%15}, {%16,%17,%18,%19}, %20, p, 1, 1, 0; }"
        : "+f"(d[0]), "+f"(d[1]), "+f"(d[2]), "+f"(d[3]), "+f"(d[4]), "+f"(d[5]), "+f"(d[6]), "+f"(d[7]), "+f"(d[8]), "+f"(d[9]), "+f"(d[10]), "+f"(d[11]), "+f"(d[12]), "+f"(d[13]), "+f"(d[14]), "+f"(d[15])
        : "r"(a[0]), "r"(a[1]), "r"(a[2]), "r"(a[3]), "l"(b), "r"(acc));
}

__device__ __forceinline__ float warp_sum(float v) {
#pragma unroll
    for (int o = 16; o; o >>= 1) v += __shfl_xor_sync(0xffffffffu, v, o);
    return v;
}
__device__ __forceinline__ uint32_t add2(uint32_t a, uint32_t b) { uint32_t r; asm("add.rn.bf16x2 %0, %1, %2;" : "=r"(r) : "r"(a), "r"(b)); return r; }
__device__ __forceinline__ uint32_t mul2(uint32_t a, uint32_t b) { uint32_t r; asm("mul.rn.bf16x2 %0, %1, %2;" : "=r"(r) : "r"(a), "r"(b)); return r; }
__device__ __forceinline__ uint32_t amax2(uint32_t m, uint32_t v) { uint32_t r; asm("max.u16x2 %0, %1, %2;" : "=r"(r) : "r"(m), "r"(v & 0x7fff7fffu)); return r; }
__device__ __forceinline__ uint32_t amax_warp(uint32_t m) { return __reduce_max_sync(0xffffffffu, max(m & 0xffffu, m >> 16)); }
__device__ __forceinline__ void ln_norm(const uint32_t (&xv)[10], uint32_t (&nv)[10]) {
    float s0 = 0, s1 = 0;
#pragma unroll
    for (int i = 0; i < 10; i++) { s0 += lo_f(xv[i]); s1 += hi_f(xv[i]); }
    const float mean = warp_sum(s0 + s1) * (1.f / DM);
    float q0 = 0, q1 = 0;
#pragma unroll
    for (int i = 0; i < 10; i++) { const float d0 = lo_f(xv[i]) - mean, d1 = hi_f(xv[i]) - mean; q0 += d0 * d0; q1 += d1 * d1; }
    const float inv = inv_std(warp_sum(q0 + q1) * (1.f / DM));
    const uint32_t mb = pack2(-mean, -mean);
#pragma unroll
    for (int i = 0; i < 10; i++) { const uint32_t d = add2(xv[i], mb); nv[i] = pack2(lo_f(d) * inv, hi_f(d) * inv); }
}
__device__ __forceinline__ void ln_mod(const uint32_t (&xv)[10], const uint32_t (&sv)[10], const uint32_t (&tv)[10], uint32_t (&hv)[10]) {
    ln_norm(xv, hv);
#pragma unroll
    for (int i = 0; i < 10; i++) hv[i] = add2(mul2(hv[i], add2(sv[i], 0x3f803f80u)), tv[i]);
}
__device__ __forceinline__ uint32_t ld_rlx(const uint32_t* f) { uint32_t v; asm volatile("ld.relaxed.gpu.global.u32 %0, [%1];" : "=r"(v) : "l"(f) : "memory"); return v; }
__device__ __forceinline__ void bump(uint32_t* f) { asm volatile("red.relaxed.gpu.global.add.u32 [%0], 1;" :: "l"(f) : "memory"); }
#define NAP 100
#define GPU_FENCE() asm volatile("fence.acq_rel.gpu;" ::: "memory")
__device__ __forceinline__ void flag_wait(const uint32_t* f, uint32_t target) {
    for (int n = 0;; n++) {
        uint32_t v; asm volatile("ld.relaxed.gpu.global.u32 %0, [%1];" : "=r"(v) : "l"(f) : "memory");
        if (v >= target) break;
        if (n > (1 << 22)) __trap();
        __nanosleep(NAP);
    }
}
__device__ __forceinline__ void flag_add(uint32_t* f, uint32_t v = 1) { asm volatile("red.release.gpu.global.add.u32 [%0], %1;" :: "l"(f), "r"(v) : "memory"); }
constexpr int N_SIDE = 36;
__device__ __forceinline__ void flags_release(int lane) {
    uint32_t old = 0;
    if (lane == 0) asm volatile("atom.relaxed.gpu.global.add.u32 %0, [%1], 1;" : "=r"(old) : "l"(&g_flags.done) : "memory");
    if (__shfl_sync(0xffffffffu, old, 0) == 96 + N_SIDE - 1)
#pragma unroll 1
        for (int i = lane; i < (int)(sizeof(Flags) / 16); i += 32) ((uint4*)&g_flags)[i] = make_uint4(0, 0, 0, 0);
}

struct ChainMaps { CUtensorMap wq, wk, wv, wo, h2, wo15, o15, slab2; };
struct ChainArgs { const bf16 *x, *mem0, *c, *wmod, *wv, *wo, *wgate, *wup, *wdown; bf16* out; int D1, D2, DG; };
constexpr uint32_t SM_BASE = 1024;
#define NRING 10
#define XORD 0
#define B5AT 41
#define QCUT 0x54
#define NCH 0
#define XA 2
#define VT 1
#define OSEND 1
#define SPOLL 0
#define QK_MASK 0x7fff
#define FW 2
#define NPRE 9
#define REG_P 208
#define REG_L (504 - 2 * REG_P)
constexpr int WO_BLK = 7 * 4096;
constexpr int C_WV = 0, C_WO = 81920, C_XR = 167936, C_VP = C_XR + 7 * 4096, C_VX = C_XR + 8 * 4096, C_QX = C_VX + 4096, C_KX = C_QX + 4096,
              C_MEM = C_KX + 4096, C_OX = C_MEM + 9216, C_VM = C_OX + 3072, C_QM = C_VM + 1024, C_KM = C_QM + 1024, C_SC = C_KM + 1024, C_BAR = C_SC + 3840;
constexpr int CB_W = C_BAR, CB_W2 = C_BAR + 8, CB_SC = C_BAR + 16, CB_XD = C_BAR + 24, CB_VX = C_BAR + 32, CB_W3 = C_BAR + 40, CB_XM = C_BAR + 48, CB_OX = C_BAR + 56,
              CB_XF = C_BAR + 64, C_LAG = C_BAR + 96, C_UN = C_BAR + 100, C_MX = C_BAR + 112;
constexpr int C_SMEM = C_BAR + 128;
#define PROF(i)
#define PROFG(i)
#define PROFV(i, v)
static_assert(C_SMEM <= 232448, "chain shared memory");
__device__ __forceinline__ uint32_t umax3(uint32_t a, uint32_t b, uint32_t c) { return max(max(a, b), c); }
__device__ __forceinline__ void wait_until(uint32_t t) {
    asm volatile("{ .reg .pred p; .reg .s32 c; .reg .u64 d;\nU_%=: mov.u64 d, %%clock64; cvt.u32.u64 c, d; sub.s32 c, c, %0; setp.lt.s32 p, c, 0; @p bra.uni U_%=; }" :: "r"(t) : "memory");
}
__device__ __forceinline__ uint32_t gtime() { uint32_t c; asm volatile("mov.u32 %0, %%globaltimer_lo;" : "=r"(c)); return c; }
__device__ __forceinline__ uint32_t opaque(uint32_t v) { uint32_t r; asm volatile("shfl.sync.bfly.b32 %0, %1, 0, 31, -1;" : "=r"(r) : "r"(v)); return r; }
__device__ __forceinline__ uint32_t lds32(uint32_t a) { uint32_t v; asm volatile("ld.shared.u32 %0, [%1];" : "=r"(v) : "r"(a) : "memory"); return v; }
__device__ __forceinline__ float2 lds64f(uint32_t a) { float2 v; asm volatile("ld.shared.v2.f32 {%0,%1}, [%2];" : "=f"(v.x), "=f"(v.y) : "r"(a) : "memory"); return v; }
__device__ __forceinline__ float4 lds128f(uint32_t a) { float4 v; asm volatile("ld.shared.v4.f32 {%0,%1,%2,%3}, [%4];" : "=f"(v.x), "=f"(v.y), "=f"(v.z), "=f"(v.w) : "r"(a) : "memory"); return v; }
__device__ __forceinline__ void sts128f(uint32_t a, float x, float y, float z, float w) { asm volatile("st.shared.v4.f32 [%0], {%1,%2,%3,%4};" :: "r"(a), "f"(x), "f"(y), "f"(z), "f"(w) : "memory"); }
__device__ __forceinline__ void lds64(uint32_t (&v)[2], uint32_t a) { asm volatile("ld.shared.v2.u32 {%0,%1}, [%2];" : "=r"(v[0]), "=r"(v[1]) : "r"(a) : "memory"); }
__device__ __forceinline__ void mma16q(float (&d)[4], const uint32_t (&a)[4], uint32_t b0, uint32_t b1) { mma16(d, a[0], a[1], a[2], a[3], b0, b1); }
__device__ __forceinline__ uint32_t f16_to_bf16(uint32_t v) {
    float lo, hi; asm("{ .reg .f16 l, h; mov.b32 {l, h}, %2; cvt.f32.f16 %0, l; cvt.f32.f16 %1, h; }" : "=f"(lo), "=f"(hi) : "r"(v));
    return pack2(lo, hi);
}
__device__ __forceinline__ uint32_t pack2h(float lo, float hi) { uint32_t r; asm("cvt.rn.f16x2.f32 %0, %1, %2;" : "=r"(r) : "f"(hi), "f"(lo)); return r; }
#define SPLIT 1
__device__ __forceinline__ void cut(uint32_t never, int n) {
    asm volatile("{ .reg .pred p; setp.ne.u32 p, %0, %1; @p bra.uni C_%=; trap; C_%=: }" :: "r"(never), "r"(n) : "memory");
}
__device__ __forceinline__ void pin(uint32_t never, uint32_t a, uint32_t b, uint32_t c, uint32_t d) {
    asm volatile("{ .reg .pred p; setp.eq.u32 p, %0, 0; @p st.shared.v4.u32 [%0], {%1,%2,%3,%4}; }" :: "r"(never), "r"(a), "r"(b), "r"(c), "r"(d) : "memory");
}
__device__ __forceinline__ void pin0(uint32_t never) {
    asm volatile("{ .reg .pred p; setp.eq.u32 p, %0, 0; @p st.shared.u32 [%0], 0; }" :: "r"(never) : "memory");
}
#define ELECTED(txt) "{ .reg .pred e; elect.sync _|e, -1; @e " txt " }"
__device__ __forceinline__ void w_bulk_s2g(void* dst, uint32_t src, int bytes) {
    asm volatile(ELECTED("cp.async.bulk.global.shared::cta.bulk_group [%0], [%1], %2;") :: "l"(dst), "r"(src), "r"(bytes) : "memory");
}
__device__ __forceinline__ void w_bump(uint32_t* f) { asm volatile(ELECTED("red.relaxed.gpu.global.add.u32 [%0], 1;") :: "l"(f) : "memory"); }
__device__ __forceinline__ void w_expect(uint32_t bar, int bytes) { asm volatile(ELECTED("mbarrier.arrive.expect_tx.shared::cta.b64 _, [%0], %1;") :: "r"(bar), "r"(bytes) : "memory"); }
__device__ __forceinline__ void w_flag_wait(const uint32_t* f, uint32_t target) {
    asm volatile("{ .reg .pred p; .reg .u32 n, v; mov.u32 n, 0;\n"
                 "F_%=: ld.relaxed.gpu.global.u32 v, [%0]; setp.ge.u32 p, v, %1; vote.sync.all.pred p, p, -1; @p bra.uni G_%=;\n"
                 "nanosleep.u32 %2; add.u32 n, n, 1; setp.lt.u32 p, n, 0x400000; @p bra.uni F_%=;\ntrap;\nG_%=: }" :: "l"(f), "r"(target), "n"(NAP) : "memory");
}
#define BULK_COMMIT()    asm volatile("cp.async.bulk.commit_group;" ::: "memory")
#define BULK_WAIT()      asm volatile("cp.async.bulk.wait_group 0;" ::: "memory")
#define BULK_WAIT_READ() asm volatile("cp.async.bulk.wait_group.read 0;" ::: "memory")
#define PROXY_FENCE()    asm volatile("fence.proxy.async.shared::cta;" ::: "memory")
__device__ __forceinline__ void send16(uint32_t dst, uint32_t bar, float a, float b, float c, float d) {
    asm volatile("st.async.shared::cluster.mbarrier::complete_tx::bytes.v4.f32 [%0], {%1,%2,%3,%4}, [%5];" :: "r"(dst), "f"(a), "f"(b), "f"(c), "f"(d), "r"(bar) : "memory");
}
__device__ __forceinline__ void send8(uint32_t dst, uint32_t bar, uint32_t a, uint32_t b) {
    asm volatile("st.async.shared::cluster.mbarrier::complete_tx::bytes.v2.b32 [%0], {%1,%2}, [%3];" :: "r"(dst), "r"(a), "r"(b), "r"(bar) : "memory");
}

__device__ __forceinline__ void seg_done(int n, int head) {
    if (n > 60 || ((n & 3) == 3 && (QK_MASK >> (n >> 2) & 1))) { GPU_FENCE(); w_bump(n > 60 ? &g_flags.seg[(n - 60) * 32 + head] : &g_flags.qk[n >> 2]); }
}
__device__ __forceinline__ uint32_t x_base(int wg, uint32_t small, int sh) { return (uint32_t)mkdesc(SM_BASE + C_XR, 16, 1024) + wg * 256 + (small >> sh); }
__device__ __forceinline__ void x_chunk(float (&acc)[16], const uint32_t (&wa)[40][4], uint32_t xl, int a0, int i, int first) {
#pragma unroll
    for (int ks = 0; ks < 4; ks++)
        wgmma_rs_n32(acc, wa[a0 + 4 * i + ks], mkdesc(0, 0, 1024) | (uint32_t)(xl + (((i ? (i - 1) * 8192 : C_MEM - C_XR) + ks * 32) >> 4)), !(first && ks == 0));
}
__device__ __forceinline__ void x_part(float (&acc)[16], const uint32_t (&wa)[40][4], uint32_t sm, int n, int wg, int w, uint32_t ln, uint32_t small) {
    const int s = n - 1; (void)s;
    uint32_t giv[8];
    auto chunk = [&](int a0, int i, int first) { x_chunk(acc, wa, x_base(wg, small, a0 ? 21 : 22), a0, i, first); };
    mbar_wait(sm + CB_XM, n & 1);
    if (n) bar_sync(5, 384);
    if (wg == 0 && w == 0) PROF(12);
    WG_FENCE();
#pragma unroll
    for (int i = 1 + XA; i < 5; i++) chunk(20, i, 0);
    chunk(20, 0, 0);
    WG_COMMIT();
    if (n) {
        if (wg == 1 && w == 1) BULK_WAIT();
        bar_sync(8, 256);
    }
    if (wg == 0 && w == 0) PROF(18);
    const uint32_t xb = sm + w * 512 + ln * 16, xw = xb + C_KX - wg * 4096, xr = xb + C_QX + wg * 4096;
    WG_WAIT(0);
#pragma unroll
    for (int i = 0; i < 8; i++) asm volatile("cvt.rn.bf16x2.f32 %0, %1, %2;" : "=r"(giv[i]) : "f"(acc[2 * i + 1]), "f"(acc[2 * i]));
#pragma unroll
    for (int p = 0; p < 2; p++) asm volatile("st.shared.v4.u32 [%0], {%1,%2,%3,%4};" :: "r"(xw + p * 2048), "r"(giv[4 * p]), "r"(giv[4 * p + 1]), "r"(giv[4 * p + 2]), "r"(giv[4 * p + 3]) : "memory");
    bar_arrive(12 + wg, 256);
    WG_FENCE();
    chunk(0, 0, 1);
    WG_COMMIT();
    chunk(0, 1, 0);
    if (XORD) chunk(0, 2, 0);
    bar_sync(13 - wg, 256);
#pragma unroll
    for (int p = 0; p < 2; p++) asm volatile("ld.shared.v4.u32 {%0,%1,%2,%3}, [%4];" : "=r"(giv[4 * p]), "=r"(giv[4 * p + 1]), "=r"(giv[4 * p + 2]), "=r"(giv[4 * p + 3]) : "r"(xr + p * 2048) : "memory");
    WG_COMMIT(); WG_WAIT(1); bar_arrive(9, 384);
    WG_FENCE();
    if (!XORD) chunk(0, 2, 0);
    chunk(0, 3, 0); chunk(0, 4, 0);
    WG_COMMIT();
    const uint32_t r = ln & 7, mi = ln >> 3, dst = sm + (wg == 0 ? C_QX : C_KX) + ((mi >> 1) * 8 + r) * 128 + (((2 * w + (mi & 1)) ^ r) << 4);
    pin(xb, giv[0], giv[4], dst, 0);
    bar_sync(10 + wg, 128);
    WG_WAIT(0);
    if (wg == 0 && w == 0) PROF(30);
    if (w == 0 && ln < 3) mbar_arrive_remote(mapa(sm + CB_XD, ln));
#pragma unroll
    for (int i = 0; i < 8; i++) { acc[2 * i] += lo_f(giv[i]); acc[2 * i + 1] += hi_f(giv[i]); }
#pragma unroll
    for (int p = 0; p < 2; p++)
        stsm4t(dst + p * 2048, pack2(acc[8 * p], acc[8 * p + 1]), pack2(acc[8 * p + 2], acc[8 * p + 3]), pack2(acc[8 * p + 4], acc[8 * p + 5]), pack2(acc[8 * p + 6], acc[8 * p + 7]));
    if (wg == 0 && w == 0) PROF(11);
}
__device__ __forceinline__ void x_fill(const ChainMaps& mp, uint32_t sm, int n, int j) {
    mbar_expect(sm + CB_XF, 24576);
    asm volatile("cp.async.bulk.tensor.3d.shared::cluster.global.mbarrier::complete_tx::bytes.multicast::cluster [%0], [%1, {0, %3, %4}], [%2], %5;"
        :: "r"(sm + C_XR + j * 8192), "l"((uint64_t)&mp.h2), "r"(sm + CB_XF), "r"(n * SEG), "r"(2 + 2 * j), "h"((uint16_t)7) : "memory");
}
__device__ __forceinline__ void x_rest(const ChainMaps& mp, uint32_t sm, int n) {
    mbar_expect(sm + CB_XM, 16384);
    tma3d(sm + C_XR + 6 * 4096, &mp.h2, n * SEG, 8, sm + CB_XM); tma3d(sm + C_MEM, &mp.h2, n * SEG, 0, sm + CB_XM);
}

#define WPOS 2
#define WP 4
#define WOPF 30
#define SDEL 0
#define EORD 0
#define BPOS 2
#define TPF 1
#define B_LATE 13
constexpr int E_B = C_WO, E_STG = 196608, EB_A = 229376, EB_B = C_BAR + 80, EB_REL = C_BAR + 104;
__device__ __forceinline__ uint32_t e_slot(int wg, int c) { return wg && c == 2 ? E_B + 98304 : wg * 49152 + c * 16384; }
constexpr int T_WG = 0, T_WU = 20480, T_WD = 40960, T_X = 65536, T_RED = 77824, T_KEY = 86016;
__device__ __forceinline__ void wo_half(const ChainMaps& mp, uint32_t sm, int blk, int c) {
    if (blk < 80 && elect()) { mbar_expect(sm + EB_B + 8 * c, 49152); tma3d(sm + E_B + c * 49152, &mp.wo15, blk / 5 * 384 + c * 192, blk % 5 * 2, sm + EB_B + 8 * c); }
}
__device__ __forceinline__ void end_loads(const ChainMaps& mp, const ChainArgs& ar, uint32_t sm, int blk, int wg) {
    const uint32_t bar = sm + EB_A + wg * 48;
    const int kp = blk / 5;
    if (elect()) {
#pragma unroll 1
        for (int c = 0; c < 6; c++) mbar_init(bar + 8 * c, c < 3 ? 1 : 4);
        PROXY_FENCE();
    }
    __syncwarp();
    bar_arrive(5, 384);
    if (EORD) bar_sync(6, 96);
    if (blk >= 80) {
        if (TPF && elect()) {
#pragma unroll 1
            for (int c = 0; c < 3; c++) asm volatile("cp.async.bulk.prefetch.L2.global [%0], 61440;" :: "l"((c == 0 ? ar.wgate : c == 1 ? ar.wup : ar.wdown) + ((blk - 80) * 2 + wg) * 30720) : "memory");
        }
        return;
    }
    const uint64_t ef = policy_stream();
#pragma unroll 1
    for (int b = B_LATE; b < 16; b++) {
        w_flag_wait(b == 15 ? &g_flags.half[kp * 2 + wg] : &g_flags.pair[b * 16 + kp], b == 15 ? 2 : 4);
#pragma unroll 1
        for (int c = 0; c < 3; c++) {
            if (b > B_LATE) mbar_wait(bar + 24 + 8 * c, (b - B_LATE - 1) & 1);
            if (elect()) { mbar_expect(bar + 8 * c, 16384); tma3d_ef(sm + e_slot(wg, c), &mp.o15, b * 128 + wg * 64, kp * 6 + c * 2, bar + 8 * c, ef); }
            __syncwarp();
        }
    }
}
__device__ __forceinline__ void end_stores(const ChainMaps& mp, uint32_t sm, int blk, int wg) {
#pragma unroll 1
    for (int b = B_LATE; b < 16 && blk < 80; b++) {
        bar_sync(12 + wg, 160);
        if (elect()) tma3d_store(&mp.slab2, (b * KSPLIT + blk / 5) * 128 + wg * 64, blk % 5 * 2, sm + E_STG + wg * 16384, 0, false);
        BULK_COMMIT(); BULK_WAIT();
        if (b < 15) bar_arrive(10 + wg, 160);
        GPU_FENCE();
        w_bump(b < 14 ? &g_flags.o[b] : &g_flags.fin[((b - 14) * 2 + wg) * 32]);
    }
    bar_arrive(8, 320);
}
__device__ __forceinline__ void last_blocks(const ChainArgs& ar, uint32_t sm, int blk, int tid) {
    const int warp = __shfl_sync(0xffffffffu, tid >> 5, 0), lane = tid & 31, wg = warp >> 2, w = warp & 3;
    const uint32_t bar = sm + EB_A + wg * 48, stg = sm + E_STG + wg * 16384 + w * 2048;
    bar_sync(5, 384);
    EPT(tid == 128, 7);
    float acc[64];
#pragma unroll
    for (int n = 0; n < 64; n++) acc[n] = 0.f;
#pragma unroll 1
    for (int b = B_LATE; b < 16 && blk < 80; b++) {
#pragma unroll 1
        for (int c = 0; c < 6; c++) {
            mbar_wait(sm + EB_B + 8 * (c >= 3), 0); mbar_wait(bar + 8 * (c >> 1), (b - B_LATE) & 1);
            const uint64_t da = mkdesc(SM_BASE + e_slot(wg, c >> 1) + (c & 1) * 8192, 16, 1024), db = mkdesc(SM_BASE + E_B + (c >= 3 ? 24576 : 0) + c * 8192, 24576, 1024);
            WG_FENCE();
#pragma unroll
            for (int ks = 0; ks < 4; ks++) wgmma_ss_n128_tb(acc, da + ks * 2, db + ks * 128, c | ks);
            WG_COMMIT();
            WG_WAIT(1);
            if ((c & 1) == 0 && c && elect()) mbar_arrive(bar + 16 + 4 * c);
        }
        if (b > B_LATE) bar_sync(10 + wg, 160);
        WG_WAIT(0);
        if (elect()) mbar_arrive(bar + 40);
        EPT(tid == 128, 13 + 15 - b);
        const int r = lane & 7, mi = lane >> 3;
#pragma unroll
        for (int p = 0; p < 8; p++) {
            const int oc = 2 * p + (mi >> 1);
            stsm4(stg + (oc >> 3) * 8192 + ((mi & 1) * 8 + r) * 128 + (((oc & 7) ^ r) << 4), pack2(acc[8 * p], acc[8 * p + 1]), pack2(acc[8 * p + 2], acc[8 * p + 3]),
                  pack2(acc[8 * p + 4], acc[8 * p + 5]), pack2(acc[8 * p + 6], acc[8 * p + 7]));
        }
        PROXY_FENCE();
        bar_arrive(12 + wg, 160);
    }
    bar_sync(8, 320);
    const int o = (tid >> 1) * FF + blk * 16 + (tid & 1) * 8;
    const bf16 *pg = ar.wgate + o, *pu = ar.wup + o, *pd = ar.wdown + tid * DM + (blk < 80 ? blk : 0) * 8;
#pragma unroll 1
    for (int i = 0; i < 6; i++) {
        const uint32_t d = sm + E_B + i * 4096 + tid * 16;
        if (i < 5) asm volatile("cp.async.cg.shared.global [%0], [%1], 16; cp.async.cg.shared.global [%0 + 20480], [%2], 16;" :: "r"(d), "l"(pg + i * 128 * FF), "l"(pu + i * 128 * FF) : "memory");
        asm volatile("cp.async.cg.shared.global [%0 + 40960], [%1], 16;" :: "r"(d), "l"(pd + i * 256 * DM) : "memory");
    }
    EPT(tid == 128, 8);
}
__device__ __forceinline__ void mod_tail(const ChainArgs& ar, const uint32_t tb, const uint32_t bar, const int blk, const int tid) {
#define TPROF(i) EPT(tid == 0, i)
    const int warp = __shfl_sync(0xffffffffu, tid >> 5, 0), lane = tid & 31, r = lane & 7, mi = lane >> 3;
    const uint32_t kb = tb + T_KEY;
    {
        uint32_t k[8];
        for (int n = 0;; n++) {
#pragma unroll
            for (int i = 0; i < 2; i++) asm volatile("ld.relaxed.gpu.global.v4.u32 {%0,%1,%2,%3}, [%4];" : "=r"(k[4 * i]), "=r"(k[4 * i + 1]), "=r"(k[4 * i + 2]), "=r"(k[4 * i + 3]) : "l"(g_key + warp * 256 + i * 128 + lane * 4) : "memory");
            if (__all_sync(0xffffffffu, (k[0] & k[1] & k[2] & k[3] & k[4] & k[5] & k[6] & k[7] & S_TOK) != 0)) break;
            if (n > (1 << 22)) __trap();
            __nanosleep(NAP);
        }
        const uint32_t m = __reduce_max_sync(0xffffffffu, max(umax3(k[0], k[1], k[2]), max(umax3(k[3], k[4], k[5]), max(k[6], k[7]))));
        asm volatile("st.shared.u32 [%0], %1; st.shared.u32 [%2], 0;" :: "r"(kb + warp * 4), "r"(m), "r"(kb + 32) : "memory");
        asm volatile("cp.async.wait_all;" ::: "memory");
        bar_sync(1, 256);
        TPROF(1);
        const uint32_t low = __reduce_min_sync(0xffffffffu, lds32(kb + r * 4));
        uint32_t cnt = 0;
#pragma unroll
        for (int i = 0; i < 8; i++) cnt += k[i] >= low ? 4 : 0;
        if (cnt) {
            uint32_t a; asm volatile("atom.shared.add.u32 %0, [%1], %2;" : "=r"(a) : "r"(kb + 32), "r"(cnt) : "memory");
#pragma unroll
            for (int i = 0; i < 8; i++) if (k[i] >= low) { asm volatile("st.shared.u32 [%0], %1;" :: "r"(kb + 512 + a), "r"(k[i]) : "memory"); a += 4; }
        }
        if (tid == 0) mbar_arrive(bar);
        bar_sync(1, 256);
        const int nc = lds32(kb + 32);
#pragma unroll 1
        for (int c = lane * 4; c < nc; c += 128) {
            const uint32_t me = lds32(kb + 512 + c);
            int rank = 0;
#pragma unroll 2
            for (int e = 0; e < nc; e += 16) {
                const float4 z = lds128f(kb + 512 + e);
                rank += (__float_as_uint(z.x) > me) + (e + 4 < nc && __float_as_uint(z.y) > me) + (e + 8 < nc && __float_as_uint(z.z) > me) + (e + 12 < nc && __float_as_uint(z.w) > me);
            }
            if (rank < 8) asm volatile("st.shared.u32 [%0], %1;" :: "r"(kb + 64 + (warp * 8 + rank) * 4), "r"(me) : "memory");
        }
        __syncwarp();
    }
    const uint32_t k0 = lds32(kb + 64 + (warp * 8 + r) * 4), k1 = lds32(kb + 64 + (warp * 8 + (lane >> 2)) * 4);
    TPROF(2);
    const int trow = ~k1 & (S_TOK - 1), tcol = (blk < 80 ? blk : 0) * 8 + (lane & 3) * 2;
    uint2 xb[5];
#pragma unroll
    for (int h = 0; h < 5; h++) xb[h] = __ldcg((const uint2*)(g_h2 + trow * DM + (warp * 5 + h) * 16 + (lane & 3) * 4));
    const uint32_t fx1 = __ldcg((const uint32_t*)(g_x1 + trow * DM + tcol)), fh2 = __ldcg((const uint32_t*)(g_h2 + trow * DM + tcol)),
                   fgb = __ldcg((const uint32_t*)(g_mod + 5 * DM + tcol));
    const float fr = __uint_as_float(((int)k1 < 0 ? k1 ^ 0x80000000u : ~k1) & 0xffff0000u);
    {
        float dg[4] = {0, 0, 0, 0}, du[4] = {0, 0, 0, 0};
        uint32_t ag[5][4], au[5][4];
#pragma unroll
        for (int h = 0; h < 5; h++) {
            const uint32_t o = tb + ((warp * 5 + h) * 16 + (r >> 1) * 4 + (mi >> 1) * 2 + (r & 1)) * 32 + (mi & 1) * 16;
            ldsm4t(ag[h], o + T_WG); ldsm4t(au[h], o + T_WU);
        }
#pragma unroll
        for (int h = 0; h < 5; h++) { mma16q(dg, ag[h], xb[h].x, xb[h].y); mma16q(du, au[h], xb[h].x, xb[h].y); }
        TPROF(3);
        sts128f(tb + T_RED + warp * 1024 + lane * 16, dg[0], dg[1], dg[2], dg[3]); sts128f(tb + T_RED + warp * 1024 + 512 + lane * 16, du[0], du[1], du[2], du[3]);
    }
    bar_sync(1, 256);
    if (warp < 2) {
        float g2[2] = {0, 0}, u2[2] = {0, 0};
#pragma unroll
        for (int i = 0; i < 8; i++) {
            const float2 a = lds64f(tb + T_RED + i * 1024 + lane * 16 + warp * 8), b = lds64f(tb + T_RED + i * 1024 + 512 + lane * 16 + warp * 8);
            g2[0] += a.x; g2[1] += a.y; u2[0] += b.x; u2[1] += b.y;
        }
        float y[2];
#pragma unroll
        for (int i = 0; i < 2; i++) { const float gq = bfr(g2[i]); y[i] = bfr(__fdividef(gq, 1.f + __expf(-gq))) * bfr(u2[i]); }
        asm volatile("st.relaxed.gpu.global.u32 [%0], %1;" :: "l"(g_gu + (blk >> 1) * 128 + lane * 4 + warp * 2 + (blk & 1)), "r"(movm_t(pack2(y[0], y[1]))) : "memory");
    }
    TPROF(4);
    if (blk < 80) {
        uint32_t a[6][4], b[6][4];
#pragma unroll
        for (int k2 = 0; k2 < 6; k2++) ldsm4t(b[k2], tb + T_WD + (warp * 6 + k2) * 512 + lane * 16);
        for (int n = 0;; n++) {
            uint32_t m = 0;
#pragma unroll
            for (int k2 = 0; k2 < 6; k2++) asm volatile("ld.relaxed.gpu.global.v4.u32 {%0,%1,%2,%3}, [%4];" : "=r"(a[k2][0]), "=r"(a[k2][1]), "=r"(a[k2][2]), "=r"(a[k2][3]) : "l"(g_gu + (warp * 6 + k2) * 128 + lane * 4) : "memory");
#pragma unroll
            for (int k2 = 0; k2 < 6; k2++) m = umax3(umax3(m, a[k2][0], a[k2][1]), a[k2][2], a[k2][3]);
            if (!__any_sync(0xffffffffu, m == ~0u)) break;
            if (n > (1 << 22)) __trap();
        }
        TPROF(5);
        float d[2][4] = {{0, 0, 0, 0}, {0, 0, 0, 0}};
#pragma unroll
        for (int k2 = 0; k2 < 6; k2++) { mma16q(d[0], a[k2], b[k2][0], b[k2][1]); mma16q(d[1], a[k2], b[k2][2], b[k2][3]); }
        asm volatile("st.shared.v2.f32 [%0], {%1,%2};" :: "r"(tb + T_X + warp * 256 + lane * 8), "f"(d[0][0] + d[1][2]), "f"(d[0][1] + d[1][3]) : "memory");
        bar_sync(1, 256);
        if (warp == 0) {
            float y0 = 0, y1 = 0;
#pragma unroll
            for (int i = 0; i < 8; i++) { const float2 z = lds64f(tb + T_X + i * 256 + lane * 8); y0 += z.x; y1 += z.y; }
            const float sg = __fdividef(1.f, 1.f + __expf(-fr));
            *(uint32_t*)(ar.out + trow * DM + tcol) = add2(fx1, mul2(fgb, add2(fh2, mul2(pack2(y0, y1), pack2(sg, sg)))));
        }
    }
    TPROF(6);
}

__global__ void __cluster_dims__(3, 1, 1) __launch_bounds__(384, 1) k_chain(const __grid_constant__ ChainMaps mp, const __grid_constant__ ChainArgs ar) {
    const int D1 = ar.D1, DG = ar.DG;
    extern __shared__ __align__(1024) uint8_t smraw[];
    const uint32_t sm = SM_BASE + ((blockIdx.x % 3) << 24);
    if (smem_u32(smraw) != sm) __trap();
    uint32_t tid; asm volatile("mov.u32 %0, %%tid.x;" : "=r"(tid));
    const int warp = __shfl_sync(0xffffffffu, tid >> 5, 0), lane = tid & 31, wg = warp >> 2, w = warp & 3;
    const int blk = blockIdx.x, head = blk / 3, j = blk % 3;
    const int col0 = head * DH + j * 64;
    asm volatile("griddepcontrol.launch_dependents;");
#define PPROF(i)
    const int r = lane & 7, mi = lane >> 3;
    const uint32_t memrd = opaque(sm + C_MEM + lane * 16);
    if (wg < 2) {
        {
            uint32_t xv[3][10];
            const int row = blk * 8 + warp, nq = row < S_TOK - 1536 ? 3 : 2;
#pragma unroll
            for (int i = 0; i < 15; i++) {
                const uint2 v = __ldcs((const uint2*)(ar.x + (row + (i < 10 || nq == 3 ? i / 5 * 768 : 0)) * DM + lane * 4 + i % 5 * 128));
                xv[i / 5][i % 5 * 2] = v.x; xv[i / 5][i % 5 * 2 + 1] = v.y;
            }
            if (tid == 32) {
#pragma unroll 1
                for (int c = 0; c < 14; c++) if (c != 12) mbar_init(sm + C_BAR + 8 * c, c == 2 ? 5 : c == 3 ? 6 : 1);
                asm volatile("fence.mbarrier_init.release.cluster;" ::: "memory");
                mbar_expect(sm + CB_SC, 2560); mbar_expect(sm + CB_OX, 2048);
            }
            if (warp == 2) {
                const uint32_t f = blk >= 28 ? ~0u : 0u;
                ((uint4*)g_acc)[blk * 32 + lane] = make_uint4(0, 0, 0, 0);
                if (blk < 76) (blk < 12 ? (uint4*)g_stamp + blk * 32 : blk < 28 ? (uint4*)g_key + (blk - 12) * 32 : (uint4*)g_gu + (blk - 28) * 32)[lane] = make_uint4(f, f, f, f);
            }
            __syncwarp();
            asm volatile("barrier.cluster.arrive.relaxed.aligned;" ::: "memory");
            PPROF(8);
#pragma unroll 1
            for (int q = 0; q < 3; q++) {
                uint32_t nv[10];
                ln_norm(xv[0], nv);
#pragma unroll
                for (int i = 0; i < 10; i++) { xv[0][i] = xv[1][i]; xv[1][i] = xv[2][i]; xv[2][i] = nv[i]; }
            }
            PPROF(9);
            if (warp < 5) {
                uint4 u;
                for (int n = 0;; n++) {
                    asm volatile("ld.relaxed.gpu.global.v4.u32 {%0,%1,%2,%3}, [%4];" : "=r"(u.x), "=r"(u.y), "=r"(u.z), "=r"(u.w) : "l"(g_flags.mod1 + tid * 4) : "memory");
                    if (__all_sync(0xffffffffu, u.x && u.y && u.z && u.w)) break;
                    cut(n, 1 << 22);
                }
                asm volatile("st.shared.v4.u32 [%0], {%1,%2,%3,%4};" :: "r"(sm + C_KX + tid * 16), "r"(~u.x), "r"(~u.y), "r"(~u.z), "r"(~u.w) : "memory");
            }
            bar_sync(8, 256);
            PPROF(2);
            uint32_t m = 0;
#pragma unroll
            for (int i = 0; i < 5; i++) {
                uint32_t t[2], u[2];
                lds64(t, sm + C_KX + lane * 8 + i * 256); lds64(u, sm + C_KX + 1280 + lane * 8 + i * 256);
                u[0] = add2(u[0], 0x3f803f80u); u[1] = add2(u[1], 0x3f803f80u);
                m = amax2(amax2(amax2(amax2(m, t[0]), u[0]), t[1]), u[1]);
#pragma unroll
                for (int q = 0; q < 3; q++)
                    if (q < nq) *(uint2*)(g_h + (row + q * 768) * DM + lane * 4 + i * 128) = make_uint2(add2(mul2(xv[q][2 * i], u[0]), t[0]), add2(mul2(xv[q][2 * i + 1], u[1]), t[1]));
            }
            asm volatile("st.shared.u32 [%0], %1;" :: "r"(sm + C_LAG), "r"((amax_warp(m) >> 7) + 1) : "memory");
            bar_sync(8, 256);
            if (tid == 0) flag_add(&g_flags.h);
            __syncwarp();
            bar_arrive(2, 288);
            PPROF(3);
            asm volatile("barrier.cluster.wait.aligned;" ::: "memory");
        }
        asm volatile("setmaxnreg.inc.sync.aligned.u32 %0;" :: "n"(REG_P));
        uint32_t wa[40][4];
        mbar_wait(sm + CB_W, 0);
#pragma unroll
        for (int ks = 0; ks < 40; ks++)
            ldsm4t(wa[ks], sm + ((wg == 0) == (ks < 20) ? C_WV : C_WO) + ((mi >> 1) * 8 + r) * 128 + (((2 * w + (mi & 1)) ^ r) << 4) + (ks % 20 / 4 * 8 + 4 * wg + (ks & 3)) * 2048);
        PPROF(5);
        bar_arrive(1, 288);
        const uint32_t qst = opaque(sm + (wg == 0 ? C_QM : C_KM) + (2 * w + (mi & 1)) * 128 + r * 16);
        const uint32_t vrd = opaque(sm + C_WV + ((mi >> 1) * 8 + r) * 128 + (((2 * w + (mi & 1)) ^ r) << 4) + 4 * wg * 2048);
        const uint32_t mrd = opaque(memrd + wg * 1024);
        float acc[16];
        auto fb = [&](int n) { return mrd + (n >> 1) * 2048 + (n & 1) * 512; };
        auto fa = [&](int k) { return vrd + (k >> 2) * 16384 + (k & 3) * 2048; };
        auto qk_out = [&](int n) {
            uint8_t* rec = g_att + (n * NH + head) * AT_REC;
            w_bulk_s2g(rec + j * 8192, sm + C_QX, 8192); w_bulk_s2g(rec + AT_KM + j * 1024, sm + C_KM, 1024);
            BULK_COMMIT();
        };
        for (int s = -1;; s++) {
          if (s >= 0) {
            x_part(acc, wa, sm, s, wg, w, opaque(mrd) >> 4 & 31, s + ar.D2);
            if (s == 0) mbar_wait(sm + CB_W2, 0);
            uint32_t b[3][4], a[4][4];
#pragma unroll
            for (int i = 0; i < 4; i++) ldsm4t(a[i], fa(4 + i));
            cut(s + ar.D2, 0);
            bar_sync(1, 384);
            if (warp == 0) { PROF(0); PROFG(24); }
            float dv[4] = {0, 0, 0, 0};
            const uint32_t xb = mrd - wg * 1024 - (C_MEM - C_VP) + w * 512;
            {
                float d[2][4] = {{0, 0, 0, 0}, {0, 0, 0, 0}}, g[2][4] = {{0, 0, 0, 0}, {0, 0, 0, 0}};
                ldsm4t(b[0], fb(0)); pin0(mrd); ldsm4t(b[1], fb(1)); pin0(mrd);
#pragma unroll
                for (int n = 0; n < 10; n++) {
                    const int c1 = n >= 10 - NCH;
                    if (n < 8) ldsm4t(b[(n + 2) % 3], fb(n + 2));
#pragma unroll
                    for (int e = 0; e < 2; e++) {
                        mma16q(g[e & c1], wa[20 + 2 * n + e], b[n % 3][2 * e], b[n % 3][2 * e + 1]); mma16q(d[e & c1], wa[2 * n + e], b[n % 3][2 * e], b[n % 3][2 * e + 1]);
                        if (n >= 2 && n < 10 - VT) mma16q(dv, a[(2 * n + e) & 3], b[n % 3][2 * e], b[n % 3][2 * e + 1]);
                        if (n >= 2 && n < 8) ldsm4t(a[(2 * n + e) & 3], fa(2 * n + 4 + e));
                    }
                    if (QCUT >> n & 1) cut(s + ar.D2, 1 + n);
                }
                const float un = __uint_as_float(lds32(sm + C_UN));
                sts128f(xb - 4096 + wg * 2048, g[0][0] + g[1][0], g[0][1] + g[1][1], g[0][2] + g[1][2], g[0][3] + g[1][3]);
#pragma unroll
                for (int k = 20 - 2 * VT; k < 20; k++) mma16q(dv, a[k & 3], b[k / 2 % 3][2 * (k & 1)], b[k / 2 % 3][2 * (k & 1) + 1]);
                bar_sync(8, 256);
                const float4 z = lds128f(xb - 4096 + (wg ^ 1) * 2048);
                sts128f(xb + wg * 2048, dv[0], dv[1], dv[2], dv[3]);
                stsm2t(qst, pack2((d[0][0] + d[1][0] + z.x) * un, (d[0][1] + d[1][1] + z.y) * un), pack2((d[0][2] + d[1][2] + z.z) * un, (d[0][3] + d[1][3] + z.w) * un));
            }
            bar_arrive(2, 384);
            if (w == 0) PROF(1 + wg);
            if (s + 1 == NSEG) break;
          }
          if (warp == 3 && s >= 0)
              asm volatile(ELECTED("st.relaxed.gpu.global.u32 [%0], %1;") :: "l"(g_stamp + (s & 3) * 384 + (blk >> 3) * 32 + (blk & 7)), "r"((gtime() & ~31u) | ((s >> 2) + 1)) : "memory");
          PROXY_FENCE();
          mbar_wait(sm + CB_XF, (s + 1) & 1);
          if (s >= 0) bar_sync(7, 384);
          WG_FENCE();
#pragma unroll
          for (int i = 0; i < 16; i++) acc[i] = 0.f;
#pragma unroll
          for (int i = 1; i <= XA; i++) x_chunk(acc, wa, x_base(wg, s + ar.D2, 20), 20, i, i == 1);
          WG_COMMIT();
          if (warp == FW && s > 0) seg_done(s - 1, head);
          WG_WAIT(0);
          if (s >= 0) {
            if (warp == 0) {
                PROF(7);
                if (elect()) x_rest(mp, sm, s + 1);
            } else {
                if (wg == 1) {
                    if (w == 1) {
                        qk_out(s);
                    }
                    if (w == 2 && blk < 10 && s + 3 < NSEG)
                        asm volatile(ELECTED("cp.async.bulk.prefetch.L2.global [%0], 4096;") :: "l"((const uint8_t*)g_h + (s + 3) * (SEG * DM * 2) + blk * 4096) : "memory");
                } else if (w == 3) {
                    if (SPOLL) wait_until(clock() + SPOLL);
                    const uint32_t l = opaque(mrd) >> 4 & 31, tag = (s >> 2) + 1, now = gtime();
                    const uint32_t* sp = g_stamp + (s & 3) * 384 + (l >> 3) * 32 + (l & 7);
                    uint32_t t[3];
                    for (int n = 0;; n++) {
#pragma unroll
                        for (int i = 0; i < 3; i++) t[i] = ld_rlx(sp + i * 128);
                        if (!__any_sync(0xffffffffu, ((t[0] ^ tag) | (t[1] ^ tag) | (t[2] ^ tag)) & 31) || n > SPIN_LIMIT) break;
                    }
                    int all = -(1 << 30), own = all;
#pragma unroll
                    for (int i = 0; i < 3; i++) { const int d = t[i] - now; all = max(all, d); if ((i * 32 + l) / 3 == head) own = d; }
                    const int lag = min(__reduce_max_sync(0xffffffffu, all) - __reduce_max_sync(0xffffffffu, own), 8000);
                    PROFV(15, lag);
                    asm volatile("st.shared.u32 [%0], %1;" :: "r"(sm + C_LAG), "r"(D1 + ((lag * DG) >> 4)) : "memory");
                    bar_arrive(6, 160);
                } else if (w == 2) {
                    if ((s & 3) == 3) w_flag_wait(&g_flags.v[((s + 1) >> 2) * 32 + head], 2);
                    if (elect()) { mbar_expect(sm + CB_VX, 4096); bulk_g2s(sm + C_VX, g_att + ((s + 1) * NH + head) * AT_REC + AT_V + j * 4096, 4096, sm + CB_VX); }
                    if ((s & 3) == 1 && s + 3 < NSEG) asm volatile("prefetch.global.L2 [%0];" :: "l"(&g_flags.v[((s + 3) >> 2) * 32]));
                    if (s + 2 < NSEG && ((s & 3) != 2 || __all_sync(0xffffffffu, ld_rlx(&g_flags.v[((s + 2) >> 2) * 32 + head]) >= 2)))
                        asm volatile("prefetch.global.L2 [%0];" :: "l"(g_att + ((s + 2) * NH + head) * AT_REC + AT_V + j * 4096 + (opaque(mrd) << 3 & 0xf80)));
                }
            }
          }
        }
        PROXY_FENCE();
        bar_sync(8, 256);
        if (warp == 5) { qk_out(NSEG - 1); BULK_WAIT(); }
        if (warp == 7) seg_done(NSEG - 2, head);
        bar_arrive(7, 384);
        const int t2 = (opaque(mrd) >> 4 & 31) + warp * 32;
        EPT(t2 == 0, 0);
        last_blocks(ar, sm, blk, t2);
        mod_tail(ar, sm + E_B, sm + EB_REL, blk, t2);
    } else {
        asm volatile("setmaxnreg.dec.sync.aligned.u32 %0;" :: "n"(REG_L));
        asm volatile("barrier.cluster.arrive.relaxed.aligned;" ::: "memory");
        if (blk < 80) {
            const int t = tid - 256;
#pragma unroll 1
            for (int i = 0; i < 10; i++)
                asm volatile("cp.async.cg.shared.global.L2::128B [%0], [%1], 16;" :: "r"(sm + C_XR + i * 2048 + t * 16), "l"(ar.wmod + ((t >> 1) + 64 * i) * (6 * DM) + blk * 16 + (t & 1) * 8) : "memory");
            float cs[5];
#pragma unroll
            for (int i = 0; i < 5; i++) cs[i] = __uint_as_float((uint32_t)__ldg((const unsigned short*)ar.c + t + 128 * i) << 16);
#pragma unroll
            for (int i = 0; i < 5; i++) asm volatile("st.shared.f32 [%0], %1;" :: "r"(sm + C_QX + (t + 128 * i) * 4), "f"(bfr(__fdividef(cs[i], 1.f + __expf(-cs[i])))) : "memory");
            asm volatile("cp.async.wait_all;" ::: "memory");
            bar_sync(3, 128);
            float a0 = 0, a1 = 0;
#pragma unroll 8
            for (int i = 0; i < 40; i++) {
                const float f = __uint_as_float(lds32(sm + C_QX + (t >> 3) * 4 + i * 64));
                const uint32_t u = lds32(sm + C_XR + t * 4 + i * 512);
                a0 += f * lo_f(u); a1 += f * hi_f(u);
            }
#pragma unroll
            for (int o = 8; o < 32; o <<= 1) { a0 += __shfl_xor_sync(0xffffffffu, a0, o); a1 += __shfl_xor_sync(0xffffffffu, a1, o); }
            asm volatile("st.shared.v2.f32 [%0], {%1,%2};" :: "r"(sm + C_QM + w * 64 + (lane & 7) * 8), "f"(a0), "f"(a1) : "memory");
            bar_sync(3, 128);
            if (w == 0) {
#pragma unroll
                for (int i = 1; i < 4; i++) { const float2 z = lds64f(sm + C_QM + i * 64 + (lane & 7) * 8); a0 += z.x; a1 += z.y; }
                const uint32_t v = pack2(a0, a1);
                asm volatile("st.relaxed.gpu.global.u32 [%0], %1;" :: "l"(g_flags.mod1 + blk * 8 + (lane & 7)), "r"(~v) : "memory");
            }
        }
        uint32_t m0[5][4], mm = 0;
#pragma unroll
        for (int i = 0; i < 20; i++) {
            const unsigned short* p = (const unsigned short*)ar.mem0 + (i & 3) * 2 * DM + (i >> 2) * 128 + tid - 256;
            m0[i >> 2][i & 3] = __ldg(p) | (uint32_t)__ldg(p + DM) << 16;
        }
        {
            asm volatile("barrier.cluster.wait.aligned;" ::: "memory");
            if (w == 3) {
                w_flag_wait(&g_flags.h, 96);
                if (elect()) { x_fill(mp, sm, 0, j); x_rest(mp, sm, 0); }
                __syncwarp();
            }
            if (w == 1) {
                const uint64_t ef = policy_stream();
#pragma unroll 1
                for (int c = 0; c < 2 * WP + 2; c++) {
                    const uint32_t bar = sm + EB_B + 8 * (c & 1);
                    if (c == WPOS) bar_sync(2, 288);
                    if (c >= 2) mbar_wait(bar, (c / 2 - 1) & 1);
                    if (elect()) {
                        if (c < 2 * WP) { mbar_expect(bar, 81920 / WP); tma2d_ef(sm + C_WV + c * (81920 / WP), c < WP ? &mp.wq : &mp.wk, col0, c % WP * (640 / WP), bar, ef); }
                        if (c >= WOPF && c < WOPF + 3) asm volatile("cp.async.bulk.prefetch.tensor.3d.L2.global [%0, {0, %1, %2}];" :: "l"((uint64_t)&mp.wo), "r"(head * DH + (c - WOPF) * 64), "r"(7 * j) : "memory");
                    }
                    __syncwarp();
                }
                if (elect()) mbar_arrive(sm + CB_W);
                bar_sync(1, 288);
                if (elect()) {
                    mbar_expect(sm + CB_W2, 81920); mbar_expect(sm + CB_W3, 3 * WO_BLK);
#pragma unroll 1
                    for (int c = 0; c < 4; c++) tma2d(sm + C_WV + c * 20480, &mp.wv, col0, c * 160, sm + CB_W2);
#pragma unroll 1
                    for (int c = 0; c < 3; c++) tma3d(sm + C_WO + c * WO_BLK, &mp.wo, head * DH + (j + c) % 3 * 64, 7 * j, sm + CB_W3);
                }
                __syncwarp();
                w_flag_wait(&g_flags.v[head], 2);
                if (elect()) { mbar_expect(sm + CB_VX, 4096); bulk_g2s(sm + C_VX, g_att + head * AT_REC + AT_V + j * 4096, 4096, sm + CB_VX); }
            } else {
                uint32_t mw = 0;
#pragma unroll 1
                for (int c = 0; c < 2; c++) {
                    mbar_wait(sm + (c ? CB_W3 : CB_W2), 0);
                    uint32_t m = 0;
                    const uint32_t end = sm + (c ? C_XR : C_WO);
#pragma unroll 1
                    for (uint32_t a = sm + c * C_WO + (w - (w > 0)) * 4096 + lane * 16; a < end; a += 3 * 4096) {
                        float4 z[8];
#pragma unroll
                        for (int i = 0; i < 8; i++) z[i] = lds128f(a + i * 512);
#pragma unroll
                        for (int i = 0; i < 8; i++) m = amax2(amax2(amax2(amax2(m, __float_as_uint(z[i].x)), __float_as_uint(z[i].y)), __float_as_uint(z[i].z)), __float_as_uint(z[i].w));
                    }
                    mw |= amax_warp(m) << (16 * c);
                }
                asm volatile("st.shared.u32 [%0], %1;" :: "r"(sm + C_KM + w * 4), "r"(mw) : "memory");
                bar_sync(3, 96);
                if (w == 0) asm volatile("st.relaxed.gpu.global.u32 [%0], %1;" :: "l"(g_flags.wmax + blk), "r"(amax2(amax2(mw, lds32(sm + C_KM + 8)), lds32(sm + C_KM + 12)) | 0x8000) : "memory");
            }
        }
        bar_sync(9, 384);
#pragma unroll
        for (int i = 0; i < 5; i++) {
            asm volatile("st.shared.v4.u32 [%0], {%1,%2,%3,%4};" :: "r"(sm + C_MEM + (tid - 256 + i * 128) * 16), "r"(m0[i][0]), "r"(m0[i][1]), "r"(m0[i][2]), "r"(m0[i][3]) : "memory");
            mm = amax2(amax2(amax2(amax2(mm, m0[i][0]), m0[i][1]), m0[i][2]), m0[i][3]);
        }
        asm volatile("st.shared.u32 [%0], %1; st.shared.u32 [%2], 0x3f800000;" :: "r"(sm + C_MX + w * 4), "r"(amax_warp(mm)), "r"(sm + C_UN) : "memory");
        int ew = __shfl_sync(0xffffffffu, lds32(sm + C_LAG), 0), es = 0;
        const uint32_t rb1 = (uint32_t)((j + 1) % 3 - j) << 24, rb2 = (uint32_t)((j + 2) % 3 - j) << 24;
        const float scale = 0.07216878364870322f;
        uint32_t va[8][4], mr = memrd;
#pragma unroll
        for (int i = 0; i < 8; i++) ldsm4t(va[i], sm + C_WV + ((mi >> 1) * 8 + r) * 128 + (((2 * w + (mi & 1)) ^ r) << 4) + i * 2048);
        bar_sync(1, 384);
        for (int s = 0; s < NSEG; s++) {
            const float un = __uint_as_float((127 - es) << 23);
            if (w == 1) {
                mbar_wait(sm + CB_XD, s & 1);
                if (s + 1 < NSEG) { if (elect()) x_fill(mp, sm, s + 1, j); }
                else { if (BPOS != 2) wo_half(mp, sm, blk, 0); if (BPOS != 0) wo_half(mp, sm, blk, 1); }
            }
            const uint32_t l0 = mr >> 4 & 31, r0 = l0 & 7, m0 = l0 >> 3;
            float vd[4];
            {
                uint32_t c[4][4];
#pragma unroll
                for (int i = 0; i < 4; i++) ldsm4t(c[i], mr + i * 512);
                float d[2][4] = {{0, 0, 0, 0}, {0, 0, 0, 0}};
#pragma unroll
                for (int i = 0; i < 8; i++) mma16q(d[i & 1], va[i], c[i >> 1][2 * (i & 1)], c[i >> 1][2 * (i & 1) + 1]);
#pragma unroll
                for (int i = 0; i < 4; i++) vd[i] = d[0][i] + d[1][i];
            }
            uint32_t zr = 0;
            if (w == 2)
                asm volatile("atom.relaxed.gpu.global.exch.b32 %0, [%1], 0;" : "=r"(zr)
                    : "l"(g_acc + ((s & 2) ^ 2) * (ACC_PAIR / 2) + (s & 1) * 512 + (blk >> 2) * 1024 + (blk & 3) * 128 + l0 * 4) : "memory");
            __syncwarp();
            uint32_t kb[4][4] = {};
            {
                const uint32_t k7 = r0 ^ (m0 << 2 & 4), kxrd = sm + C_KX + (16 * (w & 1) + 8 * (m0 & 1) + k7) * 128 + (((m0 >> 1) ^ k7) << 4);
#pragma unroll
                for (int i = 0; i < 4; i++) if (w >= 2) ldsm4(kb[i], kxrd ^ (i << 5));
            }
            const uint32_t qrd = sm + C_QM + (w == 1 ? (m0 & 1) * 2 + (m0 >> 1) : m0) * 128 + r0 * 16;
            const uint32_t scdst = sm + C_SC + j * 1280 + (w == 1 ? 1024 + l0 * 8 : (w & 1) * 512 + (l0 & 2) * 128 + (l0 >> 2) * 32 + (l0 & 1) * 16);
            const uint32_t scrd = sm + C_SC + (l0 >> 4) * 256 + (l0 & 3) * 32 + (l0 >> 2 & 3) * 8;
            const uint32_t v7 = (4 * (m0 & 1) + (r0 >> 1)) ^ (r0 << 2 & 4), vxrd = sm + C_VX + (16 * (m0 >> 1) + 8 * (r0 & 1) + v7) * 128 + (((2 * w) ^ v7) << 4);
            if (s == 0) {
                uint32_t t[3];
                for (int n = 0;; n++) {
#pragma unroll
                    for (int i = 0; i < 3; i++) t[i] = ld_rlx(g_flags.wmax + l0 + 32 * i);
                    if (__all_sync(0xffffffffu, t[0] && t[1] && t[2])) break;
                    cut(n, 1 << 22);
                }
                const uint32_t m = amax2(amax2(amax2(0, t[0]), t[1]), t[2]);
                const int e = 371 - (int)(__reduce_max_sync(0xffffffffu, m & 0xffffu) >> 7) - (int)(__reduce_max_sync(0xffffffffu, m >> 16) >> 7);
                ew = e << 16 | (min(e - ew, 100) & 0xffff);
            }
            mbar_wait(sm + CB_VX, s & 1);
            uint32_t vb[2][4];
            ldsm4t(vb[0], vxrd); ldsm4t(vb[1], vxrd ^ 16);
            const uint32_t word = sm + C_WO + (m0 & 1) * 4096 + ((m0 >> 1) * 8 + r0) * 64 + ((w ^ (r0 >> 1)) << 4);
            const uint32_t word6 = word + 6 * 4096 - (m0 & 1) * 3072;
            const uint32_t oxrd = sm + C_OX + l0 * 8;
            const uint32_t ord = oxrd + w * 256;
            const uint32_t vp = mr - (C_MEM - C_VP) + w * 512, vmst = mr + (C_VM - C_MEM) + w * 256;
            pin(mr, scdst + rb1, sm + CB_SC + rb1, scdst + rb2, sm + CB_SC + rb2); pin(mr, qrd, scdst, scrd, vp); pin(mr, word, word6, oxrd, ord);
            pin(mr, __float_as_uint(vd[0]), __float_as_uint(vd[1]), __float_as_uint(vd[2]), __float_as_uint(vd[3]));
            bar_sync(2, 384);
            const bool odd = mr & 16;
            float4 y0, y1, mx4;
            {
                uint32_t qa[2][4];
                ldsm4(qa[0], qrd); ldsm4(qa[1], qrd + 512);
                float sc[2][4] = {{0, 0, 0, 0}, {0, 0, 0, 0}};
                if (w == 1) {
                    ldsm4(kb[0], mr + (C_KM - C_MEM)); ldsm4(kb[1], mr + (C_KM - C_MEM) + 512);
                    pin0(mr); y0 = lds128f(vp); y1 = lds128f(vp + 2048); mx4 = lds128f(sm + C_MX);
#pragma unroll
                    for (int k = 0; k < 4; k++) mma16q(sc[k & 1], qa[k >> 1], kb[k >> 1][2 * (k & 1)], kb[k >> 1][2 * (k & 1) + 1]);
                    const uint32_t a0 = __float_as_uint(sc[0][0] + sc[1][2]), a1 = __float_as_uint(sc[0][1] + sc[1][3]);
                    send8(scdst + rb1, sm + CB_SC + rb1, a0, a1); send8(scdst + rb2, sm + CB_SC + rb2, a0, a1);
                    asm volatile("st.shared.v2.u32 [%0], {%1,%2};" :: "r"(scdst), "r"(a0), "r"(a1) : "memory");
                } else {
                    pin0(mr); y0 = lds128f(vp); y1 = lds128f(vp + 2048); mx4 = lds128f(sm + C_MX);
                    if (w) {
#pragma unroll
                        for (int k = 0; k < 4; k++) mma16q(sc[k & 1], kb[k], qa[k >> 1][2 * (k & 1)], qa[k >> 1][2 * (k & 1) + 1]);
                        const float a0 = sc[0][0] + sc[1][0], a1 = sc[0][2] + sc[1][2], a2 = sc[0][1] + sc[1][1], a3 = sc[0][3] + sc[1][3];
                        send16(scdst + rb1, sm + CB_SC + rb1, a0, a1, a2, a3); send16(scdst + rb2, sm + CB_SC + rb2, a0, a1, a2, a3);
                        sts128f(scdst, a0, a1, a2, a3);
                    }
                }
            }
            bar_arrive(7, 384);
            if (elect()) mbar_arrive(sm + CB_SC);
            {
                const float4 z = mx4;
                const int em = (int)(max(max(__float_as_uint(z.x), __float_as_uint(z.y)), max(__float_as_uint(z.z), __float_as_uint(z.w))) >> 7) - es;
                es = __shfl_sync(0xffffffffu, max(min((ew >> 16) - em, (int)(short)ew), -120), 0);
            }
            if (w == 0) PROF(4);
            const uint32_t vm0 = pack2((vd[0] + y0.x + y1.x) * un, (vd[1] + y0.y + y1.y) * un), vm1 = pack2((vd[2] + y0.z + y1.z) * un, (vd[3] + y0.w + y1.w) * un);
            stsm2t(vmst, vm0, vm1);
            if (s + 1 == NSEG) {
                mbar_wait(sm + CB_SC, s & 1);
                PROXY_FENCE();
                bar_sync(3, 128);
                if (w == 1) {
                    w_bulk_s2g(g_att + (s * NH + head) * AT_REC + AT_VM + j * 1024, sm + C_VM, 1024);
                    BULK_COMMIT();
                    BULK_WAIT();
                }
                __syncwarp();
                break;
            }
            cut(s + ar.D2, 0);
            mbar_wait(sm + CB_SC, s & 1);
            if (w == 0) PROF(8);
            float sv[10];
            {
                float2 z[5][3];
#pragma unroll
                for (int u = 0; u < 5; u++)
#pragma unroll
                    for (int p = 0; p < 3; p++) z[u][p] = lds64f((u < 4 ? scrd + (u >> 1) * 512 + (u & 1) * 128 : oxrd + (C_SC - C_OX) + 1024) + p * 1280);
#pragma unroll
                for (int u = 0; u < 5; u++) { sv[2 * u] = (z[u][0].x + z[u][1].x) + z[u][2].x; sv[2 * u + 1] = (z[u][0].y + z[u][1].y) + z[u][2].y; }
            }
            float mx = fmaxf(fmaxf(fmaxf(sv[0], sv[1]), fmaxf(sv[2], sv[3])), fmaxf(fmaxf(fmaxf(sv[4], sv[5]), fmaxf(sv[6], sv[7])), fmaxf(sv[8], sv[9])));
            uint32_t a[NRING][4];
            auto frag = [&](int i) { const int p = i / 7, u = i % 7, o = (p >> 1) * WO_BLK + (p & 1) * 2048;
                                     return u == 3 ? word6 + o : word + o + (u > 3 ? 1024 + (u - 4) * 8192 : u * 8192); };
            mx = fmaxf(fmaxf(mx, __shfl_xor_sync(0xffffffffu, mx, 1)), fmaxf(__shfl_xor_sync(0xffffffffu, mx, 2), __shfl_xor_sync(0xffffffffu, mx, 3)));
            pin(mr, __float_as_uint(mx), 0, 0, 0);
            {
#pragma unroll
                for (int i = 0; i < NPRE; i++) ldsm4t(a[i], frag(i));
                pin0(mr);
                const float sl2e = scale * 1.4426950408889634f, mxl = mx * sl2e;
#pragma unroll
                for (int i = 9; i >= 0; i--) asm volatile("ex2.approx.ftz.f32 %0, %1;" : "=f"(sv[i]) : "f"(fmaf(sv[i], sl2e, -mxl)));
                const uint32_t pq[4] = {pack2(sv[0], sv[1]), pack2(sv[4], sv[5]), pack2(sv[2], sv[3]), pack2(sv[6], sv[7])}, pm = pack2(sv[8], sv[9]);
                if (w == 0) PROF(6);
                float o[2][4] = {{0, 0, 0, 0}, {0, 0, 0, 0}}, o2[2][4] = {{0, 0, 0, 0}, {0, 0, 0, 0}}, sx[4] = {0, 0, 0, 0};
                mma8(sx, pm, 0, 0x3f803f80u); mma8(o[0], pm, 0, vm0); mma8(o[1], pm, 0, vm1);
                mma16q(sx, pq, 0x3f803f80u, 0x3f803f80u);
#pragma unroll
                for (int u = 0; u < 2; u++) { mma16q(o[u], pq, vb[u][0], vb[u][1]); mma16q(o2[u], pq, vb[u][2], vb[u][3]); }
                float inv; asm("rcp.approx.ftz.f32 %0, %1;" : "=f"(inv) : "f"((sx[0] + sx[2]) * __uint_as_float((127 - es) << 23)));
                const uint32_t f0 = pack2((o[0][0] + o2[0][2]) * inv, (o[0][1] + o2[0][3]) * inv), f1 = pack2((o[1][0] + o2[1][2]) * inv, (o[1][1] + o2[1][3]) * inv);
                send8(ord + 2048 + rb1, sm + CB_OX + rb1, f0, f1); send8(ord + 1024 + rb2, sm + CB_OX + rb2, f0, f1);
                asm volatile("st.shared.v2.u32 [%0], {%1,%2};" :: "r"(ord), "r"(f0), "r"(f1) : "memory");
            }
            if (w == 0) PROF(10);
#pragma unroll
            for (int i = NPRE; i < NRING; i++) ldsm4t(a[i], frag(i));
            bar_sync(3, 128);
            float e[5][4];
#pragma unroll
            for (int q = 0; q < 5; q++) e[q][0] = e[q][1] = e[q][2] = e[q][3] = 0.f;
            constexpr int LAG = 2;
            uint8_t* pdst = g_acc + ((s & 2) * (ACC_PAIR / 2) + (s & 1) * 512 + w * 2048 + j * 8192 - C_MEM - sm + mr);
#pragma unroll
            for (int h = 0; h < 3; h++) {
                uint32_t ob[4][2];
                if (h == 1) {
#pragma unroll
                    for (int i = 14 - LAG; i < 14; i++) ldsm4t(a[i % NRING], frag(i + NRING));
                    pin(mr, zr, (uint32_t)(uint64_t)pdst, (uint32_t)((uint64_t)pdst >> 32), 0);
                    mbar_wait(sm + CB_OX, s & 1);
                    if (w == 0) PROF(9);
                }
#pragma unroll
                for (int k = 0; k < 4; k++) lds64(ob[k], oxrd + h * 1024 + k * 256);
#pragma unroll
                for (int i = 14 * h; i < 14 * h + 14; i++) {
                    const int u = i % 7, k = 2 * (i / 7 & 1);
                    if (u == 3) { mma16q(e[3], a[i % NRING], ob[k][0], ob[k][1]); mma16q(e[4], a[i % NRING], ob[k + 1][0], ob[k + 1][1]); }
                    else mma16q(e[u & 3], a[i % NRING], ob[k + (u >> 2)][0], ob[k + (u >> 2)][1]);
                    if (i == B5AT) { pin(mr, a[i % NRING][0], a[i % NRING][1], a[i % NRING][2], a[i % NRING][3]); bar_arrive(5, 384); }
                    if (i >= LAG && !(i >= 14 && i < 14 + LAG) && i - LAG + NRING < 42) ldsm4t(a[(i - LAG) % NRING], frag(i - LAG + NRING));
                }
            }
            {
                const uint32_t w6 = pack2h(e[3][0] + e[4][2], e[3][1] + e[4][3]), one = 0x3c003c00u;
                asm volatile("red.relaxed.gpu.global.add.noftz.v4.f16x2 [%0], {%1,%2,%3,%4};"
                    :: "l"(pdst), "r"(pack2h(e[0][0], e[0][1])), "r"(pack2h(e[0][2], e[0][3])), "r"(pack2h(e[1][0], e[1][1])), "r"(odd ? w6 : one) : "memory");
                asm volatile("red.relaxed.gpu.global.add.noftz.v4.f16x2 [%0], {%1,%2,%3,%4};"
                    :: "l"(pdst + 1024), "r"(pack2h(e[1][2], e[1][3])), "r"(pack2h(e[2][0], e[2][1])), "r"(pack2h(e[2][2], e[2][3])), "r"(odd ? one : w6) : "memory");
            }
            const uint32_t tw = clock();
            if (w == 0) { PROF(14); PROFG(25); }
            PROXY_FENCE();
            bar_sync(6, 160);
            mr = opaque(mr);
            const uint32_t ln = mr >> 4 & 31, due = tw + lds32(sm + C_LAG);
            const uint32_t vr = sm + C_WV + ((ln >> 4) * 8 + (ln & 7)) * 128 + (((2 * w + (ln >> 3 & 1)) ^ (ln & 7)) << 4);
            const uint32_t ms0 = sm + C_MEM + w * 128 + (ln & 7) * 16 + (ln >> 3) * 512, ms1 = ms0 + (ln < 24 ? 2048 : 1536);
            if (BPOS == 2 && w == 0 && s + 2 == NSEG) wo_half(mp, sm, blk, 0);
            if (w == 2) { w_expect(sm + CB_SC, 2560); w_expect(sm + CB_OX, 2048); asm volatile("st.shared.u32 [%0], %1;" :: "r"(sm + C_UN), "r"((127 - es) << 23) : "memory"); }
            if (w == 0) { w_bulk_s2g(g_att + (s * NH + head) * AT_REC + AT_VM + j * 1024, sm + C_VM, 1024); BULK_COMMIT(); }
            const uint8_t* src = pdst - j * 8192;
            pin(mr, ms0, ms1, (uint32_t)(uint64_t)src, (uint32_t)((uint64_t)src >> 32));
            pin(mr, vr, due, 0, 0);
            cut(s + ar.D2, 1);
#pragma unroll
            for (int i = 0; i < 8; i++) ldsm4t(va[i], vr + i * 2048);
            wait_until(due);
            if (w == 0) { PROF(5); PROFG(26); }
            uint4 v[6];
            auto fetch = [&]() {
#pragma unroll
                for (int k = 0; k < 6; k++)
                    asm volatile("ld.relaxed.gpu.global.v4.u32 {%0,%1,%2,%3}, [%4];" : "=r"(v[k].x), "=r"(v[k].y), "=r"(v[k].z), "=r"(v[k].w) : "l"(src + (k >> 1) * 8192 + (k & 1) * 1024) : "memory");
            };
            fetch();
            PROFV(20 + w, 0);
            bar_sync(9, 384);
#pragma unroll 1
            for (int n = 0; __any_sync(0xffffffffu, ~((odd ? v[1].w & v[3].w & v[5].w : v[0].w & v[2].w & v[4].w)) & 0x50005000u); n++) {
                PROFV(20 + w, n + 1);
                cut(n, SPIN_LIMIT);
                fetch();
            }
            uint32_t cv[3][7];
#pragma unroll
            for (int k = 0; k < 3; k++) {
                const uint4 x = v[2 * k], y = v[2 * k + 1];
                const uint32_t u[7] = {x.x, x.y, x.z, y.x, y.y, y.z, k < 2 ? (odd ? x.w : y.w) : 0u};
#pragma unroll
                for (int i = 0; i < 7; i++) cv[k][i] = f16_to_bf16(u[i]);
                stsm4(ms0 + k * 3584, cv[k][0], cv[k][1], cv[k][2], cv[k][3]);
                if (k < 2) stsm4(ms1 + k * 3584, cv[k][4], cv[k][5], cv[k][6], cv[k][6]);
                else asm volatile("stmatrix.sync.aligned.m8n8.x2.shared.b16 [%0], {%1,%2};" :: "r"(ms1 + k * 3584), "r"(cv[k][4]), "r"(cv[k][5]) : "memory");
            }
            if (w == 0) PROF(16);
            bar_sync(1, 384);
            if (w == 0) BULK_WAIT();
            cut(s + ar.D2, 2);
            uint32_t mc = 0;
#pragma unroll
            for (int i = 0; i < 20; i++) mc = amax2(mc, cv[i / 7][i % 7]);
            asm volatile("st.shared.u32 [%0], %1;" :: "r"(sm + C_MX + w * 4), "r"(amax_warp(mc)) : "memory");
        }
        if (w >= 2) end_loads(mp, ar, sm, blk, w - 2);
        else if (w == 1) { bar_sync(5, 384); seg_done(NSEG - 1, head); EPT(true, 9); if (EORD) bar_arrive(6, 96); if (BPOS == 0) wo_half(mp, sm, blk, 1); }
        else bar_arrive(5, 384);
        if (w < 2) end_stores(mp, sm, blk, w);
        if (w == 0) { mbar_wait(sm + EB_REL, 0); flags_release(mr >> 4 & 31); }
    }
}

struct SideMaps { CUtensorMap h, wv, ost, o, wo, slab3, slab2, lnp[3]; };
constexpr int SD_ST = 14336, SD_NST = 12, SD_EPI = SD_NST * SD_ST, SD_PAR = SD_EPI + 2 * 24576, SD_BAR = SD_PAR + 6400, SD_SMEM = SD_BAR + 1024;
#define VLEAD 16
#define EARLY15 0
#define N_LIGHT 6
#define B_HELP 13
#define AUNR_ 2
constexpr int AUNR = AUNR_;
#define KSO 4
#define KSA 3
#define B_8 10
#define B_16 13
__device__ __forceinline__ int o_shift(int b) { return b >= B_16 ? 4 : b >= B_8 ? 3 : 2; }
__device__ __forceinline__ int o_split(int b) { return 1 << o_shift(b); }
__device__ __forceinline__ uint32_t o_done(int b) { return b >= B_LATE ? 160 : 4 << o_shift(b); }
__device__ __forceinline__ int next_item(int lane) {
    const int b0 = lane & 15, hi = lane >> 4;
    for (int n = 0;; n++) {
        const uint32_t w0 = ld_rlx(g_flags.qk + lane), w1 = ld_rlx(g_flags.at + lane), w2 = ld_rlx(&g_flags.c[0][0] + lane), w3 = ld_rlx(&g_flags.c[2][0] + lane), w4 = ld_rlx(&g_flags.seg[32]);
        const uint32_t o01 = __ballot_sync(0xffffffffu, lane && w2 < 32), o23 = __ballot_sync(0xffffffffu, b0 < (hi ? 14 : B_LATE) && w3 < 2u * o_split(b0));
        uint32_t ra = __ballot_sync(0xffffffffu, w0 >= (hi ? 64u : 96u));
        ra |= 0x7fffffffu >> __clz((ra & 0xffff) | 1);
        const uint32_t rb = __ballot_sync(0xffffffffu, w1 >= (hi ? o_done(b0) : 64u));
        const int bv = __ffs(o01 | 0x10000) - 1, ba = __ffs(o01 >> 16 | 0x10000) - 1, bo = __ffs(o23 | 0x10000) - 1, bl = __ffs(o23 >> 16 | 0x10000) - 1;
        if (bl == 16 && ba == 16) return -1;
        const int bc = __ffs(~ra | 0x10000) - 1;
        const bool last = ba == 15 && (w4 >= 3 || (EARLY15 && bc == 15));
        const bool r1 = (ra & ra >> 16) >> ba & 1, r2 = (rb & 0xffff) >> bo & 1, r3 = rb >> 16 >> bl & 1;
        const int kind = ba == 16 ? (bo < 16 ? 2 : 3) : last ? 1 :
                         blockIdx.x < N_LIGHT ? (r1 ? 1 : r3 ? 3 : bv < 16 ? 0 : -1) :
                         bv < 16 && (bv <= bc + VLEAD || !r2) ? 0 : r1 && ba >= B_HELP ? 1 : r2 ? 2 : r1 ? 1 : r3 ? 3 : bo < ba ? 2 : -1;
        if (kind < 0) { if (n > (1 << 20)) __trap(); __nanosleep(300); continue; }
        const int b = kind == 3 ? bl : kind == 2 ? bo : kind == 1 ? ba : bv;
        uint32_t i = 0;
        if (lane == 0) asm volatile("atom.relaxed.gpu.global.add.u32 %0, [%1], 1;" : "=r"(i) : "l"(&g_flags.c[kind][b]) : "memory");
        i = __shfl_sync(0xffffffffu, i, 0);
        if (i < (kind < 2 ? 32u : 2u * o_split(b))) return kind << 16 | b << 8 | i | ((kind == 1 ? r1 : kind == 2 ? r2 : r3) ? 128 : 0);
    }
}

template <int NP>
__device__ __forceinline__ void tile_out(const float (&acc)[8 * NP], uint32_t eb, uint32_t CH, uint32_t efull, uint32_t eempty, int& eph, int lane) {
    const int r = lane & 7, mi = lane >> 3, row = (mi & 1) * 8 + r;
    mbar_wait(eempty, eph); eph ^= 1;
#pragma unroll
    for (int p = 0; p < NP; p++) {
        const int oc = 2 * p + (mi >> 1);
        stsm4(eb + (oc >> 3) * CH + row * 128 + (((oc & 7) ^ r) << 4), pack2(acc[8 * p], acc[8 * p + 1]), pack2(acc[8 * p + 2], acc[8 * p + 3]),
              pack2(acc[8 * p + 4], acc[8 * p + 5]), pack2(acc[8 * p + 6], acc[8 * p + 7]));
    }
    asm volatile("fence.proxy.async.shared::cta;" ::: "memory");
    __syncwarp();
    if (lane == 0) mbar_arrive(efull);
}

template <int MT>
__device__ __forceinline__ void attn_tile(uint32_t base, uint32_t dst, uint32_t eempty, int eph, int lane) {
    constexpr int NK = MT ? 5 : 3;
    const int r = lane & 7, mi = lane >> 3, g = lane >> 2, t = lane & 3;
    float sc[NK][4];
#pragma unroll
    for (int n = 0; n < NK; n++) sc[n][0] = sc[n][1] = sc[n][2] = sc[n][3] = 0.f;
#pragma unroll AUNR
    for (int k2 = 0; k2 < 6; k2++) {
        const uint32_t cb = (k2 >> 1) * 8192, c0 = (k2 & 1) * 4;
        uint32_t a0[4], a1[4], bb[NK][4];
        ldsm4(a0, base + cb + (16 * MT + (mi & 1) * 8 + r) * 128 + (((c0 + (mi >> 1)) ^ r) << 4));
        ldsm4(a1, base + cb + (16 * MT + (mi & 1) * 8 + r) * 128 + (((c0 + 2 + (mi >> 1)) ^ r) << 4));
#pragma unroll
        for (int n = 0; n < NK; n++)
            ldsm4(bb[n], n < NK - 1 ? base + 4096 + cb + (8 * n + r) * 128 + (((c0 + mi) ^ r) << 4) : base + 36864 + k2 * 512 + lane * 16);
#pragma unroll
        for (int n = 0; n < NK; n++) mma16(sc[n], a0[0], a0[1], a0[2], a0[3], bb[n][0], bb[n][1]);
#pragma unroll
        for (int n = 0; n < NK; n++) mma16(sc[n], a1[0], a1[1], a1[2], a1[3], bb[n][2], bb[n][3]);
    }
    const float scale = 0.07216878364870322f, l2e = 1.4426950408889634f;
    float v[2][2 * NK], mx[2], sum[2];
#pragma unroll
    for (int hf = 0; hf < 2; hf++) {
        mx[hf] = -INFINITY;
#pragma unroll
        for (int n = 0; n < NK; n++) {
            uint32_t u = pack2(sc[n][2 * hf], sc[n][2 * hf + 1]);
            u = pack2(lo_f(u) * scale, hi_f(u) * scale);
            const int lim = 16 * MT + 8 * hf + g - 8 * n - 2 * t;
            v[hf][2 * n] = (n < NK - 1 && lim < 0) ? -1e9f : lo_f(u);
            v[hf][2 * n + 1] = (n < NK - 1 && lim < 1) ? -1e9f : hi_f(u);
            mx[hf] = fmaxf(mx[hf], fmaxf(v[hf][2 * n], v[hf][2 * n + 1]));
        }
    }
#pragma unroll
    for (int o = 1; o < 4; o <<= 1)
#pragma unroll
        for (int hf = 0; hf < 2; hf++) mx[hf] = fmaxf(mx[hf], __shfl_xor_sync(0xffffffffu, mx[hf], o));
#pragma unroll
    for (int hf = 0; hf < 2; hf++) {
        sum[hf] = 0;
#pragma unroll
        for (int q = 0; q < 2 * NK; q++) { asm("ex2.approx.ftz.f32 %0, %1;" : "=f"(v[hf][q]) : "f"((v[hf][q] - mx[hf]) * l2e)); sum[hf] += v[hf][q]; }
    }
#pragma unroll
    for (int o = 1; o < 4; o <<= 1)
#pragma unroll
        for (int hf = 0; hf < 2; hf++) sum[hf] += __shfl_xor_sync(0xffffffffu, sum[hf], o);
    uint32_t pa[NK][2];
#pragma unroll
    for (int hf = 0; hf < 2; hf++) {
        const float inv = __fdividef(1.f, sum[hf]);
#pragma unroll
        for (int n = 0; n < NK; n++) pa[n][hf] = pack2(v[hf][2 * n] * inv, v[hf][2 * n + 1] * inv);
    }
    mbar_wait(eempty, eph);
#pragma unroll AUNR
    for (int n4 = 0; n4 < 6; n4++) {
        const uint32_t cb = (n4 >> 1) * 4096, c0 = (n4 & 1) * 4;
        uint32_t bm[4], bb[2 + 2 * MT][4];
        ldsm4t(bm, base + AT_VM + n4 * 512 + lane * 16);
#pragma unroll
        for (int u = 0; u < 2 + 2 * MT; u++) ldsm4t(bb[u], base + AT_V + cb + (16 * (u >> 1) + 8 * (mi & 1) + r) * 128 + (((c0 + 2 * (u & 1) + (mi >> 1)) ^ r) << 4));
        float o[4][4];
#pragma unroll
        for (int u = 0; u < 4; u++) { o[u][0] = o[u][1] = o[u][2] = o[u][3] = 0.f; mma8(o[u], pa[NK - 1][0], pa[NK - 1][1], bm[u]); }
#pragma unroll
        for (int u = 0; u < 4 + 4 * MT; u++) mma16(o[u & 3], pa[u >> 2 << 1][0], pa[u >> 2 << 1][1], pa[(u >> 2 << 1) + 1][0], pa[(u >> 2 << 1) + 1][1], bb[u >> 1][2 * (u & 1)], bb[u >> 1][2 * (u & 1) + 1]);
#pragma unroll
        for (int p = 0; p < 2; p++)
            stsm4(dst + (n4 >> 1) * 2048 + ((mi & 1) * 8 + r) * 128 + (((c0 + 2 * p + (mi >> 1)) ^ r) << 4), pack2(o[2 * p][0], o[2 * p][1]), pack2(o[2 * p][2], o[2 * p][3]),
                  pack2(o[2 * p + 1][0], o[2 * p + 1][1]), pack2(o[2 * p + 1][2], o[2 * p + 1][3]));
    }
}

__device__ __forceinline__ uint32_t ln_row(const uint32_t (&as)[10], const uint2 (&xin)[5], int row, uint32_t par, uint32_t low, bf16* out, uint64_t ef, int lane) {
    const uint32_t pa = par + lane * 8;
    uint32_t xv[10], hv[10], sv[10], tv[10];
#pragma unroll
    for (int q = 0; q < 5; q++) {
        uint32_t ga[2], t[2], u[2];
        lds64(ga, pa + q * 256); lds64(t, pa + 1280 + q * 256); lds64(u, pa + 2560 + q * 256);
#pragma unroll
        for (int e = 0; e < 2; e++) {
            xv[2 * q + e] = add2(e ? xin[q].y : xin[q].x, mul2(ga[e], as[2 * q + e]));
            tv[2 * q + e] = t[e]; sv[2 * q + e] = u[e];
        }
    }
    ln_mod(xv, sv, tv, hv);
    float rs = 0;
#pragma unroll
    for (int q = 0; q < 5; q++) {
        const int c = row * DM + lane * 4 + q * 128;
        const uint32_t h0 = hv[2 * q], h1 = hv[2 * q + 1];
        uint32_t gb[2], wv[2];
        lds64(gb, pa + 3840 + q * 256); lds64(wv, pa + 5120 + q * 256);
        rs += (lo_f(h0) * lo_f(wv[0]) + hi_f(h0) * hi_f(wv[0])) + (lo_f(h1) * lo_f(wv[1]) + hi_f(h1) * hi_f(wv[1]));
        st_ef(out + c, make_uint2(add2(xv[2 * q], mul2(gb[0], h0)), add2(xv[2 * q + 1], mul2(gb[1], h1))), ef);
    }
    const uint32_t rb = pack2(0.f, warp_sum(rs));
    const uint32_t key = (((int)rb < 0 ? ~rb : rb | 0x80000000u) & 0xffff0000u) | (uint32_t)(2 * S_TOK - 1 - row);
    if (key > low) {
#pragma unroll
        for (int q = 0; q < 5; q++) {
            *(uint2*)(g_x1 + row * DM + lane * 4 + q * 128) = make_uint2(xv[2 * q], xv[2 * q + 1]);
            *(uint2*)(g_h2 + row * DM + lane * 4 + q * 128) = make_uint2(hv[2 * q], hv[2 * q + 1]);
        }
    }
    return key;
}
__device__ __forceinline__ void key_out(uint32_t key) {
    __syncwarp();
    if (key) asm volatile("st.release.gpu.global.u32 [%0], %1;" :: "l"(g_key + (~key & (S_TOK - 1))), "r"(key) : "memory");
}

__global__ void __launch_bounds__(384, 1) k_side(const __grid_constant__ SideMaps mp, const bf16* __restrict__ x, const bf16* __restrict__ wr, const bf16* wmod, const bf16* cvec, bf16* __restrict__ out) {
    extern __shared__ __align__(1024) uint8_t smraw[];
    const uint32_t sm = smem_u32(smraw);
    if (sm & 1023) __trap();
    const uint32_t BARS = sm + SD_BAR, FULL = BARS + 768, EMPTY = FULL + 96, EFULL = BARS + 64, EEMPTY = BARS + 80, IFULL = BARS + 96, IEMPTY = BARS + 128, IQ = BARS + 160, SCHED = BARS + 176, PARAM = BARS + 184, ADONE = BARS + 192, LOW = BARS + 224, KEYS = BARS + 256;
    const int tid = threadIdx.x, warp = __shfl_sync(0xffffffffu, tid >> 5, 0), lane = tid & 31;
    const uint64_t ef = policy_stream();
    if (tid == 0) {
#pragma unroll 1
        for (int i = 0; i < SD_NST; i++) { mbar_init(FULL + 8 * i, 1); mbar_init(EMPTY + 8 * i, 2); }
        for (int i = 0; i < 2; i++) { mbar_init(EFULL + 8 * i, 4); mbar_init(EEMPTY + 8 * i, 1); }
        for (int i = 0; i < 4; i++) { mbar_init(IFULL + 8 * i, 1); mbar_init(IEMPTY + 8 * i, 11); }
        mbar_init(SCHED, 1); mbar_init(PARAM, 1);
        sts128f(ADONE, 0, 0, 0, 0); sts128f(ADONE + 16, 0, 0, 0, 0); sts128f(LOW, 0, 0, 0, 0);
        asm volatile("fence.mbarrier_init.release.cluster;" ::: "memory");
    }
    if (SDEL) __nanosleep(SDEL);
    __syncthreads();
    if (warp >= 8) {
      asm volatile("setmaxnreg.dec.sync.aligned.u32 40;");
      if (warp == 8) {
        int st = 0, ph = 1;
        for (int q = 0;; q++) {
            mbar_wait(IFULL + 8 * (q & 3), (q >> 2) & 1);
            const int it = __shfl_sync(0xffffffffu, lds32(IQ + 4 * (q & 3)), 0);
            if (elect()) mbar_arrive(IEMPTY + 8 * (q & 3));
            if (it < 0) break;
            const int kind = it >> 16, b = (it >> 8) & 255, i = it & 63;
            const int nst = kind == 0 ? 10 : kind == 1 ? 4 : kind == 2 ? 192 >> o_shift(b) : b == 14 ? 4 : 2;
            const int ksched = kind == 0 ? 4 : kind == 2 ? nst - KSO : (it & 128) ? -1 : kind == 1 ? KSA : 0;
            if (ksched < 0 && elect()) mbar_arrive(SCHED);
            const bool look = !(it & 128);
            const int nu = kind == 2 ? 2 : 3;
            if (look && kind == 1) flag_wait(&g_flags.v[b * 32 + i], 2);
            if (look && kind == 3 && b < 14) flag_wait(&g_flags.o[b], o_done(b));
            for (int kb = 0; kb < nst; kb++) {
                if (kb < 6) mbar_wait(EMPTY + 8 * st, ph);
                mbar_wait(EMPTY + 8 * (st + nu - 1), ph);
                const uint32_t base = sm + st * SD_ST, fb = FULL + 8 * st;
                if (lane && lane < nu) mbar_arrive(fb + 8 * lane);
                if (look && kind == 1) flag_wait(&g_flags.seg[max(kb, 1) * 32 + i], 3);
                if (kb == ksched && elect()) mbar_arrive(SCHED);
                if (kind == 0) {
                    if (q == 0 && kb == 0) {
                        if (elect()) {
#pragma unroll 1
                            for (int c = 0; c < 4; c++) tma3d(sm + 3 * c * SD_ST + 16384, &mp.wv, c * 64, i * 3, FULL + 24 * c);
                        }
                        flag_wait(&g_flags.h, 96);
                    }
                    if (elect()) {
                        mbar_expect(fb, 40960);
                        tma2d(base, &mp.h, kb * 64, b * 128, fb);
                        if (q || kb >= 4) tma3d(base + 16384, &mp.wv, kb * 64, i * 3, fb);
                    }
                } else if (kind == 1) {
                    if (elect()) {
                        mbar_expect(fb, 43008);
                        asm volatile("cp.async.bulk.shared::cluster.global.mbarrier::complete_tx::bytes.L2::cache_hint [%0], [%1], %2, [%3], %4;"
                            :: "r"(base), "l"(g_att + ((b * 4 + kb) * NH + i) * AT_REC), "r"(AT_REC), "r"(fb), "l"(ef) : "memory");
                    }
                } else if (kind == 3) {
                    if (b == 14 && !(kb & 1)) flag_wait(&g_flags.fin[(kb + (i >> 4)) * 32], 80);
                    if (elect()) { mbar_expect(fb, 40960); tma3d_ef(base, &mp.lnp[o_shift(b) - 2], i * (160 >> o_shift(b)), b * KSPLIT + (kb << o_shift(b) >> 1), fb, ef); }
                } else {
                    const int k0 = ((i >> 1) * nst + kb) * 32;
                    if (elect()) { mbar_expect(fb, 28672); tma3d(base + 8192, &mp.wo, k0, (i & 1) * 5, fb); }
                    if (look && kb % 12 == 0) flag_wait(&g_flags.pair[b * 16 + k0 / 384], 4);
                    if (elect()) tma2d_ef(base, &mp.o, k0, b * 128, fb, ef);
                }
                __syncwarp();
                st += nu; if (st == SD_NST) { st = 0; ph ^= 1; }
            }
        }
      } else if (warp == 11) {
        bool fin = false, par = false;
        for (int q = 0;; q++) {
            if (q) mbar_wait(SCHED, (q - 1) & 1);
            int it = fin ? -1 : q == 0 && blockIdx.x < 32 ? (int)blockIdx.x : next_item(lane);
            if (it < 0 && !fin && blockIdx.x < 32) { it = 3 << 16 | 14 << 8 | blockIdx.x; fin = true; }
            if (lane == 0) {
                if (it >> 16 == 3) {
                    const int b = (it >> 8) & 255, nr = 64 >> o_shift(b);
                    asm volatile("cp.async.bulk.prefetch.L2.global [%0], %1;" :: "l"(x + (b * 128 + (it & 63) * nr) * DM), "r"(nr * DM * 2) : "memory");
                }
                mbar_wait(IEMPTY + 8 * (q & 3), ((q >> 2) & 1) ^ 1);
                asm volatile("st.shared.u32 [%0], %1;" :: "r"(IQ + 4 * (q & 3)), "r"(it) : "memory");
                mbar_arrive(IFULL + 8 * (q & 3));
            }
            if (it >> 16 >= 2 && (it >> 8 & 255) >= 2) {
                const uint4* kp = (const uint4*)g_key + max((it >> 8 & 255) - ((it >> 16) == 2 ? 5 : 3), 0) * 32 + lane;
                const uint4 k1 = __ldcg(kp), k2 = __ldcg(kp + 32);
                uint32_t m = max(max(max(k1.x, k1.y), max(k1.z, k1.w)), max(max(k2.x, k2.y), max(k2.z, k2.w)));
                m = max(m, __shfl_xor_sync(0xffffffffu, m, 1)); m = max(m, __shfl_xor_sync(0xffffffffu, m, 2));
                asm volatile("red.shared.max.u32 [%0], %1;" :: "r"(LOW), "r"(__reduce_min_sync(0xffffffffu, m)) : "memory");
            }
            if (!par && it >> 16 == 3) {
                par = true;
                flag_wait(&g_flags.mod, 64);
                if (lane == 0) { mbar_expect(PARAM, 6400); bulk_g2s(sm + SD_PAR, g_mod + 2 * DM, 5120, PARAM); bulk_g2s(sm + SD_PAR + 5120, wr, 1280, PARAM); }
            }
            __syncwarp();
            if (it < 0) break;
        }
        flags_release(lane);
      } else {
        if (lane == 0) {
            const int wg = warp - 9; int ph = 0;
            for (int q = 0;; q++) {
                mbar_wait(IFULL + 8 * (q & 3), (q >> 2) & 1);
                const int it = lds32(IQ + 4 * (q & 3));
                mbar_arrive(IEMPTY + 8 * (q & 3));
                if (it < 0) break;
                const int kind = it >> 16, b = (it >> 8) & 255, i = it & 63;
                if (kind == 3 && b == 14) continue;
                if (kind & 1) {
                    for (int n = 0;; n++) {
                        uint32_t d0, d1, d2, d3;
                        asm volatile("ld.volatile.shared.v4.u32 {%0,%1,%2,%3}, [%4];" : "=r"(d0), "=r"(d1), "=r"(d2), "=r"(d3) : "r"(ADONE + wg * 16) : "memory");
                        if (min(min(d0, d1), min(d2, d3)) > q) break;
                        if (n > (1 << 24)) __trap();
                        __nanosleep(40);
                    }
                    GPU_FENCE();
                    EPT(kind == 1 && b == 15 && wg, 17);
                    if (kind == 1) { bump(b == 15 ? &g_flags.half[(i & 30) + wg] : &g_flags.pair[b * 16 + (i >> 1)]); bump(&g_flags.at[b]); }
                    else {
#pragma unroll 1
                        for (int c = 0; c < 8; c++) { const uint32_t key = lds32(KEYS + (q & 7) * 64 + wg * 32 + c * 4); if (key) asm volatile("st.relaxed.gpu.global.u32 [%0], %1;" :: "l"(g_key + (~key & (S_TOK - 1))), "r"(key) : "memory"); }
                    }
                    continue;
                }
#pragma unroll 1
                for (int rd = 0; rd < (kind == 2 ? 2 : 1); rd++) {
                    mbar_wait(EFULL + 8 * wg, ph); ph ^= 1;
                    const uint32_t src = sm + SD_EPI + wg * 24576;
                    if (kind == 2) tma3d_store(rd ? &mp.slab3 : &mp.slab2, (b * KSPLIT + (i >> 1)) * 128 + wg * 64, (i & 1) * 5 + (rd ? 0 : 3), src, ef, false);
                    else {
                        uint8_t* dst = g_att + ((b * 4 + wg * 2) * NH + i) * AT_REC + AT_V;
                        asm volatile("cp.async.bulk.global.shared::cta.bulk_group.L2::cache_hint [%0], [%1], 12288, %2;" :: "l"(dst), "r"(src), "l"(ef) : "memory");
                        asm volatile("cp.async.bulk.global.shared::cta.bulk_group.L2::cache_hint [%0], [%1], 12288, %2;" :: "l"(dst + NH * AT_REC), "r"(src + 12288), "l"(ef) : "memory");
                    }
                    asm volatile("cp.async.bulk.commit_group;" ::: "memory");
                    asm volatile("cp.async.bulk.wait_group.read 0;" ::: "memory");
                    mbar_arrive(EEMPTY + 8 * wg);
                }
                asm volatile("cp.async.bulk.wait_group 0;" ::: "memory");
                GPU_FENCE();
                bump(kind == 0 ? &g_flags.v[b * 32 + i] : &g_flags.o[b]);
                if (kind == 0) bump(&g_flags.vb[b]);
            }
        }
      }
    } else {
        asm volatile("setmaxnreg.inc.sync.aligned.u32 232;");
        const int wg = warp >> 2, w = warp & 3;
        int st = 0, ph = 0, eph = 1;
        bool att = false;
        uint4 mz[4] = {}; uint2 mc = {}; float ma[8] = {0, 0, 0, 0, 0, 0, 0, 0};
        const uint32_t eb = sm + SD_EPI + wg * 24576;
        for (int q = 0;; q++) {
            mbar_wait(IFULL + 8 * (q & 3), (q >> 2) & 1);
            const int itc = __shfl_sync(0xffffffffu, lds32(IQ + 4 * (q & 3)), 0);
            __syncwarp();
            if (lane == 0) mbar_arrive(IEMPTY + 8 * (q & 3));
            if (itc < 0) break;
            const int kind = itc >> 16, b = (itc >> 8) & 255, i = itc & 63;
            if (q >= 1 && q <= 9 && blockIdx.x < 32) {
                const int t = min(tid, 199), k = t / 10 * 32 + (q - 1) * 4;
#pragma unroll
                for (int e = 0; e < 4; e++) {
                    const uint32_t cw = e & 2 ? mc.y : mc.x;
                    const float c = e & 1 ? hi_f(cw) : lo_f(cw), f = bfr(__fdividef(c, 1.f + __expf(-c)));
                    ma[0] += f * lo_f(mz[e].x); ma[1] += f * hi_f(mz[e].x); ma[2] += f * lo_f(mz[e].y); ma[3] += f * hi_f(mz[e].y);
                    ma[4] += f * lo_f(mz[e].z); ma[5] += f * hi_f(mz[e].z); ma[6] += f * lo_f(mz[e].w); ma[7] += f * hi_f(mz[e].w);
                }
                if (q < 9) {
#pragma unroll
                    for (int e = 0; e < 4; e++) mz[e] = __ldcs((const uint4*)(wmod + (k + e) * (6 * DM) + 2 * DM + blockIdx.x * 80 + t % 10 * 8));
                    mc = __ldg((const uint2*)(cvec + k));
                } else {
                    sts128f(sm + SD_PAR + t * 32, ma[0], ma[1], ma[2], ma[3]); sts128f(sm + SD_PAR + 16 + t * 32, ma[4], ma[5], ma[6], ma[7]);
                    bar_sync(1, 256);
                    if (tid < 40) {
                        float a0 = 0, a1 = 0;
#pragma unroll 4
                        for (int g = 0; g < 20; g++) { const float2 v = lds64f(sm + SD_PAR + g * 320 + tid * 8); a0 += v.x; a1 += v.y; }
                        ((uint32_t*)(g_mod + 2 * DM + blockIdx.x * 80))[tid] = pack2(a0, a1);
                    }
                    __syncwarp();
                    if (warp < 2 && lane == 0) flag_add(&g_flags.mod);
                }
            }
            if (att && kind != 1) { bar_sync(1, 256); att = false; }
            int prev = -1;
            auto next = [&](int nu) {
                WG_COMMIT();
                WG_WAIT(1);
                if (prev >= 0 && (tid & 127) < nu) mbar_arrive(EMPTY + 8 * (prev + (tid & 127)));
                prev = st;
                st += nu; if (st == SD_NST) { st = 0; ph ^= 1; }
            };
            auto desc = [](uint32_t lo, uint32_t hi) { return (uint64_t)hi << 32 | lo; };
            if (kind == 0) {
                float acc[96];
#pragma unroll
                for (int n = 0; n < 96; n++) acc[n] = 0.f;
#pragma unroll 1
                for (int kb = 0; kb < 10; kb++) {
                    mbar_wait(FULL + 8 * st, ph);
                    const uint32_t d0 = (sm + st * SD_ST) >> 4, da = d0 + wg * 512 + 0x10000, db = d0 + 1024 + 0x2000000;
                    WG_FENCE();
#pragma unroll
                    for (int ks = 0; ks < 4; ks++) wgmma_ss_n192_tb(acc, desc(da + ks * 2, 0x40000040), desc(db + ks * 128, 0x40000040), 1);
                    next(3);
                }
                WG_WAIT(0);
                if ((tid & 127) < 3) mbar_arrive(EMPTY + 8 * (prev + (tid & 127)));
                tile_out<12>(acc, eb + (w >> 1) * 12288 + (w & 1) * 2048, 4096, EFULL + 8 * wg, EEMPTY + 8 * wg, eph, lane);
            } else if (kind == 2) {
                float acc[96], acc2[64];
#pragma unroll
                for (int n = 0; n < 96; n++) acc[n] = 0.f;
#pragma unroll
                for (int n = 0; n < 64; n++) acc2[n] = 0.f;
                int kb = 192 >> o_shift(b);
#pragma unroll 1
                do {
                    mbar_wait(FULL + 8 * st, ph);
                    const uint32_t d0 = (sm + st * SD_ST) >> 4, da = d0 + wg * 256 + 0x10000, db = d0 + 512 + 0x1000000;
                    WG_FENCE();
#pragma unroll
                    for (int ks = 0; ks < 2; ks++) {
                        wgmma_ss_n192_tb(acc, desc(da + ks * 2, 0x80000020), desc(db + ks * 128, 0x40000040), 1);
                        wgmma_ss_n128_tb(acc2, desc(da + ks * 2, 0x80000020), desc(db + 768 + ks * 128, 0x40000040), 1);
                    }
                    next(2);
                } while (--kb);
                WG_WAIT(0);
                if ((tid & 127) < 2) mbar_arrive(EMPTY + 8 * (prev + (tid & 127)));
                tile_out<8>(acc2, eb + w * 2048, 8192, EFULL + 8 * wg, EEMPTY + 8 * wg, eph, lane);
                tile_out<12>(acc, eb + w * 2048, 8192, EFULL + 8 * wg, EEMPTY + 8 * wg, eph, lane);
            } else if (kind == 1) {
                const int seg = warp >> 1, mt = warp & 1;
                int sst = st + 3 * seg, sph = ph; if (sst >= SD_NST) { sst -= SD_NST; sph ^= 1; }
                ph ^= 1;
                mbar_wait(FULL + 8 * sst, sph);
                EPT(tid == 224 && b == 15, 16);
                const uint32_t base = sm + sst * SD_ST;
                if (mt) attn_tile<1>(base, eb + w * 6144, EEMPTY + 8 * wg, eph, lane);
                else attn_tile<0>(base, eb + w * 6144, EEMPTY + 8 * wg, eph, lane);
                asm volatile("fence.proxy.async.shared::cta;" ::: "memory");
                __syncwarp();
                if (lane < 3) mbar_arrive(EMPTY + 8 * (sst + lane));
                if (lane == 0) {
                    tma3d_store(&mp.ost, b * 128 + warp * 16, i * 3, eb + w * 6144, ef, false);
                    BULK_COMMIT(); BULK_WAIT();
                    asm volatile("st.release.cta.shared.u32 [%0], %1;" :: "r"(ADONE + warp * 4), "r"(q + 1) : "memory");
                }
                __syncwarp();
                att = true;
            } else {
                const int sh = o_shift(b), nr = 64 >> sh, fw = b == 14 ? wg : 0, row0 = (b + fw) * 128 + i * nr, lw = warp - 4 * fw;
                if (fw) { ph ^= st != 0; st ^= 6; }
                uint2 xin[2][5];
                uint32_t as[2][10] = {};
#pragma unroll
                for (int q2 = 0; q2 < 10; q2++) xin[q2 & 1][q2 >> 1] = ld_ef(x + (row0 + ((warp + 8 * (q2 & 1)) & (nr - 1))) * DM + lane * 4 + (q2 >> 1) * 128, ef);
                mbar_wait(PARAM, 0); mbar_wait(FULL + 8 * st, ph); mbar_wait(FULL + 8 * st + 24, ph);
                EPT((tid & 127) == 0 && b == 14, 18 + wg);
#pragma unroll 1
                for (int lrow = lw + (nr & 16) / 2; lrow >= 0 && lrow < nr; lrow -= 8) {
                    float a[20];
#pragma unroll
                    for (int q2 = 0; q2 < 20; q2++) a[q2] = 0.f;
#pragma unroll 1
                    for (int k = 0; k < (1 << sh >> 1); k++) {
                        const uint32_t ad = sm + st * SD_ST + ((k << (6 - sh)) + lrow) * 1280 + lane * 8;
                        uint32_t z[10][2];
#pragma unroll
                        for (int q2 = 0; q2 < 10; q2++) lds64(z[q2], ad + (q2 < 5 ? 0 : 3 * SD_ST) + q2 % 5 * 256);
#pragma unroll
                        for (int q2 = 0; q2 < 10; q2++) { float* p = a + q2 % 5 * 4; p[0] += lo_f(z[q2][0]); p[1] += hi_f(z[q2][0]); p[2] += lo_f(z[q2][1]); p[3] += hi_f(z[q2][1]); }
                    }
#pragma unroll
                    for (int q2 = 0; q2 < 10; q2++) { as[1][q2] = as[0][q2]; as[0][q2] = pack2(a[2 * q2], a[2 * q2 + 1]); }
                }
                bar_sync(2 + wg, 128);
                if ((tid & 127) < 6) mbar_arrive(EMPTY + 8 * (st + (tid & 127)));
                uint32_t key = 0;
#pragma unroll 1
                for (int lrow = lw; lrow < nr; lrow += 8) {
                    const int row = row0 + lrow;
                    const uint32_t k1 = ln_row(as[0], xin[0], row, sm + SD_PAR, lds32(LOW), out, ef, lane);
                    if (lane == lrow >> 3) key = k1;
#pragma unroll
                    for (int q2 = 0; q2 < 5; q2++) { as[0][2 * q2] = as[1][2 * q2]; as[0][2 * q2 + 1] = as[1][2 * q2 + 1]; xin[0][q2] = xin[1][q2]; }
                }
                if (b == 14) { EPT(tid == 128, 20); key_out(key); EPT(tid == 128, 21); }
                else {
                    if (lane < 2) asm volatile("st.shared.u32 [%0], %1;" :: "r"(KEYS + (q & 7) * 64 + warp * 8 + lane * 4), "r"(key) : "memory");
                    __syncwarp();
                    if (lane == 0) asm volatile("st.release.cta.shared.u32 [%0], %1;" :: "r"(ADONE + warp * 4), "r"(q + 1) : "memory");
                }
                ph ^= st != 0; st ^= 6;
            }
        }
    }
    __syncwarp();
    asm volatile("griddepcontrol.wait;" ::: "memory");
}

#define P_D1 550
#define P_DL 700
#define P_DG 29
typedef CUresult (*EncodeFn)(CUtensorMap*, CUtensorMapDataType, cuuint32_t, void*, const cuuint64_t*, const cuuint64_t*, const cuuint32_t*, const cuuint32_t*,
                             CUtensorMapInterleave, CUtensorMapSwizzle, CUtensorMapL2promotion, CUtensorMapFloatOOBfill);
static EncodeFn s_encode = nullptr;
static void make_map(CUtensorMap* m, const void* p, int rows, int cols, int box_rows, int box_cols = 64) {
    cuuint64_t dims[2] = {(cuuint64_t)cols, (cuuint64_t)rows}, strides[1] = {(cuuint64_t)cols * 2};
    cuuint32_t box[2] = {(cuuint32_t)box_cols, (cuuint32_t)box_rows}, es[2] = {1, 1};
    s_encode(m, CU_TENSOR_MAP_DATA_TYPE_BFLOAT16, 2, (void*)p, dims, strides, box, es, CU_TENSOR_MAP_INTERLEAVE_NONE,
             box_cols == 64 ? CU_TENSOR_MAP_SWIZZLE_128B : box_cols == 32 ? CU_TENSOR_MAP_SWIZZLE_64B : CU_TENSOR_MAP_SWIZZLE_NONE, CU_TENSOR_MAP_L2_PROMOTION_L2_256B, CU_TENSOR_MAP_FLOAT_OOB_FILL_NONE);
}
static void make_map3(CUtensorMap* m, const void* p, int rows, int cols, int box_rows, int box_chunks, int cw = 64) {
    cuuint64_t dims[3] = {(cuuint64_t)cw, (cuuint64_t)rows, (cuuint64_t)(cols / cw)}, strides[2] = {(cuuint64_t)cols * 2, (cuuint64_t)cw * 2};
    cuuint32_t box[3] = {(cuuint32_t)cw, (cuuint32_t)box_rows, (cuuint32_t)box_chunks}, es[3] = {1, 1, 1};
    s_encode(m, CU_TENSOR_MAP_DATA_TYPE_BFLOAT16, 3, (void*)p, dims, strides, box, es, CU_TENSOR_MAP_INTERLEAVE_NONE,
             cw == 64 ? CU_TENSOR_MAP_SWIZZLE_128B : CU_TENSOR_MAP_SWIZZLE_64B, CU_TENSOR_MAP_L2_PROMOTION_L2_256B, CU_TENSOR_MAP_FLOAT_OOB_FILL_NONE);
}
template <typename T> static void* sym(T& s) { void* p = nullptr; cudaGetSymbolAddress(&p, s); return p; }

extern "C" void kernel_launch(void* const* d_in, const int* in_sizes, int n_in, void* d_out, int out_size) {
    const bf16 *x = (const bf16*)d_in[0], *mem0 = (const bf16*)d_in[1], *Wq = (const bf16*)d_in[2], *Wk = (const bf16*)d_in[3],
               *Wv = (const bf16*)d_in[4], *Wo = (const bf16*)d_in[5], *wr = (const bf16*)d_in[8], *wgate = (const bf16*)d_in[9],
               *wup = (const bf16*)d_in[10], *wdown = (const bf16*)d_in[11], *c = (const bf16*)d_in[12], *wmod = (const bf16*)d_in[13];
    bf16* out = (bf16*)d_out;
    if (!s_encode) {
        cudaDriverEntryPointQueryResult qr;
        cudaGetDriverEntryPoint("cuTensorMapEncodeTiled", (void**)&s_encode, cudaEnableDefault, &qr);
        cudaFuncSetAttribute(k_side, cudaFuncAttributeMaxDynamicSharedMemorySize, SD_SMEM);
        cudaFuncSetAttribute(k_chain, cudaFuncAttributeMaxDynamicSharedMemorySize, C_SMEM);
    }
    ChainMaps cm; SideMaps sd;
    make_map(&sd.h, sym(g_h), S_TOK, DM, 128); make_map3(&sd.wv, Wv, DM, HD, 64, 3);
    make_map3(&sd.ost, sym(g_o), S_TOK, HD, 16, 3); make_map(&sd.o, sym(g_o), S_TOK, HD, 128, 32); make_map3(&sd.wo, Wo, HD, DM, 32, 5);
    make_map3(&sd.slab3, sym(g_slab), 16 * KSPLIT * 128, DM, 64, 3); make_map3(&sd.slab2, sym(g_slab), 16 * KSPLIT * 128, DM, 64, 2);
    make_map3(&cm.wo15, Wo, HD, DM, 192, 2); make_map3(&cm.o15, sym(g_o), S_TOK, HD, 64, 2); cm.slab2 = sd.slab2;
    for (int i = 0; i < 3; i++) {
        cuuint64_t dims[3] = {256, 320, 16 * KSPLIT}, strides[2] = {512, 128 * DM * 2};
        cuuint32_t box[3] = {256, 40u >> i, 2u << i}, es[3] = {1, 1, 1};
        s_encode(&sd.lnp[i], CU_TENSOR_MAP_DATA_TYPE_BFLOAT16, 3, sym(g_slab), dims, strides, box, es, CU_TENSOR_MAP_INTERLEAVE_NONE,
                 CU_TENSOR_MAP_SWIZZLE_NONE, CU_TENSOR_MAP_L2_PROMOTION_L2_256B, CU_TENSOR_MAP_FLOAT_OOB_FILL_NONE);
    }
    make_map(&cm.wq, Wq, DM, HD, 640 / WP); make_map(&cm.wk, Wk, DM, HD, 640 / WP); make_map(&cm.wv, Wv, DM, HD, 160); make_map3(&cm.wo, Wo, HD, DM, 64, 7, 32);
    make_map3(&cm.h2, sym(g_h), S_TOK, DM, 32, 2);
    ChainArgs ar = {x, mem0, c, wmod, Wv, Wo, wgate, wup, wdown, out, P_D1, P_DL, P_DG};
    k_chain<<<96, 384, C_SMEM>>>(cm, ar);
    cudaLaunchConfig_t cfg = {};
    cfg.gridDim = dim3(N_SIDE); cfg.blockDim = dim3(384); cfg.dynamicSmemBytes = SD_SMEM; cfg.stream = cudaStreamPerThread;
    cudaLaunchAttribute at[1]; at[0].id = cudaLaunchAttributeProgrammaticStreamSerialization; at[0].val.programmaticStreamSerializationAllowed = 1;
    cfg.attrs = at; cfg.numAttrs = 1;
    cudaLaunchKernelEx(&cfg, k_side, sd, x, wr, wmod, c, out);
}
```

```cpp
#include <cuda_runtime.h>
#include <cuda_bf16.h>
#include <cuda.h>
#include <stdint.h>
#include <stdio.h>
#include <string.h>
#include <stdlib.h>

typedef __nv_bfloat16 bf16;
constexpr int S_TOK = 2048, DM = 640, NH = 32, DH = 192, HD = NH * DH, NSEG = 64, SEG = 32, FF = 1536;

__device__ bf16 g_mod[6 * DM];
__device__ bf16 g_h[S_TOK * DM];
constexpr int AT_REC = 43008, AT_V = 24576, AT_KM = 36864, AT_VM = 39936;
__device__ __align__(1024) uint8_t g_att[NSEG * NH * AT_REC];
__device__ bf16 g_o[S_TOK * HD];
__device__ bf16 g_A[S_TOK * DM];
__device__ bf16 g_x1[S_TOK * DM];
__device__ bf16 g_h2[S_TOK * DM];
__device__ __align__(128) uint32_t g_key[S_TOK];
__device__ int g_idx[8];
__device__ __align__(128) uint32_t g_gu[FF / 8 * 32];
constexpr int ACC_PAIR = 24 * 1024;
__device__ __align__(1024) uint8_t g_acc[2 * ACC_PAIR];
__device__ __align__(1024) uint32_t g_stamp[4 * 12 * 32];
constexpr int KSPLIT = 16;
__device__ bf16 g_slab[16 * KSPLIT * 128 * DM];
struct __align__(128) Flags {
    uint32_t qk[16], vb[16];
    uint32_t at[16], o[16];
    uint32_t c[4][16];
    uint32_t half[32];
    uint32_t fin[4 * 32];
    uint32_t v[16 * 32];
    uint32_t seg[4 * 32];
    uint32_t pair[16 * 16];
    uint32_t h, pad2[31], done, mod, pad3[30];
    uint32_t mod1[DM];
    uint32_t wmax[96];
};
__device__ Flags g_flags;
#define EPT(c, i)

__device__ __forceinline__ uint32_t smem_u32(const void* p) { return (uint32_t)__cvta_generic_to_shared(p); }
__device__ __forceinline__ uint32_t pack2(float lo, float hi) {
    uint32_t r; asm("cvt.rn.bf16x2.f32 %0, %1, %2;" : "=r"(r) : "f"(hi), "f"(lo)); return r;
}
__device__ __forceinline__ float bfr(float x) { return __uint_as_float(pack2(0.f, x)); }
__device__ __forceinline__ float inv_std(float var) {
    float s, r; asm("sqrt.approx.f32 %0, %1;" : "=f"(s) : "f"(bfr(bfr(var) + 1e-5f))); asm("rcp.approx.f32 %0, %1;" : "=f"(r) : "f"(bfr(s))); return r;
}
__device__ __forceinline__ float lo_f(uint32_t v) { return __uint_as_float(v << 16); }
__device__ __forceinline__ float hi_f(uint32_t v) { return __uint_as_float(v & 0xffff0000u); }
__device__ __forceinline__ void mbar_init(uint32_t bar, int cnt) { asm volatile("mbarrier.init.shared::cta.b64 [%0], %1;" :: "r"(bar), "r"(cnt) : "memory"); }
__device__ __forceinline__ void mbar_expect(uint32_t bar, int bytes) { asm volatile("mbarrier.arrive.expect_tx.shared::cta.b64 _, [%0], %1;" :: "r"(bar), "r"(bytes) : "memory"); }
__device__ __forceinline__ void mbar_arrive(uint32_t bar) { asm volatile("mbarrier.arrive.shared::cta.b64 _, [%0];" :: "r"(bar) : "memory"); }
__device__ __forceinline__ bool mbar_try(uint32_t bar, int par) {
    uint32_t ok; asm volatile("{ .reg .pred p; mbarrier.try_wait.parity.shared::cta.b64 p, [%1], %2; selp.u32 %0, 1, 0, p; }" : "=r"(ok) : "r"(bar), "r"(par) : "memory"); return ok;
}
__device__ __forceinline__ bool mbar_try_cluster(uint32_t bar, int par) {
    uint32_t ok; asm volatile("{ .reg .pred p; mbarrier.try_wait.parity.acquire.cluster.shared::cta.b64 p, [%1], %2; selp.u32 %0, 1, 0, p; }" : "=r"(ok) : "r"(bar), "r"(par) : "memory"); return ok;
}
__device__ __forceinline__ bool mbar_test(uint32_t bar, uint32_t par) {
    uint32_t ok; asm volatile("{ .reg .pred p; mbarrier.test_wait.parity.shared::cta.b64 p, [%1], %2; selp.u32 %0, 1, 0, p; }" : "=r"(ok) : "r"(bar), "r"(par) : "memory"); return ok;
}
constexpr int SPIN_LIMIT = 1 << 18;
__device__ __forceinline__ void mbar_wait(uint32_t bar, uint32_t par) {
    asm volatile("{ .reg .pred p, q; .reg .u32 n; mov.u32 n, 0;\n"
                 "W_%=: mbarrier.try_wait.parity.shared::cta.b64 p, [%0], %1;\n"
                 "@p bra.uni D_%=;\n"
                 "add.u32 n, n, 1; setp.lt.u32 q, n, 0x200000; @q bra.uni W_%=;\n"
                 "trap;\n"
                 "D_%=: }" :: "r"(bar), "r"(par) : "memory");
}
__device__ __forceinline__ void tma2d(uint32_t dst, const CUtensorMap* m, int c0, int c1, uint32_t bar) {
    asm volatile("cp.async.bulk.tensor.2d.shared::cluster.global.mbarrier::complete_tx::bytes [%0], [%1, {%3, %4}], [%2];"
        :: "r"(dst), "l"((uint64_t)m), "r"(bar), "r"(c0), "r"(c1) : "memory");
}
__device__ __forceinline__ void tma2d_mc(uint32_t dst, const CUtensorMap* m, int c0, int c1, uint32_t bar, uint16_t mask) {
    asm volatile("cp.async.bulk.tensor.2d.shared::cluster.global.mbarrier::complete_tx::bytes.multicast::cluster [%0], [%1, {%3, %4}], [%2], %5;"
        :: "r"(dst), "l"((uint64_t)m), "r"(bar), "r"(c0), "r"(c1), "h"(mask) : "memory");
}
__device__ __forceinline__ uint64_t policy_stream() { uint64_t p; asm("createpolicy.fractional.L2::evict_first.b64 %0, 1.0;" : "=l"(p)); return p; }
__device__ __forceinline__ void tma2d_ef(uint32_t dst, const CUtensorMap* m, int c0, int c1, uint32_t bar, uint64_t pol) {
    asm volatile("cp.async.bulk.tensor.2d.shared::cluster.global.mbarrier::complete_tx::bytes.L2::cache_hint [%0], [%1, {%3, %4}], [%2], %5;"
        :: "r"(dst), "l"((uint64_t)m), "r"(bar), "r"(c0), "r"(c1), "l"(pol) : "memory");
}
__device__ __forceinline__ void tma3d(uint32_t dst, const CUtensorMap* m, int row, int chunk, uint32_t bar) {
    asm volatile("cp.async.bulk.tensor.3d.shared::cluster.global.mbarrier::complete_tx::bytes [%0], [%1, {0, %3, %4}], [%2];"
        :: "r"(dst), "l"((uint64_t)m), "r"(bar), "r"(row), "r"(chunk) : "memory");
}
__device__ __forceinline__ void tma3d_ef(uint32_t dst, const CUtensorMap* m, int row, int chunk, uint32_t bar, uint64_t pol) {
    asm volatile("cp.async.bulk.tensor.3d.shared::cluster.global.mbarrier::complete_tx::bytes.L2::cache_hint [%0], [%1, {0, %3, %4}], [%2], %5;"
        :: "r"(dst), "l"((uint64_t)m), "r"(bar), "r"(row), "r"(chunk), "l"(pol) : "memory");
}
__device__ __forceinline__ void tma3d_store(const CUtensorMap* m, int row, int chunk, uint32_t src, uint64_t pol, bool hint) {
    if (hint) asm volatile("cp.async.bulk.tensor.3d.global.shared::cta.bulk_group.L2::cache_hint [%0, {0, %2, %3}], [%1], %4;"
        :: "l"((uint64_t)m), "r"(src), "r"(row), "r"(chunk), "l"(pol) : "memory");
    else asm volatile("cp.async.bulk.tensor.3d.global.shared::cta.bulk_group [%0, {0, %2, %3}], [%1];"
        :: "l"((uint64_t)m), "r"(src), "r"(row), "r"(chunk) : "memory");
}
__device__ __forceinline__ bool elect() { uint32_t p; asm volatile("{ .reg .pred e; elect.sync _|e, -1; selp.u32 %0, 1, 0, e; }" : "=r"(p)); return p; }
__device__ __forceinline__ uint2 ld_ef(const void* p, uint64_t pol) {
    uint2 v; asm volatile("ld.relaxed.gpu.global.L2::cache_hint.v2.u32 {%0,%1}, [%2], %3;" : "=r"(v.x), "=r"(v.y) : "l"(p), "l"(pol)); return v;
}
__device__ __forceinline__ void st_ef(void* p, uint2 v, uint64_t pol) {
    asm volatile("st.global.L2::cache_hint.v2.u32 [%0], {%1,%2}, %3;" :: "l"(p), "r"(v.x), "r"(v.y), "l"(pol) : "memory");
}
__device__ __forceinline__ void tma2d_prefetch(const CUtensorMap* m, int c0, int c1) {
    asm volatile("cp.async.bulk.prefetch.tensor.2d.L2.global [%0, {%1, %2}];" :: "l"((uint64_t)m), "r"(c0), "r"(c1) : "memory");
}
__device__ __forceinline__ void mbar_arrive_remote(uint32_t bar) { asm volatile("mbarrier.arrive.relaxed.cluster.shared::cluster.b64 _, [%0];" :: "r"(bar) : "memory"); }
__device__ __forceinline__ void tma2d_store(const CUtensorMap* m, int c0, int c1, uint32_t src) {
    asm volatile("cp.async.bulk.tensor.2d.global.shared::cta.bulk_group [%0, {%2, %3}], [%1];"
        :: "l"((uint64_t)m), "r"(src), "r"(c0), "r"(c1) : "memory");
}
__device__ __forceinline__ void bulk_g2s(uint32_t dst, const void* src, int bytes, uint32_t bar) {
    asm volatile("cp.async.bulk.shared::cluster.global.mbarrier::complete_tx::bytes [%0], [%1], %2, [%3];" :: "r"(dst), "l"(src), "r"(bytes), "r"(bar) : "memory");
}
__device__ __forceinline__ void ldsm4(uint32_t (&r)[4], uint32_t a) {
    asm volatile("ldmatrix.sync.aligned.m8n8.x4.shared.b16 {%0,%1,%2,%3}, [%4];" : "=r"(r[0]), "=r"(r[1]), "=r"(r[2]), "=r"(r[3]) : "r"(a) : "memory");
}
__device__ __forceinline__ void ldsm4t(uint32_t (&r)[4], uint32_t a) {
    asm volatile("ldmatrix.sync.aligned.m8n8.x4.trans.shared.b16 {%0,%1,%2,%3}, [%4];" : "=r"(r[0]), "=r"(r[1]), "=r"(r[2]), "=r"(r[3]) : "r"(a) : "memory");
}
__device__ __forceinline__ void stsm4(uint32_t a, uint32_t r0, uint32_t r1, uint32_t r2, uint32_t r3) {
    asm volatile("stmatrix.sync.aligned.m8n8.x4.shared.b16 [%0], {%1,%2,%3,%4};" :: "r"(a), "r"(r0), "r"(r1), "r"(r2), "r"(r3) : "memory");
}
__device__ __forceinline__ void stsm4t(uint32_t a, uint32_t r0, uint32_t r1, uint32_t r2, uint32_t r3) {
    asm volatile("stmatrix.sync.aligned.m8n8.x4.trans.shared.b16 [%0], {%1,%2,%3,%4};" :: "r"(a), "r"(r0), "r"(r1), "r"(r2), "r"(r3) : "memory");
}
__device__ __forceinline__ void stsm2t(uint32_t a, uint32_t r0, uint32_t r1) {
    asm volatile("stmatrix.sync.aligned.m8n8.x2.trans.shared.b16 [%0], {%1,%2};" :: "r"(a), "r"(r0), "r"(r1) : "memory");
}
__device__ __forceinline__ uint32_t movm_t(uint32_t v) { uint32_t r; asm volatile("movmatrix.sync.aligned.m8n8.trans.b16 %0, %1;" : "=r"(r) : "r"(v)); return r; }
__device__ __forceinline__ void mma16(float (&d)[4], uint32_t a0, uint32_t a1, uint32_t a2, uint32_t a3, uint32_t b0, uint32_t b1) {
    asm volatile("mma.sync.aligned.m16n8k16.row.col.f32.bf16.bf16.f32 {%0,%1,%2,%3}, {%4,%5,%6,%7}, {%8,%9}, {%0,%1,%2,%3};"
        : "+f"(d[0]), "+f"(d[1]), "+f"(d[2]), "+f"(d[3]) : "r"(a0), "r"(a1), "r"(a2), "r"(a3), "r"(b0), "r"(b1));
}
__device__ __forceinline__ void mma8(float (&d)[4], uint32_t a0, uint32_t a1, uint32_t b0) {
    asm volatile("mma.sync.aligned.m16n8k8.row.col.f32.bf16.bf16.f32 {%0,%1,%2,%3}, {%4,%5}, {%6}, {%0,%1,%2,%3};"
        : "+f"(d[0]), "+f"(d[1]), "+f"(d[2]), "+f"(d[3]) : "r"(a0), "r"(a1), "r"(b0));
}
__device__ __forceinline__ uint32_t mapa(uint32_t a, uint32_t r) { uint32_t o; asm volatile("mapa.shared::cluster.u32 %0, %1, %2;" : "=r"(o) : "r"(a), "r"(r)); return o; }
__device__ __forceinline__ void bar_sync(int id, int n) { asm volatile("bar.sync %0, %1;" :: "r"(id), "r"(n) : "memory"); }
__device__ __forceinline__ void bar_arrive(int id, int n) { asm volatile("bar.arrive %0, %1;" :: "r"(id), "r"(n) : "memory"); }
__device__ __forceinline__ uint64_t mkdesc(uint32_t addr, uint32_t lbo, uint32_t sbo) {
    return (uint64_t)((addr & 0x3FFFF) >> 4) | ((uint64_t)(lbo >> 4) << 16) | ((uint64_t)(sbo >> 4) << 32) | (1ull << 62);
}
#define WG_FENCE()  asm volatile("wgmma.fence.sync.aligned;" ::: "memory")
#define WG_COMMIT() asm volatile("wgmma.commit_group.sync.aligned;" ::: "memory")
#define WG_WAIT(n)  asm volatile("wgmma.wait_group.sync.aligned %0;" :: "n"(n) : "memory")

__device__ __forceinline__ void wgmma_ss_n192_tb(float (&d)[96], uint64_t a, uint64_t b, int acc) {
    asm volatile("{ .reg .pred p; setp.ne.b32 p, %98, 0;\n"
        "wgmma.mma_async.sync.aligned.m64n192k16.f32.bf16.bf16 {%0,%1,%2,%3,%4,%5,%6,%7,%8,%9,%10,%11,%12,%13,%14,%15,%16,%17,%18,%19,%20,%21,%22,%23,%24,%25,%26,%27,%28,%29,%30,%31,%32,%33,%34,%35,%36,%37,%38,%39,%40,%41,%42,%43,%44,%45,%46,%47,%48,%49,%50,%51,%52,%53,%54,%55,%56,%57,%58,%59,%60,%61,%62,%63,%64,%65,%66,%67,%68,%69,%70,%71,%72,%73,%74,%75,%76,%77,%78,%79,%80,%81,%82,%83,%84,%85,%86,%87,%88,%89,%90,%91,%92,%93,%94,%95}, %96, %97, p, 1, 1, 0, 1; }"
        : "+f"(d[0]), "+f"(d[1]), "+f"(d[2]), "+f"(d[3]), "+f"(d[4]), "+f"(d[5]), "+f"(d[6]), "+f"(d[7]), "+f"(d[8]), "+f"(d[9]), "+f"(d[10]), "+f"(d[11]), "+f"(d[12]), "+f"(d[13]), "+f"(d[14]), "+f"(d[15]), "+f"(d[16]), "+f"(d[17]), "+f"(d[18]), "+f"(d[19]), "+f"(d[20]), "+f"(d[21]), "+f"(d[22]), "+f"(d[23]), "+f"(d[24]), "+f"(d[25]), "+f"(d[26]), "+f"(d[27]), "+f"(d[28]), "+f"(d[29]), "+f"(d[30]), "+f"(d[31]), "+f"(d[32]), "+f"(d[33]), "+f"(d[34]), "+f"(d[35]), "+f"(d[36]), "+f"(d[37]), "+f"(d[38]), "+f"(d[39]), "+f"(d[40]), "+f"(d[41]), "+f"(d[42]), "+f"(d[43]), "+f"(d[44]), "+f"(d[45]), "+f"(d[46]), "+f"(d[47]), "+f"(d[48]), "+f"(d[49]), "+f"(d[50]), "+f"(d[51]), "+f"(d[52]), "+f"(d[53]), "+f"(d[54]), "+f"(d[55]), "+f"(d[56]), "+f"(d[57]), "+f"(d[58]), "+f"(d[59]), "+f"(d[60]), "+f"(d[61]), "+f"(d[62]), "+f"(d[63]), "+f"(d[64]), "+f"(d[65]), "+f"(d[66]), "+f"(d[67]), "+f"(d[68]), "+f"(d[69]), "+f"(d[70]), "+f"(d[71]), "+f"(d[72]), "+f"(d[73]), "+f"(d[74]), "+f"(d[75]), "+f"(d[76]), "+f"(d[77]), "+f"(d[78]), "+f"(d[79]), "+f"(d[80]), "+f"(d[81]), "+f"(d[82]), "+f"(d[83]), "+f"(d[84]), "+f"(d[85]), "+f"(d[86]), "+f"(d[87]), "+f"(d[88]), "+f"(d[89]), "+f"(d[90]), "+f"(d[91]), "+f"(d[92]), "+f"(d[93]), "+f"(d[94]), "+f"(d[95])
        : "l"(a), "l"(b), "r"(acc));
}

__device__ __forceinline__ void wgmma_ss_n128_tb(float (&d)[64], uint64_t a, uint64_t b, int acc) {
    asm volatile("{ .reg .pred p; setp.ne.b32 p, %66, 0;\n"
        "wgmma.mma_async.sync.aligned.m64n128k16.f32.bf16.bf16 {%0,%1,%2,%3,%4,%5,%6,%7,%8,%9,%10,%11,%12,%13,%14,%15,%16,%17,%18,%19,%20,%21,%22,%23,%24,%25,%26,%27,%28,%29,%30,%31,%32,%33,%34,%35,%36,%37,%38,%39,%40,%41,%42,%43,%44,%45,%46,%47,%48,%49,%50,%51,%52,%53,%54,%55,%56,%57,%58,%59,%60,%61,%62,%63}, %64, %65, p, 1, 1, 0, 1; }"
        : "+f"(d[0]), "+f"(d[1]), "+f"(d[2]), "+f"(d[3]), "+f"(d[4]), "+f"(d[5]), "+f"(d[6]), "+f"(d[7]), "+f"(d[8]), "+f"(d[9]), "+f"(d[10]), "+f"(d[11]), "+f"(d[12]), "+f"(d[13]), "+f"(d[14]), "+f"(d[15]), "+f"(d[16]), "+f"(d[17]), "+f"(d[18]), "+f"(d[19]), "+f"(d[20]), "+f"(d[21]), "+f"(d[22]), "+f"(d[23]), "+f"(d[24]), "+f"(d[25]), "+f"(d[26]), "+f"(d[27]), "+f"(d[28]), "+f"(d[29]), "+f"(d[30]), "+f"(d[31]), "+f"(d[32]), "+f"(d[33]), "+f"(d[34]), "+f"(d[35]), "+f"(d[36]), "+f"(d[37]), "+f"(d[38]), "+f"(d[39]), "+f"(d[40]), "+f"(d[41]), "+f"(d[42]), "+f"(d[43]), "+f"(d[44]), "+f"(d[45]), "+f"(d[46]), "+f"(d[47]), "+f"(d[48]), "+f"(d[49]), "+f"(d[50]), "+f"(d[51]), "+f"(d[52]), "+f"(d[53]), "+f"(d[54]), "+f"(d[55]), "+f"(d[56]), "+f"(d[57]), "+f"(d[58]), "+f"(d[59]), "+f"(d[60]), "+f"(d[61]), "+f"(d[62]), "+f"(d[63])
        : "l"(a), "l"(b), "r"(acc));
}

__device__ __forceinline__ void wgmma_rs_n32(float (&d)[16], const uint32_t (&a)[4], uint64_t b, int acc) {
    asm volatile("{ .reg .pred p; setp.ne.b32 p, %21, 0;\n"
        "wgmma.mma_async.sync.aligned.m64n32k16.f32.bf16.bf16 {%0,%1,%2,%3,%4,%5,%6,%7,%8,%9,%10,%11,%12,%13,%14,%15}, {%16,%17,%18,%19}, %20, p, 1, 1, 0; }"
        : "+f"(d[0]), "+f"(d[1]), "+f"(d[2]), "+f"(d[3]), "+f"(d[4]), "+f"(d[5]), "+f"(d[6]), "+f"(d[7]), "+f"(d[8]), "+f"(d[9]), "+f"(d[10]), "+f"(d[11]), "+f"(d[12]), "+f"(d[13]), "+f"(d[14]), "+f"(d[15])
        : "r"(a[0]), "r"(a[1]), "r"(a[2]), "r"(a[3]), "l"(b), "r"(acc));
}

__device__ __forceinline__ float warp_sum(float v) {
#pragma unroll
    for (int o = 16; o; o >>= 1) v += __shfl_xor_sync(0xffffffffu, v, o);
    return v;
}
__device__ __forceinline__ uint32_t add2(uint32_t a, uint32_t b) { uint32_t r; asm("add.rn.bf16x2 %0, %1, %2;" : "=r"(r) : "r"(a), "r"(b)); return r; }
__device__ __forceinline__ uint32_t mul2(uint32_t a, uint32_t b) { uint32_t r; asm("mul.rn.bf16x2 %0, %1, %2;" : "=r"(r) : "r"(a), "r"(b)); return r; }
__device__ __forceinline__ uint32_t amax2(uint32_t m, uint32_t v) { uint32_t r; asm("max.u16x2 %0, %1, %2;" : "=r"(r) : "r"(m), "r"(v & 0x7fff7fffu)); return r; }
__device__ __forceinline__ uint32_t amax_warp(uint32_t m) { return __reduce_max_sync(0xffffffffu, max(m & 0xffffu, m >> 16)); }
__device__ __forceinline__ void ln_norm(const uint32_t (&xv)[10], uint32_t (&nv)[10]) {
    float s0 = 0, s1 = 0;
#pragma unroll
    for (int i = 0; i < 10; i++) { s0 += lo_f(xv[i]); s1 += hi_f(xv[i]); }
    const float mean = warp_sum(s0 + s1) * (1.f / DM);
    float q0 = 0, q1 = 0;
#pragma unroll
    for (int i = 0; i < 10; i++) { const float d0 = lo_f(xv[i]) - mean, d1 = hi_f(xv[i]) - mean; q0 += d0 * d0; q1 += d1 * d1; }
    const float inv = inv_std(warp_sum(q0 + q1) * (1.f / DM));
    const uint32_t mb = pack2(-mean, -mean);
#pragma unroll
    for (int i = 0; i < 10; i++) { const uint32_t d = add2(xv[i], mb); nv[i] = pack2(lo_f(d) * inv, hi_f(d) * inv); }
}
__device__ __forceinline__ void ln_mod(const uint32_t (&xv)[10], const uint32_t (&sv)[10], const uint32_t (&tv)[10], uint32_t (&hv)[10]) {
    ln_norm(xv, hv);
#pragma unroll
    for (int i = 0; i < 10; i++) hv[i] = add2(mul2(hv[i], add2(sv[i], 0x3f803f80u)), tv[i]);
}
__device__ __forceinline__ uint32_t ld_rlx(const uint32_t* f) { uint32_t v; asm volatile("ld.relaxed.gpu.global.u32 %0, [%1];" : "=r"(v) : "l"(f) : "memory"); return v; }
__device__ __forceinline__ void bump(uint32_t* f) { asm volatile("red.relaxed.gpu.global.add.u32 [%0], 1;" :: "l"(f) : "memory"); }
#define NAP 100
#define GPU_FENCE() asm volatile("fence.acq_rel.gpu;" ::: "memory")
__device__ __forceinline__ void flag_wait(const uint32_t* f, uint32_t target) {
    for (int n = 0;; n++) {
        uint32_t v; asm volatile("ld.relaxed.gpu.global.u32 %0, [%1];" : "=r"(v) : "l"(f) : "memory");
        if (v >= target) break;
        if (n > (1 << 22)) __trap();
        __nanosleep(NAP);
    }
}
__device__ __forceinline__ void flag_add(uint32_t* f, uint32_t v = 1) { asm volatile("red.release.gpu.global.add.u32 [%0], %1;" :: "l"(f), "r"(v) : "memory"); }
constexpr int N_SIDE = 36;
__device__ __forceinline__ void flags_release(int lane) {
    uint32_t old = 0;
    if (lane == 0) asm volatile("atom.relaxed.gpu.global.add.u32 %0, [%1], 1;" : "=r"(old) : "l"(&g_flags.done) : "memory");
    if (__shfl_sync(0xffffffffu, old, 0) == 96 + N_SIDE - 1)
#pragma unroll 1
        for (int i = lane; i < (int)(sizeof(Flags) / 16); i += 32) ((uint4*)&g_flags)[i] = make_uint4(0, 0, 0, 0);
}

struct ChainMaps { CUtensorMap wq, wk, wv, wo, h2, wo15, o15, slab2; };
struct ChainArgs { const bf16 *x, *mem0, *c, *wmod, *wv, *wo, *wgate, *wup, *wdown; bf16* out; int D1, D2, DG; };
constexpr uint32_t SM_BASE = 1024;
#define NRING 10
#define XORD 0
#define B5AT 38
#define QCUT 0x12
#define NCH 0
#define XA 2
#define VT 1
#define OSEND 1
#define SPOLL 0
#define QK_MASK 0x7fff
#define FW 2
#define CVF 0
#define APRE 4
#define PBAR 0
#define WLATE 1
#define QDEL 300
#define STL 0
#define B7E 1
#define VPF 1
#define NPRE 9
#define REG_P 208
#define REG_L (504 - 2 * REG_P)
constexpr int WO_BLK = 7 * 4096;
constexpr int C_WV = 0, C_WO = 81920, C_XR = 167936, C_VP = C_XR + 7 * 4096, C_VX = C_XR + 8 * 4096, C_QX = C_VX + 4096, C_KX = C_QX + 4096,
              C_MEM = C_KX + 4096, C_OX = C_MEM + 9216, C_VM = C_OX + 3072, C_QM = C_VM + 1024, C_KM = C_QM + 1024, C_SC = C_KM + 1024, C_BAR = C_SC + 3840;
constexpr int CB_W = C_BAR, CB_W2 = C_BAR + 8, CB_SC = C_BAR + 16, CB_XD = C_BAR + 24, CB_VX = C_BAR + 32, CB_W3 = C_BAR + 40, CB_XM = C_BAR + 48, CB_OX = C_BAR + 56,
              CB_XF = C_BAR + 64, C_LAG = C_BAR + 96, C_UN = C_BAR + 100, C_MX = C_BAR + 112;
constexpr int C_SMEM = C_BAR + 128;
#define PROF(i)
#define PROFG(i)
#define PROFV(i, v)
static_assert(C_SMEM <= 232448, "chain shared memory");
__device__ __forceinline__ uint32_t umax3(uint32_t a, uint32_t b, uint32_t c) { return max(max(a, b), c); }
__device__ __forceinline__ void wait_until(uint32_t t) {
    asm volatile("{ .reg .pred p; .reg .s32 c; .reg .u64 d;\nU_%=: mov.u64 d, %%clock64; cvt.u32.u64 c, d; sub.s32 c, c, %0; setp.lt.s32 p, c, 0; @p bra.uni U_%=; }" :: "r"(t) : "memory");
}
__device__ __forceinline__ uint32_t gtime() { uint32_t c; asm volatile("mov.u32 %0, %%globaltimer_lo;" : "=r"(c)); return c; }
__device__ __forceinline__ uint32_t opaque(uint32_t v) { uint32_t r; asm volatile("shfl.sync.bfly.b32 %0, %1, 0, 31, -1;" : "=r"(r) : "r"(v)); return r; }
__device__ __forceinline__ uint32_t lds32(uint32_t a) { uint32_t v; asm volatile("ld.shared.u32 %0, [%1];" : "=r"(v) : "r"(a) : "memory"); return v; }
__device__ __forceinline__ float2 lds64f(uint32_t a) { float2 v; asm volatile("ld.shared.v2.f32 {%0,%1}, [%2];" : "=f"(v.x), "=f"(v.y) : "r"(a) : "memory"); return v; }
__device__ __forceinline__ float4 lds128f(uint32_t a) { float4 v; asm volatile("ld.shared.v4.f32 {%0,%1,%2,%3}, [%4];" : "=f"(v.x), "=f"(v.y), "=f"(v.z), "=f"(v.w) : "r"(a) : "memory"); return v; }
__device__ __forceinline__ void sts128f(uint32_t a, float x, float y, float z, float w) { asm volatile("st.shared.v4.f32 [%0], {%1,%2,%3,%4};" :: "r"(a), "f"(x), "f"(y), "f"(z), "f"(w) : "memory"); }
__device__ __forceinline__ void lds64(uint32_t (&v)[2], uint32_t a) { asm volatile("ld.shared.v2.u32 {%0,%1}, [%2];" : "=r"(v[0]), "=r"(v[1]) : "r"(a) : "memory"); }
__device__ __forceinline__ void mma16q(float (&d)[4], const uint32_t (&a)[4], uint32_t b0, uint32_t b1) { mma16(d, a[0], a[1], a[2], a[3], b0, b1); }
__device__ __forceinline__ uint32_t f16_to_bf16(uint32_t v) {
    float lo, hi; asm("{ .reg .f16 l, h; mov.b32 {l, h}, %2; cvt.f32.f16 %0, l; cvt.f32.f16 %1, h; }" : "=f"(lo), "=f"(hi) : "r"(v));
    return pack2(lo, hi);
}
__device__ __forceinline__ uint32_t pack2h(float lo, float hi) { uint32_t r; asm("cvt.rn.f16x2.f32 %0, %1, %2;" : "=r"(r) : "f"(hi), "f"(lo)); return r; }
#define SPLIT 1
__device__ __forceinline__ void cut(uint32_t never, int n) {
    asm volatile("{ .reg .pred p; setp.ne.u32 p, %0, %1; @p bra.uni C_%=; trap; C_%=: }" :: "r"(never), "r"(n) : "memory");
}
__device__ __forceinline__ void pin(uint32_t never, uint32_t a, uint32_t b, uint32_t c, uint32_t d) {
    asm volatile("{ .reg .pred p; setp.eq.u32 p, %0, 0; @p st.shared.v4.u32 [%0], {%1,%2,%3,%4}; }" :: "r"(never), "r"(a), "r"(b), "r"(c), "r"(d) : "memory");
}
__device__ __forceinline__ void pin0(uint32_t never) {
    asm volatile("{ .reg .pred p; setp.eq.u32 p, %0, 0; @p st.shared.u32 [%0], 0; }" :: "r"(never) : "memory");
}
#define ELECTED(txt) "{ .reg .pred e; elect.sync _|e, -1; @e " txt " }"
__device__ __forceinline__ void w_bulk_s2g(void* dst, uint32_t src, int bytes) {
    asm volatile(ELECTED("cp.async.bulk.global.shared::cta.bulk_group [%0], [%1], %2;") :: "l"(dst), "r"(src), "r"(bytes) : "memory");
}
__device__ __forceinline__ void w_bump(uint32_t* f) { asm volatile(ELECTED("red.relaxed.gpu.global.add.u32 [%0], 1;") :: "l"(f) : "memory"); }
__device__ __forceinline__ void w_expect(uint32_t bar, int bytes) { asm volatile(ELECTED("mbarrier.arrive.expect_tx.shared::cta.b64 _, [%0], %1;") :: "r"(bar), "r"(bytes) : "memory"); }
__device__ __forceinline__ void w_flag_wait(const uint32_t* f, uint32_t target) {
    asm volatile("{ .reg .pred p; .reg .u32 n, v; mov.u32 n, 0;\n"
                 "F_%=: ld.relaxed.gpu.global.u32 v, [%0]; setp.ge.u32 p, v, %1; vote.sync.all.pred p, p, -1; @p bra.uni G_%=;\n"
                 "nanosleep.u32 %2; add.u32 n, n, 1; setp.lt.u32 p, n, 0x400000; @p bra.uni F_%=;\ntrap;\nG_%=: }" :: "l"(f), "r"(target), "n"(NAP) : "memory");
}
#define BULK_COMMIT()    asm volatile("cp.async.bulk.commit_group;" ::: "memory")
#define BULK_WAIT()      asm volatile("cp.async.bulk.wait_group 0;" ::: "memory")
#define BULK_WAIT_READ() asm volatile("cp.async.bulk.wait_group.read 0;" ::: "memory")
#define PROXY_FENCE()    asm volatile("fence.proxy.async.shared::cta;" ::: "memory")
__device__ __forceinline__ void send16(uint32_t dst, uint32_t bar, float a, float b, float c, float d) {
    asm volatile("st.async.shared::cluster.mbarrier::complete_tx::bytes.v4.f32 [%0], {%1,%2,%3,%4}, [%5];" :: "r"(dst), "f"(a), "f"(b), "f"(c), "f"(d), "r"(bar) : "memory");
}
__device__ __forceinline__ void send8(uint32_t dst, uint32_t bar, uint32_t a, uint32_t b) {
    asm volatile("st.async.shared::cluster.mbarrier::complete_tx::bytes.v2.b32 [%0], {%1,%2}, [%3];" :: "r"(dst), "r"(a), "r"(b), "r"(bar) : "memory");
}

__device__ __forceinline__ void seg_done(int n, int head) {
    if (n > 60 || ((n & 3) == 3 && (QK_MASK >> (n >> 2) & 1))) { GPU_FENCE(); w_bump(n > 60 ? &g_flags.seg[(n - 60) * 32 + head] : &g_flags.qk[n >> 2]); }
}
__device__ __forceinline__ uint32_t x_base(int wg, uint32_t small, int sh) { return (uint32_t)mkdesc(SM_BASE + C_XR, 16, 1024) + wg * 256 + (small >> sh); }
__device__ __forceinline__ void x_chunk(float (&acc)[16], const uint32_t (&wa)[40][4], uint32_t xl, int a0, int i, int first) {
#pragma unroll
    for (int ks = 0; ks < 4; ks++)
        wgmma_rs_n32(acc, wa[a0 + 4 * i + ks], mkdesc(0, 0, 1024) | (uint32_t)(xl + (((i ? (i - 1) * 8192 : C_MEM - C_XR) + ks * 32) >> 4)), !(first && ks == 0));
}
__device__ __forceinline__ void x_part(float (&acc)[16], const uint32_t (&wa)[40][4], uint32_t sm, int n, int wg, int w, uint32_t ln, uint32_t small) {
    const int s = n - 1; (void)s;
    uint32_t giv[8];
    auto chunk = [&](int a0, int i, int first) { x_chunk(acc, wa, x_base(wg, small, a0 ? 21 : 22), a0, i, first); };
    mbar_wait(sm + CB_XM, n & 1);
    if (n) bar_sync(5, 384);
    if (wg == 0 && w == 0) PROF(12);
    WG_FENCE();
#pragma unroll
    for (int i = 1 + XA; i < 5; i++) chunk(20, i, 0);
    chunk(20, 0, 0);
    WG_COMMIT();
    if (n) {
        if (wg == 1 && w == 1) BULK_WAIT();
        bar_sync(8, 256);
    }
    if (wg == 0 && w == 0) PROF(18);
    const uint32_t xb = sm + w * 512 + ln * 16, xw = xb + C_KX - wg * 4096, xr = xb + C_QX + wg * 4096;
    WG_WAIT(0);
#pragma unroll
    for (int i = 0; i < 8; i++) asm volatile("cvt.rn.bf16x2.f32 %0, %1, %2;" : "=r"(giv[i]) : "f"(acc[2 * i + 1]), "f"(acc[2 * i]));
#pragma unroll
    for (int p = 0; p < 2; p++) asm volatile("st.shared.v4.u32 [%0], {%1,%2,%3,%4};" :: "r"(xw + p * 2048), "r"(giv[4 * p]), "r"(giv[4 * p + 1]), "r"(giv[4 * p + 2]), "r"(giv[4 * p + 3]) : "memory");
    bar_arrive(12 + wg, 256);
    WG_FENCE();
    chunk(0, 0, 1);
    WG_COMMIT();
    chunk(0, 1, 0);
    if (XORD) chunk(0, 2, 0);
    bar_sync(13 - wg, 256);
#pragma unroll
    for (int p = 0; p < 2; p++) asm volatile("ld.shared.v4.u32 {%0,%1,%2,%3}, [%4];" : "=r"(giv[4 * p]), "=r"(giv[4 * p + 1]), "=r"(giv[4 * p + 2]), "=r"(giv[4 * p + 3]) : "r"(xr + p * 2048) : "memory");
    WG_COMMIT(); WG_WAIT(1); bar_arrive(9, 384);
    WG_FENCE();
    if (!XORD) chunk(0, 2, 0);
    chunk(0, 3, 0); chunk(0, 4, 0);
    WG_COMMIT();
    const uint32_t r = ln & 7, mi = ln >> 3, dst = sm + (wg == 0 ? C_QX : C_KX) + ((mi >> 1) * 8 + r) * 128 + (((2 * w + (mi & 1)) ^ r) << 4);
    pin(xb, giv[0], giv[4], dst, 0);
    bar_sync(10 + wg, 128);
    WG_WAIT(0);
    if (wg == 0 && w == 0) PROF(30);
    if (w == 0 && ln < 3) mbar_arrive_remote(mapa(sm + CB_XD, ln));
#pragma unroll
    for (int i = 0; i < 8; i++) { acc[2 * i] += lo_f(giv[i]); acc[2 * i + 1] += hi_f(giv[i]); }
#pragma unroll
    for (int p = 0; p < 2; p++)
        stsm4t(dst + p * 2048, pack2(acc[8 * p], acc[8 * p + 1]), pack2(acc[8 * p + 2], acc[8 * p + 3]), pack2(acc[8 * p + 4], acc[8 * p + 5]), pack2(acc[8 * p + 6], acc[8 * p + 7]));
    if (wg == 0 && w == 0) PROF(11);
}
__device__ __forceinline__ void x_fill(const ChainMaps& mp, uint32_t sm, int n, int j) {
    mbar_expect(sm + CB_XF, 24576);
    asm volatile("cp.async.bulk.tensor.3d.shared::cluster.global.mbarrier::complete_tx::bytes.multicast::cluster [%0], [%1, {0, %3, %4}], [%2], %5;"
        :: "r"(sm + C_XR + j * 8192), "l"((uint64_t)&mp.h2), "r"(sm + CB_XF), "r"(n * SEG), "r"(2 + 2 * j), "h"((uint16_t)7) : "memory");
}
__device__ __forceinline__ void x_rest(const ChainMaps& mp, uint32_t sm, int n) {
    mbar_expect(sm + CB_XM, 16384);
    tma3d(sm + C_XR + 6 * 4096, &mp.h2, n * SEG, 8, sm + CB_XM); tma3d(sm + C_MEM, &mp.h2, n * SEG, 0, sm + CB_XM);
}

#define WPOS 2
#define WP 4
#define WOPF 30
#define SDEL 0
#define EORD 0
#define RPF 1
#define BPOS 2
#define TPF 1
#define B_LATE 13
constexpr int E_B = C_WO, E_STG = 196608, EB_A = 229376, EB_B = C_BAR + 80, EB_REL = C_BAR + 104;
__device__ __forceinline__ uint32_t e_slot(int wg, int c) { return wg && c == 2 ? E_B + 98304 : wg * 49152 + c * 16384; }
constexpr int T_WG = 0, T_WU = 20480, T_WD = 40960, T_X = 65536, T_RED = 77824, T_KEY = 86016;
__device__ __forceinline__ void wo_half(const ChainMaps& mp, uint32_t sm, int blk, int c) {
    if (blk < 80 && elect()) { mbar_expect(sm + EB_B + 8 * c, 49152); tma3d(sm + E_B + c * 49152, &mp.wo15, blk / 5 * 384 + c * 192, blk % 5 * 2, sm + EB_B + 8 * c); }
}
__device__ __forceinline__ void end_loads(const ChainMaps& mp, const ChainArgs& ar, uint32_t sm, int blk, int wg) {
    const uint32_t bar = sm + EB_A + wg * 48;
    const int kp = blk / 5;
    if (elect()) {
#pragma unroll 1
        for (int c = 0; c < 6; c++) mbar_init(bar + 8 * c, c < 3 ? 1 : 4);
        PROXY_FENCE();
    }
    __syncwarp();
    bar_arrive(5, 384);
    if (EORD) bar_sync(6, 96);
    if (blk >= 80) {
        if (TPF && elect()) {
#pragma unroll 1
            for (int c = 0; c < 3; c++) asm volatile("cp.async.bulk.prefetch.L2.global [%0], 61440;" :: "l"((c == 0 ? ar.wgate : c == 1 ? ar.wup : ar.wdown) + ((blk - 80) * 2 + wg) * 30720) : "memory");
        }
        return;
    }
    const uint64_t ef = policy_stream();
#pragma unroll 1
    for (int b = B_LATE; b < 16; b++) {
        w_flag_wait(b == 15 ? &g_flags.half[kp * 2 + wg] : &g_flags.pair[b * 16 + kp], b == 15 ? 2 : 4);
#pragma unroll 1
        for (int c = 0; c < 3; c++) {
            if (b > B_LATE) mbar_wait(bar + 24 + 8 * c, (b - B_LATE - 1) & 1);
            if (elect()) { mbar_expect(bar + 8 * c, 16384); tma3d_ef(sm + e_slot(wg, c), &mp.o15, b * 128 + wg * 64, kp * 6 + c * 2, bar + 8 * c, ef); }
            __syncwarp();
        }
    }
}
__device__ __forceinline__ void end_stores(const ChainMaps& mp, uint32_t sm, int blk, int wg) {
#pragma unroll 1
    for (int b = B_LATE; b < 16 && blk < 80; b++) {
        bar_sync(12 + wg, 160);
        if (elect()) tma3d_store(&mp.slab2, (b * KSPLIT + blk / 5) * 128 + wg * 64, blk % 5 * 2, sm + E_STG + wg * 16384, 0, false);
        BULK_COMMIT(); BULK_WAIT();
        if (b < 15) bar_arrive(10 + wg, 160);
        GPU_FENCE();
        w_bump(b < 14 ? &g_flags.o[b] : &g_flags.fin[((b - 14) * 2 + wg) * 32]);
    }
    bar_arrive(8, 320);
}
__device__ __forceinline__ void last_blocks(const ChainArgs& ar, uint32_t sm, int blk, int tid) {
    const int warp = __shfl_sync(0xffffffffu, tid >> 5, 0), lane = tid & 31, wg = warp >> 2, w = warp & 3;
    const uint32_t bar = sm + EB_A + wg * 48, stg = sm + E_STG + wg * 16384 + w * 2048;
    bar_sync(5, 384);
    EPT(tid == 128, 7);
    float acc[64];
#pragma unroll
    for (int n = 0; n < 64; n++) acc[n] = 0.f;
#pragma unroll 1
    for (int b = B_LATE; b < 16 && blk < 80; b++) {
#pragma unroll 1
        for (int c = 0; c < 6; c++) {
            mbar_wait(sm + EB_B + 8 * (c >= 3), 0); mbar_wait(bar + 8 * (c >> 1), (b - B_LATE) & 1);
            const uint64_t da = mkdesc(SM_BASE + e_slot(wg, c >> 1) + (c & 1) * 8192, 16, 1024), db = mkdesc(SM_BASE + E_B + (c >= 3 ? 24576 : 0) + c * 8192, 24576, 1024);
            WG_FENCE();
#pragma unroll
            for (int ks = 0; ks < 4; ks++) wgmma_ss_n128_tb(acc, da + ks * 2, db + ks * 128, c | ks);
            WG_COMMIT();
            WG_WAIT(1);
            if ((c & 1) == 0 && c && elect()) mbar_arrive(bar + 16 + 4 * c);
        }
        if (b > B_LATE) bar_sync(10 + wg, 160);
        WG_WAIT(0);
        if (elect()) mbar_arrive(bar + 40);
        EPT(tid == 128, 13 + 15 - b);
        const int r = lane & 7, mi = lane >> 3;
#pragma unroll
        for (int p = 0; p < 8; p++) {
            const int oc = 2 * p + (mi >> 1);
            stsm4(stg + (oc >> 3) * 8192 + ((mi & 1) * 8 + r) * 128 + (((oc & 7) ^ r) << 4), pack2(acc[8 * p], acc[8 * p + 1]), pack2(acc[8 * p + 2], acc[8 * p + 3]),
                  pack2(acc[8 * p + 4], acc[8 * p + 5]), pack2(acc[8 * p + 6], acc[8 * p + 7]));
        }
        PROXY_FENCE();
        bar_arrive(12 + wg, 160);
    }
    bar_sync(8, 320);
    const int o = (tid >> 1) * FF + blk * 16 + (tid & 1) * 8;
    const bf16 *pg = ar.wgate + o, *pu = ar.wup + o, *pd = ar.wdown + tid * DM + (blk < 80 ? blk : 0) * 8;
#pragma unroll 1
    for (int i = 0; i < 6; i++) {
        const uint32_t d = sm + E_B + i * 4096 + tid * 16;
        if (i < 5) asm volatile("cp.async.cg.shared.global [%0], [%1], 16; cp.async.cg.shared.global [%0 + 20480], [%2], 16;" :: "r"(d), "l"(pg + i * 128 * FF), "l"(pu + i * 128 * FF) : "memory");
        asm volatile("cp.async.cg.shared.global [%0 + 40960], [%1], 16;" :: "r"(d), "l"(pd + i * 256 * DM) : "memory");
    }
    EPT(tid == 128, 8);
}
__device__ __forceinline__ void mod_tail(const ChainArgs& ar, const uint32_t tb, const uint32_t bar, const int blk, const int tid) {
#define TPROF(i) EPT(tid == 0, i)
    const int warp = __shfl_sync(0xffffffffu, tid >> 5, 0), lane = tid & 31, r = lane & 7, mi = lane >> 3;
    const uint32_t kb = tb + T_KEY;
    {
        uint32_t k[8];
        for (int n = 0;; n++) {
#pragma unroll
            for (int i = 0; i < 2; i++) asm volatile("ld.relaxed.gpu.global.v4.u32 {%0,%1,%2,%3}, [%4];" : "=r"(k[4 * i]), "=r"(k[4 * i + 1]), "=r"(k[4 * i + 2]), "=r"(k[4 * i + 3]) : "l"(g_key + warp * 256 + i * 128 + lane * 4) : "memory");
            if (__all_sync(0xffffffffu, (k[0] & k[1] & k[2] & k[3] & k[4] & k[5] & k[6] & k[7] & S_TOK) != 0)) break;
            if (n > (1 << 22)) __trap();
            __nanosleep(NAP);
        }
        const uint32_t m = __reduce_max_sync(0xffffffffu, max(umax3(k[0], k[1], k[2]), max(umax3(k[3], k[4], k[5]), max(k[6], k[7]))));
        asm volatile("st.shared.u32 [%0], %1; st.shared.u32 [%2], 0;" :: "r"(kb + warp * 4), "r"(m), "r"(kb + 32) : "memory");
        if (RPF && blk >= 93 && warp < 6) {
            uint32_t c = m;
#pragma unroll 1
            for (int it = 93; it < blk; it++) {
                uint32_t x = 0;
#pragma unroll
                for (int i = 0; i < 8; i++) x = max(x, k[i] < c ? k[i] : 0u);
                c = __reduce_max_sync(0xffffffffu, x);
            }
            if ((c & 2 * S_TOK) && lane < 2) asm volatile("cp.async.bulk.prefetch.L2.global [%0], 1280;" :: "l"((lane ? g_h2 : g_x1) + (~c & (S_TOK - 1)) * DM) : "memory");
        }
        asm volatile("cp.async.wait_all;" ::: "memory");
        bar_sync(1, 256);
        TPROF(1);
        const uint32_t low = __reduce_min_sync(0xffffffffu, lds32(kb + r * 4));
        uint32_t cnt = 0;
#pragma unroll
        for (int i = 0; i < 8; i++) cnt += k[i] >= low ? 4 : 0;
        if (cnt) {
            uint32_t a; asm volatile("atom.shared.add.u32 %0, [%1], %2;" : "=r"(a) : "r"(kb + 32), "r"(cnt) : "memory");
#pragma unroll
            for (int i = 0; i < 8; i++) if (k[i] >= low) { asm volatile("st.shared.u32 [%0], %1;" :: "r"(kb + 512 + a), "r"(k[i]) : "memory"); a += 4; }
        }
        if (tid == 0) mbar_arrive(bar);
        bar_sync(1, 256);
        const int nc = lds32(kb + 32);
#pragma unroll 1
        for (int c = lane * 4; c < nc; c += 128) {
            const uint32_t me = lds32(kb + 512 + c);
            int rank = 0;
#pragma unroll 2
            for (int e = 0; e < nc; e += 16) {
                const float4 z = lds128f(kb + 512 + e);
                rank += (__float_as_uint(z.x) > me) + (e + 4 < nc && __float_as_uint(z.y) > me) + (e + 8 < nc && __float_as_uint(z.z) > me) + (e + 12 < nc && __float_as_uint(z.w) > me);
            }
            if (rank < 8) asm volatile("st.shared.u32 [%0], %1;" :: "r"(kb + 64 + (warp * 8 + rank) * 4), "r"(me) : "memory");
        }
        __syncwarp();
    }
    const uint32_t k0 = lds32(kb + 64 + (warp * 8 + r) * 4), k1 = lds32(kb + 64 + (warp * 8 + (lane >> 2)) * 4);
    TPROF(2);
    const int trow = ~k1 & (S_TOK - 1), tcol = (blk < 80 ? blk : 0) * 8 + (lane & 3) * 2;
    uint2 xb[5];
#pragma unroll
    for (int h = 0; h < 5; h++) xb[h] = __ldcg((const uint2*)(g_h2 + trow * DM + (warp * 5 + h) * 16 + (lane & 3) * 4));
    const uint32_t fx1 = __ldcg((const uint32_t*)(g_x1 + trow * DM + tcol)), fh2 = __ldcg((const uint32_t*)(g_h2 + trow * DM + tcol)),
                   fgb = __ldcg((const uint32_t*)(g_mod + 5 * DM + tcol));
    const float fr = __uint_as_float(((int)k1 < 0 ? k1 ^ 0x80000000u : ~k1) & 0xffff0000u);
    {
        float dg[4] = {0, 0, 0, 0}, du[4] = {0, 0, 0, 0};
        uint32_t ag[5][4], au[5][4];
#pragma unroll
        for (int h = 0; h < 5; h++) {
            const uint32_t o = tb + ((warp * 5 + h) * 16 + (r >> 1) * 4 + (mi >> 1) * 2 + (r & 1)) * 32 + (mi & 1) * 16;
            ldsm4t(ag[h], o + T_WG); ldsm4t(au[h], o + T_WU);
        }
#pragma unroll
        for (int h = 0; h < 5; h++) { mma16q(dg, ag[h], xb[h].x, xb[h].y); mma16q(du, au[h], xb[h].x, xb[h].y); }
        TPROF(3);
        sts128f(tb + T_RED + warp * 1024 + lane * 16, dg[0], dg[1], dg[2], dg[3]); sts128f(tb + T_RED + warp * 1024 + 512 + lane * 16, du[0], du[1], du[2], du[3]);
    }
    bar_sync(1, 256);
    if (warp < 2) {
        float g2[2] = {0, 0}, u2[2] = {0, 0};
#pragma unroll
        for (int i = 0; i < 8; i++) {
            const float2 a = lds64f(tb + T_RED + i * 1024 + lane * 16 + warp * 8), b = lds64f(tb + T_RED + i * 1024 + 512 + lane * 16 + warp * 8);
            g2[0] += a.x; g2[1] += a.y; u2[0] += b.x; u2[1] += b.y;
        }
        float y[2];
#pragma unroll
        for (int i = 0; i < 2; i++) { const float gq = bfr(g2[i]); y[i] = bfr(__fdividef(gq, 1.f + __expf(-gq))) * bfr(u2[i]); }
        asm volatile("st.relaxed.gpu.global.u32 [%0], %1;" :: "l"(g_gu + (blk >> 1) * 128 + lane * 4 + warp * 2 + (blk & 1)), "r"(movm_t(pack2(y[0], y[1]))) : "memory");
    }
    TPROF(4);
    if (blk < 80) {
        uint32_t a[6][4], b[6][4];
#pragma unroll
        for (int k2 = 0; k2 < 6; k2++) ldsm4t(b[k2], tb + T_WD + (warp * 6 + k2) * 512 + lane * 16);
        for (int n = 0;; n++) {
            uint32_t m = 0;
#pragma unroll
            for (int k2 = 0; k2 < 6; k2++) asm volatile("ld.relaxed.gpu.global.v4.u32 {%0,%1,%2,%3}, [%4];" : "=r"(a[k2][0]), "=r"(a[k2][1]), "=r"(a[k2][2]), "=r"(a[k2][3]) : "l"(g_gu + (warp * 6 + k2) * 128 + lane * 4) : "memory");
#pragma unroll
            for (int k2 = 0; k2 < 6; k2++) m = umax3(umax3(m, a[k2][0], a[k2][1]), a[k2][2], a[k2][3]);
            if (!__any_sync(0xffffffffu, m == ~0u)) break;
            if (n > (1 << 22)) __trap();
        }
        TPROF(5);
        float d[2][4] = {{0, 0, 0, 0}, {0, 0, 0, 0}};
#pragma unroll
        for (int k2 = 0; k2 < 6; k2++) { mma16q(d[0], a[k2], b[k2][0], b[k2][1]); mma16q(d[1], a[k2], b[k2][2], b[k2][3]); }
        asm volatile("st.shared.v2.f32 [%0], {%1,%2};" :: "r"(tb + T_X + warp * 256 + lane * 8), "f"(d[0][0] + d[1][2]), "f"(d[0][1] + d[1][3]) : "memory");
        bar_sync(1, 256);
        if (warp == 0) {
            float y0 = 0, y1 = 0;
#pragma unroll
            for (int i = 0; i < 8; i++) { const float2 z = lds64f(tb + T_X + i * 256 + lane * 8); y0 += z.x; y1 += z.y; }
            const float sg = __fdividef(1.f, 1.f + __expf(-fr));
            *(uint32_t*)(ar.out + trow * DM + tcol) = add2(fx1, mul2(fgb, add2(fh2, mul2(pack2(y0, y1), pack2(sg, sg)))));
        }
    }
    TPROF(6);
}

__global__ void __cluster_dims__(3, 1, 1) __launch_bounds__(384, 1) k_chain(const __grid_constant__ ChainMaps mp, const __grid_constant__ ChainArgs ar) {
    const int D1 = ar.D1, DG = ar.DG;
    extern __shared__ __align__(1024) uint8_t smraw[];
    const uint32_t sm = SM_BASE + ((blockIdx.x % 3) << 24);
    if (smem_u32(smraw) != sm) __trap();
    uint32_t tid; asm volatile("mov.u32 %0, %%tid.x;" : "=r"(tid));
    const int warp = __shfl_sync(0xffffffffu, tid >> 5, 0), lane = tid & 31, wg = warp >> 2, w = warp & 3;
    const int blk = blockIdx.x, head = blk / 3, j = blk % 3;
    const int col0 = head * DH + j * 64;
    asm volatile("griddepcontrol.launch_dependents;");
#define PPROF(i)
    const int r = lane & 7, mi = lane >> 3;
    const uint32_t memrd = opaque(sm + C_MEM + lane * 16);
    if (wg < 2) {
        {
            uint32_t xv[3][10];
            const int row = blk * 8 + warp, nq = row < S_TOK - 1536 ? 3 : 2;
#pragma unroll
            for (int i = 0; i < 15; i++) {
                const uint2 v = __ldcs((const uint2*)(ar.x + (row + (i < 10 || nq == 3 ? i / 5 * 768 : 0)) * DM + lane * 4 + i % 5 * 128));
                xv[i / 5][i % 5 * 2] = v.x; xv[i / 5][i % 5 * 2 + 1] = v.y;
            }
            if (tid == 32) {
#pragma unroll 1
                for (int c = 0; c < 14; c++) if (c != 12) mbar_init(sm + C_BAR + 8 * c, c == 2 ? 5 : c == 3 ? 6 : 1);
                asm volatile("fence.mbarrier_init.release.cluster;" ::: "memory");
                mbar_expect(sm + CB_SC, 2560); mbar_expect(sm + CB_OX, 2048);
            }
            if (warp == 2) {
                const uint32_t f = blk >= 28 ? ~0u : 0u;
                ((uint4*)g_acc)[blk * 32 + lane] = make_uint4(0, 0, 0, 0);
                if (blk < 76) (blk < 12 ? (uint4*)g_stamp + blk * 32 : blk < 28 ? (uint4*)g_key + (blk - 12) * 32 : (uint4*)g_gu + (blk - 28) * 32)[lane] = make_uint4(f, f, f, f);
            }
            __syncwarp();
            asm volatile("barrier.cluster.arrive.relaxed.aligned;" ::: "memory");
            PPROF(8);
#pragma unroll 1
            for (int q = 0; q < 3; q++) {
                uint32_t nv[10];
                ln_norm(xv[0], nv);
#pragma unroll
                for (int i = 0; i < 10; i++) { xv[0][i] = xv[1][i]; xv[1][i] = xv[2][i]; xv[2][i] = nv[i]; }
            }
            PPROF(9);
            if (warp < 5) {
                uint4 u;
                for (int n = 0;; n++) {
                    asm volatile("ld.relaxed.gpu.global.v4.u32 {%0,%1,%2,%3}, [%4];" : "=r"(u.x), "=r"(u.y), "=r"(u.z), "=r"(u.w) : "l"(g_flags.mod1 + tid * 4) : "memory");
                    if (__all_sync(0xffffffffu, u.x && u.y && u.z && u.w)) break;
                    cut(n, 1 << 22);
                }
                asm volatile("st.shared.v4.u32 [%0], {%1,%2,%3,%4};" :: "r"(sm + C_KX + tid * 16), "r"(~u.x), "r"(~u.y), "r"(~u.z), "r"(~u.w) : "memory");
            }
            bar_sync(8, 256);
            PPROF(2);
            uint32_t m = 0;
#pragma unroll
            for (int i = 0; i < 5; i++) {
                uint32_t t[2], u[2];
                lds64(t, sm + C_KX + lane * 8 + i * 256); lds64(u, sm + C_KX + 1280 + lane * 8 + i * 256);
                u[0] = add2(u[0], 0x3f803f80u); u[1] = add2(u[1], 0x3f803f80u);
                m = amax2(amax2(amax2(amax2(m, t[0]), u[0]), t[1]), u[1]);
#pragma unroll
                for (int q = 0; q < 3; q++)
                    if (q < nq) *(uint2*)(g_h + (row + q * 768) * DM + lane * 4 + i * 128) = make_uint2(add2(mul2(xv[q][2 * i], u[0]), t[0]), add2(mul2(xv[q][2 * i + 1], u[1]), t[1]));
            }
            asm volatile("st.shared.u32 [%0], %1;" :: "r"(sm + C_LAG), "r"((amax_warp(m) >> 7) + 1) : "memory");
            bar_sync(8, 256);
            if (tid == 0) flag_add(&g_flags.h);
            __syncwarp();
            bar_arrive(2, 288);
            PPROF(3);
            asm volatile("barrier.cluster.wait.aligned;" ::: "memory");
        }
        asm volatile("setmaxnreg.inc.sync.aligned.u32 %0;" :: "n"(REG_P));
        uint32_t wa[40][4];
        mbar_wait(sm + CB_W, 0);
#pragma unroll
        for (int ks = 0; ks < 40; ks++)
            ldsm4t(wa[ks], sm + ((wg == 0) == (ks < 20) ? C_WV : C_WO) + ((mi >> 1) * 8 + r) * 128 + (((2 * w + (mi & 1)) ^ r) << 4) + (ks % 20 / 4 * 8 + 4 * wg + (ks & 3)) * 2048);
        PPROF(5);
        bar_arrive(1, 288);
        const uint32_t qst = opaque(sm + (wg == 0 ? C_QM : C_KM) + (2 * w + (mi & 1)) * 128 + r * 16);
        const uint32_t vrd = opaque(sm + C_WV + ((mi >> 1) * 8 + r) * 128 + (((2 * w + (mi & 1)) ^ r) << 4) + 4 * wg * 2048);
        const uint32_t mrd = opaque(memrd + wg * 1024);
        float acc[16];
        auto fb = [&](int n) { return mrd + (n >> 1) * 2048 + (n & 1) * 512; };
        auto fa = [&](int k) { return vrd + (k >> 2) * 16384 + (k & 3) * 2048; };
        auto qk_out = [&](int n) {
            uint8_t* rec = g_att + (n * NH + head) * AT_REC;
            w_bulk_s2g(rec + j * 8192, sm + C_QX, 8192); w_bulk_s2g(rec + AT_KM + j * 1024, sm + C_KM, 1024);
            BULK_COMMIT();
        };
        for (int s = -1;; s++) {
          if (s >= 0) {
            x_part(acc, wa, sm, s, wg, w, opaque(mrd) >> 4 & 31, s + ar.D2);
            if (s == 0) mbar_wait(sm + CB_W2, 0);
            uint32_t b[3][4], a[4][4];
#pragma unroll
            for (int i = 0; i < APRE; i++) ldsm4t(a[i], fa(4 + i));
            cut(s + ar.D2, 0);
            bar_sync(1, 384);
            if (warp == 0) { PROF(0); PROFG(24); }
            float dv[4] = {0, 0, 0, 0};
            const uint32_t xb = mrd - wg * 1024 - (C_MEM - C_VP) + w * 512;
            {
                float d[2][4] = {{0, 0, 0, 0}, {0, 0, 0, 0}}, g[2][4] = {{0, 0, 0, 0}, {0, 0, 0, 0}};
                ldsm4t(b[0], fb(0)); pin0(mrd); ldsm4t(b[1], fb(1)); pin0(mrd);
#pragma unroll
                for (int n = 0; n < 10; n++) {
                    const int c1 = n >= 10 - NCH;
                    if (n < 8) ldsm4t(b[(n + 2) % 3], fb(n + 2));
                    if (n < 2 && 2 * n >= APRE) { ldsm4t(a[2 * n], fa(4 + 2 * n)); ldsm4t(a[2 * n + 1], fa(5 + 2 * n)); }
#pragma unroll
                    for (int e = 0; e < 2; e++) {
                        mma16q(g[e & c1], wa[20 + 2 * n + e], b[n % 3][2 * e], b[n % 3][2 * e + 1]); mma16q(d[e & c1], wa[2 * n + e], b[n % 3][2 * e], b[n % 3][2 * e + 1]);
                        if (n >= 2 && n < 10 - VT) mma16q(dv, a[(2 * n + e) & 3], b[n % 3][2 * e], b[n % 3][2 * e + 1]);
                        if (n >= 2 && n < 8) ldsm4t(a[(2 * n + e) & 3], fa(2 * n + 4 + e));
                    }
                    if (QCUT >> n & 1) cut(s + ar.D2, 1 + n);
                }
                const float un = __uint_as_float(lds32(sm + C_UN));
                sts128f(xb - 4096 + wg * 2048, g[0][0] + g[1][0], g[0][1] + g[1][1], g[0][2] + g[1][2], g[0][3] + g[1][3]);
#pragma unroll
                for (int k = 20 - 2 * VT; k < 20; k++) mma16q(dv, a[k & 3], b[k / 2 % 3][2 * (k & 1)], b[k / 2 % 3][2 * (k & 1) + 1]);
                if (PBAR) bar_sync(10 + w, 64); else bar_sync(8, 256);
                const float4 z = lds128f(xb - 4096 + (wg ^ 1) * 2048);
                sts128f(xb + wg * 2048, dv[0], dv[1], dv[2], dv[3]);
                stsm2t(qst, pack2((d[0][0] + d[1][0] + z.x) * un, (d[0][1] + d[1][1] + z.y) * un), pack2((d[0][2] + d[1][2] + z.z) * un, (d[0][3] + d[1][3] + z.w) * un));
            }
            bar_arrive(2, 384);
            if (w == 0) PROF(1 + wg);
            if (s + 1 == NSEG) break;
          }
          if (!STL && warp == 3 && s >= 0)
              asm volatile(ELECTED("st.relaxed.gpu.global.u32 [%0], %1;") :: "l"(g_stamp + (s & 3) * 384 + (blk >> 3) * 32 + (blk & 7)), "r"((gtime() & ~31u) | ((s >> 2) + 1)) : "memory");
          PROXY_FENCE();
          mbar_wait(sm + CB_XF, (s + 1) & 1);
          if (s >= 0) bar_sync(7, 384);
          WG_FENCE();
#pragma unroll
          for (int i = 0; i < 16; i++) acc[i] = 0.f;
#pragma unroll
          for (int i = 1; i <= XA; i++) x_chunk(acc, wa, x_base(wg, s + ar.D2, 20), 20, i, i == 1);
          WG_COMMIT();
          if (warp == FW && s > 0) seg_done(s - 1, head);
          if (!WLATE) WG_WAIT(0);
          if (s >= 0) {
            if (warp == 0) {
                PROF(7);
                if (elect()) x_rest(mp, sm, s + 1);
            } else {
                if (wg == 1) {
                    if (w == 1) {
                        if (QDEL) wait_until(clock() + QDEL);
                        qk_out(s);
                    }
                    if (w == 2 && blk < 10 && s + 3 < NSEG)
                        asm volatile(ELECTED("cp.async.bulk.prefetch.L2.global [%0], 4096;") :: "l"((const uint8_t*)g_h + (s + 3) * (SEG * DM * 2) + blk * 4096) : "memory");
                } else if (w == 3) {
                    if (SPOLL) wait_until(clock() + SPOLL);
                    const uint32_t l = opaque(mrd) >> 4 & 31, tag = (s >> 2) + 1, now = gtime();
                    const uint32_t* sp = g_stamp + (s & 3) * 384 + (l >> 3) * 32 + (l & 7);
                    uint32_t t[3];
                    for (int n = 0;; n++) {
#pragma unroll
                        for (int i = 0; i < 3; i++) t[i] = ld_rlx(sp + i * 128);
                        if (!__any_sync(0xffffffffu, ((t[0] ^ tag) | (t[1] ^ tag) | (t[2] ^ tag)) & 31) || n > SPIN_LIMIT) break;
                    }
                    int all = -(1 << 30), own = all;
#pragma unroll
                    for (int i = 0; i < 3; i++) { const int d = t[i] - now; all = max(all, d); if ((i * 32 + l) / 3 == head) own = d; }
                    const int lag = min(__reduce_max_sync(0xffffffffu, all) - __reduce_max_sync(0xffffffffu, own), s || STL == 1 ? 8000 : 200);
                    PROFV(15, lag);
                    asm volatile("st.shared.u32 [%0], %1;" :: "r"(sm + C_LAG), "r"(D1 + ((lag * DG) >> 4)) : "memory");
                    bar_arrive(6, 160);
                } else if (w == 2) {
                    if ((s & 3) == 3) w_flag_wait(&g_flags.v[((s + 1) >> 2) * 32 + head], 2);
                    if (elect()) { mbar_expect(sm + CB_VX, 4096); bulk_g2s(sm + C_VX, g_att + ((s + 1) * NH + head) * AT_REC + AT_V + j * 4096, 4096, sm + CB_VX); }
                    if ((s & 3) == 1 && s + 3 < NSEG && blk == 20) asm volatile(ELECTED("cp.async.bulk.prefetch.L2.global [%0], 128;") :: "l"(&g_flags.v[((s + 3) >> 2) * 32]) : "memory");
                    if (s + 2 < NSEG && ((s & 3) != 2 || __all_sync(0xffffffffu, ld_rlx(&g_flags.v[((s + 2) >> 2) * 32 + head]) >= 2)))
                    {
                        if (VPF == 0) asm volatile("prefetch.global.L2 [%0];" :: "l"(g_att + ((s + 2) * NH + head) * AT_REC + AT_V + j * 4096 + (opaque(mrd) << 3 & 0xf80)));
                        if (VPF == 1) asm volatile(ELECTED("cp.async.bulk.prefetch.L2.global [%0], 4096;") :: "l"(g_att + ((s + 2) * NH + head) * AT_REC + AT_V + j * 4096) : "memory");
                    }
                }
            }
          }
          if (WLATE) WG_WAIT(0);
        }
        PROXY_FENCE();
        bar_sync(8, 256);
        if (warp == 5) { qk_out(NSEG - 1); BULK_WAIT(); }
        if (warp == 7) seg_done(NSEG - 2, head);
        const int t2 = (opaque(mrd) >> 4 & 31) + warp * 32;
        EPT(t2 == 0, 0);
        last_blocks(ar, sm, blk, t2);
        mod_tail(ar, sm + E_B, sm + EB_REL, blk, t2);
    } else {
        asm volatile("setmaxnreg.dec.sync.aligned.u32 %0;" :: "n"(REG_L));
        asm volatile("barrier.cluster.arrive.relaxed.aligned;" ::: "memory");
        if (blk < 80) {
            const int t = tid - 256;
#pragma unroll 1
            for (int i = 0; i < 10; i++)
                asm volatile("cp.async.cg.shared.global.L2::128B [%0], [%1], 16;" :: "r"(sm + C_XR + i * 2048 + t * 16), "l"(ar.wmod + ((t >> 1) + 64 * i) * (6 * DM) + blk * 16 + (t & 1) * 8) : "memory");
            float cs[5];
#pragma unroll
            for (int i = 0; i < 5; i++) cs[i] = __uint_as_float((uint32_t)__ldg((const unsigned short*)ar.c + t + 128 * i) << 16);
#pragma unroll
            for (int i = 0; i < 5; i++) asm volatile("st.shared.f32 [%0], %1;" :: "r"(sm + C_QX + (t + 128 * i) * 4), "f"(bfr(__fdividef(cs[i], 1.f + __expf(-cs[i])))) : "memory");
            asm volatile("cp.async.wait_all;" ::: "memory");
            bar_sync(3, 128);
            float a0 = 0, a1 = 0;
#pragma unroll 8
            for (int i = 0; i < 40; i++) {
                const float f = __uint_as_float(lds32(sm + C_QX + (t >> 3) * 4 + i * 64));
                const uint32_t u = lds32(sm + C_XR + t * 4 + i * 512);
                a0 += f * lo_f(u); a1 += f * hi_f(u);
            }
#pragma unroll
            for (int o = 8; o < 32; o <<= 1) { a0 += __shfl_xor_sync(0xffffffffu, a0, o); a1 += __shfl_xor_sync(0xffffffffu, a1, o); }
            asm volatile("st.shared.v2.f32 [%0], {%1,%2};" :: "r"(sm + C_QM + w * 64 + (lane & 7) * 8), "f"(a0), "f"(a1) : "memory");
            bar_sync(3, 128);
            if (w == 0) {
#pragma unroll
                for (int i = 1; i < 4; i++) { const float2 z = lds64f(sm + C_QM + i * 64 + (lane & 7) * 8); a0 += z.x; a1 += z.y; }
                const uint32_t v = pack2(a0, a1);
                asm volatile("st.relaxed.gpu.global.u32 [%0], %1;" :: "l"(g_flags.mod1 + blk * 8 + (lane & 7)), "r"(~v) : "memory");
            }
        }
        uint32_t m0[5][4], mm = 0;
#pragma unroll
        for (int i = 0; i < 20; i++) {
            const unsigned short* p = (const unsigned short*)ar.mem0 + (i & 3) * 2 * DM + (i >> 2) * 128 + tid - 256;
            m0[i >> 2][i & 3] = __ldg(p) | (uint32_t)__ldg(p + DM) << 16;
        }
        {
            asm volatile("barrier.cluster.wait.aligned;" ::: "memory");
            if (w == 3) {
                w_flag_wait(&g_flags.h, 96);
                if (elect()) { x_fill(mp, sm, 0, j); x_rest(mp, sm, 0); }
                __syncwarp();
            }
            if (w == 1) {
                const uint64_t ef = policy_stream();
#pragma unroll 1
                for (int c = 0; c < 2 * WP + 2; c++) {
                    const uint32_t bar = sm + EB_B + 8 * (c & 1);
                    if (c == WPOS) bar_sync(2, 288);
                    if (c >= 2) mbar_wait(bar, (c / 2 - 1) & 1);
                    if (elect()) {
                        if (c < 2 * WP) { mbar_expect(bar, 81920 / WP); tma2d_ef(sm + C_WV + c * (81920 / WP), c < WP ? &mp.wq : &mp.wk, col0, c % WP * (640 / WP), bar, ef); }
                        if (c >= WOPF && c < WOPF + 3) asm volatile("cp.async.bulk.prefetch.tensor.3d.L2.global [%0, {0, %1, %2}];" :: "l"((uint64_t)&mp.wo), "r"(head * DH + (c - WOPF) * 64), "r"(7 * j) : "memory");
                    }
                    __syncwarp();
                }
                if (elect()) mbar_arrive(sm + CB_W);
                bar_sync(1, 288);
                if (elect()) {
                    mbar_expect(sm + CB_W2, 81920); mbar_expect(sm + CB_W3, 3 * WO_BLK);
#pragma unroll 1
                    for (int c = 0; c < 4; c++) tma2d(sm + C_WV + c * 20480, &mp.wv, col0, c * 160, sm + CB_W2);
#pragma unroll 1
                    for (int c = 0; c < 3; c++) tma3d(sm + C_WO + c * WO_BLK, &mp.wo, head * DH + (j + c) % 3 * 64, 7 * j, sm + CB_W3);
                }
                __syncwarp();
                w_flag_wait(&g_flags.v[head], 2);
                if (elect()) { mbar_expect(sm + CB_VX, 4096); bulk_g2s(sm + C_VX, g_att + head * AT_REC + AT_V + j * 4096, 4096, sm + CB_VX); }
            } else {
                uint32_t mw = 0;
#pragma unroll 1
                for (int c = 0; c < 2; c++) {
                    mbar_wait(sm + (c ? CB_W3 : CB_W2), 0);
                    uint32_t m = 0;
                    const uint32_t end = sm + (c ? C_XR : C_WO);
#pragma unroll 1
                    for (uint32_t a = sm + c * C_WO + (w - (w > 0)) * 4096 + lane * 16; a < end; a += 3 * 4096) {
                        float4 z[8];
#pragma unroll
                        for (int i = 0; i < 8; i++) z[i] = lds128f(a + i * 512);
#pragma unroll
                        for (int i = 0; i < 8; i++) m = amax2(amax2(amax2(amax2(m, __float_as_uint(z[i].x)), __float_as_uint(z[i].y)), __float_as_uint(z[i].z)), __float_as_uint(z[i].w));
                    }
                    mw |= amax_warp(m) << (16 * c);
                }
                asm volatile("st.shared.u32 [%0], %1;" :: "r"(sm + C_KM + w * 4), "r"(mw) : "memory");
                bar_sync(3, 96);
                if (w == 0) asm volatile("st.relaxed.gpu.global.u32 [%0], %1;" :: "l"(g_flags.wmax + blk), "r"(amax2(amax2(mw, lds32(sm + C_KM + 8)), lds32(sm + C_KM + 12)) | 0x8000) : "memory");
            }
        }
        bar_sync(9, 384);
#pragma unroll
        for (int i = 0; i < 5; i++) {
            asm volatile("st.shared.v4.u32 [%0], {%1,%2,%3,%4};" :: "r"(sm + C_MEM + (tid - 256 + i * 128) * 16), "r"(m0[i][0]), "r"(m0[i][1]), "r"(m0[i][2]), "r"(m0[i][3]) : "memory");
            mm = amax2(amax2(amax2(amax2(mm, m0[i][0]), m0[i][1]), m0[i][2]), m0[i][3]);
        }
        asm volatile("st.shared.u32 [%0], %1; st.shared.u32 [%2], 0x3f800000;" :: "r"(sm + C_MX + w * 4), "r"(amax_warp(mm)), "r"(sm + C_UN) : "memory");
        int ew = __shfl_sync(0xffffffffu, lds32(sm + C_LAG), 0), es = 0;
        const uint32_t rb1 = (uint32_t)((j + 1) % 3 - j) << 24, rb2 = (uint32_t)((j + 2) % 3 - j) << 24;
        const float scale = 0.07216878364870322f;
        uint32_t va[8][4], mr = memrd;
#pragma unroll
        for (int i = 0; i < 8; i++) ldsm4t(va[i], sm + C_WV + ((mi >> 1) * 8 + r) * 128 + (((2 * w + (mi & 1)) ^ r) << 4) + i * 2048);
        bar_sync(1, 384);
        for (int s = 0; s < NSEG; s++) {
            const float un = __uint_as_float((127 - es) << 23);
            if (w == 1) {
                mbar_wait(sm + CB_XD, s & 1);
                if (s + 1 < NSEG) { if (elect()) x_fill(mp, sm, s + 1, j); }
                else { if (BPOS != 2) wo_half(mp, sm, blk, 0); if (BPOS != 0) wo_half(mp, sm, blk, 1); }
            }
            if (STL == 2 && w == 3) asm volatile(ELECTED("st.relaxed.gpu.global.u32 [%0], %1;") :: "l"(g_stamp + (s & 3) * 384 + (blk >> 3) * 32 + (blk & 7)), "r"((gtime() & ~31u) | ((s >> 2) + 1)) : "memory");
            const uint32_t l0 = mr >> 4 & 31, r0 = l0 & 7, m0 = l0 >> 3;
            float vd[4];
            {
                uint32_t c[4][4];
#pragma unroll
                for (int i = 0; i < 4; i++) ldsm4t(c[i], mr + i * 512);
                float d[2][4] = {{0, 0, 0, 0}, {0, 0, 0, 0}};
#pragma unroll
                for (int i = 0; i < 8; i++) mma16q(d[i & 1], va[i], c[i >> 1][2 * (i & 1)], c[i >> 1][2 * (i & 1) + 1]);
#pragma unroll
                for (int i = 0; i < 4; i++) vd[i] = d[0][i] + d[1][i];
            }
            uint32_t zr = 0;
            if (w == 2)
                asm volatile("atom.relaxed.gpu.global.exch.b32 %0, [%1], 0;" : "=r"(zr)
                    : "l"(g_acc + ((s & 2) ^ 2) * (ACC_PAIR / 2) + (s & 1) * 512 + (blk >> 2) * 1024 + (blk & 3) * 128 + l0 * 4) : "memory");
            __syncwarp();
            uint32_t kb[4][4] = {};
            {
                const uint32_t k7 = r0 ^ (m0 << 2 & 4), kxrd = sm + C_KX + (16 * (w & 1) + 8 * (m0 & 1) + k7) * 128 + (((m0 >> 1) ^ k7) << 4);
#pragma unroll
                for (int i = 0; i < 4; i++) if (w >= 2) ldsm4(kb[i], kxrd ^ (i << 5));
            }
            const uint32_t qrd = sm + C_QM + (w == 1 ? (m0 & 1) * 2 + (m0 >> 1) : m0) * 128 + r0 * 16;
            const uint32_t scdst = sm + C_SC + j * 1280 + (w == 1 ? 1024 + l0 * 8 : (w & 1) * 512 + (l0 & 2) * 128 + (l0 >> 2) * 32 + (l0 & 1) * 16);
            const uint32_t scrd = sm + C_SC + (l0 >> 4) * 256 + (l0 & 3) * 32 + (l0 >> 2 & 3) * 8;
            const uint32_t v7 = (4 * (m0 & 1) + (r0 >> 1)) ^ (r0 << 2 & 4), vxrd = sm + C_VX + (16 * (m0 >> 1) + 8 * (r0 & 1) + v7) * 128 + (((2 * w) ^ v7) << 4);
            if (s == 0) {
                uint32_t t[3];
                for (int n = 0;; n++) {
#pragma unroll
                    for (int i = 0; i < 3; i++) t[i] = ld_rlx(g_flags.wmax + l0 + 32 * i);
                    if (__all_sync(0xffffffffu, t[0] && t[1] && t[2])) break;
                    cut(n, 1 << 22);
                }
                const uint32_t m = amax2(amax2(amax2(0, t[0]), t[1]), t[2]);
                const int e = 371 - (int)(__reduce_max_sync(0xffffffffu, m & 0xffffu) >> 7) - (int)(__reduce_max_sync(0xffffffffu, m >> 16) >> 7);
                ew = e << 16 | (min(e - ew, 100) & 0xffff);
            }
            mbar_wait(sm + CB_VX, s & 1);
            uint32_t vb[2][4];
            ldsm4t(vb[0], vxrd); ldsm4t(vb[1], vxrd ^ 16);
            const uint32_t word = sm + C_WO + (m0 & 1) * 4096 + ((m0 >> 1) * 8 + r0) * 64 + ((w ^ (r0 >> 1)) << 4);
            const uint32_t word6 = word + 6 * 4096 - (m0 & 1) * 3072;
            const uint32_t oxrd = sm + C_OX + l0 * 8;
            const uint32_t ord = oxrd + w * 256;
            const uint32_t vp = mr - (C_MEM - C_VP) + w * 512, vmst = mr + (C_VM - C_MEM) + w * 256;
            pin(mr, scdst + rb1, sm + CB_SC + rb1, scdst + rb2, sm + CB_SC + rb2); pin(mr, qrd, scdst, scrd, vp); pin(mr, word, word6, oxrd, ord);
            pin(mr, __float_as_uint(vd[0]), __float_as_uint(vd[1]), __float_as_uint(vd[2]), __float_as_uint(vd[3]));
            bar_sync(2, 384);
            const bool odd = mr & 16;
            float4 y0, y1, mx4;
            if (s + 1 == NSEG) {
                y0 = lds128f(vp); y1 = lds128f(vp + 2048);
                stsm2t(vmst, pack2((vd[0] + y0.x + y1.x) * un, (vd[1] + y0.y + y1.y) * un), pack2((vd[2] + y0.z + y1.z) * un, (vd[3] + y0.w + y1.w) * un));
                PROXY_FENCE();
                bar_sync(3, 128);
                if (w == 1) { w_bulk_s2g(g_att + (s * NH + head) * AT_REC + AT_VM + j * 1024, sm + C_VM, 1024); BULK_COMMIT(); BULK_WAIT(); }
                break;
            }
            {
                uint32_t qa[2][4];
                ldsm4(qa[0], qrd); ldsm4(qa[1], qrd + 512);
                float sc[2][4] = {{0, 0, 0, 0}, {0, 0, 0, 0}};
                if (w == 1) {
                    ldsm4(kb[0], mr + (C_KM - C_MEM)); ldsm4(kb[1], mr + (C_KM - C_MEM) + 512);
                    pin0(mr); y0 = lds128f(vp); y1 = lds128f(vp + 2048); mx4 = lds128f(sm + C_MX);
#pragma unroll
                    for (int k = 0; k < 4; k++) mma16q(sc[k & 1], qa[k >> 1], kb[k >> 1][2 * (k & 1)], kb[k >> 1][2 * (k & 1) + 1]);
                    const uint32_t a0 = __float_as_uint(sc[0][0] + sc[1][2]), a1 = __float_as_uint(sc[0][1] + sc[1][3]);
                    if (B7E) { pin(mr, a0, a1, __float_as_uint(y1.x), 0); bar_arrive(7, 384); }
                    send8(scdst + rb1, sm + CB_SC + rb1, a0, a1); send8(scdst + rb2, sm + CB_SC + rb2, a0, a1);
                    asm volatile("st.shared.v2.u32 [%0], {%1,%2};" :: "r"(scdst), "r"(a0), "r"(a1) : "memory");
                } else {
                    pin0(mr); y0 = lds128f(vp); y1 = lds128f(vp + 2048); mx4 = lds128f(sm + C_MX);
                    if (!w) {
                        if (B7E) { pin(mr, __float_as_uint(y1.x), 0, 0, 0); bar_arrive(7, 384); }
                        if (STL == 1) asm volatile(ELECTED("st.relaxed.gpu.global.u32 [%0], %1;") :: "l"(g_stamp + (s & 3) * 384 + (blk >> 3) * 32 + (blk & 7)), "r"((gtime() & ~31u) | ((s >> 2) + 1)) : "memory");
                    } else {
#pragma unroll
                        for (int k = 0; k < 4; k++) mma16q(sc[k & 1], kb[k], qa[k >> 1][2 * (k & 1)], qa[k >> 1][2 * (k & 1) + 1]);
                        const float a0 = sc[0][0] + sc[1][0], a1 = sc[0][2] + sc[1][2], a2 = sc[0][1] + sc[1][1], a3 = sc[0][3] + sc[1][3];
                        if (B7E) { pin(mr, __float_as_uint(a0), __float_as_uint(y1.x), 0, 0); bar_arrive(7, 384); }
                        send16(scdst + rb1, sm + CB_SC + rb1, a0, a1, a2, a3); send16(scdst + rb2, sm + CB_SC + rb2, a0, a1, a2, a3);
                        sts128f(scdst, a0, a1, a2, a3);
                    }
                }
            }
            if (!B7E) bar_arrive(7, 384);
            __syncwarp();
            if (elect()) mbar_arrive(sm + CB_SC);
            {
                const float4 z = mx4;
                const int em = (int)(max(max(__float_as_uint(z.x), __float_as_uint(z.y)), max(__float_as_uint(z.z), __float_as_uint(z.w))) >> 7) - es;
                es = __shfl_sync(0xffffffffu, max(min((ew >> 16) - em, (int)(short)ew), -120), 0);
            }
            if (w == 0) PROF(4);
            const uint32_t vm0 = pack2((vd[0] + y0.x + y1.x) * un, (vd[1] + y0.y + y1.y) * un), vm1 = pack2((vd[2] + y0.z + y1.z) * un, (vd[3] + y0.w + y1.w) * un);
            stsm2t(vmst, vm0, vm1);
            cut(s + ar.D2, 0);
            mbar_wait(sm + CB_SC, s & 1);
            if (w == 0) PROF(8);
            float sv[10];
            {
                float2 z[5][3];
#pragma unroll
                for (int u = 0; u < 5; u++)
#pragma unroll
                    for (int p = 0; p < 3; p++) z[u][p] = lds64f((u < 4 ? scrd + (u >> 1) * 512 + (u & 1) * 128 : oxrd + (C_SC - C_OX) + 1024) + p * 1280);
#pragma unroll
                for (int u = 0; u < 5; u++) { sv[2 * u] = (z[u][0].x + z[u][1].x) + z[u][2].x; sv[2 * u + 1] = (z[u][0].y + z[u][1].y) + z[u][2].y; }
            }
            float mx = fmaxf(fmaxf(fmaxf(sv[0], sv[1]), fmaxf(sv[2], sv[3])), fmaxf(fmaxf(fmaxf(sv[4], sv[5]), fmaxf(sv[6], sv[7])), fmaxf(sv[8], sv[9])));
            uint32_t a[NRING][4];
            auto frag = [&](int i) { const int p = i / 7, u = i % 7, o = (p >> 1) * WO_BLK + (p & 1) * 2048;
                                     return u == 3 ? word6 + o : word + o + (u > 3 ? 1024 + (u - 4) * 8192 : u * 8192); };
            mx = fmaxf(fmaxf(mx, __shfl_xor_sync(0xffffffffu, mx, 1)), fmaxf(__shfl_xor_sync(0xffffffffu, mx, 2), __shfl_xor_sync(0xffffffffu, mx, 3)));
            pin(mr, __float_as_uint(mx), 0, 0, 0);
            {
#pragma unroll
                for (int i = 0; i < NPRE; i++) ldsm4t(a[i], frag(i));
                pin0(mr);
                const float sl2e = scale * 1.4426950408889634f, mxl = mx * sl2e;
#pragma unroll
                for (int i = 9; i >= 0; i--) asm volatile("ex2.approx.ftz.f32 %0, %1;" : "=f"(sv[i]) : "f"(fmaf(sv[i], sl2e, -mxl)));
                const uint32_t pq[4] = {pack2(sv[0], sv[1]), pack2(sv[4], sv[5]), pack2(sv[2], sv[3]), pack2(sv[6], sv[7])}, pm = pack2(sv[8], sv[9]);
                if (w == 0) PROF(6);
                float o[2][4] = {{0, 0, 0, 0}, {0, 0, 0, 0}}, o2[2][4] = {{0, 0, 0, 0}, {0, 0, 0, 0}}, sx[4] = {0, 0, 0, 0};
                mma8(sx, pm, 0, 0x3f803f80u); mma8(o[0], pm, 0, vm0); mma8(o[1], pm, 0, vm1);
                mma16q(sx, pq, 0x3f803f80u, 0x3f803f80u);
#pragma unroll
                for (int u = 0; u < 2; u++) { mma16q(o[u], pq, vb[u][0], vb[u][1]); mma16q(o2[u], pq, vb[u][2], vb[u][3]); }
                float inv; asm("rcp.approx.ftz.f32 %0, %1;" : "=f"(inv) : "f"((sx[0] + sx[2]) * __uint_as_float((127 - es) << 23)));
                const uint32_t f0 = pack2((o[0][0] + o2[0][2]) * inv, (o[0][1] + o2[0][3]) * inv), f1 = pack2((o[1][0] + o2[1][2]) * inv, (o[1][1] + o2[1][3]) * inv);
                send8(ord + 2048 + rb1, sm + CB_OX + rb1, f0, f1); send8(ord + 1024 + rb2, sm + CB_OX + rb2, f0, f1);
                asm volatile("st.shared.v2.u32 [%0], {%1,%2};" :: "r"(ord), "r"(f0), "r"(f1) : "memory");
            }
            if (w == 0) PROF(10);
#pragma unroll
            for (int i = NPRE; i < NRING; i++) ldsm4t(a[i], frag(i));
            bar_sync(3, 128);
            float e[5][4];
#pragma unroll
            for (int q = 0; q < 5; q++) e[q][0] = e[q][1] = e[q][2] = e[q][3] = 0.f;
            constexpr int LAG = 2;
            uint8_t* pdst = g_acc + ((s & 2) * (ACC_PAIR / 2) + (s & 1) * 512 + w * 2048 + j * 8192 - C_MEM - sm + mr);
#pragma unroll
            for (int h = 0; h < 3; h++) {
                uint32_t ob[4][2];
                if (h == 1) {
#pragma unroll
                    for (int i = 14 - LAG; i < 14; i++) ldsm4t(a[i % NRING], frag(i + NRING));
                    pin(mr, zr, (uint32_t)(uint64_t)pdst, (uint32_t)((uint64_t)pdst >> 32), 0);
                    mbar_wait(sm + CB_OX, s & 1);
                    if (w == 0) PROF(9);
                }
#pragma unroll
                for (int k = 0; k < 4; k++) lds64(ob[k], oxrd + h * 1024 + k * 256);
#pragma unroll
                for (int i = 14 * h; i < 14 * h + 14; i++) {
                    const int u = i % 7, k = 2 * (i / 7 & 1);
                    if (u == 3) { mma16q(e[3], a[i % NRING], ob[k][0], ob[k][1]); mma16q(e[4], a[i % NRING], ob[k + 1][0], ob[k + 1][1]); }
                    else mma16q(e[u & 3], a[i % NRING], ob[k + (u >> 2)][0], ob[k + (u >> 2)][1]);
                    if (i == B5AT) { pin(mr, a[i % NRING][0], a[i % NRING][1], a[i % NRING][2], a[i % NRING][3]); bar_arrive(5, 384); }
                    if (i >= LAG && !(i >= 14 && i < 14 + LAG) && i - LAG + NRING < 42) ldsm4t(a[(i - LAG) % NRING], frag(i - LAG + NRING));
                }
            }
            {
                const uint32_t w6 = pack2h(e[3][0] + e[4][2], e[3][1] + e[4][3]), one = 0x3c003c00u;
                asm volatile("red.relaxed.gpu.global.add.noftz.v4.f16x2 [%0], {%1,%2,%3,%4};"
                    :: "l"(pdst), "r"(pack2h(e[0][0], e[0][1])), "r"(pack2h(e[0][2], e[0][3])), "r"(pack2h(e[1][0], e[1][1])), "r"(odd ? w6 : one) : "memory");
                asm volatile("red.relaxed.gpu.global.add.noftz.v4.f16x2 [%0], {%1,%2,%3,%4};"
                    :: "l"(pdst + 1024), "r"(pack2h(e[1][2], e[1][3])), "r"(pack2h(e[2][0], e[2][1])), "r"(pack2h(e[2][2], e[2][3])), "r"(odd ? one : w6) : "memory");
            }
            const uint32_t tw = clock();
            if (w == 0) { PROF(14); PROFG(25); }
            PROXY_FENCE();
            bar_sync(6, 160);
            mr = opaque(mr);
            const uint32_t ln = mr >> 4 & 31, due = tw + lds32(sm + C_LAG);
            const uint32_t vr = sm + C_WV + ((ln >> 4) * 8 + (ln & 7)) * 128 + (((2 * w + (ln >> 3 & 1)) ^ (ln & 7)) << 4);
            const uint32_t ms0 = sm + C_MEM + w * 128 + (ln & 7) * 16 + (ln >> 3) * 512, ms1 = ms0 + (ln < 24 ? 2048 : 1536);
            if (BPOS == 2 && w == 0 && s + 2 == NSEG) wo_half(mp, sm, blk, 0);
            if (w == 2) { w_expect(sm + CB_SC, 2560); w_expect(sm + CB_OX, 2048); asm volatile("st.shared.u32 [%0], %1;" :: "r"(sm + C_UN), "r"((127 - es) << 23) : "memory"); }
            if (w == 0) { w_bulk_s2g(g_att + (s * NH + head) * AT_REC + AT_VM + j * 1024, sm + C_VM, 1024); BULK_COMMIT(); }
            const uint8_t* src = pdst - j * 8192;
            pin(mr, ms0, ms1, (uint32_t)(uint64_t)src, (uint32_t)((uint64_t)src >> 32));
            pin(mr, vr, due, 0, 0);
            cut(s + ar.D2, 1);
#pragma unroll
            for (int i = 0; i < 8; i++) ldsm4t(va[i], vr + i * 2048);
            wait_until(due);
            if (w == 0) { PROF(5); PROFG(26); }
            uint4 v[6];
            auto fetch = [&]() {
#pragma unroll
                for (int k = 0; k < 6; k++)
                    asm volatile("ld.relaxed.gpu.global.v4.u32 {%0,%1,%2,%3}, [%4];" : "=r"(v[k].x), "=r"(v[k].y), "=r"(v[k].z), "=r"(v[k].w) : "l"(src + (k >> 1) * 8192 + (k & 1) * 1024) : "memory");
            };
            fetch();
            PROFV(20 + w, 0);
            bar_sync(9, 384);
            uint32_t cv[3][7];
#pragma unroll 1
            for (int n = 0; __any_sync(0xffffffffu, ~((odd ? v[1].w & v[3].w & v[5].w : v[0].w & v[2].w & v[4].w)) & 0x50005000u); n++) {
                PROFV(20 + w, n + 1);
                cut(n, SPIN_LIMIT);
                fetch();
            }
#pragma unroll
            for (int k = 0; k < 3; k++) {
                const uint4 x = v[2 * k], y = v[2 * k + 1];
                const uint32_t u[7] = {x.x, x.y, x.z, y.x, y.y, y.z, k < 2 ? (odd ? x.w : y.w) : 0u};
#pragma unroll
                for (int i = 0; i < 7; i++) cv[k][i] = f16_to_bf16(u[i]);
                stsm4(ms0 + k * 3584, cv[k][0], cv[k][1], cv[k][2], cv[k][3]);
                if (k < 2) stsm4(ms1 + k * 3584, cv[k][4], cv[k][5], cv[k][6], cv[k][6]);
                else asm volatile("stmatrix.sync.aligned.m8n8.x2.shared.b16 [%0], {%1,%2};" :: "r"(ms1 + k * 3584), "r"(cv[k][4]), "r"(cv[k][5]) : "memory");
            }
            if (w == 0) PROF(16);
            bar_sync(1, 384);
            if (w == 0) BULK_WAIT();
            cut(s + ar.D2, 2);
            uint32_t mc = 0;
#pragma unroll
            for (int i = 0; i < 20; i++) mc = amax2(mc, cv[i / 7][i % 7]);
            asm volatile("st.shared.u32 [%0], %1;" :: "r"(sm + C_MX + w * 4), "r"(amax_warp(mc)) : "memory");
        }
        if (w >= 2) end_loads(mp, ar, sm, blk, w - 2);
        else if (w == 1) { bar_sync(5, 384); seg_done(NSEG - 1, head); EPT(true, 9); if (EORD) bar_arrive(6, 96); if (BPOS == 0) wo_half(mp, sm, blk, 1); }
        else bar_arrive(5, 384);
        if (w < 2) end_stores(mp, sm, blk, w);
        if (w == 0) { mbar_wait(sm + EB_REL, 0); flags_release(mr >> 4 & 31); }
    }
}

struct SideMaps { CUtensorMap h, wv, ost, o, wo, slab3, slab2, lnp[3]; };
constexpr int SD_ST = 14336, SD_NST = 12, SD_EPI = SD_NST * SD_ST, SD_PAR = SD_EPI + 2 * 24576, SD_BAR = SD_PAR + 6400, SD_SMEM = SD_BAR + 1024;
#define VLEAD 16
#define EARLY15 0
#define N_LIGHT 9
#define B_HELP 13
#define AUNR_ 2
constexpr int AUNR = AUNR_;
#define KSO 4
#define KSA 3
#define B_8 10
#define B_16 13
__device__ __forceinline__ int o_shift(int b) { return b >= B_16 ? 4 : b >= B_8 ? 3 : 2; }
__device__ __forceinline__ int o_split(int b) { return 1 << o_shift(b); }
__device__ __forceinline__ uint32_t o_done(int b) { return b >= B_LATE ? 160 : 4 << o_shift(b); }
__device__ __forceinline__ int next_item(int lane) {
    const int b0 = lane & 15, hi = lane >> 4;
    for (int n = 0;; n++) {
        const uint32_t w0 = ld_rlx(g_flags.qk + lane), w1 = ld_rlx(g_flags.at + lane), w2 = ld_rlx(&g_flags.c[0][0] + lane), w3 = ld_rlx(&g_flags.c[2][0] + lane), w4 = ld_rlx(&g_flags.seg[32]);
        const uint32_t o01 = __ballot_sync(0xffffffffu, lane && w2 < 32), o23 = __ballot_sync(0xffffffffu, b0 < (hi ? 14 : B_LATE) && w3 < 2u * o_split(b0));
        uint32_t ra = __ballot_sync(0xffffffffu, w0 >= (hi ? 64u : 96u));
        ra |= 0x7fffffffu >> __clz((ra & 0xffff) | 1);
        const uint32_t rb = __ballot_sync(0xffffffffu, w1 >= (hi ? o_done(b0) : 64u));
        const int bv = __ffs(o01 | 0x10000) - 1, ba = __ffs(o01 >> 16 | 0x10000) - 1, bo = __ffs(o23 | 0x10000) - 1, bl = __ffs(o23 >> 16 | 0x10000) - 1;
        if (bl == 16 && ba == 16) return -1;
        const int bc = __ffs(~ra | 0x10000) - 1;
        const bool last = ba == 15 && (w4 >= 3 || (EARLY15 && bc == 15));
        const bool r1 = (ra & ra >> 16) >> ba & 1, r2 = (rb & 0xffff) >> bo & 1, r3 = rb >> 16 >> bl & 1;
        const int kind = ba == 16 ? (bo < 16 ? 2 : 3) : last ? 1 :
                         blockIdx.x < N_LIGHT ? (r1 ? 1 : r3 ? 3 : bv < 16 ? 0 : -1) :
                         bv < 16 && (bv <= bc + VLEAD || !r2) ? 0 : r1 && ba >= B_HELP ? 1 : r2 ? 2 : r1 ? 1 : r3 ? 3 : bo < ba ? 2 : -1;
        if (kind < 0) { if (n > (1 << 20)) __trap(); __nanosleep(300); continue; }
        const int b = kind == 3 ? bl : kind == 2 ? bo : kind == 1 ? ba : bv;
        uint32_t i = 0;
        if (lane == 0) asm volatile("atom.relaxed.gpu.global.add.u32 %0, [%1], 1;" : "=r"(i) : "l"(&g_flags.c[kind][b]) : "memory");
        i = __shfl_sync(0xffffffffu, i, 0);
        if (i < (kind < 2 ? 32u : 2u * o_split(b))) return kind << 16 | b << 8 | i | ((kind == 1 ? r1 : kind == 2 ? r2 : r3) ? 128 : 0);
    }
}

template <int NP>
__device__ __forceinline__ void tile_out(const float (&acc)[8 * NP], uint32_t eb, uint32_t CH, uint32_t efull, uint32_t eempty, int& eph, int lane) {
    const int r = lane & 7, mi = lane >> 3, row = (mi & 1) * 8 + r;
    mbar_wait(eempty, eph); eph ^= 1;
#pragma unroll
    for (int p = 0; p < NP; p++) {
        const int oc = 2 * p + (mi >> 1);
        stsm4(eb + (oc >> 3) * CH + row * 128 + (((oc & 7) ^ r) << 4), pack2(acc[8 * p], acc[8 * p + 1]), pack2(acc[8 * p + 2], acc[8 * p + 3]),
              pack2(acc[8 * p + 4], acc[8 * p + 5]), pack2(acc[8 * p + 6], acc[8 * p + 7]));
    }
    asm volatile("fence.proxy.async.shared::cta;" ::: "memory");
    __syncwarp();
    if (lane == 0) mbar_arrive(efull);
}

template <int MT>
__device__ __forceinline__ void attn_tile(uint32_t base, uint32_t dst, uint32_t eempty, int eph, int lane) {
    constexpr int NK = MT ? 5 : 3;
    const int r = lane & 7, mi = lane >> 3, g = lane >> 2, t = lane & 3;
    float sc[NK][4];
#pragma unroll
    for (int n = 0; n < NK; n++) sc[n][0] = sc[n][1] = sc[n][2] = sc[n][3] = 0.f;
#pragma unroll AUNR
    for (int k2 = 0; k2 < 6; k2++) {
        const uint32_t cb = (k2 >> 1) * 8192, c0 = (k2 & 1) * 4;
        uint32_t a0[4], a1[4], bb[NK][4];
        ldsm4(a0, base + cb + (16 * MT + (mi & 1) * 8 + r) * 128 + (((c0 + (mi >> 1)) ^ r) << 4));
        ldsm4(a1, base + cb + (16 * MT + (mi & 1) * 8 + r) * 128 + (((c0 + 2 + (mi >> 1)) ^ r) << 4));
#pragma unroll
        for (int n = 0; n < NK; n++)
            ldsm4(bb[n], n < NK - 1 ? base + 4096 + cb + (8 * n + r) * 128 + (((c0 + mi) ^ r) << 4) : base + 36864 + k2 * 512 + lane * 16);
#pragma unroll
        for (int n = 0; n < NK; n++) mma16(sc[n], a0[0], a0[1], a0[2], a0[3], bb[n][0], bb[n][1]);
#pragma unroll
        for (int n = 0; n < NK; n++) mma16(sc[n], a1[0], a1[1], a1[2], a1[3], bb[n][2], bb[n][3]);
    }
    const float scale = 0.07216878364870322f, l2e = 1.4426950408889634f;
    float v[2][2 * NK], mx[2], sum[2];
#pragma unroll
    for (int hf = 0; hf < 2; hf++) {
        mx[hf] = -INFINITY;
#pragma unroll
        for (int n = 0; n < NK; n++) {
            uint32_t u = pack2(sc[n][2 * hf], sc[n][2 * hf + 1]);
            u = pack2(lo_f(u) * scale, hi_f(u) * scale);
            const int lim = 16 * MT + 8 * hf + g - 8 * n - 2 * t;
            v[hf][2 * n] = (n < NK - 1 && lim < 0) ? -1e9f : lo_f(u);
            v[hf][2 * n + 1] = (n < NK - 1 && lim < 1) ? -1e9f : hi_f(u);
            mx[hf] = fmaxf(mx[hf], fmaxf(v[hf][2 * n], v[hf][2 * n + 1]));
        }
    }
#pragma unroll
    for (int o = 1; o < 4; o <<= 1)
#pragma unroll
        for (int hf = 0; hf < 2; hf++) mx[hf] = fmaxf(mx[hf], __shfl_xor_sync(0xffffffffu, mx[hf], o));
#pragma unroll
    for (int hf = 0; hf < 2; hf++) {
        sum[hf] = 0;
#pragma unroll
        for (int q = 0; q < 2 * NK; q++) { asm("ex2.approx.ftz.f32 %0, %1;" : "=f"(v[hf][q]) : "f"((v[hf][q] - mx[hf]) * l2e)); sum[hf] += v[hf][q]; }
    }
#pragma unroll
    for (int o = 1; o < 4; o <<= 1)
#pragma unroll
        for (int hf = 0; hf < 2; hf++) sum[hf] += __shfl_xor_sync(0xffffffffu, sum[hf], o);
    uint32_t pa[NK][2];
#pragma unroll
    for (int hf = 0; hf < 2; hf++) {
        const float inv = __fdividef(1.f, sum[hf]);
#pragma unroll
        for (int n = 0; n < NK; n++) pa[n][hf] = pack2(v[hf][2 * n] * inv, v[hf][2 * n + 1] * inv);
    }
    mbar_wait(eempty, eph);
#pragma unroll AUNR
    for (int n4 = 0; n4 < 6; n4++) {
        const uint32_t cb = (n4 >> 1) * 4096, c0 = (n4 & 1) * 4;
        uint32_t bm[4], bb[2 + 2 * MT][4];
        ldsm4t(bm, base + AT_VM + n4 * 512 + lane * 16);
#pragma unroll
        for (int u = 0; u < 2 + 2 * MT; u++) ldsm4t(bb[u], base + AT_V + cb + (16 * (u >> 1) + 8 * (mi & 1) + r) * 128 + (((c0 + 2 * (u & 1) + (mi >> 1)) ^ r) << 4));
        float o[4][4];
#pragma unroll
        for (int u = 0; u < 4; u++) { o[u][0] = o[u][1] = o[u][2] = o[u][3] = 0.f; mma8(o[u], pa[NK - 1][0], pa[NK - 1][1], bm[u]); }
#pragma unroll
        for (int u = 0; u < 4 + 4 * MT; u++) mma16(o[u & 3], pa[u >> 2 << 1][0], pa[u >> 2 << 1][1], pa[(u >> 2 << 1) + 1][0], pa[(u >> 2 << 1) + 1][1], bb[u >> 1][2 * (u & 1)], bb[u >> 1][2 * (u & 1) + 1]);
#pragma unroll
        for (int p = 0; p < 2; p++)
            stsm4(dst + (n4 >> 1) * 2048 + ((mi & 1) * 8 + r) * 128 + (((c0 + 2 * p + (mi >> 1)) ^ r) << 4), pack2(o[2 * p][0], o[2 * p][1]), pack2(o[2 * p][2], o[2 * p][3]),
                  pack2(o[2 * p + 1][0], o[2 * p + 1][1]), pack2(o[2 * p + 1][2], o[2 * p + 1][3]));
    }
}

__device__ __forceinline__ uint32_t ln_row(const uint32_t (&as)[10], const uint2 (&xin)[5], int row, uint32_t par, uint32_t low, bf16* out, uint64_t ef, int lane) {
    const uint32_t pa = par + lane * 8;
    uint32_t xv[10], hv[10], sv[10], tv[10];
#pragma unroll
    for (int q = 0; q < 5; q++) {
        uint32_t ga[2], t[2], u[2];
        lds64(ga, pa + q * 256); lds64(t, pa + 1280 + q * 256); lds64(u, pa + 2560 + q * 256);
#pragma unroll
        for (int e = 0; e < 2; e++) {
            xv[2 * q + e] = add2(e ? xin[q].y : xin[q].x, mul2(ga[e], as[2 * q + e]));
            tv[2 * q + e] = t[e]; sv[2 * q + e] = u[e];
        }
    }
    ln_mod(xv, sv, tv, hv);
    float rs = 0;
#pragma unroll
    for (int q = 0; q < 5; q++) {
        const int c = row * DM + lane * 4 + q * 128;
        const uint32_t h0 = hv[2 * q], h1 = hv[2 * q + 1];
        uint32_t gb[2], wv[2];
        lds64(gb, pa + 3840 + q * 256); lds64(wv, pa + 5120 + q * 256);
        rs += (lo_f(h0) * lo_f(wv[0]) + hi_f(h0) * hi_f(wv[0])) + (lo_f(h1) * lo_f(wv[1]) + hi_f(h1) * hi_f(wv[1]));
        st_ef(out + c, make_uint2(add2(xv[2 * q], mul2(gb[0], h0)), add2(xv[2 * q + 1], mul2(gb[1], h1))), ef);
    }
    const uint32_t rb = pack2(0.f, warp_sum(rs));
    const uint32_t key = (((int)rb < 0 ? ~rb : rb | 0x80000000u) & 0xffff0000u) | (uint32_t)(4 * S_TOK - 1 - row);
    if (key < low) return key ^ (2 * S_TOK);
    {
#pragma unroll
        for (int q = 0; q < 5; q++) {
            *(uint2*)(g_x1 + row * DM + lane * 4 + q * 128) = make_uint2(xv[2 * q], xv[2 * q + 1]);
            *(uint2*)(g_h2 + row * DM + lane * 4 + q * 128) = make_uint2(hv[2 * q], hv[2 * q + 1]);
        }
    }
    return key;
}
__device__ __forceinline__ void key_out(uint32_t key) {
    __syncwarp();
    if (key) asm volatile("st.release.gpu.global.u32 [%0], %1;" :: "l"(g_key + (~key & (S_TOK - 1))), "r"(key) : "memory");
}

__global__ void __launch_bounds__(384, 1) k_side(const __grid_constant__ SideMaps mp, const bf16* __restrict__ x, const bf16* __restrict__ wr, const bf16* wmod, const bf16* cvec, bf16* __restrict__ out) {
    extern __shared__ __align__(1024) uint8_t smraw[];
    const uint32_t sm = smem_u32(smraw);
    if (sm & 1023) __trap();
    const uint32_t BARS = sm + SD_BAR, FULL = BARS + 768, EMPTY = FULL + 96, EFULL = BARS + 64, EEMPTY = BARS + 80, IFULL = BARS + 96, IEMPTY = BARS + 128, IQ = BARS + 160, SCHED = BARS + 176, PARAM = BARS + 184, ADONE = BARS + 192, LOW = BARS + 224, KEYS = BARS + 256;
    const int tid = threadIdx.x, warp = __shfl_sync(0xffffffffu, tid >> 5, 0), lane = tid & 31;
    const uint64_t ef = policy_stream();
    if (tid == 0) {
#pragma unroll 1
        for (int i = 0; i < SD_NST; i++) { mbar_init(FULL + 8 * i, 1); mbar_init(EMPTY + 8 * i, 2); }
        for (int i = 0; i < 2; i++) { mbar_init(EFULL + 8 * i, 4); mbar_init(EEMPTY + 8 * i, 1); }
        for (int i = 0; i < 4; i++) { mbar_init(IFULL + 8 * i, 1); mbar_init(IEMPTY + 8 * i, 11); }
        mbar_init(SCHED, 1); mbar_init(PARAM, 1);
        sts128f(ADONE, 0, 0, 0, 0); sts128f(ADONE + 16, 0, 0, 0, 0); sts128f(LOW, 0, 0, 0, 0);
        asm volatile("fence.mbarrier_init.release.cluster;" ::: "memory");
    }
    if (SDEL) __nanosleep(SDEL);
    __syncthreads();
    if (warp >= 8) {
      asm volatile("setmaxnreg.dec.sync.aligned.u32 40;");
      if (warp == 8) {
        int st = 0, ph = 1;
        for (int q = 0;; q++) {
            mbar_wait(IFULL + 8 * (q & 3), (q >> 2) & 1);
            const int it = __shfl_sync(0xffffffffu, lds32(IQ + 4 * (q & 3)), 0);
            if (elect()) mbar_arrive(IEMPTY + 8 * (q & 3));
            if (it < 0) break;
            const int kind = it >> 16, b = (it >> 8) & 255, i = it & 63;
            const int nst = kind == 0 ? 10 : kind == 1 ? 4 : kind == 2 ? 192 >> o_shift(b) : b == 14 ? 4 : 2;
            const int ksched = kind == 0 ? 4 : kind == 2 ? nst - KSO : (it & 128) ? -1 : kind == 1 ? KSA : 0;
            if (ksched < 0 && elect()) mbar_arrive(SCHED);
            const bool look = !(it & 128);
            const int nu = kind == 2 ? 2 : 3;
            if (look && kind == 1) flag_wait(&g_flags.v[b * 32 + i], 2);
            if (look && kind == 3 && b < 14) flag_wait(&g_flags.o[b], o_done(b));
            for (int kb = 0; kb < nst; kb++) {
                if (kb < 6) mbar_wait(EMPTY + 8 * st, ph);
                mbar_wait(EMPTY + 8 * (st + nu - 1), ph);
                const uint32_t base = sm + st * SD_ST, fb = FULL + 8 * st;
                if (lane && lane < nu) mbar_arrive(fb + 8 * lane);
                if (look && kind == 1) flag_wait(&g_flags.seg[max(kb, 1) * 32 + i], 3);
                if (kb == ksched && elect()) mbar_arrive(SCHED);
                if (kind == 0) {
                    if (q == 0 && kb == 0) {
                        if (elect()) {
#pragma unroll 1
                            for (int c = 0; c < 4; c++) tma3d(sm + 3 * c * SD_ST + 16384, &mp.wv, c * 64, i * 3, FULL + 24 * c);
                        }
                        flag_wait(&g_flags.h, 96);
                    }
                    if (elect()) {
                        mbar_expect(fb, 40960);
                        tma2d(base, &mp.h, kb * 64, b * 128, fb);
                        if (q || kb >= 4) tma3d(base + 16384, &mp.wv, kb * 64, i * 3, fb);
                    }
                } else if (kind == 1) {
                    if (elect()) {
                        mbar_expect(fb, 43008);
                        asm volatile("cp.async.bulk.shared::cluster.global.mbarrier::complete_tx::bytes.L2::cache_hint [%0], [%1], %2, [%3], %4;"
                            :: "r"(base), "l"(g_att + ((b * 4 + kb) * NH + i) * AT_REC), "r"(AT_REC), "r"(fb), "l"(ef) : "memory");
                    }
                } else if (kind == 3) {
                    if (b == 14 && !(kb & 1)) flag_wait(&g_flags.fin[(kb + (i >> 4)) * 32], 80);
                    if (elect()) { mbar_expect(fb, 40960); tma3d_ef(base, &mp.lnp[o_shift(b) - 2], i * (160 >> o_shift(b)), b * KSPLIT + (kb << o_shift(b) >> 1), fb, ef); }
                } else {
                    const int k0 = ((i >> 1) * nst + kb) * 32;
                    if (elect()) { mbar_expect(fb, 28672); tma3d(base + 8192, &mp.wo, k0, (i & 1) * 5, fb); }
                    if (look && kb % 12 == 0) flag_wait(&g_flags.pair[b * 16 + k0 / 384], 4);
                    if (elect()) tma2d_ef(base, &mp.o, k0, b * 128, fb, ef);
                }
                __syncwarp();
                st += nu; if (st == SD_NST) { st = 0; ph ^= 1; }
            }
        }
      } else if (warp == 11) {
        bool fin = false, par = false;
        for (int q = 0;; q++) {
            if (q) mbar_wait(SCHED, (q - 1) & 1);
            int it = fin ? -1 : q == 0 && blockIdx.x < 32 ? (int)blockIdx.x : next_item(lane);
            if (it < 0 && !fin && blockIdx.x < 32) { it = 3 << 16 | 14 << 8 | blockIdx.x; fin = true; }
            if (lane == 0) {
                if (it >> 16 == 3) {
                    const int b = (it >> 8) & 255, nr = 64 >> o_shift(b);
                    asm volatile("cp.async.bulk.prefetch.L2.global [%0], %1;" :: "l"(x + (b * 128 + (it & 63) * nr) * DM), "r"(nr * DM * 2) : "memory");
                }
                mbar_wait(IEMPTY + 8 * (q & 3), ((q >> 2) & 1) ^ 1);
                asm volatile("st.shared.u32 [%0], %1;" :: "r"(IQ + 4 * (q & 3)), "r"(it) : "memory");
                mbar_arrive(IFULL + 8 * (q & 3));
            }
            if (it >> 16 >= 2 && (it >> 8 & 255) >= 2) {
                const uint4* kp = (const uint4*)g_key + max((it >> 8 & 255) - ((it >> 16) == 2 ? 5 : 3), 0) * 32 + lane;
                const uint4 k1 = __ldcg(kp), k2 = __ldcg(kp + 32);
                uint32_t m = max(max(max(k1.x, k1.y), max(k1.z, k1.w)), max(max(k2.x, k2.y), max(k2.z, k2.w)));
                m = max(m, __shfl_xor_sync(0xffffffffu, m, 1)); m = max(m, __shfl_xor_sync(0xffffffffu, m, 2));
                asm volatile("red.shared.max.u32 [%0], %1;" :: "r"(LOW), "r"(__reduce_min_sync(0xffffffffu, m)) : "memory");
            }
            if (!par && it >> 16 == 3) {
                par = true;
                flag_wait(&g_flags.mod, 64);
                if (lane == 0) { mbar_expect(PARAM, 6400); bulk_g2s(sm + SD_PAR, g_mod + 2 * DM, 5120, PARAM); bulk_g2s(sm + SD_PAR + 5120, wr, 1280, PARAM); }
            }
            __syncwarp();
            if (it < 0) break;
        }
        flags_release(lane);
      } else {
        if (lane == 0) {
            const int wg = warp - 9; int ph = 0;
            for (int q = 0;; q++) {
                mbar_wait(IFULL + 8 * (q & 3), (q >> 2) & 1);
                const int it = lds32(IQ + 4 * (q & 3));
                mbar_arrive(IEMPTY + 8 * (q & 3));
                if (it < 0) break;
                const int kind = it >> 16, b = (it >> 8) & 255, i = it & 63;
                if (kind == 3 && b == 14) continue;
                if (kind & 1) {
                    for (int n = 0;; n++) {
                        uint32_t d0, d1, d2, d3;
                        asm volatile("ld.volatile.shared.v4.u32 {%0,%1,%2,%3}, [%4];" : "=r"(d0), "=r"(d1), "=r"(d2), "=r"(d3) : "r"(ADONE + wg * 16) : "memory");
                        if (min(min(d0, d1), min(d2, d3)) > q) break;
                        if (n > (1 << 24)) __trap();
                        __nanosleep(40);
                    }
                    GPU_FENCE();
                    EPT(kind == 1 && b == 15 && wg, 17);
                    if (kind == 1) { bump(b == 15 ? &g_flags.half[(i & 30) + wg] : &g_flags.pair[b * 16 + (i >> 1)]); bump(&g_flags.at[b]); }
                    else {
#pragma unroll 1
                        for (int c = 0; c < 8; c++) { const uint32_t key = lds32(KEYS + (q & 7) * 64 + wg * 32 + c * 4); if (key) asm volatile("st.relaxed.gpu.global.u32 [%0], %1;" :: "l"(g_key + (~key & (S_TOK - 1))), "r"(key) : "memory"); }
                    }
                    continue;
                }
#pragma unroll 1
                for (int rd = 0; rd < (kind == 2 ? 2 : 1); rd++) {
                    mbar_wait(EFULL + 8 * wg, ph); ph ^= 1;
                    const uint32_t src = sm + SD_EPI + wg * 24576;
                    if (kind == 2) tma3d_store(rd ? &mp.slab3 : &mp.slab2, (b * KSPLIT + (i >> 1)) * 128 + wg * 64, (i & 1) * 5 + (rd ? 0 : 3), src, ef, false);
                    else {
                        uint8_t* dst = g_att + ((b * 4 + wg * 2) * NH + i) * AT_REC + AT_V;
                        asm volatile("cp.async.bulk.global.shared::cta.bulk_group.L2::cache_hint [%0], [%1], 12288, %2;" :: "l"(dst), "r"(src), "l"(ef) : "memory");
                        asm volatile("cp.async.bulk.global.shared::cta.bulk_group.L2::cache_hint [%0], [%1], 12288, %2;" :: "l"(dst + NH * AT_REC), "r"(src + 12288), "l"(ef) : "memory");
                    }
                    asm volatile("cp.async.bulk.commit_group;" ::: "memory");
                    asm volatile("cp.async.bulk.wait_group.read 0;" ::: "memory");
                    mbar_arrive(EEMPTY + 8 * wg);
                }
                asm volatile("cp.async.bulk.wait_group 0;" ::: "memory");
                GPU_FENCE();
                bump(kind == 0 ? &g_flags.v[b * 32 + i] : &g_flags.o[b]);
                if (kind == 0) bump(&g_flags.vb[b]);
            }
        }
      }
    } else {
        asm volatile("setmaxnreg.inc.sync.aligned.u32 232;");
        const int wg = warp >> 2, w = warp & 3;
        int st = 0, ph = 0, eph = 1;
        bool att = false;
        uint4 mz[4] = {}; uint2 mc = {}; float ma[8] = {0, 0, 0, 0, 0, 0, 0, 0};
        const uint32_t eb = sm + SD_EPI + wg * 24576;
        for (int q = 0;; q++) {
            mbar_wait(IFULL + 8 * (q & 3), (q >> 2) & 1);
            const int itc = __shfl_sync(0xffffffffu, lds32(IQ + 4 * (q & 3)), 0);
            __syncwarp();
            if (lane == 0) mbar_arrive(IEMPTY + 8 * (q & 3));
            if (itc < 0) break;
            const int kind = itc >> 16, b = (itc >> 8) & 255, i = itc & 63;
            if (q >= 1 && q <= 9 && blockIdx.x < 32) {
                const int t = min(tid, 199), k = t / 10 * 32 + (q - 1) * 4;
#pragma unroll
                for (int e = 0; e < 4; e++) {
                    const uint32_t cw = e & 2 ? mc.y : mc.x;
                    const float c = e & 1 ? hi_f(cw) : lo_f(cw), f = bfr(__fdividef(c, 1.f + __expf(-c)));
                    ma[0] += f * lo_f(mz[e].x); ma[1] += f * hi_f(mz[e].x); ma[2] += f * lo_f(mz[e].y); ma[3] += f * hi_f(mz[e].y);
                    ma[4] += f * lo_f(mz[e].z); ma[5] += f * hi_f(mz[e].z); ma[6] += f * lo_f(mz[e].w); ma[7] += f * hi_f(mz[e].w);
                }
                if (q < 9) {
#pragma unroll
                    for (int e = 0; e < 4; e++) mz[e] = __ldcs((const uint4*)(wmod + (k + e) * (6 * DM) + 2 * DM + blockIdx.x * 80 + t % 10 * 8));
                    mc = __ldg((const uint2*)(cvec + k));
                } else {
                    sts128f(sm + SD_PAR + t * 32, ma[0], ma[1], ma[2], ma[3]); sts128f(sm + SD_PAR + 16 + t * 32, ma[4], ma[5], ma[6], ma[7]);
                    bar_sync(1, 256);
                    if (tid < 40) {
                        float a0 = 0, a1 = 0;
#pragma unroll 4
                        for (int g = 0; g < 20; g++) { const float2 v = lds64f(sm + SD_PAR + g * 320 + tid * 8); a0 += v.x; a1 += v.y; }
                        ((uint32_t*)(g_mod + 2 * DM + blockIdx.x * 80))[tid] = pack2(a0, a1);
                    }
                    __syncwarp();
                    if (warp < 2 && lane == 0) flag_add(&g_flags.mod);
                }
            }
            if (att && kind != 1) { bar_sync(1, 256); att = false; }
            int prev = -1;
            auto next = [&](int nu) {
                WG_COMMIT();
                WG_WAIT(1);
                if (prev >= 0 && (tid & 127) < nu) mbar_arrive(EMPTY + 8 * (prev + (tid & 127)));
                prev = st;
                st += nu; if (st == SD_NST) { st = 0; ph ^= 1; }
            };
            auto desc = [](uint32_t lo, uint32_t hi) { return (uint64_t)hi << 32 | lo; };
            if (kind == 0) {
                float acc[96];
#pragma unroll
                for (int n = 0; n < 96; n++) acc[n] = 0.f;
#pragma unroll 1
                for (int kb = 0; kb < 10; kb++) {
                    mbar_wait(FULL + 8 * st, ph);
                    const uint32_t d0 = (sm + st * SD_ST) >> 4, da = d0 + wg * 512 + 0x10000, db = d0 + 1024 + 0x2000000;
                    WG_FENCE();
#pragma unroll
                    for (int ks = 0; ks < 4; ks++) wgmma_ss_n192_tb(acc, desc(da + ks * 2, 0x40000040), desc(db + ks * 128, 0x40000040), 1);
                    next(3);
                }
                WG_WAIT(0);
                if ((tid & 127) < 3) mbar_arrive(EMPTY + 8 * (prev + (tid & 127)));
                tile_out<12>(acc, eb + (w >> 1) * 12288 + (w & 1) * 2048, 4096, EFULL + 8 * wg, EEMPTY + 8 * wg, eph, lane);
            } else if (kind == 2) {
                float acc[96], acc2[64];
#pragma unroll
                for (int n = 0; n < 96; n++) acc[n] = 0.f;
#pragma unroll
                for (int n = 0; n < 64; n++) acc2[n] = 0.f;
                int kb = 192 >> o_shift(b);
#pragma unroll 1
                do {
                    mbar_wait(FULL + 8 * st, ph);
                    const uint32_t d0 = (sm + st * SD_ST) >> 4, da = d0 + wg * 256 + 0x10000, db = d0 + 512 + 0x1000000;
                    WG_FENCE();
#pragma unroll
                    for (int ks = 0; ks < 2; ks++) {
                        wgmma_ss_n192_tb(acc, desc(da + ks * 2, 0x80000020), desc(db + ks * 128, 0x40000040), 1);
                        wgmma_ss_n128_tb(acc2, desc(da + ks * 2, 0x80000020), desc(db + 768 + ks * 128, 0x40000040), 1);
                    }
                    next(2);
                } while (--kb);
                WG_WAIT(0);
                if ((tid & 127) < 2) mbar_arrive(EMPTY + 8 * (prev + (tid & 127)));
                tile_out<8>(acc2, eb + w * 2048, 8192, EFULL + 8 * wg, EEMPTY + 8 * wg, eph, lane);
                tile_out<12>(acc, eb + w * 2048, 8192, EFULL + 8 * wg, EEMPTY + 8 * wg, eph, lane);
            } else if (kind == 1) {
                const int seg = warp >> 1, mt = warp & 1;
                int sst = st + 3 * seg, sph = ph; if (sst >= SD_NST) { sst -= SD_NST; sph ^= 1; }
                ph ^= 1;
                mbar_wait(FULL + 8 * sst, sph);
                EPT(tid == 224 && b == 15, 16);
                const uint32_t base = sm + sst * SD_ST;
                if (mt) attn_tile<1>(base, eb + w * 6144, EEMPTY + 8 * wg, eph, lane);
                else attn_tile<0>(base, eb + w * 6144, EEMPTY + 8 * wg, eph, lane);
                asm volatile("fence.proxy.async.shared::cta;" ::: "memory");
                __syncwarp();
                if (lane < 3) mbar_arrive(EMPTY + 8 * (sst + lane));
                if (lane == 0) {
                    tma3d_store(&mp.ost, b * 128 + warp * 16, i * 3, eb + w * 6144, ef, false);
                    BULK_COMMIT(); BULK_WAIT();
                    asm volatile("st.release.cta.shared.u32 [%0], %1;" :: "r"(ADONE + warp * 4), "r"(q + 1) : "memory");
                }
                __syncwarp();
                att = true;
            } else {
                const int sh = o_shift(b), nr = 64 >> sh, fw = b == 14 ? wg : 0, row0 = (b + fw) * 128 + i * nr, lw = warp - 4 * fw;
                if (fw) { ph ^= st != 0; st ^= 6; }
                uint2 xin[2][5];
                uint32_t as[2][10] = {};
#pragma unroll
                for (int q2 = 0; q2 < 10; q2++) xin[q2 & 1][q2 >> 1] = ld_ef(x + (row0 + ((warp + 8 * (q2 & 1)) & (nr - 1))) * DM + lane * 4 + (q2 >> 1) * 128, ef);
                mbar_wait(PARAM, 0); mbar_wait(FULL + 8 * st, ph); mbar_wait(FULL + 8 * st + 24, ph);
                EPT((tid & 127) == 0 && b == 14, 18 + wg);
#pragma unroll 1
                for (int lrow = lw + (nr & 16) / 2; lrow >= 0 && lrow < nr; lrow -= 8) {
                    const uint32_t one = (lane >> 3) == (lane & 3) ? 0x3f80u << (lane << 2 & 16) : 0u;
                    float a[5][4] = {};
#pragma unroll 2
                    for (int k = 0; k < (1 << sh >> 1); k++) {
                        const uint32_t ad = sm + st * SD_ST + ((k << (6 - sh)) + lrow) * 1280 + lane * 8;
#pragma unroll
                        for (int q2 = 0; q2 < 5; q2++) {
                            uint32_t z0[2], z1[2];
                            lds64(z0, ad + q2 * 256); lds64(z1, ad + 3 * SD_ST + q2 * 256);
                            mma16(a[q2], z0[0], z0[1], z1[0], z1[1], one, one);
                        }
                    }
#pragma unroll
                    for (int q2 = 0; q2 < 10; q2++) { as[1][q2] = as[0][q2]; as[0][q2] = pack2(a[q2 >> 1][2 * (q2 & 1)], a[q2 >> 1][2 * (q2 & 1) + 1]); }
                }
                bar_sync(2 + wg, 128);
                if ((tid & 127) < 6) mbar_arrive(EMPTY + 8 * (st + (tid & 127)));
                uint32_t key = 0;
#pragma unroll 1
                for (int lrow = lw; lrow < nr; lrow += 8) {
                    const int row = row0 + lrow;
                    const uint32_t k1 = ln_row(as[0], xin[0], row, sm + SD_PAR, lds32(LOW), out, ef, lane);
                    if (lane == lrow >> 3) key = k1;
#pragma unroll
                    for (int q2 = 0; q2 < 5; q2++) { as[0][2 * q2] = as[1][2 * q2]; as[0][2 * q2 + 1] = as[1][2 * q2 + 1]; xin[0][q2] = xin[1][q2]; }
                }
                if (b == 14) { EPT(tid == 128, 20); key_out(key); EPT(tid == 128, 21); }
                else {
                    if (lane < 2) asm volatile("st.shared.u32 [%0], %1;" :: "r"(KEYS + (q & 7) * 64 + warp * 8 + lane * 4), "r"(key) : "memory");
                    __syncwarp();
                    if (lane == 0) asm volatile("st.release.cta.shared.u32 [%0], %1;" :: "r"(ADONE + warp * 4), "r"(q + 1) : "memory");
                }
                ph ^= st != 0; st ^= 6;
            }
        }
    }
    __syncwarp();
    asm volatile("griddepcontrol.wait;" ::: "memory");
}

#define P_D1 500
#define P_DL 700
#define P_DG 29
typedef CUresult (*EncodeFn)(CUtensorMap*, CUtensorMapDataType, cuuint32_t, void*, const cuuint64_t*, const cuuint64_t*, const cuuint32_t*, const cuuint32_t*,
                             CUtensorMapInterleave, CUtensorMapSwizzle, CUtensorMapL2promotion, CUtensorMapFloatOOBfill);
static EncodeFn s_encode = nullptr;
static void make_map(CUtensorMap* m, const void* p, int rows, int cols, int box_rows, int box_cols = 64) {
    cuuint64_t dims[2] = {(cuuint64_t)cols, (cuuint64_t)rows}, strides[1] = {(cuuint64_t)cols * 2};
    cuuint32_t box[2] = {(cuuint32_t)box_cols, (cuuint32_t)box_rows}, es[2] = {1, 1};
    s_encode(m, CU_TENSOR_MAP_DATA_TYPE_BFLOAT16, 2, (void*)p, dims, strides, box, es, CU_TENSOR_MAP_INTERLEAVE_NONE,
             box_cols == 64 ? CU_TENSOR_MAP_SWIZZLE_128B : box_cols == 32 ? CU_TENSOR_MAP_SWIZZLE_64B : CU_TENSOR_MAP_SWIZZLE_NONE, CU_TENSOR_MAP_L2_PROMOTION_L2_256B, CU_TENSOR_MAP_FLOAT_OOB_FILL_NONE);
}
static void make_map3(CUtensorMap* m, const void* p, int rows, int cols, int box_rows, int box_chunks, int cw = 64) {
    cuuint64_t dims[3] = {(cuuint64_t)cw, (cuuint64_t)rows, (cuuint64_t)(cols / cw)}, strides[2] = {(cuuint64_t)cols * 2, (cuuint64_t)cw * 2};
    cuuint32_t box[3] = {(cuuint32_t)cw, (cuuint32_t)box_rows, (cuuint32_t)box_chunks}, es[3] = {1, 1, 1};
    s_encode(m, CU_TENSOR_MAP_DATA_TYPE_BFLOAT16, 3, (void*)p, dims, strides, box, es, CU_TENSOR_MAP_INTERLEAVE_NONE,
             cw == 64 ? CU_TENSOR_MAP_SWIZZLE_128B : CU_TENSOR_MAP_SWIZZLE_64B, CU_TENSOR_MAP_L2_PROMOTION_L2_256B, CU_TENSOR_MAP_FLOAT_OOB_FILL_NONE);
}
template <typename T> static void* sym(T& s) { void* p = nullptr; cudaGetSymbolAddress(&p, s); return p; }

extern "C" void kernel_launch(void* const* d_in, const int* in_sizes, int n_in, void* d_out, int out_size) {
    const bf16 *x = (const bf16*)d_in[0], *mem0 = (const bf16*)d_in[1], *Wq = (const bf16*)d_in[2], *Wk = (const bf16*)d_in[3],
               *Wv = (const bf16*)d_in[4], *Wo = (const bf16*)d_in[5], *wr = (const bf16*)d_in[8], *wgate = (const bf16*)d_in[9],
               *wup = (const bf16*)d_in[10], *wdown = (const bf16*)d_in[11], *c = (const bf16*)d_in[12], *wmod = (const bf16*)d_in[13];
    bf16* out = (bf16*)d_out;
    if (!s_encode) {
        cudaDriverEntryPointQueryResult qr;
        cudaGetDriverEntryPoint("cuTensorMapEncodeTiled", (void**)&s_encode, cudaEnableDefault, &qr);
        cudaFuncSetAttribute(k_side, cudaFuncAttributeMaxDynamicSharedMemorySize, SD_SMEM);
        cudaFuncSetAttribute(k_chain, cudaFuncAttributeMaxDynamicSharedMemorySize, C_SMEM);
    }
    ChainMaps cm; SideMaps sd;
    make_map(&sd.h, sym(g_h), S_TOK, DM, 128); make_map3(&sd.wv, Wv, DM, HD, 64, 3);
    make_map3(&sd.ost, sym(g_o), S_TOK, HD, 16, 3); make_map(&sd.o, sym(g_o), S_TOK, HD, 128, 32); make_map3(&sd.wo, Wo, HD, DM, 32, 5);
    make_map3(&sd.slab3, sym(g_slab), 16 * KSPLIT * 128, DM, 64, 3); make_map3(&sd.slab2, sym(g_slab), 16 * KSPLIT * 128, DM, 64, 2);
    make_map3(&cm.wo15, Wo, HD, DM, 192, 2); make_map3(&cm.o15, sym(g_o), S_TOK, HD, 64, 2); cm.slab2 = sd.slab2;
    for (int i = 0; i < 3; i++) {
        cuuint64_t dims[3] = {256, 320, 16 * KSPLIT}, strides[2] = {512, 128 * DM * 2};
        cuuint32_t box[3] = {256, 40u >> i, 2u << i}, es[3] = {1, 1, 1};
        s_encode(&sd.lnp[i], CU_TENSOR_MAP_DATA_TYPE_BFLOAT16, 3, sym(g_slab), dims, strides, box, es, CU_TENSOR_MAP_INTERLEAVE_NONE,
                 CU_TENSOR_MAP_SWIZZLE_NONE, CU_TENSOR_MAP_L2_PROMOTION_L2_256B, CU_TENSOR_MAP_FLOAT_OOB_FILL_NONE);
    }
    make_map(&cm.wq, Wq, DM, HD, 640 / WP); make_map(&cm.wk, Wk, DM, HD, 640 / WP); make_map(&cm.wv, Wv, DM, HD, 160); make_map3(&cm.wo, Wo, HD, DM, 64, 7, 32);
    make_map3(&cm.h2, sym(g_h), S_TOK, DM, 32, 2);
    ChainArgs ar = {x, mem0, c, wmod, Wv, Wo, wgate, wup, wdown, out, P_D1, P_DL, P_DG};
    k_chain<<<96, 384, C_SMEM>>>(cm, ar);
    cudaLaunchConfig_t cfg = {};
    cfg.gridDim = dim3(N_SIDE); cfg.blockDim = dim3(384); cfg.dynamicSmemBytes = SD_SMEM; cfg.stream = cudaStreamPerThread;
    cudaLaunchAttribute at[1]; at[0].id = cudaLaunchAttributeProgrammaticStreamSerialization; at[0].val.programmaticStreamSerializationAllowed = 1;
    cfg.attrs = at; cfg.numAttrs = 1;
    cudaLaunchKernelEx(&cfg, k_side, sd, x, wr, wmod, c, out);
}
```

```cpp
#include <cuda_runtime.h>
#include <cuda_bf16.h>
#include <cuda.h>
#include <stdint.h>
#include <stdio.h>
#include <string.h>
#include <stdlib.h>

typedef __nv_bfloat16 bf16;
constexpr int S_TOK = 2048, DM = 640, NH = 32, DH = 192, HD = NH * DH, NSEG = 64, SEG = 32, FF = 1536;

__device__ bf16 g_mod[6 * DM];
__device__ bf16 g_h[S_TOK * DM];
constexpr int AT_REC = 43008, AT_V = 24576, AT_KM = 36864, AT_VM = 39936;
__device__ __align__(1024) uint8_t g_att[NSEG * NH * AT_REC];
__device__ bf16 g_o[S_TOK * HD];
__device__ bf16 g_A[S_TOK * DM];
__device__ bf16 g_x1[S_TOK * DM];
__device__ bf16 g_h2[S_TOK * DM];
__device__ __align__(128) uint32_t g_key[S_TOK];
__device__ int g_idx[8];
__device__ __align__(128) uint32_t g_gu[FF / 8 * 32];
constexpr int ACC_PAIR = 24 * 1024;
__device__ __align__(1024) uint8_t g_acc[2 * ACC_PAIR];
__device__ __align__(1024) uint32_t g_stamp[4 * 12 * 32];
constexpr int KSPLIT = 16;
__device__ bf16 g_slab[16 * KSPLIT * 128 * DM];
struct __align__(128) Flags {
    uint32_t qk[16], vb[16];
    uint32_t at[16], o[16];
    uint32_t c[4][16];
    uint32_t half[32];
    uint32_t fin[4 * 32];
    uint32_t v[16 * 32];
    uint32_t seg[4 * 32];
    uint32_t pair[16 * 16];
    uint32_t h, pad2[31], done, mod, pad3[30];
    uint32_t mod1[DM];
    uint32_t wmax[96];
};
__device__ Flags g_flags;
#define EPT(c, i)

__device__ __forceinline__ uint32_t smem_u32(const void* p) { return (uint32_t)__cvta_generic_to_shared(p); }
__device__ __forceinline__ uint32_t pack2(float lo, float hi) {
    uint32_t r; asm("cvt.rn.bf16x2.f32 %0, %1, %2;" : "=r"(r) : "f"(hi), "f"(lo)); return r;
}
__device__ __forceinline__ float bfr(float x) { return __uint_as_float(pack2(0.f, x)); }
__device__ __forceinline__ float inv_std(float var) {
    float s, r; asm("sqrt.approx.f32 %0, %1;" : "=f"(s) : "f"(bfr(bfr(var) + 1e-5f))); asm("rcp.approx.f32 %0, %1;" : "=f"(r) : "f"(bfr(s))); return r;
}
__device__ __forceinline__ float lo_f(uint32_t v) { return __uint_as_float(v << 16); }
__device__ __forceinline__ float hi_f(uint32_t v) { return __uint_as_float(v & 0xffff0000u); }
__device__ __forceinline__ void mbar_init(uint32_t bar, int cnt) { asm volatile("mbarrier.init.shared::cta.b64 [%0], %1;" :: "r"(bar), "r"(cnt) : "memory"); }
__device__ __forceinline__ void mbar_expect(uint32_t bar, int bytes) { asm volatile("mbarrier.arrive.expect_tx.shared::cta.b64 _, [%0], %1;" :: "r"(bar), "r"(bytes) : "memory"); }
__device__ __forceinline__ void mbar_arrive(uint32_t bar) { asm volatile("mbarrier.arrive.shared::cta.b64 _, [%0];" :: "r"(bar) : "memory"); }
__device__ __forceinline__ bool mbar_try(uint32_t bar, int par) {
    uint32_t ok; asm volatile("{ .reg .pred p; mbarrier.try_wait.parity.shared::cta.b64 p, [%1], %2; selp.u32 %0, 1, 0, p; }" : "=r"(ok) : "r"(bar), "r"(par) : "memory"); return ok;
}
__device__ __forceinline__ bool mbar_try_cluster(uint32_t bar, int par) {
    uint32_t ok; asm volatile("{ .reg .pred p; mbarrier.try_wait.parity.acquire.cluster.shared::cta.b64 p, [%1], %2; selp.u32 %0, 1, 0, p; }" : "=r"(ok) : "r"(bar), "r"(par) : "memory"); return ok;
}
__device__ __forceinline__ bool mbar_test(uint32_t bar, uint32_t par) {
    uint32_t ok; asm volatile("{ .reg .pred p; mbarrier.test_wait.parity.shared::cta.b64 p, [%1], %2; selp.u32 %0, 1, 0, p; }" : "=r"(ok) : "r"(bar), "r"(par) : "memory"); return ok;
}
constexpr int SPIN_LIMIT = 1 << 18;
__device__ __forceinline__ void mbar_wait(uint32_t bar, uint32_t par) {
    asm volatile("{ .reg .pred p, q; .reg .u32 n; mov.u32 n, 0;\n"
                 "W_%=: mbarrier.try_wait.parity.shared::cta.b64 p, [%0], %1;\n"
                 "@p bra.uni D_%=;\n"
                 "add.u32 n, n, 1; setp.lt.u32 q, n, 0x200000; @q bra.uni W_%=;\n"
                 "trap;\n"
                 "D_%=: }" :: "r"(bar), "r"(par) : "memory");
}
__device__ __forceinline__ void tma2d(uint32_t dst, const CUtensorMap* m, int c0, int c1, uint32_t bar) {
    asm volatile("cp.async.bulk.tensor.2d.shared::cluster.global.mbarrier::complete_tx::bytes [%0], [%1, {%3, %4}], [%2];"
        :: "r"(dst), "l"((uint64_t)m), "r"(bar), "r"(c0), "r"(c1) : "memory");
}
__device__ __forceinline__ void tma2d_mc(uint32_t dst, const CUtensorMap* m, int c0, int c1, uint32_t bar, uint16_t mask) {
    asm volatile("cp.async.bulk.tensor.2d.shared::cluster.global.mbarrier::complete_tx::bytes.multicast::cluster [%0], [%1, {%3, %4}], [%2], %5;"
        :: "r"(dst), "l"((uint64_t)m), "r"(bar), "r"(c0), "r"(c1), "h"(mask) : "memory");
}
__device__ __forceinline__ uint64_t policy_stream() { uint64_t p; asm("createpolicy.fractional.L2::evict_first.b64 %0, 1.0;" : "=l"(p)); return p; }
__device__ __forceinline__ void tma2d_ef(uint32_t dst, const CUtensorMap* m, int c0, int c1, uint32_t bar, uint64_t pol) {
    asm volatile("cp.async.bulk.tensor.2d.shared::cluster.global.mbarrier::complete_tx::bytes.L2::cache_hint [%0], [%1, {%3, %4}], [%2], %5;"
        :: "r"(dst), "l"((uint64_t)m), "r"(bar), "r"(c0), "r"(c1), "l"(pol) : "memory");
}
__device__ __forceinline__ void tma3d(uint32_t dst, const CUtensorMap* m, int row, int chunk, uint32_t bar) {
    asm volatile("cp.async.bulk.tensor.3d.shared::cluster.global.mbarrier::complete_tx::bytes [%0], [%1, {0, %3, %4}], [%2];"
        :: "r"(dst), "l"((uint64_t)m), "r"(bar), "r"(row), "r"(chunk) : "memory");
}
__device__ __forceinline__ void tma3d_ef(uint32_t dst, const CUtensorMap* m, int row, int chunk, uint32_t bar, uint64_t pol) {
    asm volatile("cp.async.bulk.tensor.3d.shared::cluster.global.mbarrier::complete_tx::bytes.L2::cache_hint [%0], [%1, {0, %3, %4}], [%2], %5;"
        :: "r"(dst), "l"((uint64_t)m), "r"(bar), "r"(row), "r"(chunk), "l"(pol) : "memory");
}
__device__ __forceinline__ void tma3d_store(const CUtensorMap* m, int row, int chunk, uint32_t src, uint64_t pol, bool hint) {
    if (hint) asm volatile("cp.async.bulk.tensor.3d.global.shared::cta.bulk_group.L2::cache_hint [%0, {0, %2, %3}], [%1], %4;"
        :: "l"((uint64_t)m), "r"(src), "r"(row), "r"(chunk), "l"(pol) : "memory");
    else asm volatile("cp.async.bulk.tensor.3d.global.shared::cta.bulk_group [%0, {0, %2, %3}], [%1];"
        :: "l"((uint64_t)m), "r"(src), "r"(row), "r"(chunk) : "memory");
}
__device__ __forceinline__ bool elect() { uint32_t p; asm volatile("{ .reg .pred e; elect.sync _|e, -1; selp.u32 %0, 1, 0, e; }" : "=r"(p)); return p; }
__device__ __forceinline__ uint2 ld_ef(const void* p, uint64_t pol) {
    uint2 v; asm volatile("ld.relaxed.gpu.global.L2::cache_hint.v2.u32 {%0,%1}, [%2], %3;" : "=r"(v.x), "=r"(v.y) : "l"(p), "l"(pol)); return v;
}
__device__ __forceinline__ void st_ef(void* p, uint2 v, uint64_t pol) {
    asm volatile("st.global.L2::cache_hint.v2.u32 [%0], {%1,%2}, %3;" :: "l"(p), "r"(v.x), "r"(v.y), "l"(pol) : "memory");
}
__device__ __forceinline__ void tma2d_prefetch(const CUtensorMap* m, int c0, int c1) {
    asm volatile("cp.async.bulk.prefetch.tensor.2d.L2.global [%0, {%1, %2}];" :: "l"((uint64_t)m), "r"(c0), "r"(c1) : "memory");
}
__device__ __forceinline__ void mbar_arrive_remote(uint32_t bar) { asm volatile("mbarrier.arrive.relaxed.cluster.shared::cluster.b64 _, [%0];" :: "r"(bar) : "memory"); }
__device__ __forceinline__ void tma2d_store(const CUtensorMap* m, int c0, int c1, uint32_t src) {
    asm volatile("cp.async.bulk.tensor.2d.global.shared::cta.bulk_group [%0, {%2, %3}], [%1];"
        :: "l"((uint64_t)m), "r"(src), "r"(c0), "r"(c1) : "memory");
}
__device__ __forceinline__ void bulk_g2s(uint32_t dst, const void* src, int bytes, uint32_t bar) {
    asm volatile("cp.async.bulk.shared::cluster.global.mbarrier::complete_tx::bytes [%0], [%1], %2, [%3];" :: "r"(dst), "l"(src), "r"(bytes), "r"(bar) : "memory");
}
__device__ __forceinline__ void ldsm4(uint32_t (&r)[4], uint32_t a) {
    asm volatile("ldmatrix.sync.aligned.m8n8.x4.shared.b16 {%0,%1,%2,%3}, [%4];" : "=r"(r[0]), "=r"(r[1]), "=r"(r[2]), "=r"(r[3]) : "r"(a) : "memory");
}
__device__ __forceinline__ void ldsm4t(uint32_t (&r)[4], uint32_t a) {
    asm volatile("ldmatrix.sync.aligned.m8n8.x4.trans.shared.b16 {%0,%1,%2,%3}, [%4];" : "=r"(r[0]), "=r"(r[1]), "=r"(r[2]), "=r"(r[3]) : "r"(a) : "memory");
}
__device__ __forceinline__ void stsm4(uint32_t a, uint32_t r0, uint32_t r1, uint32_t r2, uint32_t r3) {
    asm volatile("stmatrix.sync.aligned.m8n8.x4.shared.b16 [%0], {%1,%2,%3,%4};" :: "r"(a), "r"(r0), "r"(r1), "r"(r2), "r"(r3) : "memory");
}
__device__ __forceinline__ void stsm4t(uint32_t a, uint32_t r0, uint32_t r1, uint32_t r2, uint32_t r3) {
    asm volatile("stmatrix.sync.aligned.m8n8.x4.trans.shared.b16 [%0], {%1,%2,%3,%4};" :: "r"(a), "r"(r0), "r"(r1), "r"(r2), "r"(r3) : "memory");
}
__device__ __forceinline__ void stsm2t(uint32_t a, uint32_t r0, uint32_t r1) {
    asm volatile("stmatrix.sync.aligned.m8n8.x2.trans.shared.b16 [%0], {%1,%2};" :: "r"(a), "r"(r0), "r"(r1) : "memory");
}
__device__ __forceinline__ uint32_t movm_t(uint32_t v) { uint32_t r; asm volatile("movmatrix.sync.aligned.m8n8.trans.b16 %0, %1;" : "=r"(r) : "r"(v)); return r; }
__device__ __forceinline__ void mma16(float (&d)[4], uint32_t a0, uint32_t a1, uint32_t a2, uint32_t a3, uint32_t b0, uint32_t b1) {
    asm volatile("mma.sync.aligned.m16n8k16.row.col.f32.bf16.bf16.f32 {%0,%1,%2,%3}, {%4,%5,%6,%7}, {%8,%9}, {%0,%1,%2,%3};"
        : "+f"(d[0]), "+f"(d[1]), "+f"(d[2]), "+f"(d[3]) : "r"(a0), "r"(a1), "r"(a2), "r"(a3), "r"(b0), "r"(b1));
}
__device__ __forceinline__ void mma8(float (&d)[4], uint32_t a0, uint32_t a1, uint32_t b0) {
    asm volatile("mma.sync.aligned.m16n8k8.row.col.f32.bf16.bf16.f32 {%0,%1,%2,%3}, {%4,%5}, {%6}, {%0,%1,%2,%3};"
        : "+f"(d[0]), "+f"(d[1]), "+f"(d[2]), "+f"(d[3]) : "r"(a0), "r"(a1), "r"(b0));
}
__device__ __forceinline__ uint32_t mapa(uint32_t a, uint32_t r) { uint32_t o; asm volatile("mapa.shared::cluster.u32 %0, %1, %2;" : "=r"(o) : "r"(a), "r"(r)); return o; }
__device__ __forceinline__ void bar_sync(int id, int n) { asm volatile("bar.sync %0, %1;" :: "r"(id), "r"(n) : "memory"); }
__device__ __forceinline__ void bar_arrive(int id, int n) { asm volatile("bar.arrive %0, %1;" :: "r"(id), "r"(n) : "memory"); }
__device__ __forceinline__ uint64_t mkdesc(uint32_t addr, uint32_t lbo, uint32_t sbo) {
    return (uint64_t)((addr & 0x3FFFF) >> 4) | ((uint64_t)(lbo >> 4) << 16) | ((uint64_t)(sbo >> 4) << 32) | (1ull << 62);
}
#define WG_FENCE()  asm volatile("wgmma.fence.sync.aligned;" ::: "memory")
#define WG_COMMIT() asm volatile("wgmma.commit_group.sync.aligned;" ::: "memory")
#define WG_WAIT(n)  asm volatile("wgmma.wait_group.sync.aligned %0;" :: "n"(n) : "memory")

__device__ __forceinline__ void wgmma_ss_n192_tb(float (&d)[96], uint64_t a, uint64_t b, int acc) {
    asm volatile("{ .reg .pred p; setp.ne.b32 p, %98, 0;\n"
        "wgmma.mma_async.sync.aligned.m64n192k16.f32.bf16.bf16 {%0,%1,%2,%3,%4,%5,%6,%7,%8,%9,%10,%11,%12,%13,%14,%15,%16,%17,%18,%19,%20,%21,%22,%23,%24,%25,%26,%27,%28,%29,%30,%31,%32,%33,%34,%35,%36,%37,%38,%39,%40,%41,%42,%43,%44,%45,%46,%47,%48,%49,%50,%51,%52,%53,%54,%55,%56,%57,%58,%59,%60,%61,%62,%63,%64,%65,%66,%67,%68,%69,%70,%71,%72,%73,%74,%75,%76,%77,%78,%79,%80,%81,%82,%83,%84,%85,%86,%87,%88,%89,%90,%91,%92,%93,%94,%95}, %96, %97, p, 1, 1, 0, 1; }"
        : "+f"(d[0]), "+f"(d[1]), "+f"(d[2]), "+f"(d[3]), "+f"(d[4]), "+f"(d[5]), "+f"(d[6]), "+f"(d[7]), "+f"(d[8]), "+f"(d[9]), "+f"(d[10]), "+f"(d[11]), "+f"(d[12]), "+f"(d[13]), "+f"(d[14]), "+f"(d[15]), "+f"(d[16]), "+f"(d[17]), "+f"(d[18]), "+f"(d[19]), "+f"(d[20]), "+f"(d[21]), "+f"(d[22]), "+f"(d[23]), "+f"(d[24]), "+f"(d[25]), "+f"(d[26]), "+f"(d[27]), "+f"(d[28]), "+f"(d[29]), "+f"(d[30]), "+f"(d[31]), "+f"(d[32]), "+f"(d[33]), "+f"(d[34]), "+f"(d[35]), "+f"(d[36]), "+f"(d[37]), "+f"(d[38]), "+f"(d[39]), "+f"(d[40]), "+f"(d[41]), "+f"(d[42]), "+f"(d[43]), "+f"(d[44]), "+f"(d[45]), "+f"(d[46]), "+f"(d[47]), "+f"(d[48]), "+f"(d[49]), "+f"(d[50]), "+f"(d[51]), "+f"(d[52]), "+f"(d[53]), "+f"(d[54]), "+f"(d[55]), "+f"(d[56]), "+f"(d[57]), "+f"(d[58]), "+f"(d[59]), "+f"(d[60]), "+f"(d[61]), "+f"(d[62]), "+f"(d[63]), "+f"(d[64]), "+f"(d[65]), "+f"(d[66]), "+f"(d[67]), "+f"(d[68]), "+f"(d[69]), "+f"(d[70]), "+f"(d[71]), "+f"(d[72]), "+f"(d[73]), "+f"(d[74]), "+f"(d[75]), "+f"(d[76]), "+f"(d[77]), "+f"(d[78]), "+f"(d[79]), "+f"(d[80]), "+f"(d[81]), "+f"(d[82]), "+f"(d[83]), "+f"(d[84]), "+f"(d[85]), "+f"(d[86]), "+f"(d[87]), "+f"(d[88]), "+f"(d[89]), "+f"(d[90]), "+f"(d[91]), "+f"(d[92]), "+f"(d[93]), "+f"(d[94]), "+f"(d[95])
        : "l"(a), "l"(b), "r"(acc));
}

__device__ __forceinline__ void wgmma_ss_n128_tb(float (&d)[64], uint64_t a, uint64_t b, int acc) {
    asm volatile("{ .reg .pred p; setp.ne.b32 p, %66, 0;\n"
        "wgmma.mma_async.sync.aligned.m64n128k16.f32.bf16.bf16 {%0,%1,%2,%3,%4,%5,%6,%7,%8,%9,%10,%11,%12,%13,%14,%15,%16,%17,%18,%19,%20,%21,%22,%23,%24,%25,%26,%27,%28,%29,%30,%31,%32,%33,%34,%35,%36,%37,%38,%39,%40,%41,%42,%43,%44,%45,%46,%47,%48,%49,%50,%51,%52,%53,%54,%55,%56,%57,%58,%59,%60,%61,%62,%63}, %64, %65, p, 1, 1, 0, 1; }"
        : "+f"(d[0]), "+f"(d[1]), "+f"(d[2]), "+f"(d[3]), "+f"(d[4]), "+f"(d[5]), "+f"(d[6]), "+f"(d[7]), "+f"(d[8]), "+f"(d[9]), "+f"(d[10]), "+f"(d[11]), "+f"(d[12]), "+f"(d[13]), "+f"(d[14]), "+f"(d[15]), "+f"(d[16]), "+f"(d[17]), "+f"(d[18]), "+f"(d[19]), "+f"(d[20]), "+f"(d[21]), "+f"(d[22]), "+f"(d[23]), "+f"(d[24]), "+f"(d[25]), "+f"(d[26]), "+f"(d[27]), "+f"(d[28]), "+f"(d[29]), "+f"(d[30]), "+f"(d[31]), "+f"(d[32]), "+f"(d[33]), "+f"(d[34]), "+f"(d[35]), "+f"(d[36]), "+f"(d[37]), "+f"(d[38]), "+f"(d[39]), "+f"(d[40]), "+f"(d[41]), "+f"(d[42]), "+f"(d[43]), "+f"(d[44]), "+f"(d[45]), "+f"(d[46]), "+f"(d[47]), "+f"(d[48]), "+f"(d[49]), "+f"(d[50]), "+f"(d[51]), "+f"(d[52]), "+f"(d[53]), "+f"(d[54]), "+f"(d[55]), "+f"(d[56]), "+f"(d[57]), "+f"(d[58]), "+f"(d[59]), "+f"(d[60]), "+f"(d[61]), "+f"(d[62]), "+f"(d[63])
        : "l"(a), "l"(b), "r"(acc));
}

__device__ __forceinline__ void wgmma_rs_n32(float (&d)[16], const uint32_t (&a)[4], uint64_t b, int acc) {
    asm volatile("{ .reg .pred p; setp.ne.b32 p, %21, 0;\n"
        "wgmma.mma_async.sync.aligned.m64n32k16.f32.bf16.bf16 {%0,%1,%2,%3,%4,%5,%6,%7,%8,%9,%10,%11,%12,%13,%14,%15}, {%16,%17,%18,%19}, %20, p, 1, 1, 0; }"
        : "+f"(d[0]), "+f"(d[1]), "+f"(d[2]), "+f"(d[3]), "+f"(d[4]), "+f"(d[5]), "+f"(d[6]), "+f"(d[7]), "+f"(d[8]), "+f"(d[9]), "+f"(d[10]), "+f"(d[11]), "+f"(d[12]), "+f"(d[13]), "+f"(d[14]), "+f"(d[15])
        : "r"(a[0]), "r"(a[1]), "r"(a[2]), "r"(a[3]), "l"(b), "r"(acc));
}

__device__ __forceinline__ float warp_sum(float v) {
#pragma unroll
    for (int o = 16; o; o >>= 1) v += __shfl_xor_sync(0xffffffffu, v, o);
    return v;
}
__device__ __forceinline__ uint32_t add2(uint32_t a, uint32_t b) { uint32_t r; asm("add.rn.bf16x2 %0, %1, %2;" : "=r"(r) : "r"(a), "r"(b)); return r; }
__device__ __forceinline__ uint32_t mul2(uint32_t a, uint32_t b) { uint32_t r; asm("mul.rn.bf16x2 %0, %1, %2;" : "=r"(r) : "r"(a), "r"(b)); return r; }
__device__ __forceinline__ uint32_t amax2(uint32_t m, uint32_t v) { uint32_t r; asm("max.u16x2 %0, %1, %2;" : "=r"(r) : "r"(m), "r"(v & 0x7fff7fffu)); return r; }
__device__ __forceinline__ uint32_t amax_warp(uint32_t m) { return __reduce_max_sync(0xffffffffu, max(m & 0xffffu, m >> 16)); }
__device__ __forceinline__ void ln_norm(const uint32_t (&xv)[10], uint32_t (&nv)[10]) {
    float s0 = 0, s1 = 0;
#pragma unroll
    for (int i = 0; i < 10; i++) { s0 += lo_f(xv[i]); s1 += hi_f(xv[i]); }
    const float mean = warp_sum(s0 + s1) * (1.f / DM);
    float q0 = 0, q1 = 0;
#pragma unroll
    for (int i = 0; i < 10; i++) { const float d0 = lo_f(xv[i]) - mean, d1 = hi_f(xv[i]) - mean; q0 += d0 * d0; q1 += d1 * d1; }
    const float inv = inv_std(warp_sum(q0 + q1) * (1.f / DM));
    const uint32_t mb = pack2(-mean, -mean);
#pragma unroll
    for (int i = 0; i < 10; i++) { const uint32_t d = add2(xv[i], mb); nv[i] = pack2(lo_f(d) * inv, hi_f(d) * inv); }
}
__device__ __forceinline__ void ln_mod(const uint32_t (&xv)[10], const uint32_t (&sv)[10], const uint32_t (&tv)[10], uint32_t (&hv)[10]) {
    ln_norm(xv, hv);
#pragma unroll
    for (int i = 0; i < 10; i++) hv[i] = add2(mul2(hv[i], add2(sv[i], 0x3f803f80u)), tv[i]);
}
__device__ __forceinline__ uint32_t ld_rlx(const uint32_t* f) { uint32_t v; asm volatile("ld.relaxed.gpu.global.u32 %0, [%1];" : "=r"(v) : "l"(f) : "memory"); return v; }
__device__ __forceinline__ void bump(uint32_t* f) { asm volatile("red.relaxed.gpu.global.add.u32 [%0], 1;" :: "l"(f) : "memory"); }
#define NAP 100
#define GPU_FENCE() asm volatile("fence.acq_rel.gpu;" ::: "memory")
__device__ __forceinline__ void flag_wait(const uint32_t* f, uint32_t target) {
    for (int n = 0;; n++) {
        uint32_t v; asm volatile("ld.relaxed.gpu.global.u32 %0, [%1];" : "=r"(v) : "l"(f) : "memory");
        if (v >= target) break;
        if (n > (1 << 22)) __trap();
        __nanosleep(NAP);
    }
}
__device__ __forceinline__ void flag_add(uint32_t* f, uint32_t v = 1) { asm volatile("red.release.gpu.global.add.u32 [%0], %1;" :: "l"(f), "r"(v) : "memory"); }
constexpr int N_SIDE = 36;
__device__ __forceinline__ void flags_release(int lane) {
    uint32_t old = 0;
    if (lane == 0) asm volatile("atom.relaxed.gpu.global.add.u32 %0, [%1], 1;" : "=r"(old) : "l"(&g_flags.done) : "memory");
    if (__shfl_sync(0xffffffffu, old, 0) == 96 + N_SIDE - 1)
#pragma unroll 1
        for (int i = lane; i < (int)(sizeof(Flags) / 16); i += 32) ((uint4*)&g_flags)[i] = make_uint4(0, 0, 0, 0);
}

struct ChainMaps { CUtensorMap wq, wk, wv, wo, h2, wo15, o15, slab2; };
struct ChainArgs { const bf16 *x, *mem0, *c, *wmod, *wgate, *wup, *wdown; bf16* out; int D1, D2, DG; };
constexpr uint32_t SM_BASE = 1024;
#define NRING 10
#define XORD 0
#define B5AT 38
#define QCUT 0x12
#define NCH 0
#define XA 2
#define VT 1
#define OSEND 1
#define SPOLL 0
#define BDEF 0
#define F61 1
#define IDLE 300
#define FW 2
#define RSEL 1
#define AIN 0
#define APRE 4
#define PBAR 0
#define WLATE 1
#define QDEL 300
#define STL 0
#define B7E 1
#define NPRE 9
#define REG_P 208
#define REG_L (504 - 2 * REG_P)
constexpr int WO_BLK = 7 * 4096;
constexpr int C_WV = 0, C_WO = 81920, C_XR = 167936, C_VP = C_XR + 7 * 4096, C_VX = C_XR + 8 * 4096, C_QX = C_VX + 4096, C_KX = C_QX + 4096,
              C_MEM = C_KX + 4096, C_OX = C_MEM + 9216, C_VM = C_OX + 3072, C_QM = C_VM + 1024, C_KM = C_QM + 1024, C_SC = C_KM + 1024, C_BAR = C_SC + 3840;
constexpr int CB_W = C_BAR, CB_W2 = C_BAR + 8, CB_SC = C_BAR + 16, CB_XD = C_BAR + 24, CB_VX = C_BAR + 32, CB_W3 = C_BAR + 40, CB_XM = C_BAR + 48, CB_OX = C_BAR + 56,
              CB_XF = C_BAR + 64, C_LAG = C_BAR + 96, C_UN = C_BAR + 100, C_MX = C_BAR + 112;
constexpr int C_SMEM = C_BAR + 128;
#define PROF(i)
#define PROFG(i)
#define PROFV(i, v)
static_assert(C_SMEM <= 232448, "chain shared memory");
__device__ __forceinline__ uint32_t umax3(uint32_t a, uint32_t b, uint32_t c) { return max(max(a, b), c); }
__device__ __forceinline__ void wait_until(uint32_t t) {
    asm volatile("{ .reg .pred p; .reg .s32 c; .reg .u64 d;\nU_%=: mov.u64 d, %%clock64; cvt.u32.u64 c, d; sub.s32 c, c, %0; setp.lt.s32 p, c, 0; @p bra.uni U_%=; }" :: "r"(t) : "memory");
}
__device__ __forceinline__ uint32_t gtime() { uint32_t c; asm volatile("mov.u32 %0, %%globaltimer_lo;" : "=r"(c)); return c; }
__device__ __forceinline__ uint32_t opaque(uint32_t v) { uint32_t r; asm volatile("shfl.sync.bfly.b32 %0, %1, 0, 31, -1;" : "=r"(r) : "r"(v)); return r; }
__device__ __forceinline__ uint32_t lds32(uint32_t a) { uint32_t v; asm volatile("ld.shared.u32 %0, [%1];" : "=r"(v) : "r"(a) : "memory"); return v; }
__device__ __forceinline__ float2 lds64f(uint32_t a) { float2 v; asm volatile("ld.shared.v2.f32 {%0,%1}, [%2];" : "=f"(v.x), "=f"(v.y) : "r"(a) : "memory"); return v; }
__device__ __forceinline__ float4 lds128f(uint32_t a) { float4 v; asm volatile("ld.shared.v4.f32 {%0,%1,%2,%3}, [%4];" : "=f"(v.x), "=f"(v.y), "=f"(v.z), "=f"(v.w) : "r"(a) : "memory"); return v; }
__device__ __forceinline__ void sts128f(uint32_t a, float x, float y, float z, float w) { asm volatile("st.shared.v4.f32 [%0], {%1,%2,%3,%4};" :: "r"(a), "f"(x), "f"(y), "f"(z), "f"(w) : "memory"); }
__device__ __forceinline__ void lds64(uint32_t (&v)[2], uint32_t a) { asm volatile("ld.shared.v2.u32 {%0,%1}, [%2];" : "=r"(v[0]), "=r"(v[1]) : "r"(a) : "memory"); }
__device__ __forceinline__ void mma16q(float (&d)[4], const uint32_t (&a)[4], uint32_t b0, uint32_t b1) { mma16(d, a[0], a[1], a[2], a[3], b0, b1); }
__device__ __forceinline__ uint32_t f16_to_bf16(uint32_t v) {
    float lo, hi; asm("{ .reg .f16 l, h; mov.b32 {l, h}, %2; cvt.f32.f16 %0, l; cvt.f32.f16 %1, h; }" : "=f"(lo), "=f"(hi) : "r"(v));
    return pack2(lo, hi);
}
__device__ __forceinline__ uint32_t pack2h(float lo, float hi) { uint32_t r; asm("cvt.rn.f16x2.f32 %0, %1, %2;" : "=r"(r) : "f"(hi), "f"(lo)); return r; }
#define SPLIT 1
__device__ __forceinline__ void cut(uint32_t never, int n) {
    asm volatile("{ .reg .pred p; setp.ne.u32 p, %0, %1; @p bra.uni C_%=; trap; C_%=: }" :: "r"(never), "r"(n) : "memory");
}
__device__ __forceinline__ void pin(uint32_t never, uint32_t a, uint32_t b, uint32_t c, uint32_t d) {
    asm volatile("{ .reg .pred p; setp.eq.u32 p, %0, 0; @p st.shared.v4.u32 [%0], {%1,%2,%3,%4}; }" :: "r"(never), "r"(a), "r"(b), "r"(c), "r"(d) : "memory");
}
__device__ __forceinline__ void pin0(uint32_t never) {
    asm volatile("{ .reg .pred p; setp.eq.u32 p, %0, 0; @p st.shared.u32 [%0], 0; }" :: "r"(never) : "memory");
}
#define ELECTED(txt) "{ .reg .pred e; elect.sync _|e, -1; @e " txt " }"
__device__ __forceinline__ void w_bulk_s2g(void* dst, uint32_t src, int bytes) {
    asm volatile(ELECTED("cp.async.bulk.global.shared::cta.bulk_group [%0], [%1], %2;") :: "l"(dst), "r"(src), "r"(bytes) : "memory");
}
__device__ __forceinline__ void w_bump(uint32_t* f) { asm volatile(ELECTED("red.relaxed.gpu.global.add.u32 [%0], 1;") :: "l"(f) : "memory"); }
__device__ __forceinline__ void w_expect(uint32_t bar, int bytes) { asm volatile(ELECTED("mbarrier.arrive.expect_tx.shared::cta.b64 _, [%0], %1;") :: "r"(bar), "r"(bytes) : "memory"); }
__device__ __forceinline__ void w_flag_wait(const uint32_t* f, uint32_t target) {
    asm volatile("{ .reg .pred p; .reg .u32 n, v; mov.u32 n, 0;\n"
                 "F_%=: ld.relaxed.gpu.global.u32 v, [%0]; setp.ge.u32 p, v, %1; vote.sync.all.pred p, p, -1; @p bra.uni G_%=;\n"
                 "nanosleep.u32 %2; add.u32 n, n, 1; setp.lt.u32 p, n, 0x400000; @p bra.uni F_%=;\ntrap;\nG_%=: }" :: "l"(f), "r"(target), "n"(NAP) : "memory");
}
#define BULK_COMMIT()    asm volatile("cp.async.bulk.commit_group;" ::: "memory")
#define BULK_WAIT()      asm volatile("cp.async.bulk.wait_group 0;" ::: "memory")
#define BULK_WAIT_READ() asm volatile("cp.async.bulk.wait_group.read 0;" ::: "memory")
#define PROXY_FENCE()    asm volatile("fence.proxy.async.shared::cta;" ::: "memory")
__device__ __forceinline__ void send16(uint32_t dst, uint32_t bar, float a, float b, float c, float d) {
    asm volatile("st.async.shared::cluster.mbarrier::complete_tx::bytes.v4.f32 [%0], {%1,%2,%3,%4}, [%5];" :: "r"(dst), "f"(a), "f"(b), "f"(c), "f"(d), "r"(bar) : "memory");
}
__device__ __forceinline__ void send8(uint32_t dst, uint32_t bar, uint32_t a, uint32_t b) {
    asm volatile("st.async.shared::cluster.mbarrier::complete_tx::bytes.v2.b32 [%0], {%1,%2}, [%3];" :: "r"(dst), "r"(a), "r"(b), "r"(bar) : "memory");
}

__device__ __forceinline__ void seg_done(int n, int head) { GPU_FENCE(); w_bump(&g_flags.seg[(n - 60) * 32 + head]); }
__device__ __forceinline__ uint32_t x_base(int wg, uint32_t small, int sh) { return (uint32_t)mkdesc(SM_BASE + C_XR, 16, 1024) + wg * 256 + (small >> sh); }
__device__ __forceinline__ void x_chunk(float (&acc)[16], const uint32_t (&wa)[40][4], uint32_t xl, int a0, int i, int first) {
#pragma unroll
    for (int ks = 0; ks < 4; ks++)
        wgmma_rs_n32(acc, wa[a0 + 4 * i + ks], mkdesc(0, 0, 1024) | (uint32_t)(xl + (((i ? (i - 1) * 8192 : C_MEM - C_XR) + ks * 32) >> 4)), !(first && ks == 0));
}
template <typename F>
__device__ __forceinline__ void x_part(F aside, float (&acc)[16], const uint32_t (&wa)[40][4], uint32_t sm, int n, int wg, int w, uint32_t ln, uint32_t small) {
    const int s = n - 1; (void)s;
    uint32_t giv[8];
    auto chunk = [&](int a0, int i, int first) { x_chunk(acc, wa, x_base(wg, small, a0 ? 21 : 22), a0, i, first); };
    mbar_wait(sm + CB_XM, n & 1);
    if (n) bar_sync(5, 384);
    if (wg == 0 && w == 0) PROF(12);
    WG_FENCE();
#pragma unroll
    for (int i = 1 + XA; i < 5; i++) chunk(20, i, 0);
    chunk(20, 0, 0);
    WG_COMMIT();
    if (n) {
        if (wg == 1 && w == 1) BULK_WAIT();
        bar_sync(8, 256);
    }
    if (wg == 0 && w == 0) PROF(18);
    const uint32_t xb = sm + w * 512 + ln * 16, xw = xb + C_KX - wg * 4096, xr = xb + C_QX + wg * 4096;
    WG_WAIT(0);
#pragma unroll
    for (int i = 0; i < 8; i++) asm volatile("cvt.rn.bf16x2.f32 %0, %1, %2;" : "=r"(giv[i]) : "f"(acc[2 * i + 1]), "f"(acc[2 * i]));
#pragma unroll
    for (int p = 0; p < 2; p++) asm volatile("st.shared.v4.u32 [%0], {%1,%2,%3,%4};" :: "r"(xw + p * 2048), "r"(giv[4 * p]), "r"(giv[4 * p + 1]), "r"(giv[4 * p + 2]), "r"(giv[4 * p + 3]) : "memory");
    bar_arrive(12 + wg, 256);
    WG_FENCE();
    chunk(0, 0, 1);
    WG_COMMIT();
    chunk(0, 1, 0);
    if (XORD) chunk(0, 2, 0);
    bar_sync(13 - wg, 256);
#pragma unroll
    for (int p = 0; p < 2; p++) asm volatile("ld.shared.v4.u32 {%0,%1,%2,%3}, [%4];" : "=r"(giv[4 * p]), "=r"(giv[4 * p + 1]), "=r"(giv[4 * p + 2]), "=r"(giv[4 * p + 3]) : "r"(xr + p * 2048) : "memory");
    WG_COMMIT(); WG_WAIT(1); bar_arrive(9, 384);
    WG_FENCE();
    if (!XORD) chunk(0, 2, 0);
    chunk(0, 3, 0); chunk(0, 4, 0);
    WG_COMMIT();
    const uint32_t r = ln & 7, mi = ln >> 3, dst = sm + (wg == 0 ? C_QX : C_KX) + ((mi >> 1) * 8 + r) * 128 + (((2 * w + (mi & 1)) ^ r) << 4);
    pin(xb, giv[0], giv[4], dst, 0);
    aside();
    bar_sync(10 + wg, 128);
    WG_WAIT(0);
    if (wg == 0 && w == 0) PROF(30);
    if (w == 0 && ln < 3) mbar_arrive_remote(mapa(sm + CB_XD, ln));
#pragma unroll
    for (int i = 0; i < 8; i++) { acc[2 * i] += lo_f(giv[i]); acc[2 * i + 1] += hi_f(giv[i]); }
#pragma unroll
    for (int p = 0; p < 2; p++)
        stsm4t(dst + p * 2048, pack2(acc[8 * p], acc[8 * p + 1]), pack2(acc[8 * p + 2], acc[8 * p + 3]), pack2(acc[8 * p + 4], acc[8 * p + 5]), pack2(acc[8 * p + 6], acc[8 * p + 7]));
    if (wg == 0 && w == 0) PROF(11);
}
__device__ __forceinline__ void x_fill(const ChainMaps& mp, uint32_t sm, int n, int j) {
    mbar_expect(sm + CB_XF, 24576);
    asm volatile("cp.async.bulk.tensor.3d.shared::cluster.global.mbarrier::complete_tx::bytes.multicast::cluster [%0], [%1, {0, %3, %4}], [%2], %5;"
        :: "r"(sm + C_XR + j * 8192), "l"((uint64_t)&mp.h2), "r"(sm + CB_XF), "r"(n * SEG), "r"(2 + 2 * j), "h"((uint16_t)7) : "memory");
}
__device__ __forceinline__ void x_rest(const ChainMaps& mp, uint32_t sm, int n) {
    mbar_expect(sm + CB_XM, 16384);
    tma3d(sm + C_XR + 6 * 4096, &mp.h2, n * SEG, 8, sm + CB_XM); tma3d(sm + C_MEM, &mp.h2, n * SEG, 0, sm + CB_XM);
}

#define WPOS 2
#define WP 4
#define SDEL 0
#define EORD 0
#define RPF 1
#define BPOS 2
#define TPF 1
#define B_LATE 13
constexpr int E_B = C_WO, E_STG = 196608, EB_A = 229376, EB_B = C_BAR + 80, EB_REL = C_BAR + 104;
__device__ __forceinline__ uint32_t e_slot(int wg, int c) { return wg && c == 2 ? E_B + 98304 : wg * 49152 + c * 16384; }
constexpr int T_WG = 0, T_WU = 20480, T_WD = 40960, T_X = 65536, T_RED = 77824, T_KEY = 86016;
__device__ __forceinline__ void wo_half(const ChainMaps& mp, uint32_t sm, int blk, int c) {
    if (blk < 80 && elect()) { mbar_expect(sm + EB_B + 8 * c, 49152); tma3d(sm + E_B + c * 49152, &mp.wo15, blk / 5 * 384 + c * 192, blk % 5 * 2, sm + EB_B + 8 * c); }
}
__device__ __forceinline__ void end_loads(const ChainMaps& mp, const ChainArgs& ar, uint32_t sm, int blk, int wg) {
    const uint32_t bar = sm + EB_A + wg * 48;
    const int kp = blk / 5;
    if (elect()) {
#pragma unroll 1
        for (int c = 0; c < 6; c++) mbar_init(bar + 8 * c, c < 3 ? 1 : 4);
        PROXY_FENCE();
    }
    __syncwarp();
    bar_arrive(5, 384);
    if (EORD) bar_sync(6, 96);
    if (blk >= 80) {
        if (TPF && elect()) {
#pragma unroll 1
            for (int c = 0; c < 3; c++) asm volatile("cp.async.bulk.prefetch.L2.global [%0], 61440;" :: "l"((c == 0 ? ar.wgate : c == 1 ? ar.wup : ar.wdown) + ((blk - 80) * 2 + wg) * 30720) : "memory");
        }
        return;
    }
    const uint64_t ef = policy_stream();
#pragma unroll 1
    for (int b = B_LATE; b < 16; b++) {
        w_flag_wait(b == 15 ? &g_flags.half[kp * 2 + wg] : &g_flags.pair[b * 16 + kp], b == 15 ? 2 : 4);
#pragma unroll 1
        for (int c = 0; c < 3; c++) {
            if (b > B_LATE) mbar_wait(bar + 24 + 8 * c, (b - B_LATE - 1) & 1);
            if (elect()) { mbar_expect(bar + 8 * c, 16384); tma3d_ef(sm + e_slot(wg, c), &mp.o15, b * 128 + wg * 64, kp * 6 + c * 2, bar + 8 * c, ef); }
            __syncwarp();
        }
    }
}
__device__ __forceinline__ void end_stores(const ChainMaps& mp, uint32_t sm, int blk, int wg) {
#pragma unroll 1
    for (int b = B_LATE; b < 16 && blk < 80; b++) {
        bar_sync(12 + wg, 160);
        if (elect()) tma3d_store(&mp.slab2, (b * KSPLIT + blk / 5) * 128 + wg * 64, blk % 5 * 2, sm + E_STG + wg * 16384, 0, false);
        BULK_COMMIT(); BULK_WAIT();
        if (b < 15) bar_arrive(10 + wg, 160);
        GPU_FENCE();
        w_bump(b < 14 ? &g_flags.o[b] : &g_flags.fin[((b - 14) * 2 + wg) * 32]);
    }
    bar_arrive(8, 320);
}
__device__ __forceinline__ void last_blocks(const ChainArgs& ar, uint32_t sm, int blk, int tid) {
    const int warp = __shfl_sync(0xffffffffu, tid >> 5, 0), lane = tid & 31, wg = warp >> 2, w = warp & 3;
    const uint32_t bar = sm + EB_A + wg * 48, stg = sm + E_STG + wg * 16384 + w * 2048;
    bar_sync(5, 384);
    EPT(tid == 128, 7);
    float acc[64];
#pragma unroll
    for (int n = 0; n < 64; n++) acc[n] = 0.f;
#pragma unroll 1
    for (int b = B_LATE; b < 16 && blk < 80; b++) {
#pragma unroll 1
        for (int c = 0; c < 6; c++) {
            mbar_wait(sm + EB_B + 8 * (c >= 3), 0); mbar_wait(bar + 8 * (c >> 1), (b - B_LATE) & 1);
            const uint64_t da = mkdesc(SM_BASE + e_slot(wg, c >> 1) + (c & 1) * 8192, 16, 1024), db = mkdesc(SM_BASE + E_B + (c >= 3 ? 24576 : 0) + c * 8192, 24576, 1024);
            WG_FENCE();
#pragma unroll
            for (int ks = 0; ks < 4; ks++) wgmma_ss_n128_tb(acc, da + ks * 2, db + ks * 128, c | ks);
            WG_COMMIT();
            WG_WAIT(1);
            if ((c & 1) == 0 && c && elect()) mbar_arrive(bar + 16 + 4 * c);
        }
        if (b > B_LATE) bar_sync(10 + wg, 160);
        WG_WAIT(0);
        if (elect()) mbar_arrive(bar + 40);
        EPT(tid == 128, 13 + 15 - b);
        const int r = lane & 7, mi = lane >> 3;
#pragma unroll
        for (int p = 0; p < 8; p++) {
            const int oc = 2 * p + (mi >> 1);
            stsm4(stg + (oc >> 3) * 8192 + ((mi & 1) * 8 + r) * 128 + (((oc & 7) ^ r) << 4), pack2(acc[8 * p], acc[8 * p + 1]), pack2(acc[8 * p + 2], acc[8 * p + 3]),
                  pack2(acc[8 * p + 4], acc[8 * p + 5]), pack2(acc[8 * p + 6], acc[8 * p + 7]));
        }
        PROXY_FENCE();
        bar_arrive(12 + wg, 160);
    }
    bar_sync(8, 320);
    const int o = (tid >> 1) * FF + blk * 16 + (tid & 1) * 8;
    const bf16 *pg = ar.wgate + o, *pu = ar.wup + o, *pd = ar.wdown + tid * DM + (blk < 80 ? blk : 0) * 8;
#pragma unroll 1
    for (int i = 0; i < 6; i++) {
        const uint32_t d = sm + E_B + i * 4096 + tid * 16;
        if (i < 5) asm volatile("cp.async.cg.shared.global [%0], [%1], 16; cp.async.cg.shared.global [%0 + 20480], [%2], 16;" :: "r"(d), "l"(pg + i * 128 * FF), "l"(pu + i * 128 * FF) : "memory");
        asm volatile("cp.async.cg.shared.global [%0 + 40960], [%1], 16;" :: "r"(d), "l"(pd + i * 256 * DM) : "memory");
    }
    EPT(tid == 128, 8);
}
__device__ __forceinline__ void mod_tail(const ChainArgs& ar, const uint32_t tb, const uint32_t bar, const int blk, const int tid) {
#define TPROF(i) EPT(tid == 0, i)
    const int warp = __shfl_sync(0xffffffffu, tid >> 5, 0), lane = tid & 31, r = lane & 7, mi = lane >> 3;
    const uint32_t kb = tb + T_KEY;
    {
        uint32_t k[8];
        for (int n = 0;; n++) {
#pragma unroll
            for (int i = 0; i < 2; i++) asm volatile("ld.relaxed.gpu.global.v4.u32 {%0,%1,%2,%3}, [%4];" : "=r"(k[4 * i]), "=r"(k[4 * i + 1]), "=r"(k[4 * i + 2]), "=r"(k[4 * i + 3]) : "l"(g_key + warp * 256 + i * 128 + lane * 4) : "memory");
            if (__all_sync(0xffffffffu, (k[0] & k[1] & k[2] & k[3] & k[4] & k[5] & k[6] & k[7] & S_TOK) != 0)) break;
            if (n > (1 << 22)) __trap();
            __nanosleep(NAP);
        }
        const uint32_t m = __reduce_max_sync(0xffffffffu, max(umax3(k[0], k[1], k[2]), max(umax3(k[3], k[4], k[5]), max(k[6], k[7]))));
        asm volatile("st.shared.u32 [%0], %1; st.shared.u32 [%2], 0;" :: "r"(kb + warp * 4), "r"(m), "r"(kb + 32) : "memory");
        if (RPF && blk >= 93 && warp < 6) {
            uint32_t c = m;
#pragma unroll 1
            for (int it = 93; it < blk; it++) {
                uint32_t x = 0;
#pragma unroll
                for (int i = 0; i < 8; i++) x = max(x, k[i] < c ? k[i] : 0u);
                c = __reduce_max_sync(0xffffffffu, x);
            }
            if ((c & 2 * S_TOK) && lane < 2) asm volatile("cp.async.bulk.prefetch.L2.global [%0], 1280;" :: "l"((lane ? g_h2 : g_x1) + (~c & (S_TOK - 1)) * DM) : "memory");
        }
        asm volatile("cp.async.wait_all;" ::: "memory");
        bar_sync(1, 256);
        TPROF(1);
        const uint32_t low = __reduce_min_sync(0xffffffffu, lds32(kb + r * 4));
        uint32_t cnt = 0;
#pragma unroll
        for (int i = 0; i < 8; i++) cnt += k[i] >= low ? 4 : 0;
        if (cnt) {
            uint32_t a; asm volatile("atom.shared.add.u32 %0, [%1], %2;" : "=r"(a) : "r"(kb + 32), "r"(cnt) : "memory");
#pragma unroll
            for (int i = 0; i < 8; i++) if (k[i] >= low) { asm volatile("st.shared.u32 [%0], %1;" :: "r"(kb + 512 + a), "r"(k[i]) : "memory"); a += 4; }
        }
        if (tid == 0) mbar_arrive(bar);
        bar_sync(1, 256);
        const int nc = lds32(kb + 32);
#pragma unroll 1
        for (int c = lane * 4; c < nc; c += 128) {
            const uint32_t me = lds32(kb + 512 + c);
            int rank = 0;
#pragma unroll 2
            for (int e = 0; e < nc; e += 16) {
                const float4 z = lds128f(kb + 512 + e);
                rank += (__float_as_uint(z.x) > me) + (e + 4 < nc && __float_as_uint(z.y) > me) + (e + 8 < nc && __float_as_uint(z.z) > me) + (e + 12 < nc && __float_as_uint(z.w) > me);
            }
            if (rank < 8) asm volatile("st.shared.u32 [%0], %1;" :: "r"(kb + 64 + (warp * 8 + rank) * 4), "r"(me) : "memory");
        }
        __syncwarp();
    }
    const uint32_t k0 = lds32(kb + 64 + (warp * 8 + r) * 4), k1 = lds32(kb + 64 + (warp * 8 + (lane >> 2)) * 4);
    TPROF(2);
    const int trow = ~k1 & (S_TOK - 1), tcol = (blk < 80 ? blk : 0) * 8 + (lane & 3) * 2;
    uint2 xb[5];
#pragma unroll
    for (int h = 0; h < 5; h++) xb[h] = __ldcg((const uint2*)(g_h2 + trow * DM + (warp * 5 + h) * 16 + (lane & 3) * 4));
    const uint32_t fx1 = __ldcg((const uint32_t*)(g_x1 + trow * DM + tcol)), fh2 = __ldcg((const uint32_t*)(g_h2 + trow * DM + tcol)),
                   fgb = __ldcg((const uint32_t*)(g_mod + 5 * DM + tcol));
    const float fr = __uint_as_float(((int)k1 < 0 ? k1 ^ 0x80000000u : ~k1) & 0xffff0000u);
    {
        float dg[4] = {0, 0, 0, 0}, du[4] = {0, 0, 0, 0};
        uint32_t ag[5][4], au[5][4];
#pragma unroll
        for (int h = 0; h < 5; h++) {
            const uint32_t o = tb + ((warp * 5 + h) * 16 + (r >> 1) * 4 + (mi >> 1) * 2 + (r & 1)) * 32 + (mi & 1) * 16;
            ldsm4t(ag[h], o + T_WG); ldsm4t(au[h], o + T_WU);
        }
#pragma unroll
        for (int h = 0; h < 5; h++) { mma16q(dg, ag[h], xb[h].x, xb[h].y); mma16q(du, au[h], xb[h].x, xb[h].y); }
        TPROF(3);
        sts128f(tb + T_RED + warp * 1024 + lane * 16, dg[0], dg[1], dg[2], dg[3]); sts128f(tb + T_RED + warp * 1024 + 512 + lane * 16, du[0], du[1], du[2], du[3]);
    }
    bar_sync(1, 256);
    if (warp < 2) {
        float g2[2] = {0, 0}, u2[2] = {0, 0};
#pragma unroll
        for (int i = 0; i < 8; i++) {
            const float2 a = lds64f(tb + T_RED + i * 1024 + lane * 16 + warp * 8), b = lds64f(tb + T_RED + i * 1024 + 512 + lane * 16 + warp * 8);
            g2[0] += a.x; g2[1] += a.y; u2[0] += b.x; u2[1] += b.y;
        }
        float y[2];
#pragma unroll
        for (int i = 0; i < 2; i++) { const float gq = bfr(g2[i]); y[i] = bfr(__fdividef(gq, 1.f + __expf(-gq))) * bfr(u2[i]); }
        asm volatile("st.relaxed.gpu.global.u32 [%0], %1;" :: "l"(g_gu + (blk >> 1) * 128 + lane * 4 + warp * 2 + (blk & 1)), "r"(movm_t(pack2(y[0], y[1]))) : "memory");
    }
    TPROF(4);
    if (blk < 80) {
        uint32_t a[6][4], b[6][4];
#pragma unroll
        for (int k2 = 0; k2 < 6; k2++) ldsm4t(b[k2], tb + T_WD + (warp * 6 + k2) * 512 + lane * 16);
        for (int n = 0;; n++) {
            uint32_t m = 0;
#pragma unroll
            for (int k2 = 0; k2 < 6; k2++) asm volatile("ld.relaxed.gpu.global.v4.u32 {%0,%1,%2,%3}, [%4];" : "=r"(a[k2][0]), "=r"(a[k2][1]), "=r"(a[k2][2]), "=r"(a[k2][3]) : "l"(g_gu + (warp * 6 + k2) * 128 + lane * 4) : "memory");
#pragma unroll
            for (int k2 = 0; k2 < 6; k2++) m = umax3(umax3(m, a[k2][0], a[k2][1]), a[k2][2], a[k2][3]);
            if (!__any_sync(0xffffffffu, m == ~0u)) break;
            if (n > (1 << 22)) __trap();
        }
        TPROF(5);
        float d[2][4] = {{0, 0, 0, 0}, {0, 0, 0, 0}};
#pragma unroll
        for (int k2 = 0; k2 < 6; k2++) { mma16q(d[0], a[k2], b[k2][0], b[k2][1]); mma16q(d[1], a[k2], b[k2][2], b[k2][3]); }
        asm volatile("st.shared.v2.f32 [%0], {%1,%2};" :: "r"(tb + T_X + warp * 256 + lane * 8), "f"(d[0][0] + d[1][2]), "f"(d[0][1] + d[1][3]) : "memory");
        bar_sync(1, 256);
        if (warp == 0) {
            float y0 = 0, y1 = 0;
#pragma unroll
            for (int i = 0; i < 8; i++) { const float2 z = lds64f(tb + T_X + i * 256 + lane * 8); y0 += z.x; y1 += z.y; }
            const float sg = __fdividef(1.f, 1.f + __expf(-fr));
            *(uint32_t*)(ar.out + trow * DM + tcol) = add2(fx1, mul2(fgb, add2(fh2, mul2(pack2(y0, y1), pack2(sg, sg)))));
        }
    }
    TPROF(6);
}

__global__ void __cluster_dims__(3, 1, 1) __launch_bounds__(384, 1) k_chain(const __grid_constant__ ChainMaps mp, const __grid_constant__ ChainArgs ar) {
    const int D1 = ar.D1, DG = ar.DG;
    extern __shared__ __align__(1024) uint8_t smraw[];
    const uint32_t sm = SM_BASE + ((blockIdx.x % 3) << 24);
    if (smem_u32(smraw) != sm) __trap();
    uint32_t tid; asm volatile("mov.u32 %0, %%tid.x;" : "=r"(tid));
    const int warp = __shfl_sync(0xffffffffu, tid >> 5, 0), lane = tid & 31, wg = warp >> 2, w = warp & 3;
    const int blk = blockIdx.x, head = blk / 3, j = blk % 3;
    const int col0 = head * DH + j * 64;
    asm volatile("griddepcontrol.launch_dependents;");
#define PPROF(i)
    const int r = lane & 7, mi = lane >> 3;
    const uint32_t memrd = opaque(sm + C_MEM + lane * 16);
    if (wg < 2) {
        {
            uint32_t xv[3][10];
            const int row = blk * 8 + warp, nq = row < S_TOK - 1536 ? 3 : 2;
#pragma unroll
            for (int i = 0; i < 15; i++) {
                const uint2 v = __ldcs((const uint2*)(ar.x + (row + (i < 10 || nq == 3 ? i / 5 * 768 : 0)) * DM + lane * 4 + i % 5 * 128));
                xv[i / 5][i % 5 * 2] = v.x; xv[i / 5][i % 5 * 2 + 1] = v.y;
            }
            if (tid == 32) {
#pragma unroll 1
                for (int c = 0; c < 14; c++) if (c != 12) mbar_init(sm + C_BAR + 8 * c, c == 2 ? 5 : c == 3 ? 6 : 1);
                asm volatile("fence.mbarrier_init.release.cluster;" ::: "memory");
                mbar_expect(sm + CB_SC, 2560); mbar_expect(sm + CB_OX, 2048);
            }
            if (warp == 2) {
                const uint32_t f = blk >= 28 ? ~0u : 0u;
                ((uint4*)g_acc)[blk * 32 + lane] = make_uint4(0, 0, 0, 0);
                if (blk < 76) (blk < 12 ? (uint4*)g_stamp + blk * 32 : blk < 28 ? (uint4*)g_key + (blk - 12) * 32 : (uint4*)g_gu + (blk - 28) * 32)[lane] = make_uint4(f, f, f, f);
            }
            __syncwarp();
            asm volatile("barrier.cluster.arrive.relaxed.aligned;" ::: "memory");
            PPROF(8);
#pragma unroll 1
            for (int q = 0; q < 3; q++) {
                uint32_t nv[10];
                ln_norm(xv[0], nv);
#pragma unroll
                for (int i = 0; i < 10; i++) { xv[0][i] = xv[1][i]; xv[1][i] = xv[2][i]; xv[2][i] = nv[i]; }
            }
            PPROF(9);
            if (warp < 5) {
                uint4 u;
                for (int n = 0;; n++) {
                    asm volatile("ld.relaxed.gpu.global.v4.u32 {%0,%1,%2,%3}, [%4];" : "=r"(u.x), "=r"(u.y), "=r"(u.z), "=r"(u.w) : "l"(g_flags.mod1 + tid * 4) : "memory");
                    if (__all_sync(0xffffffffu, u.x && u.y && u.z && u.w)) break;
                    cut(n, 1 << 22);
                }
                asm volatile("st.shared.v4.u32 [%0], {%1,%2,%3,%4};" :: "r"(sm + C_KX + tid * 16), "r"(~u.x), "r"(~u.y), "r"(~u.z), "r"(~u.w) : "memory");
            }
            bar_sync(8, 256);
            PPROF(2);
            uint32_t m = 0;
#pragma unroll
            for (int i = 0; i < 5; i++) {
                uint32_t t[2], u[2];
                lds64(t, sm + C_KX + lane * 8 + i * 256); lds64(u, sm + C_KX + 1280 + lane * 8 + i * 256);
                u[0] = add2(u[0], 0x3f803f80u); u[1] = add2(u[1], 0x3f803f80u);
                m = amax2(amax2(amax2(amax2(m, t[0]), u[0]), t[1]), u[1]);
#pragma unroll
                for (int q = 0; q < 3; q++)
                    if (q < nq) *(uint2*)(g_h + (row + q * 768) * DM + lane * 4 + i * 128) = make_uint2(add2(mul2(xv[q][2 * i], u[0]), t[0]), add2(mul2(xv[q][2 * i + 1], u[1]), t[1]));
            }
            asm volatile("st.shared.u32 [%0], %1;" :: "r"(sm + C_LAG), "r"((amax_warp(m) >> 7) + 1) : "memory");
            bar_sync(8, 256);
            if (tid == 0) flag_add(&g_flags.h);
            __syncwarp();
            bar_arrive(2, 288);
            PPROF(3);
            asm volatile("barrier.cluster.wait.aligned;" ::: "memory");
        }
        asm volatile("setmaxnreg.inc.sync.aligned.u32 %0;" :: "n"(REG_P));
        uint32_t wa[40][4];
        mbar_wait(sm + CB_W, 0);
#pragma unroll
        for (int ks = 0; ks < 40; ks++)
            ldsm4t(wa[ks], sm + ((wg == 0) == (ks < 20) ? C_WV : C_WO) + ((mi >> 1) * 8 + r) * 128 + (((2 * w + (mi & 1)) ^ r) << 4) + (ks % 20 / 4 * 8 + 4 * wg + (ks & 3)) * 2048);
        PPROF(5);
        bar_arrive(1, 288);
        const uint32_t qst = opaque(sm + (wg == 0 ? C_QM : C_KM) + (2 * w + (mi & 1)) * 128 + r * 16);
        const uint32_t vrd = opaque(sm + C_WV + ((mi >> 1) * 8 + r) * 128 + (((2 * w + (mi & 1)) ^ r) << 4) + 4 * wg * 2048);
        const uint32_t mrd = opaque(memrd + wg * 1024);
        float acc[16];
        auto fb = [&](int n) { return mrd + (n >> 1) * 2048 + (n & 1) * 512; };
        auto fa = [&](int k) { return vrd + (k >> 2) * 16384 + (k & 3) * 2048; };
        auto qk_out = [&](int n) {
            uint8_t* rec = g_att + (n * NH + head) * AT_REC;
            w_bulk_s2g(rec + j * 8192, sm + C_QX, 8192); w_bulk_s2g(rec + AT_KM + j * 1024, sm + C_KM, 1024);
            BULK_COMMIT();
        };
        for (int s = -1;; s++) {
          if (s >= 0) {
            uint32_t b[3][4], a[4][4];
            x_part([&]() {
                if (AIN && s == 0) mbar_wait(sm + CB_W2, 0);
#pragma unroll
                for (int i = 0; i < AIN; i++) ldsm4t(a[i], fa(4 + i));
            }, acc, wa, sm, s, wg, w, opaque(mrd) >> 4 & 31, s + ar.D2);
            if (!AIN && s == 0) mbar_wait(sm + CB_W2, 0);
#pragma unroll
            for (int i = AIN; i < APRE; i++) ldsm4t(a[i], fa(4 + i));
            cut(s + ar.D2, 0);
            bar_sync(1, 384);
            if (warp == 0) { PROF(0); PROFG(24); }
            float dv[4] = {0, 0, 0, 0};
            const uint32_t xb = mrd - wg * 1024 - (C_MEM - C_VP) + w * 512;
            {
                float d[2][4] = {{0, 0, 0, 0}, {0, 0, 0, 0}}, g[2][4] = {{0, 0, 0, 0}, {0, 0, 0, 0}};
                ldsm4t(b[0], fb(0)); pin0(mrd); ldsm4t(b[1], fb(1)); pin0(mrd);
#pragma unroll
                for (int n = 0; n < 10; n++) {
                    const int c1 = n >= 10 - NCH;
                    if (n < 8) ldsm4t(b[(n + 2) % 3], fb(n + 2));
                    if (n < 2 && 2 * n >= APRE) { ldsm4t(a[2 * n], fa(4 + 2 * n)); ldsm4t(a[2 * n + 1], fa(5 + 2 * n)); }
#pragma unroll
                    for (int e = 0; e < 2; e++) {
                        mma16q(g[e & c1], wa[20 + 2 * n + e], b[n % 3][2 * e], b[n % 3][2 * e + 1]); mma16q(d[e & c1], wa[2 * n + e], b[n % 3][2 * e], b[n % 3][2 * e + 1]);
                        if (n >= 2 && n < 10 - VT) mma16q(dv, a[(2 * n + e) & 3], b[n % 3][2 * e], b[n % 3][2 * e + 1]);
                        if (n >= 2 && n < 8) ldsm4t(a[(2 * n + e) & 3], fa(2 * n + 4 + e));
                    }
                    if (QCUT >> n & 1) cut(s + ar.D2, 1 + n);
                }
                const float un = __uint_as_float(lds32(sm + C_UN));
                sts128f(xb - 4096 + wg * 2048, g[0][0] + g[1][0], g[0][1] + g[1][1], g[0][2] + g[1][2], g[0][3] + g[1][3]);
#pragma unroll
                for (int k = 20 - 2 * VT; k < 20; k++) mma16q(dv, a[k & 3], b[k / 2 % 3][2 * (k & 1)], b[k / 2 % 3][2 * (k & 1) + 1]);
                if (PBAR) bar_sync(10 + w, 64); else bar_sync(8, 256);
                const float4 z = lds128f(xb - 4096 + (wg ^ 1) * 2048);
                sts128f(xb + wg * 2048, dv[0], dv[1], dv[2], dv[3]);
                stsm2t(qst, pack2((d[0][0] + d[1][0] + z.x) * un, (d[0][1] + d[1][1] + z.y) * un), pack2((d[0][2] + d[1][2] + z.z) * un, (d[0][3] + d[1][3] + z.w) * un));
            }
            bar_arrive(2, 384);
            if (w == 0) PROF(1 + wg);
            if (s + 1 == NSEG) break;
          }
          if (!STL && warp == 3 && s >= 0)
              asm volatile(ELECTED("st.relaxed.gpu.global.u32 [%0], %1;") :: "l"(g_stamp + (s & 3) * 384 + (blk >> 3) * 32 + (blk & 7)), "r"((gtime() & ~31u) | ((s >> 2) + 1)) : "memory");
          PROXY_FENCE();
          mbar_wait(sm + CB_XF, (s + 1) & 1);
          if (s >= 0) bar_sync(7, 384);
          WG_FENCE();
#pragma unroll
          for (int i = 0; i < 16; i++) acc[i] = 0.f;
#pragma unroll
          for (int i = 1; i <= XA; i++) x_chunk(acc, wa, x_base(wg, s + ar.D2, 20), 20, i, i == 1);
          WG_COMMIT();
          if (warp == FW && s > 1) {
              if ((s & 3) == 0) { GPU_FENCE(); if (!BDEF) w_bump(&g_flags.qk[(s >> 2) - 1]); }
              if (BDEF && (s & 3) == 1) w_bump(&g_flags.qk[(s >> 2) - 1]);
              if (F61 && s == 62) seg_done(61, head);
          }
          if (!WLATE) WG_WAIT(0);
          if (s >= 0) {
            if (warp == 0) {
                PROF(7);
                if (elect()) x_rest(mp, sm, s + 1);
            } else {
                if (wg == 1) {
                    if (w == 1) {
                        if (QDEL) wait_until(clock() + QDEL);
                        qk_out(s);
                    }
                    if (w == 2 && blk < 20 && (s & 1) && s + 3 < NSEG)
                        asm volatile(ELECTED("cp.async.bulk.prefetch.L2.global [%0], 4096;") :: "l"((const uint8_t*)g_h + (s + 3) * (SEG * DM * 2) + blk * 4096) : "memory");
                } else if (w == 3) {
                    if (SPOLL) wait_until(clock() + SPOLL);
                    const uint32_t l = opaque(mrd) >> 4 & 31, tag = (s >> 2) + 1, now = gtime();
                    const uint32_t* sp = g_stamp + (s & 3) * 384 + (l >> 3) * 32 + (l & 7);
                    uint32_t t[3];
                    for (int n = 0;; n++) {
#pragma unroll
                        for (int i = 0; i < 3; i++) t[i] = ld_rlx(sp + i * 128);
                        if (!__any_sync(0xffffffffu, ((t[0] ^ tag) | (t[1] ^ tag) | (t[2] ^ tag)) & 31) || n > SPIN_LIMIT) break;
                    }
                    int all = -(1 << 30), own = all;
#pragma unroll
                    for (int i = 0; i < 3; i++) { const int d = t[i] - now; all = max(all, d); if ((i * 32 + l) / 3 == head) own = d; }
                    const int lag = min(__reduce_max_sync(0xffffffffu, all) - __reduce_max_sync(0xffffffffu, own), s || STL == 1 ? 8000 : 200);
                    PROFV(15, lag);
                    asm volatile("st.shared.u32 [%0], %1;" :: "r"(sm + C_LAG), "r"(D1 + ((lag * DG) >> 4)) : "memory");
                    bar_arrive(6, 160);
                } else if (w == 2) {
                    if ((s & 3) == 3) w_flag_wait(&g_flags.v[((s + 1) >> 2) * 32 + head], 2);
                    if (elect()) { mbar_expect(sm + CB_VX, 4096); bulk_g2s(sm + C_VX, g_att + ((s + 1) * NH + head) * AT_REC + AT_V + j * 4096, 4096, sm + CB_VX); }
                    if ((s & 3) == 1 && s + 3 < NSEG && blk == 20) asm volatile(ELECTED("cp.async.bulk.prefetch.L2.global [%0], 128;") :: "l"(&g_flags.v[((s + 3) >> 2) * 32]) : "memory");
                    if (s + 2 < NSEG && (s & 3) && ((s & 3) != 2 || __all_sync(0xffffffffu, ld_rlx(&g_flags.v[((s + 2) >> 2) * 32 + head]) >= 2))) {
                        const uint8_t* p = g_att + ((s + 2) * NH + head) * AT_REC + AT_V + j * 4096;
                        asm volatile(ELECTED("cp.async.bulk.prefetch.L2.global [%0], 4096;") :: "l"(p) : "memory");
                        if ((s & 3) == 3) asm volatile(ELECTED("cp.async.bulk.prefetch.L2.global [%0], 4096;") :: "l"(p + NH * AT_REC) : "memory");
                    }
                }
            }
          }
          if (WLATE) WG_WAIT(0);
        }
        PROXY_FENCE();
        bar_sync(8, 256);
        if (warp == 5) { qk_out(NSEG - 1); BULK_WAIT(); }
        if (warp == 7) { seg_done(NSEG - 2, head); if (!F61) w_bump(&g_flags.seg[32 + head]); }
        const int t2 = (opaque(mrd) >> 4 & 31) + warp * 32;
        EPT(t2 == 0, 0);
        last_blocks(ar, sm, blk, t2);
        mod_tail(ar, sm + E_B, sm + EB_REL, blk, t2);
    } else {
        asm volatile("setmaxnreg.dec.sync.aligned.u32 %0;" :: "n"(REG_L));
        asm volatile("barrier.cluster.arrive.relaxed.aligned;" ::: "memory");
        if (blk < 80) {
            const int t = tid - 256;
#pragma unroll 1
            for (int i = 0; i < 10; i++)
                asm volatile("cp.async.cg.shared.global.L2::128B [%0], [%1], 16;" :: "r"(sm + C_XR + i * 2048 + t * 16), "l"(ar.wmod + ((t >> 1) + 64 * i) * (6 * DM) + blk * 16 + (t & 1) * 8) : "memory");
            float cs[5];
#pragma unroll
            for (int i = 0; i < 5; i++) cs[i] = __uint_as_float((uint32_t)__ldg((const unsigned short*)ar.c + t + 128 * i) << 16);
#pragma unroll
            for (int i = 0; i < 5; i++) asm volatile("st.shared.f32 [%0], %1;" :: "r"(sm + C_QX + (t + 128 * i) * 4), "f"(bfr(__fdividef(cs[i], 1.f + __expf(-cs[i])))) : "memory");
            asm volatile("cp.async.wait_all;" ::: "memory");
            bar_sync(3, 128);
            float a0 = 0, a1 = 0;
#pragma unroll 8
            for (int i = 0; i < 40; i++) {
                const float f = __uint_as_float(lds32(sm + C_QX + (t >> 3) * 4 + i * 64));
                const uint32_t u = lds32(sm + C_XR + t * 4 + i * 512);
                a0 += f * lo_f(u); a1 += f * hi_f(u);
            }
#pragma unroll
            for (int o = 8; o < 32; o <<= 1) { a0 += __shfl_xor_sync(0xffffffffu, a0, o); a1 += __shfl_xor_sync(0xffffffffu, a1, o); }
            asm volatile("st.shared.v2.f32 [%0], {%1,%2};" :: "r"(sm + C_QM + w * 64 + (lane & 7) * 8), "f"(a0), "f"(a1) : "memory");
            bar_sync(3, 128);
            if (w == 0) {
#pragma unroll
                for (int i = 1; i < 4; i++) { const float2 z = lds64f(sm + C_QM + i * 64 + (lane & 7) * 8); a0 += z.x; a1 += z.y; }
                const uint32_t v = pack2(a0, a1);
                asm volatile("st.relaxed.gpu.global.u32 [%0], %1;" :: "l"(g_flags.mod1 + blk * 8 + (lane & 7)), "r"(~v) : "memory");
            }
        }
        uint32_t m0[5][4], mm = 0;
#pragma unroll
        for (int i = 0; i < 20; i++) {
            const unsigned short* p = (const unsigned short*)ar.mem0 + (i & 3) * 2 * DM + (i >> 2) * 128 + tid - 256;
            m0[i >> 2][i & 3] = __ldg(p) | (uint32_t)__ldg(p + DM) << 16;
        }
        {
            asm volatile("barrier.cluster.wait.aligned;" ::: "memory");
            if (w == 3) {
                w_flag_wait(&g_flags.h, 96);
                if (elect()) { x_fill(mp, sm, 0, j); x_rest(mp, sm, 0); }
                __syncwarp();
            }
            if (w == 1) {
                const uint64_t ef = policy_stream();
#pragma unroll 1
                for (int c = 0; c < 2 * WP + 2; c++) {
                    const uint32_t bar = sm + EB_B + 8 * (c & 1);
                    if (c == WPOS) bar_sync(2, 288);
                    if (c >= 2) mbar_wait(bar, (c / 2 - 1) & 1);
                    if (elect()) {
                        if (c < 2 * WP) { mbar_expect(bar, 81920 / WP); tma2d_ef(sm + C_WV + c * (81920 / WP), c < WP ? &mp.wq : &mp.wk, col0, c % WP * (640 / WP), bar, ef); }
                        if (c == 2 * WP + 1) mbar_arrive(sm + CB_W);
                    }
                    __syncwarp();
                }
                bar_sync(1, 288);
                if (elect()) {
                    mbar_expect(sm + CB_W2, 81920); mbar_expect(sm + CB_W3, 3 * WO_BLK);
#pragma unroll 1
                    for (int c = 0; c < 4; c++) tma2d(sm + C_WV + c * 20480, &mp.wv, col0, c * 160, sm + CB_W2);
#pragma unroll 1
                    for (int c = 0; c < 3; c++) tma3d(sm + C_WO + c * WO_BLK, &mp.wo, head * DH + (j + c) % 3 * 64, 7 * j, sm + CB_W3);
                }
                __syncwarp();
            } else {
                uint32_t mw = 0;
#pragma unroll 1
                for (int c = 0; c < 2; c++) {
                    mbar_wait(sm + (c ? CB_W3 : CB_W2), 0);
                    uint32_t m = 0;
                    const uint32_t end = sm + (c ? C_XR : C_WO);
#pragma unroll 1
                    for (uint32_t a = sm + c * C_WO + (w - (w > 0)) * 4096 + lane * 16; a < end; a += 3 * 4096) {
                        float4 z[8];
#pragma unroll
                        for (int i = 0; i < 8; i++) z[i] = lds128f(a + i * 512);
#pragma unroll
                        for (int i = 0; i < 8; i++) m = amax2(amax2(amax2(amax2(m, __float_as_uint(z[i].x)), __float_as_uint(z[i].y)), __float_as_uint(z[i].z)), __float_as_uint(z[i].w));
                    }
                    mw |= amax_warp(m) << (16 * c);
                }
                asm volatile("st.shared.u32 [%0], %1;" :: "r"(sm + C_KM + w * 4), "r"(mw) : "memory");
                bar_sync(3, 96);
                if (w == 0) asm volatile("st.relaxed.gpu.global.u32 [%0], %1;" :: "l"(g_flags.wmax + blk), "r"(amax2(amax2(mw, lds32(sm + C_KM + 8)), lds32(sm + C_KM + 12)) | 0x8000) : "memory");
            }
        }
        bar_sync(9, 384);
#pragma unroll
        for (int i = 0; i < 5; i++) {
            asm volatile("st.shared.v4.u32 [%0], {%1,%2,%3,%4};" :: "r"(sm + C_MEM + (tid - 256 + i * 128) * 16), "r"(m0[i][0]), "r"(m0[i][1]), "r"(m0[i][2]), "r"(m0[i][3]) : "memory");
            mm = amax2(amax2(amax2(amax2(mm, m0[i][0]), m0[i][1]), m0[i][2]), m0[i][3]);
        }
        asm volatile("st.shared.u32 [%0], %1; st.shared.u32 [%2], 0x3f800000;" :: "r"(sm + C_MX + w * 4), "r"(amax_warp(mm)), "r"(sm + C_UN) : "memory");
        int ew = __shfl_sync(0xffffffffu, lds32(sm + C_LAG), 0), es = 0;
        const uint32_t rb1 = (uint32_t)((j + 1) % 3 - j) << 24, rb2 = (uint32_t)((j + 2) % 3 - j) << 24;
        const float scale = 0.07216878364870322f;
        uint32_t va[8][4], mr = memrd;
#pragma unroll
        for (int i = 0; i < 8; i++) ldsm4t(va[i], sm + C_WV + ((mi >> 1) * 8 + r) * 128 + (((2 * w + (mi & 1)) ^ r) << 4) + i * 2048);
        bar_sync(1, 384);
        if (w == 0) {
            w_flag_wait(&g_flags.v[head], 2);
            if (elect()) { mbar_expect(sm + CB_VX, 4096); bulk_g2s(sm + C_VX, g_att + head * AT_REC + AT_V + j * 4096, 4096, sm + CB_VX); }
        }
        for (int s = 0; s < NSEG; s++) {
            const float un = __uint_as_float((127 - es) << 23);
            if (w == 1) {
                mbar_wait(sm + CB_XD, s & 1);
                if (s + 1 < NSEG) { if (elect()) x_fill(mp, sm, s + 1, j); }
                else { if (BPOS != 2) wo_half(mp, sm, blk, 0); if (BPOS != 0) wo_half(mp, sm, blk, 1); }
            }
            if (STL == 2 && w == 3) asm volatile(ELECTED("st.relaxed.gpu.global.u32 [%0], %1;") :: "l"(g_stamp + (s & 3) * 384 + (blk >> 3) * 32 + (blk & 7)), "r"((gtime() & ~31u) | ((s >> 2) + 1)) : "memory");
            const uint32_t l0 = mr >> 4 & 31, r0 = l0 & 7, m0 = l0 >> 3;
            float vd[4];
            {
                uint32_t c[4][4];
#pragma unroll
                for (int i = 0; i < 4; i++) ldsm4t(c[i], mr + i * 512);
                float d[2][4] = {{0, 0, 0, 0}, {0, 0, 0, 0}};
#pragma unroll
                for (int i = 0; i < 8; i++) mma16q(d[i & 1], va[i], c[i >> 1][2 * (i & 1)], c[i >> 1][2 * (i & 1) + 1]);
#pragma unroll
                for (int i = 0; i < 4; i++) vd[i] = d[0][i] + d[1][i];
            }
            uint32_t zr = 0;
            if (w == 2)
                asm volatile("atom.relaxed.gpu.global.exch.b32 %0, [%1], 0;" : "=r"(zr)
                    : "l"(g_acc + ((s & 2) ^ 2) * (ACC_PAIR / 2) + (s & 1) * 512 + (blk >> 2) * 1024 + (blk & 3) * 128 + l0 * 4) : "memory");
            __syncwarp();
            uint32_t kb[4][4] = {};
            {
                const uint32_t k7 = r0 ^ (m0 << 2 & 4), kxrd = sm + C_KX + (16 * (w & 1) + 8 * (m0 & 1) + k7) * 128 + (((m0 >> 1) ^ k7) << 4);
#pragma unroll
                for (int i = 0; i < 4; i++) if (w >= 2) ldsm4(kb[i], kxrd ^ (i << 5));
            }
            const uint32_t qrd = sm + C_QM + (w == 1 ? (m0 & 1) * 2 + (m0 >> 1) : m0) * 128 + r0 * 16;
            const uint32_t scdst = sm + C_SC + j * 1280 + (w == 1 ? 1024 + l0 * 8 : (w & 1) * 512 + (l0 & 2) * 128 + (l0 >> 2) * 32 + (l0 & 1) * 16);
            const uint32_t scrd = sm + C_SC + (l0 >> 4) * 256 + (l0 & 3) * 32 + (l0 >> 2 & 3) * 8;
            const uint32_t v7 = (4 * (m0 & 1) + (r0 >> 1)) ^ (r0 << 2 & 4), vxrd = sm + C_VX + (16 * (m0 >> 1) + 8 * (r0 & 1) + v7) * 128 + (((2 * w) ^ v7) << 4);
            if (s == 0) {
                uint32_t t[3];
                for (int n = 0;; n++) {
#pragma unroll
                    for (int i = 0; i < 3; i++) t[i] = ld_rlx(g_flags.wmax + l0 + 32 * i);
                    if (__all_sync(0xffffffffu, t[0] && t[1] && t[2])) break;
                    cut(n, 1 << 22);
                }
                const uint32_t m = amax2(amax2(amax2(0, t[0]), t[1]), t[2]);
                const int e = 371 - (int)(__reduce_max_sync(0xffffffffu, m & 0xffffu) >> 7) - (int)(__reduce_max_sync(0xffffffffu, m >> 16) >> 7);
                ew = e << 16 | (min(e - ew, 100) & 0xffff);
            }
            mbar_wait(sm + CB_VX, s & 1);
            uint32_t vb[2][4];
            ldsm4t(vb[0], vxrd); ldsm4t(vb[1], vxrd ^ 16);
            const uint32_t word = sm + C_WO + (m0 & 1) * 4096 + ((m0 >> 1) * 8 + r0) * 64 + ((w ^ (r0 >> 1)) << 4);
            const uint32_t word6 = word + 6 * 4096 - (m0 & 1) * 3072;
            const uint32_t oxrd = sm + C_OX + l0 * 8;
            const uint32_t ord = oxrd + w * 256;
            const uint32_t vp = mr - (C_MEM - C_VP) + w * 512, vmst = mr + (C_VM - C_MEM) + w * 256;
            pin(mr, scdst + rb1, sm + CB_SC + rb1, scdst + rb2, sm + CB_SC + rb2); pin(mr, qrd, scdst, scrd, vp); pin(mr, word, word6, oxrd, ord);
            pin(mr, __float_as_uint(vd[0]), __float_as_uint(vd[1]), __float_as_uint(vd[2]), __float_as_uint(vd[3]));
            bar_sync(2, 384);
            const bool odd = mr & 16;
            float4 y0, y1, mx4;
            if (s + 1 == NSEG) {
                y0 = lds128f(vp); y1 = lds128f(vp + 2048);
                stsm2t(vmst, pack2((vd[0] + y0.x + y1.x) * un, (vd[1] + y0.y + y1.y) * un), pack2((vd[2] + y0.z + y1.z) * un, (vd[3] + y0.w + y1.w) * un));
                PROXY_FENCE();
                bar_sync(3, 128);
                if (w == 1) { w_bulk_s2g(g_att + (s * NH + head) * AT_REC + AT_VM + j * 1024, sm + C_VM, 1024); BULK_COMMIT(); BULK_WAIT(); }
                break;
            }
            {
                uint32_t qa[2][4];
                ldsm4(qa[0], qrd); ldsm4(qa[1], qrd + 512);
                float sc[2][4] = {{0, 0, 0, 0}, {0, 0, 0, 0}};
                if (w == 1) {
                    ldsm4(kb[0], mr + (C_KM - C_MEM)); ldsm4(kb[1], mr + (C_KM - C_MEM) + 512);
                    pin0(mr); y0 = lds128f(vp); y1 = lds128f(vp + 2048); mx4 = lds128f(sm + C_MX);
#pragma unroll
                    for (int k = 0; k < 4; k++) mma16q(sc[k & 1], qa[k >> 1], kb[k >> 1][2 * (k & 1)], kb[k >> 1][2 * (k & 1) + 1]);
                    const uint32_t a0 = __float_as_uint(sc[0][0] + sc[1][2]), a1 = __float_as_uint(sc[0][1] + sc[1][3]);
                    if (B7E) { pin(mr, a0, a1, __float_as_uint(y1.x), 0); bar_arrive(7, 384); }
                    send8(scdst + rb1, sm + CB_SC + rb1, a0, a1); send8(scdst + rb2, sm + CB_SC + rb2, a0, a1);
                    asm volatile("st.shared.v2.u32 [%0], {%1,%2};" :: "r"(scdst), "r"(a0), "r"(a1) : "memory");
                } else {
                    pin0(mr); y0 = lds128f(vp); y1 = lds128f(vp + 2048); mx4 = lds128f(sm + C_MX);
                    if (!w) {
                        if (B7E) { pin(mr, __float_as_uint(y1.x), 0, 0, 0); bar_arrive(7, 384); }
                        if (STL == 1) asm volatile(ELECTED("st.relaxed.gpu.global.u32 [%0], %1;") :: "l"(g_stamp + (s & 3) * 384 + (blk >> 3) * 32 + (blk & 7)), "r"((gtime() & ~31u) | ((s >> 2) + 1)) : "memory");
                    } else {
#pragma unroll
                        for (int k = 0; k < 4; k++) mma16q(sc[k & 1], kb[k], qa[k >> 1][2 * (k & 1)], qa[k >> 1][2 * (k & 1) + 1]);
                        const float a0 = sc[0][0] + sc[1][0], a1 = sc[0][2] + sc[1][2], a2 = sc[0][1] + sc[1][1], a3 = sc[0][3] + sc[1][3];
                        if (B7E) { pin(mr, __float_as_uint(a0), __float_as_uint(y1.x), 0, 0); bar_arrive(7, 384); }
                        send16(scdst + rb1, sm + CB_SC + rb1, a0, a1, a2, a3); send16(scdst + rb2, sm + CB_SC + rb2, a0, a1, a2, a3);
                        sts128f(scdst, a0, a1, a2, a3);
                    }
                }
            }
            if (!B7E) bar_arrive(7, 384);
            __syncwarp();
            if (elect()) mbar_arrive(sm + CB_SC);
            {
                const float4 z = mx4;
                const int em = (int)(max(max(__float_as_uint(z.x), __float_as_uint(z.y)), max(__float_as_uint(z.z), __float_as_uint(z.w))) >> 7) - es;
                es = __shfl_sync(0xffffffffu, max(min((ew >> 16) - em, (int)(short)ew), -120), 0);
            }
            if (w == 0) PROF(4);
            const uint32_t vm0 = pack2((vd[0] + y0.x + y1.x) * un, (vd[1] + y0.y + y1.y) * un), vm1 = pack2((vd[2] + y0.z + y1.z) * un, (vd[3] + y0.w + y1.w) * un);
            stsm2t(vmst, vm0, vm1);
            cut(s + ar.D2, 0);
            mbar_wait(sm + CB_SC, s & 1);
            if (w == 0) PROF(8);
            float sv[10];
            {
                float2 z[5][3];
#pragma unroll
                for (int u = 0; u < 5; u++)
#pragma unroll
                    for (int p = 0; p < 3; p++) z[u][p] = lds64f((u < 4 ? scrd + (u >> 1) * 512 + (u & 1) * 128 : oxrd + (C_SC - C_OX) + 1024) + p * 1280);
#pragma unroll
                for (int u = 0; u < 5; u++) { sv[2 * u] = (z[u][0].x + z[u][1].x) + z[u][2].x; sv[2 * u + 1] = (z[u][0].y + z[u][1].y) + z[u][2].y; }
            }
            float mx = fmaxf(fmaxf(fmaxf(sv[0], sv[1]), fmaxf(sv[2], sv[3])), fmaxf(fmaxf(fmaxf(sv[4], sv[5]), fmaxf(sv[6], sv[7])), fmaxf(sv[8], sv[9])));
            uint32_t a[NRING][4];
            auto frag = [&](int i) { const int p = i / 7, u = i % 7, o = (p >> 1) * WO_BLK + (p & 1) * 2048;
                                     return u == 3 ? word6 + o : word + o + (u > 3 ? 1024 + (u - 4) * 8192 : u * 8192); };
            mx = fmaxf(fmaxf(mx, __shfl_xor_sync(0xffffffffu, mx, 1)), fmaxf(__shfl_xor_sync(0xffffffffu, mx, 2), __shfl_xor_sync(0xffffffffu, mx, 3)));
            pin(mr, __float_as_uint(mx), 0, 0, 0);
            {
#pragma unroll
                for (int i = 0; i < NPRE; i++) ldsm4t(a[i], frag(i));
                pin0(mr);
                const float sl2e = scale * 1.4426950408889634f, mxl = mx * sl2e;
#pragma unroll
                for (int i = 9; i >= 0; i--) asm volatile("ex2.approx.ftz.f32 %0, %1;" : "=f"(sv[i]) : "f"(fmaf(sv[i], sl2e, -mxl)));
                const uint32_t pq[4] = {pack2(sv[0], sv[1]), pack2(sv[4], sv[5]), pack2(sv[2], sv[3]), pack2(sv[6], sv[7])}, pm = pack2(sv[8], sv[9]);
                if (w == 0) PROF(6);
                float o[2][4] = {{0, 0, 0, 0}, {0, 0, 0, 0}}, o2[2][4] = {{0, 0, 0, 0}, {0, 0, 0, 0}}, sx[4] = {0, 0, 0, 0};
                mma8(sx, pm, 0, 0x3f803f80u); mma8(o[0], pm, 0, vm0); mma8(o[1], pm, 0, vm1);
                mma16q(sx, pq, 0x3f803f80u, 0x3f803f80u);
#pragma unroll
                for (int u = 0; u < 2; u++) { mma16q(o[u], pq, vb[u][0], vb[u][1]); mma16q(o2[u], pq, vb[u][2], vb[u][3]); }
                float inv; asm("rcp.approx.ftz.f32 %0, %1;" : "=f"(inv) : "f"((sx[0] + sx[2]) * __uint_as_float((127 - es) << 23)));
                const uint32_t f0 = pack2((o[0][0] + o2[0][2]) * inv, (o[0][1] + o2[0][3]) * inv), f1 = pack2((o[1][0] + o2[1][2]) * inv, (o[1][1] + o2[1][3]) * inv);
                send8(ord + 2048 + rb1, sm + CB_OX + rb1, f0, f1); send8(ord + 1024 + rb2, sm + CB_OX + rb2, f0, f1);
                asm volatile("st.shared.v2.u32 [%0], {%1,%2};" :: "r"(ord), "r"(f0), "r"(f1) : "memory");
            }
            if (w == 0) PROF(10);
#pragma unroll
            for (int i = NPRE; i < NRING; i++) ldsm4t(a[i], frag(i));
            bar_sync(3, 128);
            float e[5][4];
#pragma unroll
            for (int q = 0; q < 5; q++) e[q][0] = e[q][1] = e[q][2] = e[q][3] = 0.f;
            constexpr int LAG = 2;
            uint8_t* pdst = g_acc + ((s & 2) * (ACC_PAIR / 2) + (s & 1) * 512 + w * 2048 + j * 8192 - C_MEM - sm + mr);
#pragma unroll
            for (int h = 0; h < 3; h++) {
                uint32_t ob[4][2];
                if (h == 1) {
#pragma unroll
                    for (int i = 14 - LAG; i < 14; i++) ldsm4t(a[i % NRING], frag(i + NRING));
                    pin(mr, zr, (uint32_t)(uint64_t)pdst, (uint32_t)((uint64_t)pdst >> 32), 0);
                    mbar_wait(sm + CB_OX, s & 1);
                    if (w == 0) PROF(9);
                }
#pragma unroll
                for (int k = 0; k < 4; k++) lds64(ob[k], oxrd + h * 1024 + k * 256);
#pragma unroll
                for (int i = 14 * h; i < 14 * h + 14; i++) {
                    const int u = i % 7, k = 2 * (i / 7 & 1);
                    if (u == 3) { mma16q(e[3], a[i % NRING], ob[k][0], ob[k][1]); mma16q(e[4], a[i % NRING], ob[k + 1][0], ob[k + 1][1]); }
                    else mma16q(e[u & 3], a[i % NRING], ob[k + (u >> 2)][0], ob[k + (u >> 2)][1]);
                    if (i == B5AT) { pin(mr, a[i % NRING][0], a[i % NRING][1], a[i % NRING][2], a[i % NRING][3]); bar_arrive(5, 384); }
                    if (i >= LAG && !(i >= 14 && i < 14 + LAG) && i - LAG + NRING < 42) ldsm4t(a[(i - LAG) % NRING], frag(i - LAG + NRING));
                }
            }
            {
                const uint32_t w6 = pack2h(e[3][0] + e[4][2], e[3][1] + e[4][3]), one = 0x3c003c00u;
                asm volatile("red.relaxed.gpu.global.add.noftz.v4.f16x2 [%0], {%1,%2,%3,%4};"
                    :: "l"(pdst), "r"(pack2h(e[0][0], e[0][1])), "r"(pack2h(e[0][2], e[0][3])), "r"(pack2h(e[1][0], e[1][1])), "r"(odd ? w6 : one) : "memory");
                asm volatile("red.relaxed.gpu.global.add.noftz.v4.f16x2 [%0], {%1,%2,%3,%4};"
                    :: "l"(pdst + 1024), "r"(pack2h(e[1][2], e[1][3])), "r"(pack2h(e[2][0], e[2][1])), "r"(pack2h(e[2][2], e[2][3])), "r"(odd ? one : w6) : "memory");
            }
            const uint32_t tw = clock();
            if (w == 0) { PROF(14); PROFG(25); }
            PROXY_FENCE();
            bar_sync(6, 160);
            mr = opaque(mr);
            const uint32_t ln = mr >> 4 & 31, due = tw + lds32(sm + C_LAG);
            const uint32_t vr = sm + C_WV + ((ln >> 4) * 8 + (ln & 7)) * 128 + (((2 * w + (ln >> 3 & 1)) ^ (ln & 7)) << 4);
            const uint32_t ms0 = sm + C_MEM + w * 128 + (ln & 7) * 16 + (ln >> 3) * 512, ms1 = ms0 + (ln < 24 ? 2048 : 1536);
            if (BPOS == 2 && w == 0 && s + 2 == NSEG) wo_half(mp, sm, blk, 0);
            if (w == 2) { w_expect(sm + CB_SC, 2560); w_expect(sm + CB_OX, 2048); asm volatile("st.shared.u32 [%0], %1;" :: "r"(sm + C_UN), "r"((127 - es) << 23) : "memory"); }
            if (w == 0) { w_bulk_s2g(g_att + (s * NH + head) * AT_REC + AT_VM + j * 1024, sm + C_VM, 1024); BULK_COMMIT(); }
            const uint8_t* src = pdst - j * 8192;
            pin(mr, ms0, ms1, (uint32_t)(uint64_t)src, (uint32_t)((uint64_t)src >> 32));
            pin(mr, vr, due, 0, 0);
            cut(s + ar.D2, 1);
#pragma unroll
            for (int i = 0; i < 8; i++) ldsm4t(va[i], vr + i * 2048);
            wait_until(due);
            if (w == 0) { PROF(5); PROFG(26); }
            uint4 v[6];
            auto fetch = [&]() {
#pragma unroll
                for (int k = 0; k < 6; k++)
                    asm volatile("ld.relaxed.gpu.global.v4.u32 {%0,%1,%2,%3}, [%4];" : "=r"(v[k].x), "=r"(v[k].y), "=r"(v[k].z), "=r"(v[k].w) : "l"(src + (k >> 1) * 8192 + (k & 1) * 1024) : "memory");
            };
            fetch();
            PROFV(20 + w, 0);
            bar_sync(9, 384);
            uint32_t cv[3][7];
#pragma unroll 1
            for (int n = 0; __any_sync(0xffffffffu, ~((odd ? v[1].w & v[3].w & v[5].w : v[0].w & v[2].w & v[4].w)) & 0x50005000u); n++) {
                PROFV(20 + w, n + 1);
                cut(n, SPIN_LIMIT);
                uint32_t miss = 0;
#pragma unroll
                for (int k = 0; k < 3; k++) miss |= (~(odd ? v[2 * k + 1].w : v[2 * k].w) & 0x50005000u) ? (odd ? 2u : 1u) << (2 * k) : 0u;
                miss |= __shfl_xor_sync(0xffffffffu, miss, 1);
#pragma unroll
                for (int k = 0; k < 6; k++)
                    asm volatile("{ .reg .pred q; setp.ne.u32 q, %5, 0; @q ld.relaxed.gpu.global.v4.u32 {%0,%1,%2,%3}, [%4]; }" : "+r"(v[k].x), "+r"(v[k].y), "+r"(v[k].z), "+r"(v[k].w)
                        : "l"(src + (k >> 1) * 8192 + (k & 1) * 1024), "r"(miss & (1u << k)) : "memory");
            }
#pragma unroll
            for (int k = 0; k < 3; k++) {
                const uint4 x = v[2 * k], y = v[2 * k + 1];
                const uint32_t u[7] = {x.x, x.y, x.z, y.x, y.y, y.z, k < 2 ? (odd ? x.w : y.w) : 0u};
#pragma unroll
                for (int i = 0; i < 7; i++) cv[k][i] = f16_to_bf16(u[i]);
                stsm4(ms0 + k * 3584, cv[k][0], cv[k][1], cv[k][2], cv[k][3]);
                if (k < 2) stsm4(ms1 + k * 3584, cv[k][4], cv[k][5], cv[k][6], cv[k][6]);
                else asm volatile("stmatrix.sync.aligned.m8n8.x2.shared.b16 [%0], {%1,%2};" :: "r"(ms1 + k * 3584), "r"(cv[k][4]), "r"(cv[k][5]) : "memory");
            }
            if (w == 0) PROF(16);
            bar_sync(1, 384);
            if (w == 0) BULK_WAIT();
            cut(s + ar.D2, 2);
            uint32_t mc = 0;
#pragma unroll
            for (int i = 0; i < 20; i++) mc = amax2(mc, cv[i / 7][i % 7]);
            asm volatile("st.shared.u32 [%0], %1;" :: "r"(sm + C_MX + w * 4), "r"(amax_warp(mc)) : "memory");
        }
        if (w >= 2) end_loads(mp, ar, sm, blk, w - 2);
        else if (w == 1) { bar_sync(5, 384); seg_done(NSEG - 1, head); EPT(true, 9); if (EORD) bar_arrive(6, 96); if (BPOS == 0) wo_half(mp, sm, blk, 1); }
        else bar_arrive(5, 384);
        if (w < 2) end_stores(mp, sm, blk, w);
        if (w == 0) { mbar_wait(sm + EB_REL, 0); flags_release(mr >> 4 & 31); }
    }
}

struct SideMaps { CUtensorMap h, wv, ost, o, wo, slab, lnp[3]; };
constexpr int SD_ST = 14336, SD_NST = 12, SD_EPI = SD_NST * SD_ST, SD_PAR = SD_EPI + 2 * 24576, SD_BAR = SD_PAR + 6400, SD_SMEM = SD_BAR + 1024;
#define VLEAD 16
#define EARLY15 1
#define N_LIGHT 9
#define B_HELP 13
#define AUNR_ 2
constexpr int AUNR = AUNR_;
#define VKS 4
#define RATE 0
#define SGP 300
#define SG0 0
#define KSO 4
#define KSA 3
#define B_8 10
#define B_16 13
__device__ __forceinline__ int o_shift(int b) { return b >= B_16 ? 4 : b >= B_8 ? 3 : 2; }
__device__ __forceinline__ int o_split(int b) { return 1 << o_shift(b); }
__device__ __forceinline__ uint32_t o_done(int b) { return b >= B_LATE ? 160 : 4 << o_shift(b); }
__device__ __forceinline__ int next_item(int lane) {
    const int b0 = lane & 15, hi = lane >> 4;
    for (int n = 0;; n++) {
        const uint32_t w0 = ld_rlx(g_flags.qk + lane), w1 = ld_rlx(g_flags.at + lane), w2 = ld_rlx(&g_flags.c[0][0] + lane), w3 = ld_rlx(&g_flags.c[2][0] + lane), w4 = ld_rlx(&g_flags.seg[32]);
        const uint32_t o01 = __ballot_sync(0xffffffffu, lane && w2 < 32), o23 = __ballot_sync(0xffffffffu, b0 < (hi ? 14 : B_LATE) && w3 < 2u * o_split(b0));
        uint32_t ra = __ballot_sync(0xffffffffu, w0 >= (hi ? 64u : 96u));
        const uint32_t rb = __ballot_sync(0xffffffffu, w1 >= (hi ? o_done(b0) : 64u));
        const int bv = __ffs(o01 | 0x10000) - 1, ba = __ffs(o01 >> 16 | 0x10000) - 1, bo = __ffs(o23 | 0x10000) - 1, bl = __ffs(o23 >> 16 | 0x10000) - 1;
        if (bl == 16 && ba == 16) return -1;
        const int bc = __ffs(~ra | 0x10000) - 1;
        const bool last = ba == 15 && (w4 >= 3 || (EARLY15 && bc == 15));
        const bool r1 = (ra & ra >> 16) >> ba & 1, r2 = (rb & 0xffff) >> bo & 1, r3 = rb >> 16 >> bl & 1;
        const int kind = ba == 16 ? (bo < 16 ? 2 : 3) : last ? 1 :
                         blockIdx.x < N_LIGHT ? (r1 ? 1 : r3 ? 3 : bv < 16 ? 0 : -1) :
                         bv < 16 && (bv <= bc + VLEAD || !r2) ? 0 : r1 && ba >= B_HELP ? 1 : r2 ? 2 : r1 ? 1 : r3 ? 3 : bo < ba ? 2 : -1;
        if (kind < 0) { if (n > (1 << 20)) __trap(); __nanosleep(IDLE); continue; }
        const int b = kind == 3 ? bl : kind == 2 ? bo : kind == 1 ? ba : bv;
        uint32_t i = 0;
        if (lane == 0) asm volatile("atom.relaxed.gpu.global.add.u32 %0, [%1], 1;" : "=r"(i) : "l"(&g_flags.c[kind][b]) : "memory");
        i = __shfl_sync(0xffffffffu, i, 0);
        if (i < (kind < 2 ? 32u : 2u * o_split(b))) return kind << 16 | b << 8 | i | ((kind == 1 ? r1 : kind == 2 ? r2 : r3) ? 128 : 0);
    }
}

template <int NP>
__device__ __forceinline__ void tile_out(const float (&acc)[8 * NP], uint32_t eb, uint32_t CH, uint32_t efull, uint32_t eempty, int& eph, int lane) {
    const int r = lane & 7, mi = lane >> 3, row = (mi & 1) * 8 + r;
    mbar_wait(eempty, eph); eph ^= 1;
#pragma unroll
    for (int p = 0; p < NP; p++) {
        const int oc = 2 * p + (mi >> 1);
        stsm4(eb + (oc >> 3) * CH + row * 128 + (((oc & 7) ^ r) << 4), pack2(acc[8 * p], acc[8 * p + 1]), pack2(acc[8 * p + 2], acc[8 * p + 3]),
              pack2(acc[8 * p + 4], acc[8 * p + 5]), pack2(acc[8 * p + 6], acc[8 * p + 7]));
    }
    asm volatile("fence.proxy.async.shared::cta;" ::: "memory");
    __syncwarp();
    if (lane == 0) mbar_arrive(efull);
}

template <int MT>
__device__ __forceinline__ void attn_tile(uint32_t base, uint32_t dst, uint32_t eempty, int eph, int lane) {
    constexpr int NK = MT ? 5 : 3;
    const int r = lane & 7, mi = lane >> 3, g = lane >> 2, t = lane & 3;
    float sc[NK][4];
#pragma unroll
    for (int n = 0; n < NK; n++) sc[n][0] = sc[n][1] = sc[n][2] = sc[n][3] = 0.f;
#pragma unroll AUNR
    for (int k2 = 0; k2 < 6; k2++) {
        const uint32_t cb = (k2 >> 1) * 8192, c0 = (k2 & 1) * 4;
        uint32_t a0[4], a1[4], bb[NK][4];
        ldsm4(a0, base + cb + (16 * MT + (mi & 1) * 8 + r) * 128 + (((c0 + (mi >> 1)) ^ r) << 4));
        ldsm4(a1, base + cb + (16 * MT + (mi & 1) * 8 + r) * 128 + (((c0 + 2 + (mi >> 1)) ^ r) << 4));
#pragma unroll
        for (int n = 0; n < NK; n++)
            ldsm4(bb[n], n < NK - 1 ? base + 4096 + cb + (8 * n + r) * 128 + (((c0 + mi) ^ r) << 4) : base + 36864 + k2 * 512 + lane * 16);
#pragma unroll
        for (int n = 0; n < NK; n++) mma16(sc[n], a0[0], a0[1], a0[2], a0[3], bb[n][0], bb[n][1]);
#pragma unroll
        for (int n = 0; n < NK; n++) mma16(sc[n], a1[0], a1[1], a1[2], a1[3], bb[n][2], bb[n][3]);
    }
    const float scale = 0.07216878364870322f, l2e = 1.4426950408889634f;
    float v[2][2 * NK], mx[2], sum[2];
#pragma unroll
    for (int hf = 0; hf < 2; hf++) {
        mx[hf] = -INFINITY;
#pragma unroll
        for (int n = 0; n < NK; n++) {
            uint32_t u = pack2(sc[n][2 * hf], sc[n][2 * hf + 1]);
            u = pack2(lo_f(u) * scale, hi_f(u) * scale);
            const int lim = 16 * MT + 8 * hf + g - 8 * n - 2 * t;
            v[hf][2 * n] = (n < NK - 1 && lim < 0) ? -1e9f : lo_f(u);
            v[hf][2 * n + 1] = (n < NK - 1 && lim < 1) ? -1e9f : hi_f(u);
            mx[hf] = fmaxf(mx[hf], fmaxf(v[hf][2 * n], v[hf][2 * n + 1]));
        }
    }
#pragma unroll
    for (int o = 1; o < 4; o <<= 1)
#pragma unroll
        for (int hf = 0; hf < 2; hf++) mx[hf] = fmaxf(mx[hf], __shfl_xor_sync(0xffffffffu, mx[hf], o));
#pragma unroll
    for (int hf = 0; hf < 2; hf++) {
        sum[hf] = 0;
#pragma unroll
        for (int q = 0; q < 2 * NK; q++) { asm("ex2.approx.ftz.f32 %0, %1;" : "=f"(v[hf][q]) : "f"((v[hf][q] - mx[hf]) * l2e)); sum[hf] += v[hf][q]; }
    }
#pragma unroll
    for (int o = 1; o < 4; o <<= 1)
#pragma unroll
        for (int hf = 0; hf < 2; hf++) sum[hf] += __shfl_xor_sync(0xffffffffu, sum[hf], o);
    uint32_t pa[NK][2];
#pragma unroll
    for (int hf = 0; hf < 2; hf++) {
        const float inv = __fdividef(1.f, sum[hf]);
#pragma unroll
        for (int n = 0; n < NK; n++) pa[n][hf] = pack2(v[hf][2 * n] * inv, v[hf][2 * n + 1] * inv);
    }
    mbar_wait(eempty, eph);
#pragma unroll AUNR
    for (int n4 = 0; n4 < 6; n4++) {
        const uint32_t cb = (n4 >> 1) * 4096, c0 = (n4 & 1) * 4;
        uint32_t bm[4], bb[2 + 2 * MT][4];
        ldsm4t(bm, base + AT_VM + n4 * 512 + lane * 16);
#pragma unroll
        for (int u = 0; u < 2 + 2 * MT; u++) ldsm4t(bb[u], base + AT_V + cb + (16 * (u >> 1) + 8 * (mi & 1) + r) * 128 + (((c0 + 2 * (u & 1) + (mi >> 1)) ^ r) << 4));
        float o[4][4];
#pragma unroll
        for (int u = 0; u < 4; u++) { o[u][0] = o[u][1] = o[u][2] = o[u][3] = 0.f; mma8(o[u], pa[NK - 1][0], pa[NK - 1][1], bm[u]); }
#pragma unroll
        for (int u = 0; u < 4 + 4 * MT; u++) mma16(o[u & 3], pa[u >> 2 << 1][0], pa[u >> 2 << 1][1], pa[(u >> 2 << 1) + 1][0], pa[(u >> 2 << 1) + 1][1], bb[u >> 1][2 * (u & 1)], bb[u >> 1][2 * (u & 1) + 1]);
#pragma unroll
        for (int p = 0; p < 2; p++)
            stsm4(dst + (n4 >> 1) * 2048 + ((mi & 1) * 8 + r) * 128 + (((c0 + 2 * p + (mi >> 1)) ^ r) << 4), pack2(o[2 * p][0], o[2 * p][1]), pack2(o[2 * p][2], o[2 * p][3]),
                  pack2(o[2 * p + 1][0], o[2 * p + 1][1]), pack2(o[2 * p + 1][2], o[2 * p + 1][3]));
    }
}

__device__ __forceinline__ uint32_t ln_row(const uint32_t (&as)[10], const uint2 (&xin)[5], int row, uint32_t par, uint32_t low, bf16* out, uint64_t ef, int lane) {
    const uint32_t pa = par + lane * 8;
    uint32_t xv[10], hv[10], sv[10], tv[10];
#pragma unroll
    for (int q = 0; q < 5; q++) {
        uint32_t ga[2], t[2], u[2];
        lds64(ga, pa + q * 256); lds64(t, pa + 1280 + q * 256); lds64(u, pa + 2560 + q * 256);
#pragma unroll
        for (int e = 0; e < 2; e++) {
            xv[2 * q + e] = add2(e ? xin[q].y : xin[q].x, mul2(ga[e], as[2 * q + e]));
            tv[2 * q + e] = t[e]; sv[2 * q + e] = u[e];
        }
    }
    ln_mod(xv, sv, tv, hv);
    float rs = 0;
#pragma unroll
    for (int q = 0; q < 5; q++) {
        const int c = row * DM + lane * 4 + q * 128;
        const uint32_t h0 = hv[2 * q], h1 = hv[2 * q + 1];
        uint32_t gb[2], wv[2];
        lds64(gb, pa + 3840 + q * 256); lds64(wv, pa + 5120 + q * 256);
        rs += (lo_f(h0) * lo_f(wv[0]) + hi_f(h0) * hi_f(wv[0])) + (lo_f(h1) * lo_f(wv[1]) + hi_f(h1) * hi_f(wv[1]));
        st_ef(out + c, make_uint2(add2(xv[2 * q], mul2(gb[0], h0)), add2(xv[2 * q + 1], mul2(gb[1], h1))), ef);
    }
    const uint32_t rb = pack2(0.f, warp_sum(rs));
    const uint32_t key = (((int)rb < 0 ? ~rb : rb | 0x80000000u) & 0xffff0000u) | (uint32_t)(4 * S_TOK - 1 - row);
    if (key < low) return key ^ (2 * S_TOK);
    {
#pragma unroll
        for (int q = 0; q < 5; q++) {
            *(uint2*)(g_x1 + row * DM + lane * 4 + q * 128) = make_uint2(xv[2 * q], xv[2 * q + 1]);
            *(uint2*)(g_h2 + row * DM + lane * 4 + q * 128) = make_uint2(hv[2 * q], hv[2 * q + 1]);
        }
    }
    return key;
}
__device__ __forceinline__ void key_out(uint32_t key) {
    __syncwarp();
    if (key) asm volatile("st.release.gpu.global.u32 [%0], %1;" :: "l"(g_key + (~key & (S_TOK - 1))), "r"(key) : "memory");
}

__global__ void __launch_bounds__(384, 1) k_side(const __grid_constant__ SideMaps mp, const bf16* __restrict__ x, const bf16* __restrict__ wr, const bf16* wmod, const bf16* cvec, bf16* __restrict__ out) {
    extern __shared__ __align__(1024) uint8_t smraw[];
    const uint32_t sm = smem_u32(smraw);
    if (sm & 1023) __trap();
    const uint32_t BARS = sm + SD_BAR, FULL = BARS + 768, EMPTY = FULL + 96, EFULL = BARS + 64, EEMPTY = BARS + 80, IFULL = BARS + 96, IEMPTY = BARS + 128, IQ = BARS + 160, SCHED = BARS + 176, PARAM = BARS + 184, ADONE = BARS + 192, LOW = BARS + 224, KEYS = BARS + 256;
    const int tid = threadIdx.x, warp = __shfl_sync(0xffffffffu, tid >> 5, 0), lane = tid & 31;
    const uint64_t ef = policy_stream();
    if (tid == 0) {
#pragma unroll 1
        for (int i = 0; i < SD_NST; i++) { mbar_init(FULL + 8 * i, 1); mbar_init(EMPTY + 8 * i, 2); }
        for (int i = 0; i < 2; i++) { mbar_init(EFULL + 8 * i, 4); mbar_init(EEMPTY + 8 * i, 1); }
        for (int i = 0; i < 4; i++) { mbar_init(IFULL + 8 * i, 1); mbar_init(IEMPTY + 8 * i, 11); }
        mbar_init(SCHED, 1); mbar_init(PARAM, 1);
        sts128f(ADONE, 0, 0, 0, 0); sts128f(ADONE + 16, 0, 0, 0, 0); sts128f(LOW, 0, 0, 0, 0);
        asm volatile("fence.mbarrier_init.release.cluster;" ::: "memory");
    }
    if (SDEL) __nanosleep(SDEL);
    __syncthreads();
    if (warp >= 8) {
      asm volatile("setmaxnreg.dec.sync.aligned.u32 40;");
      if (warp == 8) {
        int st = 0, ph = 1;
        uint32_t tn = clock();
        auto pace = [&](int bytes, bool on) { if (RATE && on) { wait_until(tn); tn = clock() + bytes / (RATE ? RATE : 1); } };
        for (int q = 0;; q++) {
            mbar_wait(IFULL + 8 * (q & 3), (q >> 2) & 1);
            const int it = __shfl_sync(0xffffffffu, lds32(IQ + 4 * (q & 3)), 0);
            if (elect()) mbar_arrive(IEMPTY + 8 * (q & 3));
            if (it < 0) break;
            const int kind = it >> 16, b = (it >> 8) & 255, i = it & 63;
            const int nst = kind == 0 ? 10 : kind == 1 ? 4 : kind == 2 ? 192 >> o_shift(b) : b == 14 ? 4 : 2;
            const int ksched = kind == 0 ? 4 : kind == 2 ? nst - KSO : (it & 128) ? -1 : kind == 1 ? KSA : 0;
            if (ksched < 0 && elect()) mbar_arrive(SCHED);
            const bool look = !(it & 128);
            const int nu = kind == 2 ? 2 : 3;
            if (look && kind == 1) flag_wait(&g_flags.v[b * 32 + i], 2);
            if (look && kind == 3 && b < 14) flag_wait(&g_flags.o[b], o_done(b));
            for (int kb = 0; kb < nst; kb++) {
                if (kb < 6) mbar_wait(EMPTY + 8 * st, ph);
                mbar_wait(EMPTY + 8 * (st + nu - 1), ph);
                const uint32_t base = sm + st * SD_ST, fb = FULL + 8 * st;
                if (lane && lane < nu) mbar_arrive(fb + 8 * lane);
                if (look && kind == 1) flag_wait(&g_flags.seg[max(kb, 1) * 32 + i], 3);
                if (kb == ksched && elect()) mbar_arrive(SCHED);
                if (kind == 0) {
                    if (q == 0 && kb == 0) {
                        if (elect()) {
#pragma unroll 1
                            for (int c = 0; c < 4; c++) tma3d(sm + 3 * c * SD_ST + 16384, &mp.wv, c * 64, i * 3, FULL + 24 * c);
                        }
                        flag_wait(&g_flags.h, 96);
                    }
                    pace(16384, q);
                    if (elect()) { mbar_expect(fb, 40960); tma2d(base, &mp.h, kb * 64, b * 128, fb); }
                    __syncwarp();
                    pace(24576, q);
                    if ((q || kb >= 4) && elect()) tma3d(base + 16384, &mp.wv, kb * 64, i * 3, fb);
                } else if (kind == 1) {
                    if (elect()) mbar_expect(fb, AT_REC);
#pragma unroll 1
                    for (int u = 0; u < 3; u++) {
                        pace(SD_ST, !look || kb < 2);
                        if (elect()) asm volatile("cp.async.bulk.shared::cluster.global.mbarrier::complete_tx::bytes.L2::cache_hint [%0], [%1], %2, [%3], %4;"
                            :: "r"(base + u * SD_ST), "l"(g_att + ((b * 4 + kb) * NH + i) * AT_REC + u * SD_ST), "n"(SD_ST), "r"(fb), "l"(ef) : "memory");
                        __syncwarp();
                    }
                } else if (kind == 3) {
                    if (b == 14 && !(kb & 1)) flag_wait(&g_flags.fin[(kb + (i >> 4)) * 32], 80);
                    pace(40960, b < B_LATE);
                    if (elect()) { mbar_expect(fb, 40960); tma3d_ef(base, &mp.lnp[o_shift(b) - 2], i * (160 >> o_shift(b)), b * KSPLIT + (kb << o_shift(b) >> 1), fb, ef); }
                } else {
                    const int k0 = ((i >> 1) * nst + kb) * 32;
                    pace(20480, true);
                    if (elect()) { mbar_expect(fb, 28672); tma3d(base + 8192, &mp.wo, k0, (i & 1) * 5, fb); }
                    __syncwarp();
                    if (look && kb % 12 == 0) flag_wait(&g_flags.pair[b * 16 + k0 / 384], 4);
                    pace(8192, true);
                    if (elect()) tma2d_ef(base, &mp.o, k0, b * 128, fb, ef);
                }
                __syncwarp();
                st += nu; if (st == SD_NST) { st = 0; ph ^= 1; }
            }
        }
      } else if (warp == 11) {
        bool fin = false, par = false;
        for (int q = 0;; q++) {
            if (q) mbar_wait(SCHED, (q - 1) & 1);
            int it = fin ? -1 : q == 0 && blockIdx.x < 32 ? (int)blockIdx.x : next_item(lane);
            if (it < 0 && !fin && blockIdx.x < 32) { it = 3 << 16 | 14 << 8 | blockIdx.x; fin = true; }
            if (lane == 0) {
                if (it >> 16 == 3) {
                    const int b = (it >> 8) & 255, nr = 64 >> o_shift(b);
                    asm volatile("cp.async.bulk.prefetch.L2.global [%0], %1;" :: "l"(x + (b * 128 + (it & 63) * nr) * DM), "r"(nr * DM * 2) : "memory");
                }
                mbar_wait(IEMPTY + 8 * (q & 3), ((q >> 2) & 1) ^ 1);
                asm volatile("st.shared.u32 [%0], %1;" :: "r"(IQ + 4 * (q & 3)), "r"(it) : "memory");
                mbar_arrive(IFULL + 8 * (q & 3));
            }
            if (it >> 16 >= 2 && (it >> 8 & 255) >= 2) {
                const uint4* kp = (const uint4*)g_key + max((it >> 8 & 255) - ((it >> 16) == 2 ? 5 : 3), 0) * 32 + lane;
                const uint4 k1 = __ldcg(kp), k2 = __ldcg(kp + 32);
                uint32_t m = max(max(max(k1.x, k1.y), max(k1.z, k1.w)), max(max(k2.x, k2.y), max(k2.z, k2.w)));
                m = max(m, __shfl_xor_sync(0xffffffffu, m, 1)); m = max(m, __shfl_xor_sync(0xffffffffu, m, 2));
                asm volatile("red.shared.max.u32 [%0], %1;" :: "r"(LOW), "r"(__reduce_min_sync(0xffffffffu, m)) : "memory");
            }
            if (!par && it >> 16 == 3) {
                par = true;
                flag_wait(&g_flags.mod, 64);
                if (lane == 0) { mbar_expect(PARAM, 6400); bulk_g2s(sm + SD_PAR, g_mod + 2 * DM, 5120, PARAM); bulk_g2s(sm + SD_PAR + 5120, wr, 1280, PARAM); }
            }
            __syncwarp();
            if (it < 0) break;
        }
        flags_release(lane);
      } else {
        if (lane == 0) {
            const int wg = warp - 9; int ph = 0;
            for (int q = 0;; q++) {
                mbar_wait(IFULL + 8 * (q & 3), (q >> 2) & 1);
                const int it = lds32(IQ + 4 * (q & 3));
                mbar_arrive(IEMPTY + 8 * (q & 3));
                if (it < 0) break;
                const int kind = it >> 16, b = (it >> 8) & 255, i = it & 63;
                if (kind == 3 && b == 14) continue;
                if (kind & 1) {
                    for (int n = 0;; n++) {
                        uint32_t d0, d1, d2, d3;
                        asm volatile("ld.volatile.shared.v4.u32 {%0,%1,%2,%3}, [%4];" : "=r"(d0), "=r"(d1), "=r"(d2), "=r"(d3) : "r"(ADONE + wg * 16) : "memory");
                        if (min(min(d0, d1), min(d2, d3)) > q) break;
                        if (n > (1 << 24)) __trap();
                        __nanosleep(40);
                    }
                    GPU_FENCE();
                    EPT(kind == 1 && b == 15 && wg, 17);
                    if (kind == 1) { bump(b == 15 ? &g_flags.half[(i & 30) + wg] : &g_flags.pair[b * 16 + (i >> 1)]); bump(&g_flags.at[b]); }
                    else {
#pragma unroll 1
                        for (int c = 0; c < 8; c++) { const uint32_t key = lds32(KEYS + (q & 7) * 64 + wg * 32 + c * 4); if (key) asm volatile("st.relaxed.gpu.global.u32 [%0], %1;" :: "l"(g_key + (~key & (S_TOK - 1))), "r"(key) : "memory"); }
                    }
                    continue;
                }
#pragma unroll 1
                for (int rd = 0; rd < (kind == 2 ? 2 : 1); rd++) {
                    mbar_wait(EFULL + 8 * wg, ph); ph ^= 1;
                    const uint32_t src = sm + SD_EPI + wg * 24576;
#pragma unroll 1
                    for (int c = 0; c < (kind ? 2 + rd : 6); c++) {
                        if (c && q) __nanosleep(kind && !rd ? SG0 : kind ? 2 * SGP : SGP);
                        if (kind) tma2d_store(&mp.slab, ((i & 1) * 5 + (rd ? 0 : 3) + c) * 64, (b * KSPLIT + (i >> 1)) * 128 + wg * 64, src + c * 8192);
                        else asm volatile("cp.async.bulk.global.shared::cta.bulk_group.L2::cache_hint [%0], [%1], 4096, %2;"
                            :: "l"(g_att + ((b * 4 + wg * 2 + c / 3) * NH + i) * AT_REC + AT_V + c % 3 * 4096), "r"(src + c * 4096), "l"(ef) : "memory");
                    }
                    asm volatile("cp.async.bulk.commit_group;" ::: "memory");
                    asm volatile("cp.async.bulk.wait_group.read 0;" ::: "memory");
                    mbar_arrive(EEMPTY + 8 * wg);
                }
                asm volatile("cp.async.bulk.wait_group 0;" ::: "memory");
                GPU_FENCE();
                bump(kind == 0 ? &g_flags.v[b * 32 + i] : &g_flags.o[b]);
                if (kind == 0) bump(&g_flags.vb[b]);
            }
        }
      }
    } else {
        asm volatile("setmaxnreg.inc.sync.aligned.u32 232;");
        const int wg = warp >> 2, w = warp & 3;
        int st = 0, ph = 0, eph = 1;
        bool att = false;
        uint4 mz[4] = {}; uint2 mc = {}; float ma[8] = {0, 0, 0, 0, 0, 0, 0, 0};
        const uint32_t eb = sm + SD_EPI + wg * 24576;
        for (int q = 0;; q++) {
            mbar_wait(IFULL + 8 * (q & 3), (q >> 2) & 1);
            const int itc = __shfl_sync(0xffffffffu, lds32(IQ + 4 * (q & 3)), 0);
            __syncwarp();
            if (lane == 0) mbar_arrive(IEMPTY + 8 * (q & 3));
            if (itc < 0) break;
            const int kind = itc >> 16, b = (itc >> 8) & 255, i = itc & 63;
            if (q >= 1 && q <= 9 && blockIdx.x < 32) {
                const int t = min(tid, 199), k = t / 10 * 32 + (q - 1) * 4;
#pragma unroll
                for (int e = 0; e < 4; e++) {
                    const uint32_t cw = e & 2 ? mc.y : mc.x;
                    const float c = e & 1 ? hi_f(cw) : lo_f(cw), f = bfr(__fdividef(c, 1.f + __expf(-c)));
                    ma[0] += f * lo_f(mz[e].x); ma[1] += f * hi_f(mz[e].x); ma[2] += f * lo_f(mz[e].y); ma[3] += f * hi_f(mz[e].y);
                    ma[4] += f * lo_f(mz[e].z); ma[5] += f * hi_f(mz[e].z); ma[6] += f * lo_f(mz[e].w); ma[7] += f * hi_f(mz[e].w);
                }
                if (q < 9) {
#pragma unroll
                    for (int e = 0; e < 4; e++) mz[e] = __ldcs((const uint4*)(wmod + (k + e) * (6 * DM) + 2 * DM + blockIdx.x * 80 + t % 10 * 8));
                    mc = __ldg((const uint2*)(cvec + k));
                } else {
                    sts128f(sm + SD_PAR + t * 32, ma[0], ma[1], ma[2], ma[3]); sts128f(sm + SD_PAR + 16 + t * 32, ma[4], ma[5], ma[6], ma[7]);
                    bar_sync(1, 256);
                    if (tid < 40) {
                        float a0 = 0, a1 = 0;
#pragma unroll 4
                        for (int g = 0; g < 20; g++) { const float2 v = lds64f(sm + SD_PAR + g * 320 + tid * 8); a0 += v.x; a1 += v.y; }
                        ((uint32_t*)(g_mod + 2 * DM + blockIdx.x * 80))[tid] = pack2(a0, a1);
                    }
                    __syncwarp();
                    if (warp < 2 && lane == 0) flag_add(&g_flags.mod);
                }
            }
            if (att && kind != 1) { bar_sync(1, 256); att = false; }
            int prev = -1;
            auto next = [&](int nu) {
                WG_COMMIT();
                WG_WAIT(1);
                if (prev >= 0 && (tid & 127) < nu) mbar_arrive(EMPTY + 8 * (prev + (tid & 127)));
                prev = st;
                st += nu; if (st == SD_NST) { st = 0; ph ^= 1; }
            };
            auto desc = [](uint32_t lo, uint32_t hi) { return (uint64_t)hi << 32 | lo; };
            if (kind == 0) {
                float acc[96];
#pragma unroll
                for (int n = 0; n < 96; n++) acc[n] = 0.f;
#pragma unroll 1
                for (int kb = 0; kb < 10; kb++) {
                    mbar_wait(FULL + 8 * st, ph);
                    const uint32_t d0 = (sm + st * SD_ST) >> 4, da = d0 + wg * 512 + 0x10000, db = d0 + 1024 + 0x2000000;
                    WG_FENCE();
#pragma unroll
                    for (int ks = 0; ks < VKS; ks++) wgmma_ss_n192_tb(acc, desc(da + ks * 2, 0x40000040), desc(db + ks * 128, 0x40000040), 1);
                    next(3);
                }
                WG_WAIT(0);
                if ((tid & 127) < 3) mbar_arrive(EMPTY + 8 * (prev + (tid & 127)));
                tile_out<12>(acc, eb + (w >> 1) * 12288 + (w & 1) * 2048, 4096, EFULL + 8 * wg, EEMPTY + 8 * wg, eph, lane);
            } else if (kind == 2) {
                float acc[96], acc2[64];
#pragma unroll
                for (int n = 0; n < 96; n++) acc[n] = 0.f;
#pragma unroll
                for (int n = 0; n < 64; n++) acc2[n] = 0.f;
                int kb = 192 >> o_shift(b);
#pragma unroll 1
                do {
                    mbar_wait(FULL + 8 * st, ph);
                    const uint32_t d0 = (sm + st * SD_ST) >> 4, da = d0 + wg * 256 + 0x10000, db = d0 + 512 + 0x1000000;
                    WG_FENCE();
#pragma unroll
                    for (int ks = 0; ks < 2; ks++) {
                        wgmma_ss_n192_tb(acc, desc(da + ks * 2, 0x80000020), desc(db + ks * 128, 0x40000040), 1);
                        wgmma_ss_n128_tb(acc2, desc(da + ks * 2, 0x80000020), desc(db + 768 + ks * 128, 0x40000040), 1);
                    }
                    next(2);
                } while (--kb);
                WG_WAIT(0);
                if ((tid & 127) < 2) mbar_arrive(EMPTY + 8 * (prev + (tid & 127)));
                tile_out<8>(acc2, eb + w * 2048, 8192, EFULL + 8 * wg, EEMPTY + 8 * wg, eph, lane);
                tile_out<12>(acc, eb + w * 2048, 8192, EFULL + 8 * wg, EEMPTY + 8 * wg, eph, lane);
            } else if (kind == 1) {
                const int seg = warp >> 1, mt = warp & 1;
                int sst = st + 3 * seg, sph = ph; if (sst >= SD_NST) { sst -= SD_NST; sph ^= 1; }
                ph ^= 1;
                mbar_wait(FULL + 8 * sst, sph);
                EPT(tid == 224 && b == 15, 16);
                const uint32_t base = sm + sst * SD_ST;
                if (mt) attn_tile<1>(base, eb + w * 6144, EEMPTY + 8 * wg, eph, lane);
                else attn_tile<0>(base, eb + w * 6144, EEMPTY + 8 * wg, eph, lane);
                asm volatile("fence.proxy.async.shared::cta;" ::: "memory");
                __syncwarp();
                if (lane < 3) mbar_arrive(EMPTY + 8 * (sst + lane));
                if (lane == 0) {
                    tma3d_store(&mp.ost, b * 128 + warp * 16, i * 3, eb + w * 6144, ef, false);
                    BULK_COMMIT(); BULK_WAIT();
                    asm volatile("st.release.cta.shared.u32 [%0], %1;" :: "r"(ADONE + warp * 4), "r"(q + 1) : "memory");
                }
                __syncwarp();
                att = true;
            } else {
                const int sh = o_shift(b), nr = 64 >> sh, fw = b == 14 ? wg : 0, row0 = (b + fw) * 128 + i * nr, lw = warp - 4 * fw;
                if (fw) { ph ^= st != 0; st ^= 6; }
                uint2 xin[2][5];
                uint32_t as[2][10] = {};
#pragma unroll
                for (int q2 = 0; q2 < 10; q2++) xin[q2 & 1][q2 >> 1] = ld_ef(x + (row0 + ((warp + 8 * (q2 & 1)) & (nr - 1))) * DM + lane * 4 + (q2 >> 1) * 128, ef);
                mbar_wait(PARAM, 0); mbar_wait(FULL + 8 * st, ph); mbar_wait(FULL + 8 * st + 24, ph);
                EPT((tid & 127) == 0 && b == 14, 18 + wg);
#pragma unroll 1
                for (int lrow = lw + (nr & 16) / 2; lrow >= 0 && lrow < nr; lrow -= 8) {
                    const uint32_t one = (lane >> 3) == (lane & 3) ? 0x3f80u << (lane << 2 & 16) : 0u;
                    float a[5][4] = {};
#pragma unroll 2
                    for (int k = 0; k < (1 << sh >> 1); k++) {
                        const uint32_t ad = sm + st * SD_ST + ((k << (6 - sh)) + lrow) * 1280 + lane * 8;
#pragma unroll
                        for (int q2 = 0; q2 < 5; q2++) {
                            uint32_t z0[2], z1[2];
                            lds64(z0, ad + q2 * 256); lds64(z1, ad + 3 * SD_ST + q2 * 256);
                            mma16(a[q2], z0[0], z0[1], z1[0], z1[1], one, one);
                        }
                    }
#pragma unroll
                    for (int q2 = 0; q2 < 10; q2++) { as[1][q2] = as[0][q2]; as[0][q2] = pack2(a[q2 >> 1][2 * (q2 & 1)], a[q2 >> 1][2 * (q2 & 1) + 1]); }
                }
                bar_sync(2 + wg, 128);
                if ((tid & 127) < 6) mbar_arrive(EMPTY + 8 * (st + (tid & 127)));
                uint32_t key = 0;
#pragma unroll 1
                for (int lrow = lw; lrow < nr; lrow += 8) {
                    const int row = row0 + lrow;
                    const uint32_t k1 = ln_row(as[0], xin[0], row, sm + SD_PAR, lds32(LOW), out, ef, lane);
                    if (lane == lrow >> 3) key = k1;
#pragma unroll
                    for (int q2 = 0; q2 < 5; q2++) { as[0][2 * q2] = as[1][2 * q2]; as[0][2 * q2 + 1] = as[1][2 * q2 + 1]; xin[0][q2] = xin[1][q2]; }
                }
                if (b == 14) { EPT(tid == 128, 20); key_out(key); EPT(tid == 128, 21); }
                else {
                    if (lane < 2) asm volatile("st.shared.u32 [%0], %1;" :: "r"(KEYS + (q & 7) * 64 + warp * 8 + lane * 4), "r"(key) : "memory");
                    __syncwarp();
                    if (lane == 0) asm volatile("st.release.cta.shared.u32 [%0], %1;" :: "r"(ADONE + warp * 4), "r"(q + 1) : "memory");
                }
                ph ^= st != 0; st ^= 6;
            }
        }
    }
    __syncwarp();
    asm volatile("griddepcontrol.wait;" ::: "memory");
}

#define P_D1 500
#define P_DL 700
#define P_DG 29
typedef CUresult (*EncodeFn)(CUtensorMap*, CUtensorMapDataType, cuuint32_t, void*, const cuuint64_t*, const cuuint64_t*, const cuuint32_t*, const cuuint32_t*,
                             CUtensorMapInterleave, CUtensorMapSwizzle, CUtensorMapL2promotion, CUtensorMapFloatOOBfill);
static EncodeFn s_encode = nullptr;
static void make_map(CUtensorMap* m, const void* p, int rows, int cols, int box_rows, int box_cols = 64) {
    cuuint64_t dims[2] = {(cuuint64_t)cols, (cuuint64_t)rows}, strides[1] = {(cuuint64_t)cols * 2};
    cuuint32_t box[2] = {(cuuint32_t)box_cols, (cuuint32_t)box_rows}, es[2] = {1, 1};
    s_encode(m, CU_TENSOR_MAP_DATA_TYPE_BFLOAT16, 2, (void*)p, dims, strides, box, es, CU_TENSOR_MAP_INTERLEAVE_NONE,
             box_cols == 64 ? CU_TENSOR_MAP_SWIZZLE_128B : box_cols == 32 ? CU_TENSOR_MAP_SWIZZLE_64B : CU_TENSOR_MAP_SWIZZLE_NONE, CU_TENSOR_MAP_L2_PROMOTION_L2_256B, CU_TENSOR_MAP_FLOAT_OOB_FILL_NONE);
}
static void make_map3(CUtensorMap* m, const void* p, int rows, int cols, int box_rows, int box_chunks, int cw = 64) {
    cuuint64_t dims[3] = {(cuuint64_t)cw, (cuuint64_t)rows, (cuuint64_t)(cols / cw)}, strides[2] = {(cuuint64_t)cols * 2, (cuuint64_t)cw * 2};
    cuuint32_t box[3] = {(cuuint32_t)cw, (cuuint32_t)box_rows, (cuuint32_t)box_chunks}, es[3] = {1, 1, 1};
    s_encode(m, CU_TENSOR_MAP_DATA_TYPE_BFLOAT16, 3, (void*)p, dims, strides, box, es, CU_TENSOR_MAP_INTERLEAVE_NONE,
             cw == 64 ? CU_TENSOR_MAP_SWIZZLE_128B : CU_TENSOR_MAP_SWIZZLE_64B, CU_TENSOR_MAP_L2_PROMOTION_L2_256B, CU_TENSOR_MAP_FLOAT_OOB_FILL_NONE);
}
template <typename T> static void* sym(T& s) { void* p = nullptr; cudaGetSymbolAddress(&p, s); return p; }

extern "C" void kernel_launch(void* const* d_in, const int* in_sizes, int n_in, void* d_out, int out_size) {
    const bf16 *x = (const bf16*)d_in[0], *mem0 = (const bf16*)d_in[1], *Wq = (const bf16*)d_in[2], *Wk = (const bf16*)d_in[3],
               *Wv = (const bf16*)d_in[4], *Wo = (const bf16*)d_in[5], *wr = (const bf16*)d_in[8], *wgate = (const bf16*)d_in[9],
               *wup = (const bf16*)d_in[10], *wdown = (const bf16*)d_in[11], *c = (const bf16*)d_in[12], *wmod = (const bf16*)d_in[13];
    bf16* out = (bf16*)d_out;
    if (!s_encode) {
        cudaDriverEntryPointQueryResult qr;
        cudaGetDriverEntryPoint("cuTensorMapEncodeTiled", (void**)&s_encode, cudaEnableDefault, &qr);
        cudaFuncSetAttribute(k_side, cudaFuncAttributeMaxDynamicSharedMemorySize, SD_SMEM);
        cudaFuncSetAttribute(k_chain, cudaFuncAttributeMaxDynamicSharedMemorySize, C_SMEM);
    }
    ChainMaps cm; SideMaps sd;
    make_map(&sd.h, sym(g_h), S_TOK, DM, 128); make_map3(&sd.wv, Wv, DM, HD, 64, 3);
    make_map3(&sd.ost, sym(g_o), S_TOK, HD, 16, 3); make_map(&sd.o, sym(g_o), S_TOK, HD, 128, 32); make_map3(&sd.wo, Wo, HD, DM, 32, 5);
    make_map(&sd.slab, sym(g_slab), 16 * KSPLIT * 128, DM, 64); make_map3(&cm.slab2, sym(g_slab), 16 * KSPLIT * 128, DM, 64, 2);
    make_map3(&cm.wo15, Wo, HD, DM, 192, 2); make_map3(&cm.o15, sym(g_o), S_TOK, HD, 64, 2);
    for (int i = 0; i < 3; i++) {
        cuuint64_t dims[3] = {256, 320, 16 * KSPLIT}, strides[2] = {512, 128 * DM * 2};
        cuuint32_t box[3] = {256, 40u >> i, 2u << i}, es[3] = {1, 1, 1};
        s_encode(&sd.lnp[i], CU_TENSOR_MAP_DATA_TYPE_BFLOAT16, 3, sym(g_slab), dims, strides, box, es, CU_TENSOR_MAP_INTERLEAVE_NONE,
                 CU_TENSOR_MAP_SWIZZLE_NONE, CU_TENSOR_MAP_L2_PROMOTION_L2_256B, CU_TENSOR_MAP_FLOAT_OOB_FILL_NONE);
    }
    make_map(&cm.wq, Wq, DM, HD, 640 / WP); make_map(&cm.wk, Wk, DM, HD, 640 / WP); make_map(&cm.wv, Wv, DM, HD, 160); make_map3(&cm.wo, Wo, HD, DM, 64, 7, 32);
    make_map3(&cm.h2, sym(g_h), S_TOK, DM, 32, 2);
    ChainArgs ar = {x, mem0, c, wmod, wgate, wup, wdown, out, P_D1, P_DL, P_DG};
    k_chain<<<96, 384, C_SMEM>>>(cm, ar);
    cudaLaunchConfig_t cfg = {};
    cfg.gridDim = dim3(N_SIDE); cfg.blockDim = dim3(384); cfg.dynamicSmemBytes = SD_SMEM; cfg.stream = cudaStreamPerThread;
    cudaLaunchAttribute at[1]; at[0].id = cudaLaunchAttributeProgrammaticStreamSerialization; at[0].val.programmaticStreamSerializationAllowed = 1;
    cfg.attrs = at; cfg.numAttrs = 1;
    cudaLaunchKernelEx(&cfg, k_side, sd, x, wr, wmod, c, out);
}
```

```cpp
#include <cuda_runtime.h>
#include <cuda_bf16.h>
#include <cuda.h>
#include <stdint.h>
#include <stdio.h>
#include <string.h>
#include <stdlib.h>

typedef __nv_bfloat16 bf16;
constexpr int S_TOK = 2048, DM = 640, NH = 32, DH = 192, HD = NH * DH, NSEG = 64, SEG = 32, FF = 1536;

__device__ bf16 g_mod[6 * DM];
__device__ bf16 g_h[S_TOK * DM];
constexpr int AT_REC = 43008, AT_KM = 24576, AT_VM = 27648, AT_V = 30720;
__device__ __align__(1024) uint8_t g_att[NSEG * NH * AT_REC];
__device__ bf16 g_o[S_TOK * HD];
__device__ bf16 g_A[S_TOK * DM];
__device__ bf16 g_x1[S_TOK * DM];
__device__ bf16 g_h2[S_TOK * DM];
__device__ __align__(128) uint32_t g_key[S_TOK];
__device__ int g_idx[8];
__device__ __align__(128) uint32_t g_gu[FF / 8 * 32];
constexpr int ACC_PAIR = 24 * 1024;
__device__ __align__(1024) uint8_t g_acc[2 * ACC_PAIR];
__device__ __align__(1024) uint32_t g_stamp[4 * 12 * 32];
constexpr int KSPLIT = 16;
__device__ bf16 g_slab[16 * KSPLIT * 128 * DM];
struct __align__(128) Flags {
    uint32_t qk[16], vb[16];
    uint32_t at[16], o[16];
    uint32_t c[4][16];
    uint32_t half[32];
    uint32_t fin[4 * 32];
    uint32_t v[16 * 32];
    uint32_t seg[4 * 32];
    uint32_t pair[16 * 16];
    uint32_t h, pad2[31], done, mod, pad3[30];
    uint32_t mod1[DM];
    uint32_t wmax[96];
};
__device__ Flags g_flags;
#define EPT(c, i)

__device__ __forceinline__ uint32_t smem_u32(const void* p) { return (uint32_t)__cvta_generic_to_shared(p); }
__device__ __forceinline__ uint32_t pack2(float lo, float hi) {
    uint32_t r; asm("cvt.rn.bf16x2.f32 %0, %1, %2;" : "=r"(r) : "f"(hi), "f"(lo)); return r;
}
__device__ __forceinline__ float bfr(float x) { return __uint_as_float(pack2(0.f, x)); }
__device__ __forceinline__ float inv_std(float var) {
    float s, r; asm("sqrt.approx.f32 %0, %1;" : "=f"(s) : "f"(bfr(bfr(var) + 1e-5f))); asm("rcp.approx.f32 %0, %1;" : "=f"(r) : "f"(bfr(s))); return r;
}
__device__ __forceinline__ float lo_f(uint32_t v) { return __uint_as_float(v << 16); }
__device__ __forceinline__ float hi_f(uint32_t v) { return __uint_as_float(v & 0xffff0000u); }
__device__ __forceinline__ void mbar_init(uint32_t bar, int cnt) { asm volatile("mbarrier.init.shared::cta.b64 [%0], %1;" :: "r"(bar), "r"(cnt) : "memory"); }
__device__ __forceinline__ void mbar_expect(uint32_t bar, int bytes) { asm volatile("mbarrier.arrive.expect_tx.shared::cta.b64 _, [%0], %1;" :: "r"(bar), "r"(bytes) : "memory"); }
__device__ __forceinline__ void mbar_arrive(uint32_t bar) { asm volatile("mbarrier.arrive.shared::cta.b64 _, [%0];" :: "r"(bar) : "memory"); }
__device__ __forceinline__ bool mbar_try(uint32_t bar, int par) {
    uint32_t ok; asm volatile("{ .reg .pred p; mbarrier.try_wait.parity.shared::cta.b64 p, [%1], %2; selp.u32 %0, 1, 0, p; }" : "=r"(ok) : "r"(bar), "r"(par) : "memory"); return ok;
}
__device__ __forceinline__ bool mbar_try_cluster(uint32_t bar, int par) {
    uint32_t ok; asm volatile("{ .reg .pred p; mbarrier.try_wait.parity.acquire.cluster.shared::cta.b64 p, [%1], %2; selp.u32 %0, 1, 0, p; }" : "=r"(ok) : "r"(bar), "r"(par) : "memory"); return ok;
}
__device__ __forceinline__ bool mbar_test(uint32_t bar, uint32_t par) {
    uint32_t ok; asm volatile("{ .reg .pred p; mbarrier.test_wait.parity.shared::cta.b64 p, [%1], %2; selp.u32 %0, 1, 0, p; }" : "=r"(ok) : "r"(bar), "r"(par) : "memory"); return ok;
}
constexpr int SPIN_LIMIT = 1 << 18;
__device__ __forceinline__ void mbar_wait(uint32_t bar, uint32_t par) {
    asm volatile("{ .reg .pred p, q; .reg .u32 n; mov.u32 n, 0;\n"
                 "W_%=: mbarrier.try_wait.parity.shared::cta.b64 p, [%0], %1;\n"
                 "@p bra.uni D_%=;\n"
                 "add.u32 n, n, 1; setp.lt.u32 q, n, 0x200000; @q bra.uni W_%=;\n"
                 "trap;\n"
                 "D_%=: }" :: "r"(bar), "r"(par) : "memory");
}
__device__ __forceinline__ void tma2d(uint32_t dst, const CUtensorMap* m, int c0, int c1, uint32_t bar) {
    asm volatile("cp.async.bulk.tensor.2d.shared::cluster.global.mbarrier::complete_tx::bytes [%0], [%1, {%3, %4}], [%2];"
        :: "r"(dst), "l"((uint64_t)m), "r"(bar), "r"(c0), "r"(c1) : "memory");
}
__device__ __forceinline__ void tma2d_mc(uint32_t dst, const CUtensorMap* m, int c0, int c1, uint32_t bar, uint16_t mask) {
    asm volatile("cp.async.bulk.tensor.2d.shared::cluster.global.mbarrier::complete_tx::bytes.multicast::cluster [%0], [%1, {%3, %4}], [%2], %5;"
        :: "r"(dst), "l"((uint64_t)m), "r"(bar), "r"(c0), "r"(c1), "h"(mask) : "memory");
}
__device__ __forceinline__ uint64_t policy_stream() { uint64_t p; asm("createpolicy.fractional.L2::evict_first.b64 %0, 1.0;" : "=l"(p)); return p; }
__device__ __forceinline__ void tma2d_ef(uint32_t dst, const CUtensorMap* m, int c0, int c1, uint32_t bar, uint64_t pol) {
    asm volatile("cp.async.bulk.tensor.2d.shared::cluster.global.mbarrier::complete_tx::bytes.L2::cache_hint [%0], [%1, {%3, %4}], [%2], %5;"
        :: "r"(dst), "l"((uint64_t)m), "r"(bar), "r"(c0), "r"(c1), "l"(pol) : "memory");
}
__device__ __forceinline__ void tma3d(uint32_t dst, const CUtensorMap* m, int row, int chunk, uint32_t bar) {
    asm volatile("cp.async.bulk.tensor.3d.shared::cluster.global.mbarrier::complete_tx::bytes [%0], [%1, {0, %3, %4}], [%2];"
        :: "r"(dst), "l"((uint64_t)m), "r"(bar), "r"(row), "r"(chunk) : "memory");
}
__device__ __forceinline__ void tma3d_ef(uint32_t dst, const CUtensorMap* m, int row, int chunk, uint32_t bar, uint64_t pol) {
    asm volatile("cp.async.bulk.tensor.3d.shared::cluster.global.mbarrier::complete_tx::bytes.L2::cache_hint [%0], [%1, {0, %3, %4}], [%2], %5;"
        :: "r"(dst), "l"((uint64_t)m), "r"(bar), "r"(row), "r"(chunk), "l"(pol) : "memory");
}
__device__ __forceinline__ void tma3d_store(const CUtensorMap* m, int row, int chunk, uint32_t src, uint64_t pol, bool hint) {
    if (hint) asm volatile("cp.async.bulk.tensor.3d.global.shared::cta.bulk_group.L2::cache_hint [%0, {0, %2, %3}], [%1], %4;"
        :: "l"((uint64_t)m), "r"(src), "r"(row), "r"(chunk), "l"(pol) : "memory");
    else asm volatile("cp.async.bulk.tensor.3d.global.shared::cta.bulk_group [%0, {0, %2, %3}], [%1];"
        :: "l"((uint64_t)m), "r"(src), "r"(row), "r"(chunk) : "memory");
}
__device__ __forceinline__ bool elect() { uint32_t p; asm volatile("{ .reg .pred e; elect.sync _|e, -1; selp.u32 %0, 1, 0, e; }" : "=r"(p)); return p; }
__device__ __forceinline__ uint2 ld_ef(const void* p, uint64_t pol) {
    uint2 v; asm volatile("ld.relaxed.gpu.global.L2::cache_hint.v2.u32 {%0,%1}, [%2], %3;" : "=r"(v.x), "=r"(v.y) : "l"(p), "l"(pol)); return v;
}
__device__ __forceinline__ void st_ef(void* p, uint2 v, uint64_t pol) {
    asm volatile("st.global.L2::cache_hint.v2.u32 [%0], {%1,%2}, %3;" :: "l"(p), "r"(v.x), "r"(v.y), "l"(pol) : "memory");
}
__device__ __forceinline__ void tma2d_prefetch(const CUtensorMap* m, int c0, int c1) {
    asm volatile("cp.async.bulk.prefetch.tensor.2d.L2.global [%0, {%1, %2}];" :: "l"((uint64_t)m), "r"(c0), "r"(c1) : "memory");
}
__device__ __forceinline__ void mbar_arrive_remote(uint32_t bar) { asm volatile("mbarrier.arrive.relaxed.cluster.shared::cluster.b64 _, [%0];" :: "r"(bar) : "memory"); }
__device__ __forceinline__ void tma2d_store(const CUtensorMap* m, int c0, int c1, uint32_t src) {
    asm volatile("cp.async.bulk.tensor.2d.global.shared::cta.bulk_group [%0, {%2, %3}], [%1];"
        :: "l"((uint64_t)m), "r"(src), "r"(c0), "r"(c1) : "memory");
}
__device__ __forceinline__ void bulk_g2s(uint32_t dst, const void* src, int bytes, uint32_t bar) {
    asm volatile("cp.async.bulk.shared::cluster.global.mbarrier::complete_tx::bytes [%0], [%1], %2, [%3];" :: "r"(dst), "l"(src), "r"(bytes), "r"(bar) : "memory");
}
__device__ __forceinline__ void ldsm4(uint32_t (&r)[4], uint32_t a) {
    asm volatile("ldmatrix.sync.aligned.m8n8.x4.shared.b16 {%0,%1,%2,%3}, [%4];" : "=r"(r[0]), "=r"(r[1]), "=r"(r[2]), "=r"(r[3]) : "r"(a) : "memory");
}
__device__ __forceinline__ void ldsm4t(uint32_t (&r)[4], uint32_t a) {
    asm volatile("ldmatrix.sync.aligned.m8n8.x4.trans.shared.b16 {%0,%1,%2,%3}, [%4];" : "=r"(r[0]), "=r"(r[1]), "=r"(r[2]), "=r"(r[3]) : "r"(a) : "memory");
}
__device__ __forceinline__ void stsm4(uint32_t a, uint32_t r0, uint32_t r1, uint32_t r2, uint32_t r3) {
    asm volatile("stmatrix.sync.aligned.m8n8.x4.shared.b16 [%0], {%1,%2,%3,%4};" :: "r"(a), "r"(r0), "r"(r1), "r"(r2), "r"(r3) : "memory");
}
__device__ __forceinline__ void stsm4t(uint32_t a, uint32_t r0, uint32_t r1, uint32_t r2, uint32_t r3) {
    asm volatile("stmatrix.sync.aligned.m8n8.x4.trans.shared.b16 [%0], {%1,%2,%3,%4};" :: "r"(a), "r"(r0), "r"(r1), "r"(r2), "r"(r3) : "memory");
}
__device__ __forceinline__ void stsm2t(uint32_t a, uint32_t r0, uint32_t r1) {
    asm volatile("stmatrix.sync.aligned.m8n8.x2.trans.shared.b16 [%0], {%1,%2};" :: "r"(a), "r"(r0), "r"(r1) : "memory");
}
__device__ __forceinline__ uint32_t movm_t(uint32_t v) { uint32_t r; asm volatile("movmatrix.sync.aligned.m8n8.trans.b16 %0, %1;" : "=r"(r) : "r"(v)); return r; }
__device__ __forceinline__ void mma16(float (&d)[4], uint32_t a0, uint32_t a1, uint32_t a2, uint32_t a3, uint32_t b0, uint32_t b1) {
    asm volatile("mma.sync.aligned.m16n8k16.row.col.f32.bf16.bf16.f32 {%0,%1,%2,%3}, {%4,%5,%6,%7}, {%8,%9}, {%0,%1,%2,%3};"
        : "+f"(d[0]), "+f"(d[1]), "+f"(d[2]), "+f"(d[3]) : "r"(a0), "r"(a1), "r"(a2), "r"(a3), "r"(b0), "r"(b1));
}
__device__ __forceinline__ void mma8(float (&d)[4], uint32_t a0, uint32_t a1, uint32_t b0) {
    asm volatile("mma.sync.aligned.m16n8k8.row.col.f32.bf16.bf16.f32 {%0,%1,%2,%3}, {%4,%5}, {%6}, {%0,%1,%2,%3};"
        : "+f"(d[0]), "+f"(d[1]), "+f"(d[2]), "+f"(d[3]) : "r"(a0), "r"(a1), "r"(b0));
}
__device__ __forceinline__ uint32_t mapa(uint32_t a, uint32_t r) { uint32_t o; asm volatile("mapa.shared::cluster.u32 %0, %1, %2;" : "=r"(o) : "r"(a), "r"(r)); return o; }
__device__ __forceinline__ void bar_sync(int id, int n) { asm volatile("bar.sync %0, %1;" :: "r"(id), "r"(n) : "memory"); }
__device__ __forceinline__ void bar_arrive(int id, int n) { asm volatile("bar.arrive %0, %1;" :: "r"(id), "r"(n) : "memory"); }
__device__ __forceinline__ uint64_t mkdesc(uint32_t addr, uint32_t lbo, uint32_t sbo) {
    return (uint64_t)((addr & 0x3FFFF) >> 4) | ((uint64_t)(lbo >> 4) << 16) | ((uint64_t)(sbo >> 4) << 32) | (1ull << 62);
}
#define WG_FENCE()  asm volatile("wgmma.fence.sync.aligned;" ::: "memory")
#define WG_COMMIT() asm volatile("wgmma.commit_group.sync.aligned;" ::: "memory")
#define WG_WAIT(n)  asm volatile("wgmma.wait_group.sync.aligned %0;" :: "n"(n) : "memory")

__device__ __forceinline__ void wgmma_ss_n192_tb(float (&d)[96], uint64_t a, uint64_t b, int acc) {
    asm volatile("{ .reg .pred p; setp.ne.b32 p, %98, 0;\n"
        "wgmma.mma_async.sync.aligned.m64n192k16.f32.bf16.bf16 {%0,%1,%2,%3,%4,%5,%6,%7,%8,%9,%10,%11,%12,%13,%14,%15,%16,%17,%18,%19,%20,%21,%22,%23,%24,%25,%26,%27,%28,%29,%30,%31,%32,%33,%34,%35,%36,%37,%38,%39,%40,%41,%42,%43,%44,%45,%46,%47,%48,%49,%50,%51,%52,%53,%54,%55,%56,%57,%58,%59,%60,%61,%62,%63,%64,%65,%66,%67,%68,%69,%70,%71,%72,%73,%74,%75,%76,%77,%78,%79,%80,%81,%82,%83,%84,%85,%86,%87,%88,%89,%90,%91,%92,%93,%94,%95}, %96, %97, p, 1, 1, 0, 1; }"
        : "+f"(d[0]), "+f"(d[1]), "+f"(d[2]), "+f"(d[3]), "+f"(d[4]), "+f"(d[5]), "+f"(d[6]), "+f"(d[7]), "+f"(d[8]), "+f"(d[9]), "+f"(d[10]), "+f"(d[11]), "+f"(d[12]), "+f"(d[13]), "+f"(d[14]), "+f"(d[15]), "+f"(d[16]), "+f"(d[17]), "+f"(d[18]), "+f"(d[19]), "+f"(d[20]), "+f"(d[21]), "+f"(d[22]), "+f"(d[23]), "+f"(d[24]), "+f"(d[25]), "+f"(d[26]), "+f"(d[27]), "+f"(d[28]), "+f"(d[29]), "+f"(d[30]), "+f"(d[31]), "+f"(d[32]), "+f"(d[33]), "+f"(d[34]), "+f"(d[35]), "+f"(d[36]), "+f"(d[37]), "+f"(d[38]), "+f"(d[39]), "+f"(d[40]), "+f"(d[41]), "+f"(d[42]), "+f"(d[43]), "+f"(d[44]), "+f"(d[45]), "+f"(d[46]), "+f"(d[47]), "+f"(d[48]), "+f"(d[49]), "+f"(d[50]), "+f"(d[51]), "+f"(d[52]), "+f"(d[53]), "+f"(d[54]), "+f"(d[55]), "+f"(d[56]), "+f"(d[57]), "+f"(d[58]), "+f"(d[59]), "+f"(d[60]), "+f"(d[61]), "+f"(d[62]), "+f"(d[63]), "+f"(d[64]), "+f"(d[65]), "+f"(d[66]), "+f"(d[67]), "+f"(d[68]), "+f"(d[69]), "+f"(d[70]), "+f"(d[71]), "+f"(d[72]), "+f"(d[73]), "+f"(d[74]), "+f"(d[75]), "+f"(d[76]), "+f"(d[77]), "+f"(d[78]), "+f"(d[79]), "+f"(d[80]), "+f"(d[81]), "+f"(d[82]), "+f"(d[83]), "+f"(d[84]), "+f"(d[85]), "+f"(d[86]), "+f"(d[87]), "+f"(d[88]), "+f"(d[89]), "+f"(d[90]), "+f"(d[91]), "+f"(d[92]), "+f"(d[93]), "+f"(d[94]), "+f"(d[95])
        : "l"(a), "l"(b), "r"(acc));
}

__device__ __forceinline__ void wgmma_ss_n128_tb(float (&d)[64], uint64_t a, uint64_t b, int acc) {
    asm volatile("{ .reg .pred p; setp.ne.b32 p, %66, 0;\n"
        "wgmma.mma_async.sync.aligned.m64n128k16.f32.bf16.bf16 {%0,%1,%2,%3,%4,%5,%6,%7,%8,%9,%10,%11,%12,%13,%14,%15,%16,%17,%18,%19,%20,%21,%22,%23,%24,%25,%26,%27,%28,%29,%30,%31,%32,%33,%34,%35,%36,%37,%38,%39,%40,%41,%42,%43,%44,%45,%46,%47,%48,%49,%50,%51,%52,%53,%54,%55,%56,%57,%58,%59,%60,%61,%62,%63}, %64, %65, p, 1, 1, 0, 1; }"
        : "+f"(d[0]), "+f"(d[1]), "+f"(d[2]), "+f"(d[3]), "+f"(d[4]), "+f"(d[5]), "+f"(d[6]), "+f"(d[7]), "+f"(d[8]), "+f"(d[9]), "+f"(d[10]), "+f"(d[11]), "+f"(d[12]), "+f"(d[13]), "+f"(d[14]), "+f"(d[15]), "+f"(d[16]), "+f"(d[17]), "+f"(d[18]), "+f"(d[19]), "+f"(d[20]), "+f"(d[21]), "+f"(d[22]), "+f"(d[23]), "+f"(d[24]), "+f"(d[25]), "+f"(d[26]), "+f"(d[27]), "+f"(d[28]), "+f"(d[29]), "+f"(d[30]), "+f"(d[31]), "+f"(d[32]), "+f"(d[33]), "+f"(d[34]), "+f"(d[35]), "+f"(d[36]), "+f"(d[37]), "+f"(d[38]), "+f"(d[39]), "+f"(d[40]), "+f"(d[41]), "+f"(d[42]), "+f"(d[43]), "+f"(d[44]), "+f"(d[45]), "+f"(d[46]), "+f"(d[47]), "+f"(d[48]), "+f"(d[49]), "+f"(d[50]), "+f"(d[51]), "+f"(d[52]), "+f"(d[53]), "+f"(d[54]), "+f"(d[55]), "+f"(d[56]), "+f"(d[57]), "+f"(d[58]), "+f"(d[59]), "+f"(d[60]), "+f"(d[61]), "+f"(d[62]), "+f"(d[63])
        : "l"(a), "l"(b), "r"(acc));
}

__device__ __forceinline__ void wgmma_rs_n32(float (&d)[16], const uint32_t (&a)[4], uint64_t b, int acc) {
    asm volatile("{ .reg .pred p; setp.ne.b32 p, %21, 0;\n"
        "wgmma.mma_async.sync.aligned.m64n32k16.f32.bf16.bf16 {%0,%1,%2,%3,%4,%5,%6,%7,%8,%9,%10,%11,%12,%13,%14,%15}, {%16,%17,%18,%19}, %20, p, 1, 1, 0; }"
        : "+f"(d[0]), "+f"(d[1]), "+f"(d[2]), "+f"(d[3]), "+f"(d[4]), "+f"(d[5]), "+f"(d[6]), "+f"(d[7]), "+f"(d[8]), "+f"(d[9]), "+f"(d[10]), "+f"(d[11]), "+f"(d[12]), "+f"(d[13]), "+f"(d[14]), "+f"(d[15])
        : "r"(a[0]), "r"(a[1]), "r"(a[2]), "r"(a[3]), "l"(b), "r"(acc));
}

__device__ __forceinline__ float warp_sum(float v) {
#pragma unroll
    for (int o = 16; o; o >>= 1) v += __shfl_xor_sync(0xffffffffu, v, o);
    return v;
}
__device__ __forceinline__ uint32_t add2(uint32_t a, uint32_t b) { uint32_t r; asm("add.rn.bf16x2 %0, %1, %2;" : "=r"(r) : "r"(a), "r"(b)); return r; }
__device__ __forceinline__ uint32_t mul2(uint32_t a, uint32_t b) { uint32_t r; asm("mul.rn.bf16x2 %0, %1, %2;" : "=r"(r) : "r"(a), "r"(b)); return r; }
__device__ __forceinline__ uint32_t amax2(uint32_t m, uint32_t v) { uint32_t r; asm("max.u16x2 %0, %1, %2;" : "=r"(r) : "r"(m), "r"(v & 0x7fff7fffu)); return r; }
__device__ __forceinline__ uint32_t amax_warp(uint32_t m) { return __reduce_max_sync(0xffffffffu, max(m & 0xffffu, m >> 16)); }
__device__ __forceinline__ void ln_norm(const uint32_t (&xv)[10], uint32_t (&nv)[10]) {
    float s0 = 0, s1 = 0;
#pragma unroll
    for (int i = 0; i < 10; i++) { s0 += lo_f(xv[i]); s1 += hi_f(xv[i]); }
    const float mean = warp_sum(s0 + s1) * (1.f / DM);
    float q0 = 0, q1 = 0;
#pragma unroll
    for (int i = 0; i < 10; i++) { const float d0 = lo_f(xv[i]) - mean, d1 = hi_f(xv[i]) - mean; q0 += d0 * d0; q1 += d1 * d1; }
    const float inv = inv_std(warp_sum(q0 + q1) * (1.f / DM));
    const uint32_t mb = pack2(-mean, -mean);
#pragma unroll
    for (int i = 0; i < 10; i++) { const uint32_t d = add2(xv[i], mb); nv[i] = pack2(lo_f(d) * inv, hi_f(d) * inv); }
}
__device__ __forceinline__ void ln_mod(const uint32_t (&xv)[10], const uint32_t (&sv)[10], const uint32_t (&tv)[10], uint32_t (&hv)[10]) {
    ln_norm(xv, hv);
#pragma unroll
    for (int i = 0; i < 10; i++) hv[i] = add2(mul2(hv[i], add2(sv[i], 0x3f803f80u)), tv[i]);
}
__device__ __forceinline__ uint32_t ld_rlx(const uint32_t* f) { uint32_t v; asm volatile("ld.relaxed.gpu.global.u32 %0, [%1];" : "=r"(v) : "l"(f) : "memory"); return v; }
__device__ __forceinline__ void bump(uint32_t* f) { asm volatile("red.relaxed.gpu.global.add.u32 [%0], 1;" :: "l"(f) : "memory"); }
#define NAP 100
#define GPU_FENCE() asm volatile("fence.acq_rel.gpu;" ::: "memory")
__device__ __forceinline__ void flag_wait(const uint32_t* f, uint32_t target) {
    for (int n = 0;; n++) {
        uint32_t v; asm volatile("ld.relaxed.gpu.global.u32 %0, [%1];" : "=r"(v) : "l"(f) : "memory");
        if (v >= target) break;
        if (n > (1 << 22)) __trap();
        __nanosleep(NAP);
    }
}
__device__ __forceinline__ void flag_add(uint32_t* f, uint32_t v = 1) { asm volatile("red.release.gpu.global.add.u32 [%0], %1;" :: "l"(f), "r"(v) : "memory"); }
constexpr int N_SIDE = 36;
__device__ __forceinline__ void flags_release(int lane) {
    uint32_t old = 0;
    if (lane == 0) asm volatile("atom.relaxed.gpu.global.add.u32 %0, [%1], 1;" : "=r"(old) : "l"(&g_flags.done) : "memory");
    if (__shfl_sync(0xffffffffu, old, 0) == 96 + N_SIDE - 1)
#pragma unroll 1
        for (int i = lane; i < (int)(sizeof(Flags) / 16); i += 32) ((uint4*)&g_flags)[i] = make_uint4(0, 0, 0, 0);
}

struct ChainMaps { CUtensorMap wq, wk, wv, wo, h2, wo15, o15, slab2; };
struct ChainArgs { const bf16 *x, *mem0, *c, *wmod, *wgate, *wup, *wdown; bf16* out; int D1, D2, DG; };
constexpr uint32_t SM_BASE = 1024;
#define NRING 10
#define XORD 0
#define B5AT 38
#define QCUT 0x12
#define NCH 0
#define XA 2
#define VT 1
#define OSEND 1
#define SPOLL 0
#define BDEF 0
#define F61 1
#define IDLE 300
#define FW 2
#define RSEL 1
#define AIN 0
#define APRE 4
#define PBAR 0
#define WLATE 1
#define QDEL 300
#define STL 0
#define B7E 1
#define H24 0
#define NPRE 9
#define REG_P 208
#define REG_L (504 - 2 * REG_P)
constexpr int WO_BLK = 7 * 4096;
constexpr int C_WV = 0, C_WO = 81920, C_XR = 167936, C_VP = C_XR + 7 * 4096, C_VX = C_XR + 8 * 4096, C_QX = C_VX + 4096, C_KX = C_QX + 4096,
              C_MEM = C_KX + 4096, C_OX = C_MEM + 9216, C_VM = C_OX + 3072, C_QM = C_VM + 1024, C_KM = C_QM + 1024, C_SC = C_KM + 1024, C_BAR = C_SC + 3840;
constexpr int CB_W = C_BAR, CB_W2 = C_BAR + 8, CB_SC = C_BAR + 16, CB_XD = C_BAR + 24, CB_VX = C_BAR + 32, CB_W3 = C_BAR + 40, CB_XM = C_BAR + 48, CB_OX = C_BAR + 56,
              CB_XF = C_BAR + 64, C_LAG = C_BAR + 96, C_UN = C_BAR + 100, C_MX = C_BAR + 112;
constexpr int C_SMEM = C_BAR + 128;
#define PROF(i)
#define PROFG(i)
#define PROFV(i, v)
static_assert(C_SMEM <= 232448, "chain shared memory");
__device__ __forceinline__ uint32_t umax3(uint32_t a, uint32_t b, uint32_t c) { return max(max(a, b), c); }
__device__ __forceinline__ void wait_until(uint32_t t) {
    asm volatile("{ .reg .pred p; .reg .s32 c; .reg .u64 d;\nU_%=: mov.u64 d, %%clock64; cvt.u32.u64 c, d; sub.s32 c, c, %0; setp.lt.s32 p, c, 0; @p bra.uni U_%=; }" :: "r"(t) : "memory");
}
__device__ __forceinline__ uint32_t gtime() { uint32_t c; asm volatile("mov.u32 %0, %%globaltimer_lo;" : "=r"(c)); return c; }
__device__ __forceinline__ uint32_t opaque(uint32_t v) { uint32_t r; asm volatile("shfl.sync.bfly.b32 %0, %1, 0, 31, -1;" : "=r"(r) : "r"(v)); return r; }
__device__ __forceinline__ uint32_t lds32(uint32_t a) { uint32_t v; asm volatile("ld.shared.u32 %0, [%1];" : "=r"(v) : "r"(a) : "memory"); return v; }
__device__ __forceinline__ float2 lds64f(uint32_t a) { float2 v; asm volatile("ld.shared.v2.f32 {%0,%1}, [%2];" : "=f"(v.x), "=f"(v.y) : "r"(a) : "memory"); return v; }
__device__ __forceinline__ float4 lds128f(uint32_t a) { float4 v; asm volatile("ld.shared.v4.f32 {%0,%1,%2,%3}, [%4];" : "=f"(v.x), "=f"(v.y), "=f"(v.z), "=f"(v.w) : "r"(a) : "memory"); return v; }
__device__ __forceinline__ void sts128f(uint32_t a, float x, float y, float z, float w) { asm volatile("st.shared.v4.f32 [%0], {%1,%2,%3,%4};" :: "r"(a), "f"(x), "f"(y), "f"(z), "f"(w) : "memory"); }
__device__ __forceinline__ void lds64(uint32_t (&v)[2], uint32_t a) { asm volatile("ld.shared.v2.u32 {%0,%1}, [%2];" : "=r"(v[0]), "=r"(v[1]) : "r"(a) : "memory"); }
__device__ __forceinline__ void mma16q(float (&d)[4], const uint32_t (&a)[4], uint32_t b0, uint32_t b1) { mma16(d, a[0], a[1], a[2], a[3], b0, b1); }
__device__ __forceinline__ uint32_t f16_to_bf16(uint32_t v) {
    float lo, hi; asm("{ .reg .f16 l, h; mov.b32 {l, h}, %2; cvt.f32.f16 %0, l; cvt.f32.f16 %1, h; }" : "=f"(lo), "=f"(hi) : "r"(v));
    return pack2(lo, hi);
}
__device__ __forceinline__ uint32_t pack2h(float lo, float hi) { uint32_t r; asm("cvt.rn.f16x2.f32 %0, %1, %2;" : "=r"(r) : "f"(hi), "f"(lo)); return r; }
#define SPLIT 1
__device__ __forceinline__ void cut(uint32_t never, int n) {
    asm volatile("{ .reg .pred p; setp.ne.u32 p, %0, %1; @p bra.uni C_%=; trap; C_%=: }" :: "r"(never), "r"(n) : "memory");
}
__device__ __forceinline__ void pin(uint32_t never, uint32_t a, uint32_t b, uint32_t c, uint32_t d) {
    asm volatile("{ .reg .pred p; setp.eq.u32 p, %0, 0; @p st.shared.v4.u32 [%0], {%1,%2,%3,%4}; }" :: "r"(never), "r"(a), "r"(b), "r"(c), "r"(d) : "memory");
}
__device__ __forceinline__ void pin0(uint32_t never) {
    asm volatile("{ .reg .pred p; setp.eq.u32 p, %0, 0; @p st.shared.u32 [%0], 0; }" :: "r"(never) : "memory");
}
#define ELECTED(txt) "{ .reg .pred e; elect.sync _|e, -1; @e " txt " }"
__device__ __forceinline__ void w_bulk_s2g(void* dst, uint32_t src, int bytes) {
    asm volatile(ELECTED("cp.async.bulk.global.shared::cta.bulk_group [%0], [%1], %2;") :: "l"(dst), "r"(src), "r"(bytes) : "memory");
}
__device__ __forceinline__ void w_bump(uint32_t* f) { asm volatile(ELECTED("red.relaxed.gpu.global.add.u32 [%0], 1;") :: "l"(f) : "memory"); }
__device__ __forceinline__ void w_expect(uint32_t bar, int bytes) { asm volatile(ELECTED("mbarrier.arrive.expect_tx.shared::cta.b64 _, [%0], %1;") :: "r"(bar), "r"(bytes) : "memory"); }
__device__ __forceinline__ void w_flag_wait(const uint32_t* f, uint32_t target) {
    asm volatile("{ .reg .pred p; .reg .u32 n, v; mov.u32 n, 0;\n"
                 "F_%=: ld.relaxed.gpu.global.u32 v, [%0]; setp.ge.u32 p, v, %1; vote.sync.all.pred p, p, -1; @p bra.uni G_%=;\n"
                 "nanosleep.u32 %2; add.u32 n, n, 1; setp.lt.u32 p, n, 0x400000; @p bra.uni F_%=;\ntrap;\nG_%=: }" :: "l"(f), "r"(target), "n"(NAP) : "memory");
}
#define BULK_COMMIT()    asm volatile("cp.async.bulk.commit_group;" ::: "memory")
#define BULK_WAIT()      asm volatile("cp.async.bulk.wait_group 0;" ::: "memory")
#define BULK_WAIT_READ() asm volatile("cp.async.bulk.wait_group.read 0;" ::: "memory")
#define PROXY_FENCE()    asm volatile("fence.proxy.async.shared::cta;" ::: "memory")
__device__ __forceinline__ void send16(uint32_t dst, uint32_t bar, float a, float b, float c, float d) {
    asm volatile("st.async.shared::cluster.mbarrier::complete_tx::bytes.v4.f32 [%0], {%1,%2,%3,%4}, [%5];" :: "r"(dst), "f"(a), "f"(b), "f"(c), "f"(d), "r"(bar) : "memory");
}
__device__ __forceinline__ void send8(uint32_t dst, uint32_t bar, uint32_t a, uint32_t b) {
    asm volatile("st.async.shared::cluster.mbarrier::complete_tx::bytes.v2.b32 [%0], {%1,%2}, [%3];" :: "r"(dst), "r"(a), "r"(b), "r"(bar) : "memory");
}

__device__ __forceinline__ void seg_done(int n, int head) { GPU_FENCE(); w_bump(&g_flags.seg[(n - 60) * 32 + head]); }
__device__ __forceinline__ uint32_t x_base(int wg, uint32_t small, int sh) { return (uint32_t)mkdesc(SM_BASE + C_XR, 16, 1024) + wg * 256 + (small >> sh); }
__device__ __forceinline__ void x_chunk(float (&acc)[16], const uint32_t (&wa)[40][4], uint32_t xl, int a0, int i, int first) {
#pragma unroll
    for (int ks = 0; ks < 4; ks++)
        wgmma_rs_n32(acc, wa[a0 + 4 * i + ks], mkdesc(0, 0, 1024) | (uint32_t)(xl + (((i ? (i - 1) * 8192 : C_MEM - C_XR) + ks * 32) >> 4)), !(first && ks == 0));
}
template <typename F>
__device__ __forceinline__ void x_part(F aside, float (&acc)[16], const uint32_t (&wa)[40][4], uint32_t sm, int n, int wg, int w, uint32_t ln, uint32_t small) {
    const int s = n - 1; (void)s;
    uint32_t giv[12];
    auto chunk = [&](int a0, int i, int first) { x_chunk(acc, wa, x_base(wg, small, a0 ? 21 : 22), a0, i, first); };
    mbar_wait(sm + CB_XM, n & 1);
    if (n) bar_sync(5, 384);
    if (wg == 0 && w == 0) PROF(12);
    WG_FENCE();
#pragma unroll
    for (int i = 1 + XA; i < 5; i++) chunk(20, i, 0);
    chunk(20, 0, 0);
    WG_COMMIT();
    if (n) {
        if (wg == 1 && w == 1) BULK_WAIT();
        bar_sync(8, 256);
    }
    if (wg == 0 && w == 0) PROF(18);
    const uint32_t xb = sm + w * 512 + ln * 16, xw = xb + C_KX - wg * 4096, xr = xb + C_QX + wg * 4096;
    WG_WAIT(0);
#pragma unroll
    for (int i = 0; i < 8; i++) asm volatile("cvt.rn.bf16x2.f32 %0, %1, %2;" : "=r"(giv[i]) : "f"(acc[2 * i + 1]), "f"(acc[2 * i]));
#pragma unroll
    for (int p = 0; p < 2 + H24; p++)
        asm volatile("st.shared.v4.u32 [%0], {%1,%2,%3,%4};" :: "r"(p < 2 ? xw + p * 2048 : xb + (wg ? C_SC : C_OX + 1024)), "r"(giv[4 * p]), "r"(giv[4 * p + 1]), "r"(giv[4 * p + 2]), "r"(giv[4 * p + 3]) : "memory");
    bar_arrive(12 + wg, 256);
    WG_FENCE();
    chunk(0, 0, 1);
    WG_COMMIT();
    chunk(0, 1, 0);
    if (XORD) chunk(0, 2, 0);
    bar_sync(13 - wg, 256);
#pragma unroll
    for (int p = 0; p < 2 + H24; p++)
        asm volatile("ld.shared.v4.u32 {%0,%1,%2,%3}, [%4];" : "=r"(giv[4 * p]), "=r"(giv[4 * p + 1]), "=r"(giv[4 * p + 2]), "=r"(giv[4 * p + 3]) : "r"(p < 2 ? xr + p * 2048 : xb + (wg ? C_OX + 1024 : C_SC)) : "memory");
    WG_COMMIT(); WG_WAIT(1); bar_arrive(9, 384);
    WG_FENCE();
    if (!XORD) chunk(0, 2, 0);
    chunk(0, 3, 0); chunk(0, 4, 0);
    WG_COMMIT();
    const uint32_t r = ln & 7, mi = ln >> 3, dst = sm + (wg == 0 ? C_QX : C_KX) + ((mi >> 1) * 8 + r) * 128 + (((2 * w + (mi & 1)) ^ r) << 4);
    pin(xb, giv[0], giv[4], dst, 0);
    aside();
    bar_sync(10 + wg, 128);
    WG_WAIT(0);
    if (wg == 0 && w == 0) PROF(30);
    if (w == 0 && ln < 3) mbar_arrive_remote(mapa(sm + CB_XD, ln));
#pragma unroll
    for (int i = 0; i < 8; i++) { acc[2 * i] += lo_f(giv[i]); acc[2 * i + 1] += hi_f(giv[i]); }
#pragma unroll
    for (int p = 0; p < 2; p++)
        stsm4t(dst + p * 2048, pack2(acc[8 * p], acc[8 * p + 1]), pack2(acc[8 * p + 2], acc[8 * p + 3]), pack2(acc[8 * p + 4], acc[8 * p + 5]), pack2(acc[8 * p + 6], acc[8 * p + 7]));
    if (wg == 0 && w == 0) PROF(11);
}
__device__ __forceinline__ void x_fill(const ChainMaps& mp, uint32_t sm, int n, int j) {
    mbar_expect(sm + CB_XF, 24576);
    asm volatile("cp.async.bulk.tensor.3d.shared::cluster.global.mbarrier::complete_tx::bytes.multicast::cluster [%0], [%1, {0, %3, %4}], [%2], %5;"
        :: "r"(sm + C_XR + j * 8192), "l"((uint64_t)&mp.h2), "r"(sm + CB_XF), "r"(n * SEG), "r"(2 + 2 * j), "h"((uint16_t)7) : "memory");
}
__device__ __forceinline__ void x_rest(const ChainMaps& mp, uint32_t sm, int n) {
    mbar_expect(sm + CB_XM, 16384);
    tma3d(sm + C_XR + 6 * 4096, &mp.h2, n * SEG, 8, sm + CB_XM); tma3d(sm + C_MEM, &mp.h2, n * SEG, 0, sm + CB_XM);
}

#define WPOS 2
#define WP 4
#define SDEL 0
#define EORD 0
#define RPF 1
#define TDEL 2500
#define BPOS 2
#define TPF 1
#define B_LATE 13
constexpr int E_B = C_WO, E_STG = 196608, EB_A = 229376, EB_B = C_BAR + 80, EB_REL = C_BAR + 104;
__device__ __forceinline__ uint32_t e_slot(int wg, int c) { return wg && c == 2 ? E_B + 98304 : wg * 49152 + c * 16384; }
constexpr int T_WG = 0, T_WU = 20480, T_WD = 40960, T_X = 65536, T_RED = 77824, T_KEY = 86016;
__device__ __forceinline__ void wo_half(const ChainMaps& mp, uint32_t sm, int blk, int c) {
    if (blk < 80 && elect()) { mbar_expect(sm + EB_B + 8 * c, 49152); tma3d(sm + E_B + c * 49152, &mp.wo15, blk / 5 * 384 + c * 192, blk % 5 * 2, sm + EB_B + 8 * c); }
}
__device__ __forceinline__ void end_loads(const ChainMaps& mp, const ChainArgs& ar, uint32_t sm, int blk, int wg) {
    const uint32_t bar = sm + EB_A + wg * 48;
    const int kp = blk / 5;
    if (elect()) {
#pragma unroll 1
        for (int c = 0; c < 6; c++) mbar_init(bar + 8 * c, c < 3 ? 1 : 4);
        PROXY_FENCE();
    }
    __syncwarp();
    bar_arrive(5, 384);
    if (EORD) bar_sync(6, 96);
    if (blk >= 80) {
        if (TPF && elect()) {
#pragma unroll 1
            for (int c = 0; c < 3; c++) asm volatile("cp.async.bulk.prefetch.L2.global [%0], 61440;" :: "l"((c == 0 ? ar.wgate : c == 1 ? ar.wup : ar.wdown) + ((blk - 80) * 2 + wg) * 30720) : "memory");
        }
        return;
    }
    const uint64_t ef = policy_stream();
#pragma unroll 1
    for (int b = B_LATE; b < 16; b++) {
        w_flag_wait(b == 15 ? &g_flags.half[kp * 2 + wg] : &g_flags.pair[b * 16 + kp], b == 15 ? 2 : 4);
#pragma unroll 1
        for (int c = 0; c < 3; c++) {
            if (b > B_LATE) mbar_wait(bar + 24 + 8 * c, (b - B_LATE - 1) & 1);
            if (elect()) { mbar_expect(bar + 8 * c, 16384); tma3d_ef(sm + e_slot(wg, c), &mp.o15, b * 128 + wg * 64, kp * 6 + c * 2, bar + 8 * c, ef); }
            __syncwarp();
        }
    }
}
__device__ __forceinline__ void end_stores(const ChainMaps& mp, uint32_t sm, int blk, int wg) {
#pragma unroll 1
    for (int b = B_LATE; b < 16 && blk < 80; b++) {
        bar_sync(12 + wg, 160);
        if (elect()) tma3d_store(&mp.slab2, (b * KSPLIT + blk / 5) * 128 + wg * 64, blk % 5 * 2, sm + E_STG + wg * 16384, 0, false);
        BULK_COMMIT(); BULK_WAIT();
        if (b < 15) bar_arrive(10 + wg, 160);
        GPU_FENCE();
        w_bump(b < 14 ? &g_flags.o[b] : &g_flags.fin[((b - 14) * 2 + wg) * 32]);
    }
    bar_arrive(8, 320);
}
__device__ __forceinline__ void last_blocks(const ChainArgs& ar, uint32_t sm, int blk, int tid) {
    const int warp = __shfl_sync(0xffffffffu, tid >> 5, 0), lane = tid & 31, wg = warp >> 2, w = warp & 3;
    const uint32_t bar = sm + EB_A + wg * 48, stg = sm + E_STG + wg * 16384 + w * 2048;
    bar_sync(5, 384);
    EPT(tid == 128, 7);
    float acc[64];
#pragma unroll
    for (int n = 0; n < 64; n++) acc[n] = 0.f;
#pragma unroll 1
    for (int b = B_LATE; b < 16 && blk < 80; b++) {
#pragma unroll 1
        for (int c = 0; c < 6; c++) {
            mbar_wait(sm + EB_B + 8 * (c >= 3), 0); mbar_wait(bar + 8 * (c >> 1), (b - B_LATE) & 1);
            const uint64_t da = mkdesc(SM_BASE + e_slot(wg, c >> 1) + (c & 1) * 8192, 16, 1024), db = mkdesc(SM_BASE + E_B + (c >= 3 ? 24576 : 0) + c * 8192, 24576, 1024);
            WG_FENCE();
#pragma unroll
            for (int ks = 0; ks < 4; ks++) wgmma_ss_n128_tb(acc, da + ks * 2, db + ks * 128, c | ks);
            WG_COMMIT();
            WG_WAIT(1);
            if ((c & 1) == 0 && c && elect()) mbar_arrive(bar + 16 + 4 * c);
        }
        if (b > B_LATE) bar_sync(10 + wg, 160);
        WG_WAIT(0);
        if (elect()) mbar_arrive(bar + 40);
        EPT(tid == 128, 13 + 15 - b);
        const int r = lane & 7, mi = lane >> 3;
#pragma unroll
        for (int p = 0; p < 8; p++) {
            const int oc = 2 * p + (mi >> 1);
            stsm4(stg + (oc >> 3) * 8192 + ((mi & 1) * 8 + r) * 128 + (((oc & 7) ^ r) << 4), pack2(acc[8 * p], acc[8 * p + 1]), pack2(acc[8 * p + 2], acc[8 * p + 3]),
                  pack2(acc[8 * p + 4], acc[8 * p + 5]), pack2(acc[8 * p + 6], acc[8 * p + 7]));
        }
        PROXY_FENCE();
        bar_arrive(12 + wg, 160);
    }
    bar_sync(8, 320);
    if (TDEL && blk < 80) wait_until(clock() + TDEL);
    const int o = (tid >> 1) * FF + blk * 16 + (tid & 1) * 8;
    const bf16 *pg = ar.wgate + o, *pu = ar.wup + o, *pd = ar.wdown + tid * DM + (blk < 80 ? blk : 0) * 8;
#pragma unroll 1
    for (int i = 0; i < 6; i++) {
        const uint32_t d = sm + E_B + i * 4096 + tid * 16;
        if (i < 5) asm volatile("cp.async.cg.shared.global [%0], [%1], 16; cp.async.cg.shared.global [%0 + 20480], [%2], 16;" :: "r"(d), "l"(pg + i * 128 * FF), "l"(pu + i * 128 * FF) : "memory");
        asm volatile("cp.async.cg.shared.global [%0 + 40960], [%1], 16;" :: "r"(d), "l"(pd + i * 256 * DM) : "memory");
    }
    EPT(tid == 128, 8);
}
__device__ __forceinline__ void mod_tail(const ChainArgs& ar, const uint32_t tb, const uint32_t bar, const int blk, const int tid) {
#define TPROF(i) EPT(tid == 0, i)
    const int warp = __shfl_sync(0xffffffffu, tid >> 5, 0), lane = tid & 31, r = lane & 7, mi = lane >> 3;
    const uint32_t kb = tb + T_KEY;
    {
        uint32_t k[8];
        for (int n = 0;; n++) {
#pragma unroll
            for (int i = 0; i < 2; i++) asm volatile("ld.relaxed.gpu.global.v4.u32 {%0,%1,%2,%3}, [%4];" : "=r"(k[4 * i]), "=r"(k[4 * i + 1]), "=r"(k[4 * i + 2]), "=r"(k[4 * i + 3]) : "l"(g_key + warp * 256 + i * 128 + lane * 4) : "memory");
            if (__all_sync(0xffffffffu, (k[0] & k[1] & k[2] & k[3] & k[4] & k[5] & k[6] & k[7] & S_TOK) != 0)) break;
            if (n > (1 << 22)) __trap();
            __nanosleep(NAP);
        }
        const uint32_t m = __reduce_max_sync(0xffffffffu, max(umax3(k[0], k[1], k[2]), max(umax3(k[3], k[4], k[5]), max(k[6], k[7]))));
        asm volatile("st.shared.u32 [%0], %1; st.shared.u32 [%2], 0;" :: "r"(kb + warp * 4), "r"(m), "r"(kb + 32) : "memory");
        if (RPF && blk >= 93 && warp < 6) {
            uint32_t c = m;
#pragma unroll 1
            for (int it = 93; it < blk; it++) {
                uint32_t x = 0;
#pragma unroll
                for (int i = 0; i < 8; i++) x = max(x, k[i] < c ? k[i] : 0u);
                c = __reduce_max_sync(0xffffffffu, x);
            }
            if ((c & 2 * S_TOK) && lane < 2) asm volatile("cp.async.bulk.prefetch.L2.global [%0], 1280;" :: "l"((lane ? g_h2 : g_x1) + (~c & (S_TOK - 1)) * DM) : "memory");
        }
        asm volatile("cp.async.wait_all;" ::: "memory");
        bar_sync(1, 256);
        TPROF(1);
        const uint32_t low = __reduce_min_sync(0xffffffffu, lds32(kb + r * 4));
        uint32_t cnt = 0;
#pragma unroll
        for (int i = 0; i < 8; i++) cnt += k[i] >= low ? 4 : 0;
        if (cnt) {
            uint32_t a; asm volatile("atom.shared.add.u32 %0, [%1], %2;" : "=r"(a) : "r"(kb + 32), "r"(cnt) : "memory");
#pragma unroll
            for (int i = 0; i < 8; i++) if (k[i] >= low) { asm volatile("st.shared.u32 [%0], %1;" :: "r"(kb + 512 + a), "r"(k[i]) : "memory"); a += 4; }
        }
        if (tid == 0) mbar_arrive(bar);
        bar_sync(1, 256);
        const int nc = lds32(kb + 32);
#pragma unroll 1
        for (int c = lane * 4; c < nc; c += 128) {
            const uint32_t me = lds32(kb + 512 + c);
            int rank = 0;
#pragma unroll 2
            for (int e = 0; e < nc; e += 16) {
                const float4 z = lds128f(kb + 512 + e);
                rank += (__float_as_uint(z.x) > me) + (e + 4 < nc && __float_as_uint(z.y) > me) + (e + 8 < nc && __float_as_uint(z.z) > me) + (e + 12 < nc && __float_as_uint(z.w) > me);
            }
            if (rank < 8) asm volatile("st.shared.u32 [%0], %1;" :: "r"(kb + 64 + (warp * 8 + rank) * 4), "r"(me) : "memory");
        }
        __syncwarp();
    }
    const uint32_t k0 = lds32(kb + 64 + (warp * 8 + r) * 4), k1 = lds32(kb + 64 + (warp * 8 + (lane >> 2)) * 4);
    TPROF(2);
    const int trow = ~k1 & (S_TOK - 1), tcol = (blk < 80 ? blk : 0) * 8 + (lane & 3) * 2;
    uint2 xb[5];
#pragma unroll
    for (int h = 0; h < 5; h++) xb[h] = __ldcg((const uint2*)(g_h2 + trow * DM + (warp * 5 + h) * 16 + (lane & 3) * 4));
    const uint32_t fx1 = __ldcg((const uint32_t*)(g_x1 + trow * DM + tcol)), fh2 = __ldcg((const uint32_t*)(g_h2 + trow * DM + tcol)),
                   fgb = __ldcg((const uint32_t*)(g_mod + 5 * DM + tcol));
    const float fr = __uint_as_float(((int)k1 < 0 ? k1 ^ 0x80000000u : ~k1) & 0xffff0000u);
    {
        float dg[4] = {0, 0, 0, 0}, du[4] = {0, 0, 0, 0};
        uint32_t ag[5][4], au[5][4];
#pragma unroll
        for (int h = 0; h < 5; h++) {
            const uint32_t o = tb + ((warp * 5 + h) * 16 + (r >> 1) * 4 + (mi >> 1) * 2 + (r & 1)) * 32 + (mi & 1) * 16;
            ldsm4t(ag[h], o + T_WG); ldsm4t(au[h], o + T_WU);
        }
#pragma unroll
        for (int h = 0; h < 5; h++) { mma16q(dg, ag[h], xb[h].x, xb[h].y); mma16q(du, au[h], xb[h].x, xb[h].y); }
        TPROF(3);
        sts128f(tb + T_RED + warp * 1024 + lane * 16, dg[0], dg[1], dg[2], dg[3]); sts128f(tb + T_RED + warp * 1024 + 512 + lane * 16, du[0], du[1], du[2], du[3]);
    }
    bar_sync(1, 256);
    if (warp < 2) {
        float g2[2] = {0, 0}, u2[2] = {0, 0};
#pragma unroll
        for (int i = 0; i < 8; i++) {
            const float2 a = lds64f(tb + T_RED + i * 1024 + lane * 16 + warp * 8), b = lds64f(tb + T_RED + i * 1024 + 512 + lane * 16 + warp * 8);
            g2[0] += a.x; g2[1] += a.y; u2[0] += b.x; u2[1] += b.y;
        }
        float y[2];
#pragma unroll
        for (int i = 0; i < 2; i++) { const float gq = bfr(g2[i]); y[i] = bfr(__fdividef(gq, 1.f + __expf(-gq))) * bfr(u2[i]); }
        asm volatile("st.relaxed.gpu.global.u32 [%0], %1;" :: "l"(g_gu + (blk >> 1) * 128 + lane * 4 + warp * 2 + (blk & 1)), "r"(movm_t(pack2(y[0], y[1]))) : "memory");
    }
    TPROF(4);
    if (blk < 80) {
        uint32_t a[6][4], b[6][4];
#pragma unroll
        for (int k2 = 0; k2 < 6; k2++) ldsm4t(b[k2], tb + T_WD + (warp * 6 + k2) * 512 + lane * 16);
        for (int n = 0;; n++) {
            uint32_t m = 0;
#pragma unroll
            for (int k2 = 0; k2 < 6; k2++) asm volatile("ld.relaxed.gpu.global.v4.u32 {%0,%1,%2,%3}, [%4];" : "=r"(a[k2][0]), "=r"(a[k2][1]), "=r"(a[k2][2]), "=r"(a[k2][3]) : "l"(g_gu + (warp * 6 + k2) * 128 + lane * 4) : "memory");
#pragma unroll
            for (int k2 = 0; k2 < 6; k2++) m = umax3(umax3(m, a[k2][0], a[k2][1]), a[k2][2], a[k2][3]);
            if (!__any_sync(0xffffffffu, m == ~0u)) break;
            if (n > (1 << 22)) __trap();
        }
        TPROF(5);
        float d[2][4] = {{0, 0, 0, 0}, {0, 0, 0, 0}};
#pragma unroll
        for (int k2 = 0; k2 < 6; k2++) { mma16q(d[0], a[k2], b[k2][0], b[k2][1]); mma16q(d[1], a[k2], b[k2][2], b[k2][3]); }
        asm volatile("st.shared.v2.f32 [%0], {%1,%2};" :: "r"(tb + T_X + warp * 256 + lane * 8), "f"(d[0][0] + d[1][2]), "f"(d[0][1] + d[1][3]) : "memory");
        bar_sync(1, 256);
        if (warp == 0) {
            float y0 = 0, y1 = 0;
#pragma unroll
            for (int i = 0; i < 8; i++) { const float2 z = lds64f(tb + T_X + i * 256 + lane * 8); y0 += z.x; y1 += z.y; }
            const float sg = __fdividef(1.f, 1.f + __expf(-fr));
            *(uint32_t*)(ar.out + trow * DM + tcol) = add2(fx1, mul2(fgb, add2(fh2, mul2(pack2(y0, y1), pack2(sg, sg)))));
        }
    }
    TPROF(6);
}

__global__ void __cluster_dims__(3, 1, 1) __launch_bounds__(384, 1) k_chain(const __grid_constant__ ChainMaps mp, const __grid_constant__ ChainArgs ar) {
    const int D1 = ar.D1, DG = ar.DG;
    extern __shared__ __align__(1024) uint8_t smraw[];
    const uint32_t sm = SM_BASE + ((blockIdx.x % 3) << 24);
    if (smem_u32(smraw) != sm) __trap();
    uint32_t tid; asm volatile("mov.u32 %0, %%tid.x;" : "=r"(tid));
    const int warp = __shfl_sync(0xffffffffu, tid >> 5, 0), lane = tid & 31, wg = warp >> 2, w = warp & 3;
    const int blk = blockIdx.x, head = blk / 3, j = blk % 3;
    const int col0 = head * DH + j * 64;
    asm volatile("griddepcontrol.launch_dependents;");
#define PPROF(i)
    const int r = lane & 7, mi = lane >> 3;
    const uint32_t memrd = opaque(sm + C_MEM + lane * 16);
    if (wg < 2) {
        {
            uint32_t xv[3][10];
            const int row = blk * 8 + warp, nq = row < S_TOK - 1536 ? 3 : 2;
#pragma unroll
            for (int i = 0; i < 15; i++) {
                const uint2 v = __ldcs((const uint2*)(ar.x + (row + (i < 10 || nq == 3 ? i / 5 * 768 : 0)) * DM + lane * 4 + i % 5 * 128));
                xv[i / 5][i % 5 * 2] = v.x; xv[i / 5][i % 5 * 2 + 1] = v.y;
            }
            if (tid == 32) {
#pragma unroll 1
                for (int c = 0; c < 14; c++) if (c != 12) mbar_init(sm + C_BAR + 8 * c, c == 2 ? 5 : c == 3 ? 6 : 1);
                asm volatile("fence.mbarrier_init.release.cluster;" ::: "memory");
                mbar_expect(sm + CB_SC, 2560); mbar_expect(sm + CB_OX, 2048);
            }
            if (warp == 2) {
                const uint32_t f = blk >= 28 ? ~0u : 0u;
                ((uint4*)g_acc)[blk * 32 + lane] = make_uint4(0, 0, 0, 0);
                if (blk < 76) (blk < 12 ? (uint4*)g_stamp + blk * 32 : blk < 28 ? (uint4*)g_key + (blk - 12) * 32 : (uint4*)g_gu + (blk - 28) * 32)[lane] = make_uint4(f, f, f, f);
            }
            __syncwarp();
            asm volatile("barrier.cluster.arrive.relaxed.aligned;" ::: "memory");
            PPROF(8);
#pragma unroll 1
            for (int q = 0; q < 3; q++) {
                uint32_t nv[10];
                ln_norm(xv[0], nv);
#pragma unroll
                for (int i = 0; i < 10; i++) { xv[0][i] = xv[1][i]; xv[1][i] = xv[2][i]; xv[2][i] = nv[i]; }
            }
            PPROF(9);
            if (warp < 5) {
                uint4 u;
                for (int n = 0;; n++) {
                    asm volatile("ld.relaxed.gpu.global.v4.u32 {%0,%1,%2,%3}, [%4];" : "=r"(u.x), "=r"(u.y), "=r"(u.z), "=r"(u.w) : "l"(g_flags.mod1 + tid * 4) : "memory");
                    if (__all_sync(0xffffffffu, u.x && u.y && u.z && u.w)) break;
                    cut(n, 1 << 22);
                }
                asm volatile("st.shared.v4.u32 [%0], {%1,%2,%3,%4};" :: "r"(sm + C_KX + tid * 16), "r"(~u.x), "r"(~u.y), "r"(~u.z), "r"(~u.w) : "memory");
            }
            bar_sync(8, 256);
            PPROF(2);
            uint32_t m = 0;
#pragma unroll
            for (int i = 0; i < 5; i++) {
                uint32_t t[2], u[2];
                lds64(t, sm + C_KX + lane * 8 + i * 256); lds64(u, sm + C_KX + 1280 + lane * 8 + i * 256);
                u[0] = add2(u[0], 0x3f803f80u); u[1] = add2(u[1], 0x3f803f80u);
                m = amax2(amax2(amax2(amax2(m, t[0]), u[0]), t[1]), u[1]);
#pragma unroll
                for (int q = 0; q < 3; q++)
                    if (q < nq) *(uint2*)(g_h + (row + q * 768) * DM + lane * 4 + i * 128) = make_uint2(add2(mul2(xv[q][2 * i], u[0]), t[0]), add2(mul2(xv[q][2 * i + 1], u[1]), t[1]));
            }
            asm volatile("st.shared.u32 [%0], %1;" :: "r"(sm + C_LAG), "r"((amax_warp(m) >> 7) + 1) : "memory");
            bar_sync(8, 256);
            if (tid == 0) flag_add(&g_flags.h);
            __syncwarp();
            bar_arrive(2, 288);
            PPROF(3);
            asm volatile("barrier.cluster.wait.aligned;" ::: "memory");
        }
        asm volatile("setmaxnreg.inc.sync.aligned.u32 %0;" :: "n"(REG_P));
        uint32_t wa[40][4];
        mbar_wait(sm + CB_W, 0);
#pragma unroll
        for (int ks = 0; ks < 40; ks++)
            ldsm4t(wa[ks], sm + ((wg == 0) == (ks < 20) ? C_WV : C_WO) + ((mi >> 1) * 8 + r) * 128 + (((2 * w + (mi & 1)) ^ r) << 4) + (ks % 20 / 4 * 8 + 4 * wg + (ks & 3)) * 2048);
        PPROF(5);
        bar_arrive(1, 288);
        const uint32_t qst = opaque(sm + (wg == 0 ? C_QM : C_KM) + (2 * w + (mi & 1)) * 128 + r * 16);
        const uint32_t vrd = opaque(sm + C_WV + ((mi >> 1) * 8 + r) * 128 + (((2 * w + (mi & 1)) ^ r) << 4) + 4 * wg * 2048);
        const uint32_t mrd = opaque(memrd + wg * 1024);
        float acc[16];
        auto fb = [&](int n) { return mrd + (n >> 1) * 2048 + (n & 1) * 512; };
        auto fa = [&](int k) { return vrd + (k >> 2) * 16384 + (k & 3) * 2048; };
        auto qk_out = [&](int n) {
            uint8_t* rec = g_att + (n * NH + head) * AT_REC;
            w_bulk_s2g(rec + j * 8192, sm + C_QX, 8192); w_bulk_s2g(rec + AT_KM + j * 1024, sm + C_KM, 1024);
            BULK_COMMIT();
        };
        for (int s = -1;; s++) {
          if (s >= 0) {
            uint32_t b[3][4], a[4][4];
            x_part([&]() {
                if (AIN && s == 0) mbar_wait(sm + CB_W2, 0);
#pragma unroll
                for (int i = 0; i < AIN; i++) ldsm4t(a[i], fa(4 + i));
            }, acc, wa, sm, s, wg, w, opaque(mrd) >> 4 & 31, s + ar.D2);
            if (!AIN && s == 0) mbar_wait(sm + CB_W2, 0);
#pragma unroll
            for (int i = AIN; i < APRE; i++) ldsm4t(a[i], fa(4 + i));
            cut(s + ar.D2, 0);
            bar_sync(1, 384);
            if (warp == 0) { PROF(0); PROFG(24); }
            float dv[4] = {0, 0, 0, 0};
            const uint32_t xb = mrd - wg * 1024 - (C_MEM - C_VP) + w * 512;
            {
                float d[2][4] = {{0, 0, 0, 0}, {0, 0, 0, 0}}, g[2][4] = {{0, 0, 0, 0}, {0, 0, 0, 0}};
                ldsm4t(b[0], fb(0)); pin0(mrd); ldsm4t(b[1], fb(1)); pin0(mrd);
#pragma unroll
                for (int n = 0; n < 10; n++) {
                    const int c1 = n >= 10 - NCH;
                    if (n < 8) ldsm4t(b[(n + 2) % 3], fb(n + 2));
                    if (n < 2 && 2 * n >= APRE) { ldsm4t(a[2 * n], fa(4 + 2 * n)); ldsm4t(a[2 * n + 1], fa(5 + 2 * n)); }
#pragma unroll
                    for (int e = 0; e < 2; e++) {
                        mma16q(g[e & c1], wa[20 + 2 * n + e], b[n % 3][2 * e], b[n % 3][2 * e + 1]); mma16q(d[e & c1], wa[2 * n + e], b[n % 3][2 * e], b[n % 3][2 * e + 1]);
                        if (n >= 2 && n < 10 - VT) mma16q(dv, a[(2 * n + e) & 3], b[n % 3][2 * e], b[n % 3][2 * e + 1]);
                        if (n >= 2 && n < 8) ldsm4t(a[(2 * n + e) & 3], fa(2 * n + 4 + e));
                    }
                    if (QCUT >> n & 1) cut(s + ar.D2, 1 + n);
                }
                const float un = __uint_as_float(lds32(sm + C_UN));
                sts128f(xb - 4096 + wg * 2048, g[0][0] + g[1][0], g[0][1] + g[1][1], g[0][2] + g[1][2], g[0][3] + g[1][3]);
#pragma unroll
                for (int k = 20 - 2 * VT; k < 20; k++) mma16q(dv, a[k & 3], b[k / 2 % 3][2 * (k & 1)], b[k / 2 % 3][2 * (k & 1) + 1]);
                if (PBAR) bar_sync(10 + w, 64); else bar_sync(8, 256);
                const float4 z = lds128f(xb - 4096 + (wg ^ 1) * 2048);
                sts128f(xb + wg * 2048, dv[0], dv[1], dv[2], dv[3]);
                stsm2t(qst, pack2((d[0][0] + d[1][0] + z.x) * un, (d[0][1] + d[1][1] + z.y) * un), pack2((d[0][2] + d[1][2] + z.z) * un, (d[0][3] + d[1][3] + z.w) * un));
            }
            bar_arrive(2, 384);
            if (w == 0) PROF(1 + wg);
            if (s + 1 == NSEG) break;
          }
          if (!STL && warp == 3 && s >= 0)
              asm volatile(ELECTED("st.relaxed.gpu.global.u32 [%0], %1;") :: "l"(g_stamp + (s & 3) * 384 + (blk >> 3) * 32 + (blk & 7)), "r"((gtime() & ~31u) | ((s >> 2) + 1)) : "memory");
          PROXY_FENCE();
          mbar_wait(sm + CB_XF, (s + 1) & 1);
          if (s >= 0) bar_sync(7, 384);
          WG_FENCE();
#pragma unroll
          for (int i = 0; i < 16; i++) acc[i] = 0.f;
#pragma unroll
          for (int i = 1; i <= XA; i++) x_chunk(acc, wa, x_base(wg, s + ar.D2, 20), 20, i, i == 1);
          WG_COMMIT();
          if (warp == FW && s > 1) {
              if ((s & 3) == 0) { GPU_FENCE(); if (!BDEF) w_bump(&g_flags.qk[(s >> 2) - 1]); }
              if (BDEF && (s & 3) == 1) w_bump(&g_flags.qk[(s >> 2) - 1]);
              if (F61 && s == 62) seg_done(61, head);
          }
          if (!WLATE) WG_WAIT(0);
          if (s >= 0) {
            if (warp == 0) {
                PROF(7);
                if (elect()) x_rest(mp, sm, s + 1);
            } else {
                if (wg == 1) {
                    if (w == 1) {
                        if (QDEL) wait_until(clock() + QDEL);
                        qk_out(s);
                    }
                    if (w == 2 && blk < 20 && (s & 1) && s + 3 < NSEG)
                        asm volatile(ELECTED("cp.async.bulk.prefetch.L2.global [%0], 4096;") :: "l"((const uint8_t*)g_h + (s + 3) * (SEG * DM * 2) + blk * 4096) : "memory");
                } else if (w == 3) {
                    if (SPOLL) wait_until(clock() + SPOLL);
                    const uint32_t l = opaque(mrd) >> 4 & 31, tag = (s >> 2) + 1, now = gtime();
                    const uint32_t* sp = g_stamp + (s & 3) * 384 + (l >> 3) * 32 + (l & 7);
                    uint32_t t[3];
                    for (int n = 0;; n++) {
#pragma unroll
                        for (int i = 0; i < 3; i++) t[i] = ld_rlx(sp + i * 128);
                        if (!__any_sync(0xffffffffu, ((t[0] ^ tag) | (t[1] ^ tag) | (t[2] ^ tag)) & 31) || n > SPIN_LIMIT) break;
                    }
                    int all = -(1 << 30), own = all;
#pragma unroll
                    for (int i = 0; i < 3; i++) { const int d = t[i] - now; all = max(all, d); if ((i * 32 + l) / 3 == head) own = d; }
                    const int lag = min(__reduce_max_sync(0xffffffffu, all) - __reduce_max_sync(0xffffffffu, own), s || STL == 1 ? 8000 : 200);
                    PROFV(15, lag);
                    asm volatile("st.shared.u32 [%0], %1;" :: "r"(sm + C_LAG), "r"(D1 + ((lag * DG) >> 4)) : "memory");
                    bar_arrive(6, 160);
                } else if (w == 2) {
                    if ((s & 3) == 3) w_flag_wait(&g_flags.v[((s + 1) >> 2) * 32 + head], 2);
                    if (elect()) { mbar_expect(sm + CB_VX, 4096); bulk_g2s(sm + C_VX, g_att + ((s + 1) * NH + head) * AT_REC + AT_V + j * 4096, 4096, sm + CB_VX); }
                    if ((s & 3) == 1 && s + 3 < NSEG && blk == 20) asm volatile(ELECTED("cp.async.bulk.prefetch.L2.global [%0], 128;") :: "l"(&g_flags.v[((s + 3) >> 2) * 32]) : "memory");
                    if (s + 2 < NSEG && (s & 3) && ((s & 3) != 2 || __all_sync(0xffffffffu, ld_rlx(&g_flags.v[((s + 2) >> 2) * 32 + head]) >= 2))) {
                        const uint8_t* p = g_att + ((s + 2) * NH + head) * AT_REC + AT_V + j * 4096;
                        asm volatile(ELECTED("cp.async.bulk.prefetch.L2.global [%0], 4096;") :: "l"(p) : "memory");
                        if ((s & 3) == 3) asm volatile(ELECTED("cp.async.bulk.prefetch.L2.global [%0], 4096;") :: "l"(p + NH * AT_REC) : "memory");
                    }
                }
            }
          }
          if (WLATE) WG_WAIT(0);
        }
        PROXY_FENCE();
        bar_sync(8, 256);
        if (warp == 5) { qk_out(NSEG - 1); BULK_WAIT(); }
        if (warp == 7) { seg_done(NSEG - 2, head); if (!F61) w_bump(&g_flags.seg[32 + head]); }
        const int t2 = (opaque(mrd) >> 4 & 31) + warp * 32;
        EPT(t2 == 0, 0);
        last_blocks(ar, sm, blk, t2);
        mod_tail(ar, sm + E_B, sm + EB_REL, blk, t2);
    } else {
        asm volatile("setmaxnreg.dec.sync.aligned.u32 %0;" :: "n"(REG_L));
        asm volatile("barrier.cluster.arrive.relaxed.aligned;" ::: "memory");
        if (blk < 80) {
            const int t = tid - 256;
#pragma unroll 1
            for (int i = 0; i < 10; i++)
                asm volatile("cp.async.cg.shared.global.L2::128B [%0], [%1], 16;" :: "r"(sm + C_XR + i * 2048 + t * 16), "l"(ar.wmod + ((t >> 1) + 64 * i) * (6 * DM) + blk * 16 + (t & 1) * 8) : "memory");
            float cs[5];
#pragma unroll
            for (int i = 0; i < 5; i++) cs[i] = __uint_as_float((uint32_t)__ldg((const unsigned short*)ar.c + t + 128 * i) << 16);
#pragma unroll
            for (int i = 0; i < 5; i++) asm volatile("st.shared.f32 [%0], %1;" :: "r"(sm + C_QX + (t + 128 * i) * 4), "f"(bfr(__fdividef(cs[i], 1.f + __expf(-cs[i])))) : "memory");
            asm volatile("cp.async.wait_all;" ::: "memory");
            bar_sync(3, 128);
            float a0 = 0, a1 = 0;
#pragma unroll 8
            for (int i = 0; i < 40; i++) {
                const float f = __uint_as_float(lds32(sm + C_QX + (t >> 3) * 4 + i * 64));
                const uint32_t u = lds32(sm + C_XR + t * 4 + i * 512);
                a0 += f * lo_f(u); a1 += f * hi_f(u);
            }
#pragma unroll
            for (int o = 8; o < 32; o <<= 1) { a0 += __shfl_xor_sync(0xffffffffu, a0, o); a1 += __shfl_xor_sync(0xffffffffu, a1, o); }
            asm volatile("st.shared.v2.f32 [%0], {%1,%2};" :: "r"(sm + C_QM + w * 64 + (lane & 7) * 8), "f"(a0), "f"(a1) : "memory");
            bar_sync(3, 128);
            if (w == 0) {
#pragma unroll
                for (int i = 1; i < 4; i++) { const float2 z = lds64f(sm + C_QM + i * 64 + (lane & 7) * 8); a0 += z.x; a1 += z.y; }
                const uint32_t v = pack2(a0, a1);
                asm volatile("st.relaxed.gpu.global.u32 [%0], %1;" :: "l"(g_flags.mod1 + blk * 8 + (lane & 7)), "r"(~v) : "memory");
            }
        }
        uint32_t m0[5][4], mm = 0;
#pragma unroll
        for (int i = 0; i < 20; i++) {
            const unsigned short* p = (const unsigned short*)ar.mem0 + (i & 3) * 2 * DM + (i >> 2) * 128 + tid - 256;
            m0[i >> 2][i & 3] = __ldg(p) | (uint32_t)__ldg(p + DM) << 16;
        }
        {
            asm volatile("barrier.cluster.wait.aligned;" ::: "memory");
            if (w == 3) {
                w_flag_wait(&g_flags.h, 96);
                if (elect()) { x_fill(mp, sm, 0, j); x_rest(mp, sm, 0); }
                __syncwarp();
            }
            if (w == 1) {
                const uint64_t ef = policy_stream();
#pragma unroll 1
                for (int c = 0; c < 2 * WP + 2; c++) {
                    const uint32_t bar = sm + EB_B + 8 * (c & 1);
                    if (c == WPOS) bar_sync(2, 288);
                    if (c >= 2) mbar_wait(bar, (c / 2 - 1) & 1);
                    if (elect()) {
                        if (c < 2 * WP) { mbar_expect(bar, 81920 / WP); tma2d_ef(sm + C_WV + c * (81920 / WP), c < WP ? &mp.wq : &mp.wk, col0, c % WP * (640 / WP), bar, ef); }
                        if (c == 2 * WP + 1) mbar_arrive(sm + CB_W);
                    }
                    __syncwarp();
                }
                bar_sync(1, 288);
                if (elect()) {
                    mbar_expect(sm + CB_W2, 81920); mbar_expect(sm + CB_W3, 3 * WO_BLK);
#pragma unroll 1
                    for (int c = 0; c < 4; c++) tma2d(sm + C_WV + c * 20480, &mp.wv, col0, c * 160, sm + CB_W2);
#pragma unroll 1
                    for (int c = 0; c < 3; c++) tma3d(sm + C_WO + c * WO_BLK, &mp.wo, head * DH + (j + c) % 3 * 64, 7 * j, sm + CB_W3);
                }
                __syncwarp();
            } else {
                uint32_t mw = 0;
#pragma unroll 1
                for (int c = 0; c < 2; c++) {
                    mbar_wait(sm + (c ? CB_W3 : CB_W2), 0);
                    uint32_t m = 0;
                    const uint32_t end = sm + (c ? C_XR : C_WO);
#pragma unroll 1
                    for (uint32_t a = sm + c * C_WO + (w - (w > 0)) * 4096 + lane * 16; a < end; a += 3 * 4096) {
                        float4 z[8];
#pragma unroll
                        for (int i = 0; i < 8; i++) z[i] = lds128f(a + i * 512);
#pragma unroll
                        for (int i = 0; i < 8; i++) m = amax2(amax2(amax2(amax2(m, __float_as_uint(z[i].x)), __float_as_uint(z[i].y)), __float_as_uint(z[i].z)), __float_as_uint(z[i].w));
                    }
                    mw |= amax_warp(m) << (16 * c);
                }
                asm volatile("st.shared.u32 [%0], %1;" :: "r"(sm + C_KM + w * 4), "r"(mw) : "memory");
                bar_sync(3, 96);
                if (w == 0) asm volatile("st.relaxed.gpu.global.u32 [%0], %1;" :: "l"(g_flags.wmax + blk), "r"(amax2(amax2(mw, lds32(sm + C_KM + 8)), lds32(sm + C_KM + 12)) | 0x8000) : "memory");
            }
        }
        bar_sync(9, 384);
#pragma unroll
        for (int i = 0; i < 5; i++) {
            asm volatile("st.shared.v4.u32 [%0], {%1,%2,%3,%4};" :: "r"(sm + C_MEM + (tid - 256 + i * 128) * 16), "r"(m0[i][0]), "r"(m0[i][1]), "r"(m0[i][2]), "r"(m0[i][3]) : "memory");
            mm = amax2(amax2(amax2(amax2(mm, m0[i][0]), m0[i][1]), m0[i][2]), m0[i][3]);
        }
        asm volatile("st.shared.u32 [%0], %1; st.shared.u32 [%2], 0x3f800000;" :: "r"(sm + C_MX + w * 4), "r"(amax_warp(mm)), "r"(sm + C_UN) : "memory");
        int ew = __shfl_sync(0xffffffffu, lds32(sm + C_LAG), 0), es = 0;
        const uint32_t rb1 = (uint32_t)((j + 1) % 3 - j) << 24, rb2 = (uint32_t)((j + 2) % 3 - j) << 24;
        const float scale = 0.07216878364870322f;
        uint32_t va[8][4], mr = memrd;
#pragma unroll
        for (int i = 0; i < 8; i++) ldsm4t(va[i], sm + C_WV + ((mi >> 1) * 8 + r) * 128 + (((2 * w + (mi & 1)) ^ r) << 4) + i * 2048);
        bar_sync(1, 384);
        if (w == 0) {
            w_flag_wait(&g_flags.v[head], 2);
            if (elect()) { mbar_expect(sm + CB_VX, 4096); bulk_g2s(sm + C_VX, g_att + head * AT_REC + AT_V + j * 4096, 4096, sm + CB_VX); }
        }
        for (int s = 0; s < NSEG; s++) {
            const float un = __uint_as_float((127 - es) << 23);
            if (w == 1) {
                mbar_wait(sm + CB_XD, s & 1);
                if (s + 1 < NSEG) { if (elect()) x_fill(mp, sm, s + 1, j); }
                else { if (BPOS != 2) wo_half(mp, sm, blk, 0); if (BPOS != 0) wo_half(mp, sm, blk, 1); }
            }
            if (STL == 2 && w == 3) asm volatile(ELECTED("st.relaxed.gpu.global.u32 [%0], %1;") :: "l"(g_stamp + (s & 3) * 384 + (blk >> 3) * 32 + (blk & 7)), "r"((gtime() & ~31u) | ((s >> 2) + 1)) : "memory");
            const uint32_t l0 = mr >> 4 & 31, r0 = l0 & 7, m0 = l0 >> 3;
            float vd[4];
            {
                uint32_t c[4][4];
#pragma unroll
                for (int i = 0; i < 4; i++) ldsm4t(c[i], mr + i * 512);
                float d[2][4] = {{0, 0, 0, 0}, {0, 0, 0, 0}};
#pragma unroll
                for (int i = 0; i < 8; i++) mma16q(d[i & 1], va[i], c[i >> 1][2 * (i & 1)], c[i >> 1][2 * (i & 1) + 1]);
#pragma unroll
                for (int i = 0; i < 4; i++) vd[i] = d[0][i] + d[1][i];
            }
            uint32_t zr = 0;
            if (w == 2)
                asm volatile("atom.relaxed.gpu.global.exch.b32 %0, [%1], 0;" : "=r"(zr)
                    : "l"(g_acc + ((s & 2) ^ 2) * (ACC_PAIR / 2) + (s & 1) * 512 + (blk >> 2) * 1024 + (blk & 3) * 128 + l0 * 4) : "memory");
            __syncwarp();
            uint32_t kb[4][4] = {};
            {
                const uint32_t k7 = r0 ^ (m0 << 2 & 4), kxrd = sm + C_KX + (16 * (w & 1) + 8 * (m0 & 1) + k7) * 128 + (((m0 >> 1) ^ k7) << 4);
#pragma unroll
                for (int i = 0; i < 4; i++) if (w >= 2) ldsm4(kb[i], kxrd ^ (i << 5));
            }
            const uint32_t qrd = sm + C_QM + (w == 1 ? (m0 & 1) * 2 + (m0 >> 1) : m0) * 128 + r0 * 16;
            const uint32_t scdst = sm + C_SC + j * 1280 + (w == 1 ? 1024 + l0 * 8 : (w & 1) * 512 + (l0 & 2) * 128 + (l0 >> 2) * 32 + (l0 & 1) * 16);
            const uint32_t scrd = sm + C_SC + (l0 >> 4) * 256 + (l0 & 3) * 32 + (l0 >> 2 & 3) * 8;
            const uint32_t v7 = (4 * (m0 & 1) + (r0 >> 1)) ^ (r0 << 2 & 4), vxrd = sm + C_VX + (16 * (m0 >> 1) + 8 * (r0 & 1) + v7) * 128 + (((2 * w) ^ v7) << 4);
            if (s == 0) {
                uint32_t t[3];
                for (int n = 0;; n++) {
#pragma unroll
                    for (int i = 0; i < 3; i++) t[i] = ld_rlx(g_flags.wmax + l0 + 32 * i);
                    if (__all_sync(0xffffffffu, t[0] && t[1] && t[2])) break;
                    cut(n, 1 << 22);
                }
                const uint32_t m = amax2(amax2(amax2(0, t[0]), t[1]), t[2]);
                const int e = 371 - (int)(__reduce_max_sync(0xffffffffu, m & 0xffffu) >> 7) - (int)(__reduce_max_sync(0xffffffffu, m >> 16) >> 7);
                ew = e << 16 | (min(e - ew, 100) & 0xffff);
            }
            mbar_wait(sm + CB_VX, s & 1);
            uint32_t vb[2][4];
            ldsm4t(vb[0], vxrd); ldsm4t(vb[1], vxrd ^ 16);
            const uint32_t word = sm + C_WO + (m0 & 1) * 4096 + ((m0 >> 1) * 8 + r0) * 64 + ((w ^ (r0 >> 1)) << 4);
            const uint32_t word6 = word + 6 * 4096 - (m0 & 1) * 3072;
            const uint32_t oxrd = sm + C_OX + l0 * 8;
            const uint32_t ord = oxrd + w * 256;
            const uint32_t vp = mr - (C_MEM - C_VP) + w * 512, vmst = mr + (C_VM - C_MEM) + w * 256;
            pin(mr, scdst + rb1, sm + CB_SC + rb1, scdst + rb2, sm + CB_SC + rb2); pin(mr, qrd, scdst, scrd, vp); pin(mr, word, word6, oxrd, ord);
            pin(mr, __float_as_uint(vd[0]), __float_as_uint(vd[1]), __float_as_uint(vd[2]), __float_as_uint(vd[3]));
            bar_sync(2, 384);
            const bool odd = mr & 16;
            float4 y0, y1, mx4;
            if (s + 1 == NSEG) {
                y0 = lds128f(vp); y1 = lds128f(vp + 2048);
                stsm2t(vmst, pack2((vd[0] + y0.x + y1.x) * un, (vd[1] + y0.y + y1.y) * un), pack2((vd[2] + y0.z + y1.z) * un, (vd[3] + y0.w + y1.w) * un));
                PROXY_FENCE();
                bar_sync(3, 128);
                if (w == 1) { w_bulk_s2g(g_att + (s * NH + head) * AT_REC + AT_VM + j * 1024, sm + C_VM, 1024); BULK_COMMIT(); BULK_WAIT(); }
                break;
            }
            {
                uint32_t qa[2][4];
                ldsm4(qa[0], qrd); ldsm4(qa[1], qrd + 512);
                float sc[2][4] = {{0, 0, 0, 0}, {0, 0, 0, 0}};
                if (w == 1) {
                    ldsm4(kb[0], mr + (C_KM - C_MEM)); ldsm4(kb[1], mr + (C_KM - C_MEM) + 512);
                    pin0(mr); y0 = lds128f(vp); y1 = lds128f(vp + 2048); mx4 = lds128f(sm + C_MX);
#pragma unroll
                    for (int k = 0; k < 4; k++) mma16q(sc[k & 1], qa[k >> 1], kb[k >> 1][2 * (k & 1)], kb[k >> 1][2 * (k & 1) + 1]);
                    const uint32_t a0 = __float_as_uint(sc[0][0] + sc[1][2]), a1 = __float_as_uint(sc[0][1] + sc[1][3]);
                    if (B7E) { pin(mr, a0, a1, __float_as_uint(y1.x), 0); bar_arrive(7, 384); }
                    send8(scdst + rb1, sm + CB_SC + rb1, a0, a1); send8(scdst + rb2, sm + CB_SC + rb2, a0, a1);
                    asm volatile("st.shared.v2.u32 [%0], {%1,%2};" :: "r"(scdst), "r"(a0), "r"(a1) : "memory");
                } else {
                    pin0(mr); y0 = lds128f(vp); y1 = lds128f(vp + 2048); mx4 = lds128f(sm + C_MX);
                    if (!w) {
                        if (B7E) { pin(mr, __float_as_uint(y1.x), 0, 0, 0); bar_arrive(7, 384); }
                        if (STL == 1) asm volatile(ELECTED("st.relaxed.gpu.global.u32 [%0], %1;") :: "l"(g_stamp + (s & 3) * 384 + (blk >> 3) * 32 + (blk & 7)), "r"((gtime() & ~31u) | ((s >> 2) + 1)) : "memory");
                    } else {
#pragma unroll
                        for (int k = 0; k < 4; k++) mma16q(sc[k & 1], kb[k], qa[k >> 1][2 * (k & 1)], qa[k >> 1][2 * (k & 1) + 1]);
                        const float a0 = sc[0][0] + sc[1][0], a1 = sc[0][2] + sc[1][2], a2 = sc[0][1] + sc[1][1], a3 = sc[0][3] + sc[1][3];
                        if (B7E) { pin(mr, __float_as_uint(a0), __float_as_uint(y1.x), 0, 0); bar_arrive(7, 384); }
                        send16(scdst + rb1, sm + CB_SC + rb1, a0, a1, a2, a3); send16(scdst + rb2, sm + CB_SC + rb2, a0, a1, a2, a3);
                        sts128f(scdst, a0, a1, a2, a3);
                    }
                }
            }
            if (!B7E) bar_arrive(7, 384);
            __syncwarp();
            if (elect()) mbar_arrive(sm + CB_SC);
            {
                const float4 z = mx4;
                const int em = (int)(max(max(__float_as_uint(z.x), __float_as_uint(z.y)), max(__float_as_uint(z.z), __float_as_uint(z.w))) >> 7) - es;
                es = __shfl_sync(0xffffffffu, max(min((ew >> 16) - em, (int)(short)ew), -120), 0);
            }
            if (w == 0) PROF(4);
            const uint32_t vm0 = pack2((vd[0] + y0.x + y1.x) * un, (vd[1] + y0.y + y1.y) * un), vm1 = pack2((vd[2] + y0.z + y1.z) * un, (vd[3] + y0.w + y1.w) * un);
            stsm2t(vmst, vm0, vm1);
            cut(s + ar.D2, 0);
            mbar_wait(sm + CB_SC, s & 1);
            if (w == 0) PROF(8);
            float sv[10];
            {
                float2 z[5][3];
#pragma unroll
                for (int u = 0; u < 5; u++)
#pragma unroll
                    for (int p = 0; p < 3; p++) z[u][p] = lds64f((u < 4 ? scrd + (u >> 1) * 512 + (u & 1) * 128 : oxrd + (C_SC - C_OX) + 1024) + p * 1280);
#pragma unroll
                for (int u = 0; u < 5; u++) { sv[2 * u] = (z[u][0].x + z[u][1].x) + z[u][2].x; sv[2 * u + 1] = (z[u][0].y + z[u][1].y) + z[u][2].y; }
            }
            float mx = fmaxf(fmaxf(fmaxf(sv[0], sv[1]), fmaxf(sv[2], sv[3])), fmaxf(fmaxf(fmaxf(sv[4], sv[5]), fmaxf(sv[6], sv[7])), fmaxf(sv[8], sv[9])));
            uint32_t a[NRING][4];
            auto frag = [&](int i) { const int p = i / 7, u = i % 7, o = (p >> 1) * WO_BLK + (p & 1) * 2048;
                                     return u == 3 ? word6 + o : word + o + (u > 3 ? 1024 + (u - 4) * 8192 : u * 8192); };
            mx = fmaxf(fmaxf(mx, __shfl_xor_sync(0xffffffffu, mx, 1)), fmaxf(__shfl_xor_sync(0xffffffffu, mx, 2), __shfl_xor_sync(0xffffffffu, mx, 3)));
            pin(mr, __float_as_uint(mx), 0, 0, 0);
            {
#pragma unroll
                for (int i = 0; i < NPRE; i++) ldsm4t(a[i], frag(i));
                pin0(mr);
                const float sl2e = scale * 1.4426950408889634f, mxl = mx * sl2e;
#pragma unroll
                for (int i = 9; i >= 0; i--) asm volatile("ex2.approx.ftz.f32 %0, %1;" : "=f"(sv[i]) : "f"(fmaf(sv[i], sl2e, -mxl)));
                const uint32_t pq[4] = {pack2(sv[0], sv[1]), pack2(sv[4], sv[5]), pack2(sv[2], sv[3]), pack2(sv[6], sv[7])}, pm = pack2(sv[8], sv[9]);
                if (w == 0) PROF(6);
                float o[2][4] = {{0, 0, 0, 0}, {0, 0, 0, 0}}, o2[2][4] = {{0, 0, 0, 0}, {0, 0, 0, 0}}, sx[4] = {0, 0, 0, 0};
                mma8(sx, pm, 0, 0x3f803f80u); mma8(o[0], pm, 0, vm0); mma8(o[1], pm, 0, vm1);
                mma16q(sx, pq, 0x3f803f80u, 0x3f803f80u);
#pragma unroll
                for (int u = 0; u < 2; u++) { mma16q(o[u], pq, vb[u][0], vb[u][1]); mma16q(o2[u], pq, vb[u][2], vb[u][3]); }
                float inv; asm("rcp.approx.ftz.f32 %0, %1;" : "=f"(inv) : "f"((sx[0] + sx[2]) * __uint_as_float((127 - es) << 23)));
                const uint32_t f0 = pack2((o[0][0] + o2[0][2]) * inv, (o[0][1] + o2[0][3]) * inv), f1 = pack2((o[1][0] + o2[1][2]) * inv, (o[1][1] + o2[1][3]) * inv);
                send8(ord + 2048 + rb1, sm + CB_OX + rb1, f0, f1); send8(ord + 1024 + rb2, sm + CB_OX + rb2, f0, f1);
                asm volatile("st.shared.v2.u32 [%0], {%1,%2};" :: "r"(ord), "r"(f0), "r"(f1) : "memory");
            }
            if (w == 0) PROF(10);
#pragma unroll
            for (int i = NPRE; i < NRING; i++) ldsm4t(a[i], frag(i));
            bar_sync(3, 128);
            float e[5][4];
#pragma unroll
            for (int q = 0; q < 5; q++) e[q][0] = e[q][1] = e[q][2] = e[q][3] = 0.f;
            constexpr int LAG = 2;
            uint8_t* pdst = g_acc + ((s & 2) * (ACC_PAIR / 2) + (s & 1) * 512 + w * 2048 + j * 8192 - C_MEM - sm + mr);
#pragma unroll
            for (int h = 0; h < 3; h++) {
                uint32_t ob[4][2];
                if (h == 1) {
#pragma unroll
                    for (int i = 14 - LAG; i < 14; i++) ldsm4t(a[i % NRING], frag(i + NRING));
                    pin(mr, zr, (uint32_t)(uint64_t)pdst, (uint32_t)((uint64_t)pdst >> 32), 0);
                    mbar_wait(sm + CB_OX, s & 1);
                    if (w == 0) PROF(9);
                }
#pragma unroll
                for (int k = 0; k < 4; k++) lds64(ob[k], oxrd + h * 1024 + k * 256);
#pragma unroll
                for (int i = 14 * h; i < 14 * h + 14; i++) {
                    const int u = i % 7, k = 2 * (i / 7 & 1);
                    if (u == 3) { mma16q(e[3], a[i % NRING], ob[k][0], ob[k][1]); mma16q(e[4], a[i % NRING], ob[k + 1][0], ob[k + 1][1]); }
                    else mma16q(e[u & 3], a[i % NRING], ob[k + (u >> 2)][0], ob[k + (u >> 2)][1]);
                    if (i == B5AT) { pin(mr, a[i % NRING][0], a[i % NRING][1], a[i % NRING][2], a[i % NRING][3]); bar_arrive(5, 384); }
                    if (i >= LAG && !(i >= 14 && i < 14 + LAG) && i - LAG + NRING < 42) ldsm4t(a[(i - LAG) % NRING], frag(i - LAG + NRING));
                }
            }
            {
                const uint32_t w6 = pack2h(e[3][0] + e[4][2], e[3][1] + e[4][3]), one = 0x3c003c00u;
                asm volatile("red.relaxed.gpu.global.add.noftz.v4.f16x2 [%0], {%1,%2,%3,%4};"
                    :: "l"(pdst), "r"(pack2h(e[0][0], e[0][1])), "r"(pack2h(e[0][2], e[0][3])), "r"(pack2h(e[1][0], e[1][1])), "r"(odd ? w6 : one) : "memory");
                asm volatile("red.relaxed.gpu.global.add.noftz.v4.f16x2 [%0], {%1,%2,%3,%4};"
                    :: "l"(pdst + 1024), "r"(pack2h(e[1][2], e[1][3])), "r"(pack2h(e[2][0], e[2][1])), "r"(pack2h(e[2][2], e[2][3])), "r"(odd ? one : w6) : "memory");
            }
            const uint32_t tw = clock();
            if (w == 0) { PROF(14); PROFG(25); }
            PROXY_FENCE();
            bar_sync(6, 160);
            mr = opaque(mr);
            const uint32_t ln = mr >> 4 & 31, due = tw + lds32(sm + C_LAG);
            const uint32_t vr = sm + C_WV + ((ln >> 4) * 8 + (ln & 7)) * 128 + (((2 * w + (ln >> 3 & 1)) ^ (ln & 7)) << 4);
            const uint32_t ms0 = sm + C_MEM + w * 128 + (ln & 7) * 16 + (ln >> 3) * 512, ms1 = ms0 + (ln < 24 ? 2048 : 1536);
            if (BPOS == 2 && w == 0 && s + 2 == NSEG) wo_half(mp, sm, blk, 0);
            if (w == 2) { w_expect(sm + CB_SC, 2560); w_expect(sm + CB_OX, 2048); asm volatile("st.shared.u32 [%0], %1;" :: "r"(sm + C_UN), "r"((127 - es) << 23) : "memory"); }
            if (w == 0) { w_bulk_s2g(g_att + (s * NH + head) * AT_REC + AT_VM + j * 1024, sm + C_VM, 1024); BULK_COMMIT(); }
            const uint8_t* src = pdst - j * 8192;
            pin(mr, ms0, ms1, (uint32_t)(uint64_t)src, (uint32_t)((uint64_t)src >> 32));
            pin(mr, vr, due, 0, 0);
            cut(s + ar.D2, 1);
#pragma unroll
            for (int i = 0; i < 8; i++) ldsm4t(va[i], vr + i * 2048);
            wait_until(due);
            if (w == 0) { PROF(5); PROFG(26); }
            uint4 v[6];
            auto fetch = [&]() {
#pragma unroll
                for (int k = 0; k < 6; k++)
                    asm volatile("ld.relaxed.gpu.global.v4.u32 {%0,%1,%2,%3}, [%4];" : "=r"(v[k].x), "=r"(v[k].y), "=r"(v[k].z), "=r"(v[k].w) : "l"(src + (k >> 1) * 8192 + (k & 1) * 1024) : "memory");
            };
            fetch();
            PROFV(20 + w, 0);
            bar_sync(9, 384);
            uint32_t cv[3][7];
#pragma unroll 1
            for (int n = 0; __any_sync(0xffffffffu, ~((odd ? v[1].w & v[3].w & v[5].w : v[0].w & v[2].w & v[4].w)) & 0x50005000u); n++) {
                PROFV(20 + w, n + 1);
                cut(n, SPIN_LIMIT);
                uint32_t miss = 0;
#pragma unroll
                for (int k = 0; k < 3; k++) miss |= (~(odd ? v[2 * k + 1].w : v[2 * k].w) & 0x50005000u) ? (odd ? 2u : 1u) << (2 * k) : 0u;
                miss |= __shfl_xor_sync(0xffffffffu, miss, 1);
#pragma unroll
                for (int k = 0; k < 6; k++)
                    asm volatile("{ .reg .pred q; setp.ne.u32 q, %5, 0; @q ld.relaxed.gpu.global.v4.u32 {%0,%1,%2,%3}, [%4]; }" : "+r"(v[k].x), "+r"(v[k].y), "+r"(v[k].z), "+r"(v[k].w)
                        : "l"(src + (k >> 1) * 8192 + (k & 1) * 1024), "r"(miss & (1u << k)) : "memory");
            }
#pragma unroll
            for (int k = 0; k < 3; k++) {
                const uint4 x = v[2 * k], y = v[2 * k + 1];
                const uint32_t u[7] = {x.x, x.y, x.z, y.x, y.y, y.z, k < 2 ? (odd ? x.w : y.w) : 0u};
#pragma unroll
                for (int i = 0; i < 7; i++) cv[k][i] = f16_to_bf16(u[i]);
                stsm4(ms0 + k * 3584, cv[k][0], cv[k][1], cv[k][2], cv[k][3]);
                if (k < 2) stsm4(ms1 + k * 3584, cv[k][4], cv[k][5], cv[k][6], cv[k][6]);
                else asm volatile("stmatrix.sync.aligned.m8n8.x2.shared.b16 [%0], {%1,%2};" :: "r"(ms1 + k * 3584), "r"(cv[k][4]), "r"(cv[k][5]) : "memory");
            }
            if (w == 0) PROF(16);
            bar_sync(1, 384);
            if (w == 0) BULK_WAIT();
            cut(s + ar.D2, 2);
            uint32_t mc = 0;
#pragma unroll
            for (int i = 0; i < 20; i++) mc = amax2(mc, cv[i / 7][i % 7]);
            asm volatile("st.shared.u32 [%0], %1;" :: "r"(sm + C_MX + w * 4), "r"(amax_warp(mc)) : "memory");
        }
        if (w >= 2) end_loads(mp, ar, sm, blk, w - 2);
        else if (w == 1) { bar_sync(5, 384); seg_done(NSEG - 1, head); EPT(true, 9); if (EORD) bar_arrive(6, 96); if (BPOS == 0) wo_half(mp, sm, blk, 1); }
        else bar_arrive(5, 384);
        if (w < 2) end_stores(mp, sm, blk, w);
        if (w == 0) { mbar_wait(sm + EB_REL, 0); flags_release(mr >> 4 & 31); }
    }
}

struct SideMaps { CUtensorMap h, wv, ost, o, wo, slab, lnp[3]; };
constexpr int SD_ST = 14336, SD_NST = 12, SD_EPI = SD_NST * SD_ST, SD_PAR = SD_EPI + 2 * 24576, SD_BAR = SD_PAR + 6400, SD_SMEM = SD_BAR + 1024;
#define VLEAD 16
#define EARLY15 1
#define N_LIGHT 9
#define B_HELP 13
#define AUNR_ 2
constexpr int AUNR = AUNR_;
#define VKS 4
#define ADEF 1
#define SGP 400
#define SG0 0
#define KSO 4
#define KSA 3
#define B_8 10
#define B_16 13
__device__ __forceinline__ int o_shift(int b) { return b >= B_16 ? 4 : b >= B_8 ? 3 : 2; }
__device__ __forceinline__ int o_split(int b) { return 1 << o_shift(b); }
__device__ __forceinline__ uint32_t o_done(int b) { return b >= B_LATE ? 160 : 4 << o_shift(b); }
__device__ __forceinline__ int next_item(int lane) {
    const int b0 = lane & 15, hi = lane >> 4;
    for (int n = 0;; n++) {
        const uint32_t w0 = ld_rlx(g_flags.qk + lane), w1 = ld_rlx(g_flags.at + lane), w2 = ld_rlx(&g_flags.c[0][0] + lane), w3 = ld_rlx(&g_flags.c[2][0] + lane), w4 = ld_rlx(&g_flags.seg[32]);
        const uint32_t o01 = __ballot_sync(0xffffffffu, lane && w2 < 32), o23 = __ballot_sync(0xffffffffu, b0 < (hi ? 14 : B_LATE) && w3 < 2u * o_split(b0));
        uint32_t ra = __ballot_sync(0xffffffffu, w0 >= (hi ? 64u : 96u));
        const uint32_t rb = __ballot_sync(0xffffffffu, w1 >= (hi ? o_done(b0) : 64u));
        const int bv = __ffs(o01 | 0x10000) - 1, ba = __ffs(o01 >> 16 | 0x10000) - 1, bo = __ffs(o23 | 0x10000) - 1, bl = __ffs(o23 >> 16 | 0x10000) - 1;
        if (bl == 16 && ba == 16) return -1;
        const int bc = __ffs(~ra | 0x10000) - 1;
        const bool last = ba == 15 && (w4 >= 3 || (EARLY15 && bc == 15));
        const bool r1 = (ra & ra >> 16) >> ba & 1, r2 = (rb & 0xffff) >> bo & 1, r3 = rb >> 16 >> bl & 1;
        const int kind = ba == 16 ? (bo < 16 ? 2 : 3) : last ? 1 :
                         blockIdx.x < N_LIGHT ? (r1 ? 1 : r3 ? 3 : bv < 16 ? 0 : -1) :
                         bv < 16 && (bv <= bc + VLEAD || !r2) ? 0 : r1 && ba >= B_HELP ? 1 : r2 ? 2 : r1 ? 1 : r3 ? 3 : bo < ba ? 2 : -1;
        if (kind < 0) { if (n > (1 << 20)) __trap(); __nanosleep(IDLE); continue; }
        const int b = kind == 3 ? bl : kind == 2 ? bo : kind == 1 ? ba : bv;
        uint32_t i = 0;
        if (lane == 0) asm volatile("atom.relaxed.gpu.global.add.u32 %0, [%1], 1;" : "=r"(i) : "l"(&g_flags.c[kind][b]) : "memory");
        i = __shfl_sync(0xffffffffu, i, 0);
        if (i < (kind < 2 ? 32u : 2u * o_split(b))) return kind << 16 | b << 8 | i | ((kind == 1 ? r1 : kind == 2 ? r2 : r3) ? 128 : 0);
    }
}

template <int NP>
__device__ __forceinline__ void tile_out(const float (&acc)[8 * NP], uint32_t eb, uint32_t CH, uint32_t efull, uint32_t eempty, int& eph, int lane) {
    const int r = lane & 7, mi = lane >> 3, row = (mi & 1) * 8 + r;
    mbar_wait(eempty, eph); eph ^= 1;
#pragma unroll
    for (int p = 0; p < NP; p++) {
        const int oc = 2 * p + (mi >> 1);
        stsm4(eb + (oc >> 3) * CH + row * 128 + (((oc & 7) ^ r) << 4), pack2(acc[8 * p], acc[8 * p + 1]), pack2(acc[8 * p + 2], acc[8 * p + 3]),
              pack2(acc[8 * p + 4], acc[8 * p + 5]), pack2(acc[8 * p + 6], acc[8 * p + 7]));
    }
    asm volatile("fence.proxy.async.shared::cta;" ::: "memory");
    __syncwarp();
    if (lane == 0) mbar_arrive(efull);
}

template <int MT, typename F, typename G>
__device__ __forceinline__ void attn_tile(uint32_t base, uint32_t dst, int lane, F scores_done, G before_values) {
    constexpr int NK = MT ? 5 : 3;
    const int r = lane & 7, mi = lane >> 3, g = lane >> 2, t = lane & 3;
    float sc[NK][4];
#pragma unroll
    for (int n = 0; n < NK; n++) sc[n][0] = sc[n][1] = sc[n][2] = sc[n][3] = 0.f;
#pragma unroll AUNR
    for (int k2 = 0; k2 < 6; k2++) {
        const uint32_t cb = (k2 >> 1) * 8192, c0 = (k2 & 1) * 4;
        uint32_t a0[4], a1[4], bb[NK][4];
        ldsm4(a0, base + cb + (16 * MT + (mi & 1) * 8 + r) * 128 + (((c0 + (mi >> 1)) ^ r) << 4));
        ldsm4(a1, base + cb + (16 * MT + (mi & 1) * 8 + r) * 128 + (((c0 + 2 + (mi >> 1)) ^ r) << 4));
#pragma unroll
        for (int n = 0; n < NK; n++)
            ldsm4(bb[n], n < NK - 1 ? base + 4096 + cb + (8 * n + r) * 128 + (((c0 + mi) ^ r) << 4) : base + AT_KM + k2 * 512 + lane * 16);
#pragma unroll
        for (int n = 0; n < NK; n++) mma16(sc[n], a0[0], a0[1], a0[2], a0[3], bb[n][0], bb[n][1]);
#pragma unroll
        for (int n = 0; n < NK; n++) mma16(sc[n], a1[0], a1[1], a1[2], a1[3], bb[n][2], bb[n][3]);
    }
    scores_done();
    const float scale = 0.07216878364870322f, l2e = 1.4426950408889634f;
    float v[2][2 * NK], mx[2], sum[2];
#pragma unroll
    for (int hf = 0; hf < 2; hf++) {
        mx[hf] = -INFINITY;
#pragma unroll
        for (int n = 0; n < NK; n++) {
            uint32_t u = pack2(sc[n][2 * hf], sc[n][2 * hf + 1]);
            u = pack2(lo_f(u) * scale, hi_f(u) * scale);
            const int lim = 16 * MT + 8 * hf + g - 8 * n - 2 * t;
            v[hf][2 * n] = (n < NK - 1 && lim < 0) ? -1e9f : lo_f(u);
            v[hf][2 * n + 1] = (n < NK - 1 && lim < 1) ? -1e9f : hi_f(u);
            mx[hf] = fmaxf(mx[hf], fmaxf(v[hf][2 * n], v[hf][2 * n + 1]));
        }
    }
#pragma unroll
    for (int o = 1; o < 4; o <<= 1)
#pragma unroll
        for (int hf = 0; hf < 2; hf++) mx[hf] = fmaxf(mx[hf], __shfl_xor_sync(0xffffffffu, mx[hf], o));
#pragma unroll
    for (int hf = 0; hf < 2; hf++) {
        sum[hf] = 0;
#pragma unroll
        for (int q = 0; q < 2 * NK; q++) { asm("ex2.approx.ftz.f32 %0, %1;" : "=f"(v[hf][q]) : "f"((v[hf][q] - mx[hf]) * l2e)); sum[hf] += v[hf][q]; }
    }
#pragma unroll
    for (int o = 1; o < 4; o <<= 1)
#pragma unroll
        for (int hf = 0; hf < 2; hf++) sum[hf] += __shfl_xor_sync(0xffffffffu, sum[hf], o);
    uint32_t pa[NK][2];
#pragma unroll
    for (int hf = 0; hf < 2; hf++) {
        const float inv = __fdividef(1.f, sum[hf]);
#pragma unroll
        for (int n = 0; n < NK; n++) pa[n][hf] = pack2(v[hf][2 * n] * inv, v[hf][2 * n + 1] * inv);
    }
    before_values();
#pragma unroll AUNR
    for (int n4 = 0; n4 < 6; n4++) {
        const uint32_t cb = (n4 >> 1) * 4096, c0 = (n4 & 1) * 4;
        uint32_t bm[4], bb[2 + 2 * MT][4];
        ldsm4t(bm, base + AT_VM + n4 * 512 + lane * 16);
#pragma unroll
        for (int u = 0; u < 2 + 2 * MT; u++) ldsm4t(bb[u], base + AT_V + cb + (16 * (u >> 1) + 8 * (mi & 1) + r) * 128 + (((c0 + 2 * (u & 1) + (mi >> 1)) ^ r) << 4));
        float o[4][4];
#pragma unroll
        for (int u = 0; u < 4; u++) { o[u][0] = o[u][1] = o[u][2] = o[u][3] = 0.f; mma8(o[u], pa[NK - 1][0], pa[NK - 1][1], bm[u]); }
#pragma unroll
        for (int u = 0; u < 4 + 4 * MT; u++) mma16(o[u & 3], pa[u >> 2 << 1][0], pa[u >> 2 << 1][1], pa[(u >> 2 << 1) + 1][0], pa[(u >> 2 << 1) + 1][1], bb[u >> 1][2 * (u & 1)], bb[u >> 1][2 * (u & 1) + 1]);
#pragma unroll
        for (int p = 0; p < 2; p++)
            stsm4(dst + (n4 >> 1) * 2048 + ((mi & 1) * 8 + r) * 128 + (((c0 + 2 * p + (mi >> 1)) ^ r) << 4), pack2(o[2 * p][0], o[2 * p][1]), pack2(o[2 * p][2], o[2 * p][3]),
                  pack2(o[2 * p + 1][0], o[2 * p + 1][1]), pack2(o[2 * p + 1][2], o[2 * p + 1][3]));
    }
}

__device__ __forceinline__ uint32_t ln_row(const uint32_t (&as)[10], const uint2 (&xin)[5], int row, uint32_t par, uint32_t low, bf16* out, uint64_t ef, int lane) {
    const uint32_t pa = par + lane * 8;
    uint32_t xv[10], hv[10], sv[10], tv[10];
#pragma unroll
    for (int q = 0; q < 5; q++) {
        uint32_t ga[2], t[2], u[2];
        lds64(ga, pa + q * 256); lds64(t, pa + 1280 + q * 256); lds64(u, pa + 2560 + q * 256);
#pragma unroll
        for (int e = 0; e < 2; e++) {
            xv[2 * q + e] = add2(e ? xin[q].y : xin[q].x, mul2(ga[e], as[2 * q + e]));
            tv[2 * q + e] = t[e]; sv[2 * q + e] = u[e];
        }
    }
    ln_mod(xv, sv, tv, hv);
    float rs = 0;
#pragma unroll
    for (int q = 0; q < 5; q++) {
        const int c = row * DM + lane * 4 + q * 128;
        const uint32_t h0 = hv[2 * q], h1 = hv[2 * q + 1];
        uint32_t gb[2], wv[2];
        lds64(gb, pa + 3840 + q * 256); lds64(wv, pa + 5120 + q * 256);
        rs += (lo_f(h0) * lo_f(wv[0]) + hi_f(h0) * hi_f(wv[0])) + (lo_f(h1) * lo_f(wv[1]) + hi_f(h1) * hi_f(wv[1]));
        st_ef(out + c, make_uint2(add2(xv[2 * q], mul2(gb[0], h0)), add2(xv[2 * q + 1], mul2(gb[1], h1))), ef);
    }
    const uint32_t rb = pack2(0.f, warp_sum(rs));
    const uint32_t key = (((int)rb < 0 ? ~rb : rb | 0x80000000u) & 0xffff0000u) | (uint32_t)(4 * S_TOK - 1 - row);
    if (key < low) return key ^ (2 * S_TOK);
    {
#pragma unroll
        for (int q = 0; q < 5; q++) {
            *(uint2*)(g_x1 + row * DM + lane * 4 + q * 128) = make_uint2(xv[2 * q], xv[2 * q + 1]);
            *(uint2*)(g_h2 + row * DM + lane * 4 + q * 128) = make_uint2(hv[2 * q], hv[2 * q + 1]);
        }
    }
    return key;
}
__device__ __forceinline__ void key_out(uint32_t key) {
    __syncwarp();
    if (key) asm volatile("st.release.gpu.global.u32 [%0], %1;" :: "l"(g_key + (~key & (S_TOK - 1))), "r"(key) : "memory");
}

__global__ void __launch_bounds__(384, 1) k_side(const __grid_constant__ SideMaps mp, const bf16* __restrict__ x, const bf16* __restrict__ wr, const bf16* wmod, const bf16* cvec, bf16* __restrict__ out) {
    extern __shared__ __align__(1024) uint8_t smraw[];
    const uint32_t sm = smem_u32(smraw);
    if (sm & 1023) __trap();
    const uint32_t BARS = sm + SD_BAR, FULL = BARS + 768, EMPTY = FULL + 96, EFULL = BARS + 64, EEMPTY = BARS + 80, IFULL = BARS + 96, IEMPTY = BARS + 128, IQ = BARS + 160, SCHED = BARS + 176, PARAM = BARS + 184, ADONE = BARS + 192, LOW = BARS + 224, KEYS = BARS + 256;
    const int tid = threadIdx.x, warp = __shfl_sync(0xffffffffu, tid >> 5, 0), lane = tid & 31;
    const uint64_t ef = policy_stream();
    if (tid == 0) {
#pragma unroll 1
        for (int i = 0; i < SD_NST; i++) { mbar_init(FULL + 8 * i, 1); mbar_init(EMPTY + 8 * i, 2); }
        for (int i = 0; i < 2; i++) { mbar_init(EFULL + 8 * i, 4); mbar_init(EEMPTY + 8 * i, 1); }
        for (int i = 0; i < 4; i++) { mbar_init(IFULL + 8 * i, 1); mbar_init(IEMPTY + 8 * i, 11); }
        mbar_init(SCHED, 1); mbar_init(PARAM, 1);
        sts128f(ADONE, 0, 0, 0, 0); sts128f(ADONE + 16, 0, 0, 0, 0); sts128f(LOW, 0, 0, 0, 0);
        asm volatile("fence.mbarrier_init.release.cluster;" ::: "memory");
    }
    if (SDEL) __nanosleep(SDEL);
    __syncthreads();
    if (warp >= 8) {
      asm volatile("setmaxnreg.dec.sync.aligned.u32 40;");
      if (warp == 8) {
        int st = 0, ph = 1;
        bool patt = false;
        for (int q = 0;; q++) {
            mbar_wait(IFULL + 8 * (q & 3), (q >> 2) & 1);
            const int it = __shfl_sync(0xffffffffu, lds32(IQ + 4 * (q & 3)), 0);
            if (elect()) mbar_arrive(IEMPTY + 8 * (q & 3));
            if (it < 0) break;
            const int kind = it >> 16, b = (it >> 8) & 255, i = it & 63;
            const int nst = kind == 0 ? 10 : kind == 1 ? 4 : kind == 2 ? 192 >> o_shift(b) : b == 14 ? 4 : 2;
            const int ksched = kind == 0 ? 4 : kind == 2 ? nst - KSO : (it & 128) ? -1 : kind == 1 ? KSA : 0;
            if (ksched < 0 && elect()) mbar_arrive(SCHED);
            const bool look = !(it & 128);
            const int nu = kind == 2 ? 2 : 3;
            if (look && kind == 1) flag_wait(&g_flags.v[b * 32 + i], 2);
            if (look && kind == 3 && b < 14) flag_wait(&g_flags.o[b], o_done(b));
            if (kind == 1) {
#pragma unroll 1
                for (int u = 0; u < 8; u++) {
                    const int sec = look ? u & 1 : 0xd4 >> u & 1, sg = look ? u >> 1 : 0xed84 >> 2 * u & 3;
                    int p = st + 3 * sg, pp = ph; if (p >= SD_NST) { p -= SD_NST; pp ^= 1; }
                    if (sec || !patt) mbar_wait(EMPTY + 8 * p + 8, pp);
                    mbar_wait(EMPTY + 8 * p + 16 * sec, pp);
                    if (look && !sec) { flag_wait(&g_flags.seg[max(sg, 1) * 32 + i], 3); if (sg == ksched && elect()) mbar_arrive(SCHED); }
                    if (elect()) {
                        const uint32_t fb = FULL + 8 * p + 16 * sec, off = sec ? AT_VM : 0, n = sec ? AT_REC - AT_VM : AT_VM;
                        if (sec) mbar_arrive(fb - 8);
                        mbar_expect(fb, n);
                        asm volatile("cp.async.bulk.shared::cluster.global.mbarrier::complete_tx::bytes.L2::cache_hint [%0], [%1], %2, [%3], %4;"
                            :: "r"(sm + p * SD_ST + off), "l"(g_att + ((b * 4 + sg) * NH + i) * AT_REC + off), "r"(n), "r"(fb), "l"(ef) : "memory");
                    }
                    __syncwarp();
                }
                ph ^= 1; patt = true;
                continue;
            }
            patt = false;
            for (int kb = 0; kb < nst; kb++) {
                if (kb < 6) mbar_wait(EMPTY + 8 * st, ph);
                mbar_wait(EMPTY + 8 * (st + nu - 1), ph);
                const uint32_t base = sm + st * SD_ST, fb = FULL + 8 * st;
                if (lane && lane < nu) mbar_arrive(fb + 8 * lane);
                if (kb == ksched && elect()) mbar_arrive(SCHED);
                if (kind == 0) {
                    if (q == 0 && kb == 0) {
                        if (elect()) {
#pragma unroll 1
                            for (int c = 0; c < 4; c++) tma3d(sm + 3 * c * SD_ST + 16384, &mp.wv, c * 64, i * 3, FULL + 24 * c);
                        }
                        flag_wait(&g_flags.h, 96);
                    }
                    if (elect()) { mbar_expect(fb, 40960); tma2d(base, &mp.h, kb * 64, b * 128, fb); }
                    __syncwarp();
                    if ((q || kb >= 4) && elect()) tma3d(base + 16384, &mp.wv, kb * 64, i * 3, fb);
                } else if (kind == 3) {
                    if (b == 14 && !(kb & 1)) flag_wait(&g_flags.fin[(kb + (i >> 4)) * 32], 80);
                    if (elect()) { mbar_expect(fb, 40960); tma3d_ef(base, &mp.lnp[o_shift(b) - 2], i * (160 >> o_shift(b)), b * KSPLIT + (kb << o_shift(b) >> 1), fb, ef); }
                } else {
                    const int k0 = ((i >> 1) * nst + kb) * 32;
                    if (elect()) { mbar_expect(fb, 28672); tma3d(base + 8192, &mp.wo, k0, (i & 1) * 5, fb); }
                    __syncwarp();
                    if (look && kb % 12 == 0) flag_wait(&g_flags.pair[b * 16 + k0 / 384], 4);
                    if (elect()) tma2d_ef(base, &mp.o, k0, b * 128, fb, ef);
                }
                __syncwarp();
                st += nu; if (st == SD_NST) { st = 0; ph ^= 1; }
            }
        }
      } else if (warp == 11) {
        bool fin = false, par = false;
        for (int q = 0;; q++) {
            if (q) mbar_wait(SCHED, (q - 1) & 1);
            int it = fin ? -1 : q == 0 && blockIdx.x < 32 ? (int)blockIdx.x : next_item(lane);
            if (it < 0 && !fin && blockIdx.x < 32) { it = 3 << 16 | 14 << 8 | blockIdx.x; fin = true; }
            if (lane == 0) {
                if (it >> 16 == 3) {
                    const int b = (it >> 8) & 255, nr = 64 >> o_shift(b);
                    asm volatile("cp.async.bulk.prefetch.L2.global [%0], %1;" :: "l"(x + (b * 128 + (it & 63) * nr) * DM), "r"(nr * DM * 2) : "memory");
                }
                mbar_wait(IEMPTY + 8 * (q & 3), ((q >> 2) & 1) ^ 1);
                asm volatile("st.shared.u32 [%0], %1;" :: "r"(IQ + 4 * (q & 3)), "r"(it) : "memory");
                mbar_arrive(IFULL + 8 * (q & 3));
            }
            if (it >> 16 >= 2 && (it >> 8 & 255) >= 2) {
                const uint4* kp = (const uint4*)g_key + max((it >> 8 & 255) - ((it >> 16) == 2 ? 5 : 3), 0) * 32 + lane;
                const uint4 k1 = __ldcg(kp), k2 = __ldcg(kp + 32);
                uint32_t m = max(max(max(k1.x, k1.y), max(k1.z, k1.w)), max(max(k2.x, k2.y), max(k2.z, k2.w)));
                m = max(m, __shfl_xor_sync(0xffffffffu, m, 1)); m = max(m, __shfl_xor_sync(0xffffffffu, m, 2));
                asm volatile("red.shared.max.u32 [%0], %1;" :: "r"(LOW), "r"(__reduce_min_sync(0xffffffffu, m)) : "memory");
            }
            if (!par && it >> 16 == 3) {
                par = true;
                flag_wait(&g_flags.mod, 64);
                if (lane == 0) { mbar_expect(PARAM, 6400); bulk_g2s(sm + SD_PAR, g_mod + 2 * DM, 5120, PARAM); bulk_g2s(sm + SD_PAR + 5120, wr, 1280, PARAM); }
            }
            __syncwarp();
            if (it < 0) break;
        }
        flags_release(lane);
      } else {
        if (lane == 0) {
            const int wg = warp - 9; int ph = 0;
            for (int q = 0;; q++) {
                mbar_wait(IFULL + 8 * (q & 3), (q >> 2) & 1);
                const int it = lds32(IQ + 4 * (q & 3));
                mbar_arrive(IEMPTY + 8 * (q & 3));
                if (it < 0) break;
                const int kind = it >> 16, b = (it >> 8) & 255, i = it & 63;
                if (kind == 3 && b == 14) continue;
                if (kind & 1) {
                    for (int n = 0;; n++) {
                        uint32_t d0, d1, d2, d3;
                        asm volatile("ld.volatile.shared.v4.u32 {%0,%1,%2,%3}, [%4];" : "=r"(d0), "=r"(d1), "=r"(d2), "=r"(d3) : "r"(ADONE + wg * 16) : "memory");
                        if (min(min(d0, d1), min(d2, d3)) > q) break;
                        if (n > (1 << 24)) __trap();
                        __nanosleep(40);
                    }
                    GPU_FENCE();
                    EPT(kind == 1 && b == 15 && wg, 17);
                    if (kind == 1) { bump(b == 15 ? &g_flags.half[(i & 30) + wg] : &g_flags.pair[b * 16 + (i >> 1)]); bump(&g_flags.at[b]); }
                    else {
#pragma unroll 1
                        for (int c = 0; c < 8; c++) { const uint32_t key = lds32(KEYS + (q & 7) * 64 + wg * 32 + c * 4); if (key) asm volatile("st.relaxed.gpu.global.u32 [%0], %1;" :: "l"(g_key + (~key & (S_TOK - 1))), "r"(key) : "memory"); }
                    }
                    continue;
                }
#pragma unroll 1
                for (int rd = 0; rd < (kind == 2 ? 2 : 1); rd++) {
                    mbar_wait(EFULL + 8 * wg, ph); ph ^= 1;
                    const uint32_t src = sm + SD_EPI + wg * 24576;
#pragma unroll 1
                    for (int c = 0; c < (kind ? 2 + rd : 6); c++) {
                        if (c && q) __nanosleep(kind && !rd ? SG0 : kind ? 2 * SGP : SGP);
                        if (kind) tma2d_store(&mp.slab, ((i & 1) * 5 + (rd ? 0 : 3) + c) * 64, (b * KSPLIT + (i >> 1)) * 128 + wg * 64, src + c * 8192);
                        else asm volatile("cp.async.bulk.global.shared::cta.bulk_group.L2::cache_hint [%0], [%1], 4096, %2;"
                            :: "l"(g_att + ((b * 4 + wg * 2 + c / 3) * NH + i) * AT_REC + AT_V + c % 3 * 4096), "r"(src + c * 4096), "l"(ef) : "memory");
                    }
                    asm volatile("cp.async.bulk.commit_group;" ::: "memory");
                    asm volatile("cp.async.bulk.wait_group.read 0;" ::: "memory");
                    mbar_arrive(EEMPTY + 8 * wg);
                }
                asm volatile("cp.async.bulk.wait_group 0;" ::: "memory");
                GPU_FENCE();
                bump(kind == 0 ? &g_flags.v[b * 32 + i] : &g_flags.o[b]);
                if (kind == 0) bump(&g_flags.vb[b]);
            }
        }
      }
    } else {
        asm volatile("setmaxnreg.inc.sync.aligned.u32 232;");
        const int wg = warp >> 2, w = warp & 3;
        int st = 0, ph = 0, eph = 1;
        bool att = false;
        uint4 mz[4] = {}; uint2 mc = {}; float ma[8] = {0, 0, 0, 0, 0, 0, 0, 0};
        const uint32_t eb = sm + SD_EPI + wg * 24576;
        for (int q = 0;; q++) {
            mbar_wait(IFULL + 8 * (q & 3), (q >> 2) & 1);
            const int itc = __shfl_sync(0xffffffffu, lds32(IQ + 4 * (q & 3)), 0);
            __syncwarp();
            if (lane == 0) mbar_arrive(IEMPTY + 8 * (q & 3));
            if (itc < 0) break;
            const int kind = itc >> 16, b = (itc >> 8) & 255, i = itc & 63;
            if (q >= 1 && q <= 9 && blockIdx.x < 32) {
                const int t = min(tid, 199), k = t / 10 * 32 + (q - 1) * 4;
#pragma unroll
                for (int e = 0; e < 4; e++) {
                    const uint32_t cw = e & 2 ? mc.y : mc.x;
                    const float c = e & 1 ? hi_f(cw) : lo_f(cw), f = bfr(__fdividef(c, 1.f + __expf(-c)));
                    ma[0] += f * lo_f(mz[e].x); ma[1] += f * hi_f(mz[e].x); ma[2] += f * lo_f(mz[e].y); ma[3] += f * hi_f(mz[e].y);
                    ma[4] += f * lo_f(mz[e].z); ma[5] += f * hi_f(mz[e].z); ma[6] += f * lo_f(mz[e].w); ma[7] += f * hi_f(mz[e].w);
                }
                if (q < 9) {
#pragma unroll
                    for (int e = 0; e < 4; e++) mz[e] = __ldcs((const uint4*)(wmod + (k + e) * (6 * DM) + 2 * DM + blockIdx.x * 80 + t % 10 * 8));
                    mc = __ldg((const uint2*)(cvec + k));
                } else {
                    sts128f(sm + SD_PAR + t * 32, ma[0], ma[1], ma[2], ma[3]); sts128f(sm + SD_PAR + 16 + t * 32, ma[4], ma[5], ma[6], ma[7]);
                    bar_sync(1, 256);
                    if (tid < 40) {
                        float a0 = 0, a1 = 0;
#pragma unroll 4
                        for (int g = 0; g < 20; g++) { const float2 v = lds64f(sm + SD_PAR + g * 320 + tid * 8); a0 += v.x; a1 += v.y; }
                        ((uint32_t*)(g_mod + 2 * DM + blockIdx.x * 80))[tid] = pack2(a0, a1);
                    }
                    __syncwarp();
                    if (warp < 2 && lane == 0) flag_add(&g_flags.mod);
                }
            }
            if (att && kind != 1) { bar_sync(1, 256); att = false; }
            int prev = -1;
            auto next = [&](int nu) {
                WG_COMMIT();
                WG_WAIT(1);
                if (prev >= 0 && (tid & 127) < nu) mbar_arrive(EMPTY + 8 * (prev + (tid & 127)));
                prev = st;
                st += nu; if (st == SD_NST) { st = 0; ph ^= 1; }
            };
            auto desc = [](uint32_t lo, uint32_t hi) { return (uint64_t)hi << 32 | lo; };
            if (kind == 0) {
                float acc[96];
#pragma unroll
                for (int n = 0; n < 96; n++) acc[n] = 0.f;
#pragma unroll 1
                for (int kb = 0; kb < 10; kb++) {
                    mbar_wait(FULL + 8 * st, ph);
                    const uint32_t d0 = (sm + st * SD_ST) >> 4, da = d0 + wg * 512 + 0x10000, db = d0 + 1024 + 0x2000000;
                    WG_FENCE();
#pragma unroll
                    for (int ks = 0; ks < VKS; ks++) wgmma_ss_n192_tb(acc, desc(da + ks * 2, 0x40000040), desc(db + ks * 128, 0x40000040), 1);
                    next(3);
                }
                WG_WAIT(0);
                if ((tid & 127) < 3) mbar_arrive(EMPTY + 8 * (prev + (tid & 127)));
                tile_out<12>(acc, eb + (w >> 1) * 12288 + (w & 1) * 2048, 4096, EFULL + 8 * wg, EEMPTY + 8 * wg, eph, lane);
            } else if (kind == 2) {
                float acc[96], acc2[64];
#pragma unroll
                for (int n = 0; n < 96; n++) acc[n] = 0.f;
#pragma unroll
                for (int n = 0; n < 64; n++) acc2[n] = 0.f;
                int kb = 192 >> o_shift(b);
#pragma unroll 1
                do {
                    mbar_wait(FULL + 8 * st, ph);
                    const uint32_t d0 = (sm + st * SD_ST) >> 4, da = d0 + wg * 256 + 0x10000, db = d0 + 512 + 0x1000000;
                    WG_FENCE();
#pragma unroll
                    for (int ks = 0; ks < 2; ks++) {
                        wgmma_ss_n192_tb(acc, desc(da + ks * 2, 0x80000020), desc(db + ks * 128, 0x40000040), 1);
                        wgmma_ss_n128_tb(acc2, desc(da + ks * 2, 0x80000020), desc(db + 768 + ks * 128, 0x40000040), 1);
                    }
                    next(2);
                } while (--kb);
                WG_WAIT(0);
                if ((tid & 127) < 2) mbar_arrive(EMPTY + 8 * (prev + (tid & 127)));
                tile_out<8>(acc2, eb + w * 2048, 8192, EFULL + 8 * wg, EEMPTY + 8 * wg, eph, lane);
                tile_out<12>(acc, eb + w * 2048, 8192, EFULL + 8 * wg, EEMPTY + 8 * wg, eph, lane);
            } else if (kind == 1) {
                const int seg = warp >> 1, mt = warp & 1;
                int sst = st + 3 * seg, sph = ph; if (sst >= SD_NST) { sst -= SD_NST; sph ^= 1; }
                ph ^= 1;
                mbar_wait(FULL + 8 * sst, sph);
                EPT(tid == 224 && b == 15, 16);
                const uint32_t base = sm + sst * SD_ST;
                auto f1 = [&]() { __syncwarp(); if (lane == 0) mbar_arrive(EMPTY + 8 * sst); };
                auto f2 = [&]() {
                    mbar_wait(EEMPTY + 8 * wg, eph);
                    BULK_WAIT();
                    if (lane == 0) asm volatile("st.release.cta.shared.u32 [%0], %1;" :: "r"(ADONE + warp * 4), "r"(q) : "memory");
                    mbar_wait(FULL + 8 * sst + 16, sph);
                };
                if (mt) attn_tile<1>(base, eb + w * 6144, lane, f1, f2);
                else attn_tile<0>(base, eb + w * 6144, lane, f1, f2);
                asm volatile("fence.proxy.async.shared::cta;" ::: "memory");
                __syncwarp();
                if (lane < 2) mbar_arrive(EMPTY + 8 * (sst + 1 + lane));
                if (lane == 0) {
                    tma3d_store(&mp.ost, b * 128 + warp * 16, i * 3, eb + w * 6144, ef, false);
                    BULK_COMMIT();
                    if (!ADEF || !mbar_test(IFULL + 8 * (q + 1 & 3), (q + 1 >> 2) & 1) || (lds32(IQ + 4 * (q + 1 & 3)) & 0xffff0080u) != 0x10080u) {
                        BULK_WAIT();
                        asm volatile("st.release.cta.shared.u32 [%0], %1;" :: "r"(ADONE + warp * 4), "r"(q + 1) : "memory");
                    }
                }
                __syncwarp();
                att = true;
            } else {
                const int sh = o_shift(b), nr = 64 >> sh, fw = b == 14 ? wg : 0, row0 = (b + fw) * 128 + i * nr, lw = warp - 4 * fw;
                if (fw) { ph ^= st != 0; st ^= 6; }
                uint2 xin[2][5];
                uint32_t as[2][10] = {};
#pragma unroll
                for (int q2 = 0; q2 < 10; q2++) xin[q2 & 1][q2 >> 1] = ld_ef(x + (row0 + ((warp + 8 * (q2 & 1)) & (nr - 1))) * DM + lane * 4 + (q2 >> 1) * 128, ef);
                mbar_wait(PARAM, 0); mbar_wait(FULL + 8 * st, ph); mbar_wait(FULL + 8 * st + 24, ph);
                EPT((tid & 127) == 0 && b == 14, 18 + wg);
#pragma unroll 1
                for (int lrow = lw + (nr & 16) / 2; lrow >= 0 && lrow < nr; lrow -= 8) {
                    const uint32_t one = (lane >> 3) == (lane & 3) ? 0x3f80u << (lane << 2 & 16) : 0u;
                    float a[5][4] = {};
#pragma unroll 2
                    for (int k = 0; k < (1 << sh >> 1); k++) {
                        const uint32_t ad = sm + st * SD_ST + ((k << (6 - sh)) + lrow) * 1280 + lane * 8;
#pragma unroll
                        for (int q2 = 0; q2 < 5; q2++) {
                            uint32_t z0[2], z1[2];
                            lds64(z0, ad + q2 * 256); lds64(z1, ad + 3 * SD_ST + q2 * 256);
                            mma16(a[q2], z0[0], z0[1], z1[0], z1[1], one, one);
                        }
                    }
#pragma unroll
                    for (int q2 = 0; q2 < 10; q2++) { as[1][q2] = as[0][q2]; as[0][q2] = pack2(a[q2 >> 1][2 * (q2 & 1)], a[q2 >> 1][2 * (q2 & 1) + 1]); }
                }
                bar_sync(2 + wg, 128);
                if ((tid & 127) < 6) mbar_arrive(EMPTY + 8 * (st + (tid & 127)));
                uint32_t key = 0;
#pragma unroll 1
                for (int lrow = lw; lrow < nr; lrow += 8) {
                    const int row = row0 + lrow;
                    const uint32_t k1 = ln_row(as[0], xin[0], row, sm + SD_PAR, lds32(LOW), out, ef, lane);
                    if (lane == lrow >> 3) key = k1;
#pragma unroll
                    for (int q2 = 0; q2 < 5; q2++) { as[0][2 * q2] = as[1][2 * q2]; as[0][2 * q2 + 1] = as[1][2 * q2 + 1]; xin[0][q2] = xin[1][q2]; }
                }
                if (b == 14) { EPT(tid == 128, 20); key_out(key); EPT(tid == 128, 21); }
                else {
                    if (lane < 2) asm volatile("st.shared.u32 [%0], %1;" :: "r"(KEYS + (q & 7) * 64 + warp * 8 + lane * 4), "r"(key) : "memory");
                    __syncwarp();
                    if (lane == 0) asm volatile("st.release.cta.shared.u32 [%0], %1;" :: "r"(ADONE + warp * 4), "r"(q + 1) : "memory");
                }
                ph ^= st != 0; st ^= 6;
            }
        }
    }
    __syncwarp();
    asm volatile("griddepcontrol.wait;" ::: "memory");
}

#define P_D1 500
#define P_DL 700
#define P_DG 29
typedef CUresult (*EncodeFn)(CUtensorMap*, CUtensorMapDataType, cuuint32_t, void*, const cuuint64_t*, const cuuint64_t*, const cuuint32_t*, const cuuint32_t*,
                             CUtensorMapInterleave, CUtensorMapSwizzle, CUtensorMapL2promotion, CUtensorMapFloatOOBfill);
static EncodeFn s_encode = nullptr;
static void make_map(CUtensorMap* m, const void* p, int rows, int cols, int box_rows, int box_cols = 64) {
    cuuint64_t dims[2] = {(cuuint64_t)cols, (cuuint64_t)rows}, strides[1] = {(cuuint64_t)cols * 2};
    cuuint32_t box[2] = {(cuuint32_t)box_cols, (cuuint32_t)box_rows}, es[2] = {1, 1};
    s_encode(m, CU_TENSOR_MAP_DATA_TYPE_BFLOAT16, 2, (void*)p, dims, strides, box, es, CU_TENSOR_MAP_INTERLEAVE_NONE,
             box_cols == 64 ? CU_TENSOR_MAP_SWIZZLE_128B : box_cols == 32 ? CU_TENSOR_MAP_SWIZZLE_64B : CU_TENSOR_MAP_SWIZZLE_NONE, CU_TENSOR_MAP_L2_PROMOTION_L2_256B, CU_TENSOR_MAP_FLOAT_OOB_FILL_NONE);
}
static void make_map3(CUtensorMap* m, const void* p, int rows, int cols, int box_rows, int box_chunks, int cw = 64) {
    cuuint64_t dims[3] = {(cuuint64_t)cw, (cuuint64_t)rows, (cuuint64_t)(cols / cw)}, strides[2] = {(cuuint64_t)cols * 2, (cuuint64_t)cw * 2};
    cuuint32_t box[3] = {(cuuint32_t)cw, (cuuint32_t)box_rows, (cuuint32_t)box_chunks}, es[3] = {1, 1, 1};
    s_encode(m, CU_TENSOR_MAP_DATA_TYPE_BFLOAT16, 3, (void*)p, dims, strides, box, es, CU_TENSOR_MAP_INTERLEAVE_NONE,
             cw == 64 ? CU_TENSOR_MAP_SWIZZLE_128B : CU_TENSOR_MAP_SWIZZLE_64B, CU_TENSOR_MAP_L2_PROMOTION_L2_256B, CU_TENSOR_MAP_FLOAT_OOB_FILL_NONE);
}
template <typename T> static void* sym(T& s) { void* p = nullptr; cudaGetSymbolAddress(&p, s); return p; }

extern "C" void kernel_launch(void* const* d_in, const int* in_sizes, int n_in, void* d_out, int out_size) {
    const bf16 *x = (const bf16*)d_in[0], *mem0 = (const bf16*)d_in[1], *Wq = (const bf16*)d_in[2], *Wk = (const bf16*)d_in[3],
               *Wv = (const bf16*)d_in[4], *Wo = (const bf16*)d_in[5], *wr = (const bf16*)d_in[8], *wgate = (const bf16*)d_in[9],
               *wup = (const bf16*)d_in[10], *wdown = (const bf16*)d_in[11], *c = (const bf16*)d_in[12], *wmod = (const bf16*)d_in[13];
    bf16* out = (bf16*)d_out;
    if (!s_encode) {
        cudaDriverEntryPointQueryResult qr;
        cudaGetDriverEntryPoint("cuTensorMapEncodeTiled", (void**)&s_encode, cudaEnableDefault, &qr);
        cudaFuncSetAttribute(k_side, cudaFuncAttributeMaxDynamicSharedMemorySize, SD_SMEM);
        cudaFuncSetAttribute(k_chain, cudaFuncAttributeMaxDynamicSharedMemorySize, C_SMEM);
    }
    ChainMaps cm; SideMaps sd;
    make_map(&sd.h, sym(g_h), S_TOK, DM, 128); make_map3(&sd.wv, Wv, DM, HD, 64, 3);
    make_map3(&sd.ost, sym(g_o), S_TOK, HD, 16, 3); make_map(&sd.o, sym(g_o), S_TOK, HD, 128, 32); make_map3(&sd.wo, Wo, HD, DM, 32, 5);
    make_map(&sd.slab, sym(g_slab), 16 * KSPLIT * 128, DM, 64); make_map3(&cm.slab2, sym(g_slab), 16 * KSPLIT * 128, DM, 64, 2);
    make_map3(&cm.wo15, Wo, HD, DM, 192, 2); make_map3(&cm.o15, sym(g_o), S_TOK, HD, 64, 2);
    for (int i = 0; i < 3; i++) {
        cuuint64_t dims[3] = {256, 320, 16 * KSPLIT}, strides[2] = {512, 128 * DM * 2};
        cuuint32_t box[3] = {256, 40u >> i, 2u << i}, es[3] = {1, 1, 1};
        s_encode(&sd.lnp[i], CU_TENSOR_MAP_DATA_TYPE_BFLOAT16, 3, sym(g_slab), dims, strides, box, es, CU_TENSOR_MAP_INTERLEAVE_NONE,
                 CU_TENSOR_MAP_SWIZZLE_NONE, CU_TENSOR_MAP_L2_PROMOTION_L2_256B, CU_TENSOR_MAP_FLOAT_OOB_FILL_NONE);
    }
    make_map(&cm.wq, Wq, DM, HD, 640 / WP); make_map(&cm.wk, Wk, DM, HD, 640 / WP); make_map(&cm.wv, Wv, DM, HD, 160); make_map3(&cm.wo, Wo, HD, DM, 64, 7, 32);
    make_map3(&cm.h2, sym(g_h), S_TOK, DM, 32, 2);
    ChainArgs ar = {x, mem0, c, wmod, wgate, wup, wdown, out, P_D1, P_DL, P_DG};
    k_chain<<<96, 384, C_SMEM>>>(cm, ar);
    cudaLaunchConfig_t cfg = {};
    cfg.gridDim = dim3(N_SIDE); cfg.blockDim = dim3(384); cfg.dynamicSmemBytes = SD_SMEM; cfg.stream = cudaStreamPerThread;
    cudaLaunchAttribute at[1]; at[0].id = cudaLaunchAttributeProgrammaticStreamSerialization; at[0].val.programmaticStreamSerializationAllowed = 1;
    cfg.attrs = at; cfg.numAttrs = 1;
    cudaLaunchKernelEx(&cfg, k_side, sd, x, wr, wmod, c, out);
}
```

```cpp
#include <cuda_runtime.h>
#include <cuda_bf16.h>
#include <cuda.h>
#include <stdint.h>
#include <stdio.h>
#include <string.h>
#include <stdlib.h>

typedef __nv_bfloat16 bf16;
constexpr int S_TOK = 2048, DM = 640, NH = 32, DH = 192, HD = NH * DH, NSEG = 64, SEG = 32, FF = 1536;

__device__ bf16 g_mod[6 * DM];
__device__ bf16 g_h[S_TOK * DM];
constexpr int AT_REC = 43008, AT_KM = 24576, AT_VM = 27648, AT_V = 30720;
__device__ __align__(1024) uint8_t g_att[NSEG * NH * AT_REC];
__device__ bf16 g_o[S_TOK * HD];
__device__ bf16 g_A[S_TOK * DM];
__device__ bf16 g_x1[S_TOK * DM];
__device__ bf16 g_h2[S_TOK * DM];
__device__ __align__(128) uint32_t g_key[S_TOK];
__device__ int g_idx[8];
__device__ __align__(128) uint32_t g_gu[FF / 8 * 32];
constexpr int ACC_PAIR = 24 * 1024;
__device__ __align__(1024) uint8_t g_acc[2 * ACC_PAIR];
__device__ __align__(1024) uint32_t g_stamp[4 * 12 * 32];
constexpr int KSPLIT = 16;
__device__ bf16 g_slab[16 * KSPLIT * 128 * DM];
struct __align__(128) Flags {
    uint32_t qk[16], vb[16];
    uint32_t at[16], o[16];
    uint32_t c[4][16];
    uint32_t half[32];
    uint32_t fin[4 * 32];
    uint32_t v[16 * 32];
    uint32_t seg[4 * 32];
    uint32_t pair[16 * 16];
    uint32_t h, pad2[31], done, mod, pad3[30];
    uint32_t mod1[DM];
    uint32_t wmax[96];
};
__device__ Flags g_flags;
#define EPT(c, i)

__device__ __forceinline__ uint32_t smem_u32(const void* p) { return (uint32_t)__cvta_generic_to_shared(p); }
__device__ __forceinline__ uint32_t pack2(float lo, float hi) {
    uint32_t r; asm("cvt.rn.bf16x2.f32 %0, %1, %2;" : "=r"(r) : "f"(hi), "f"(lo)); return r;
}
__device__ __forceinline__ float bfr(float x) { return __uint_as_float(pack2(0.f, x)); }
__device__ __forceinline__ float inv_std(float var) {
    float s, r; asm("sqrt.approx.f32 %0, %1;" : "=f"(s) : "f"(bfr(bfr(var) + 1e-5f))); asm("rcp.approx.f32 %0, %1;" : "=f"(r) : "f"(bfr(s))); return r;
}
__device__ __forceinline__ float lo_f(uint32_t v) { return __uint_as_float(v << 16); }
__device__ __forceinline__ float hi_f(uint32_t v) { return __uint_as_float(v & 0xffff0000u); }
__device__ __forceinline__ void mbar_init(uint32_t bar, int cnt) { asm volatile("mbarrier.init.shared::cta.b64 [%0], %1;" :: "r"(bar), "r"(cnt) : "memory"); }
__device__ __forceinline__ void mbar_expect(uint32_t bar, int bytes) { asm volatile("mbarrier.arrive.expect_tx.shared::cta.b64 _, [%0], %1;" :: "r"(bar), "r"(bytes) : "memory"); }
__device__ __forceinline__ void mbar_arrive(uint32_t bar) { asm volatile("mbarrier.arrive.shared::cta.b64 _, [%0];" :: "r"(bar) : "memory"); }
__device__ __forceinline__ bool mbar_try(uint32_t bar, int par) {
    uint32_t ok; asm volatile("{ .reg .pred p; mbarrier.try_wait.parity.shared::cta.b64 p, [%1], %2; selp.u32 %0, 1, 0, p; }" : "=r"(ok) : "r"(bar), "r"(par) : "memory"); return ok;
}
__device__ __forceinline__ bool mbar_try_cluster(uint32_t bar, int par) {
    uint32_t ok; asm volatile("{ .reg .pred p; mbarrier.try_wait.parity.acquire.cluster.shared::cta.b64 p, [%1], %2; selp.u32 %0, 1, 0, p; }" : "=r"(ok) : "r"(bar), "r"(par) : "memory"); return ok;
}
__device__ __forceinline__ bool mbar_test(uint32_t bar, uint32_t par) {
    uint32_t ok; asm volatile("{ .reg .pred p; mbarrier.test_wait.parity.shared::cta.b64 p, [%1], %2; selp.u32 %0, 1, 0, p; }" : "=r"(ok) : "r"(bar), "r"(par) : "memory"); return ok;
}
constexpr int SPIN_LIMIT = 1 << 18;
__device__ __forceinline__ void mbar_wait(uint32_t bar, uint32_t par) {
    asm volatile("{ .reg .pred p, q; .reg .u32 n; mov.u32 n, 0;\n"
                 "W_%=: mbarrier.try_wait.parity.shared::cta.b64 p, [%0], %1;\n"
                 "@p bra.uni D_%=;\n"
                 "add.u32 n, n, 1; setp.lt.u32 q, n, 0x200000; @q bra.uni W_%=;\n"
                 "trap;\n"
                 "D_%=: }" :: "r"(bar), "r"(par) : "memory");
}
__device__ __forceinline__ void tma2d(uint32_t dst, const CUtensorMap* m, int c0, int c1, uint32_t bar) {
    asm volatile("cp.async.bulk.tensor.2d.shared::cluster.global.mbarrier::complete_tx::bytes [%0], [%1, {%3, %4}], [%2];"
        :: "r"(dst), "l"((uint64_t)m), "r"(bar), "r"(c0), "r"(c1) : "memory");
}
__device__ __forceinline__ void tma2d_mc(uint32_t dst, const CUtensorMap* m, int c0, int c1, uint32_t bar, uint16_t mask) {
    asm volatile("cp.async.bulk.tensor.2d.shared::cluster.global.mbarrier::complete_tx::bytes.multicast::cluster [%0], [%1, {%3, %4}], [%2], %5;"
        :: "r"(dst), "l"((uint64_t)m), "r"(bar), "r"(c0), "r"(c1), "h"(mask) : "memory");
}
__device__ __forceinline__ uint64_t policy_stream() { uint64_t p; asm("createpolicy.fractional.L2::evict_first.b64 %0, 1.0;" : "=l"(p)); return p; }
__device__ __forceinline__ void tma2d_ef(uint32_t dst, const CUtensorMap* m, int c0, int c1, uint32_t bar, uint64_t pol) {
    asm volatile("cp.async.bulk.tensor.2d.shared::cluster.global.mbarrier::complete_tx::bytes.L2::cache_hint [%0], [%1, {%3, %4}], [%2], %5;"
        :: "r"(dst), "l"((uint64_t)m), "r"(bar), "r"(c0), "r"(c1), "l"(pol) : "memory");
}
__device__ __forceinline__ void tma3d(uint32_t dst, const CUtensorMap* m, int row, int chunk, uint32_t bar) {
    asm volatile("cp.async.bulk.tensor.3d.shared::cluster.global.mbarrier::complete_tx::bytes [%0], [%1, {0, %3, %4}], [%2];"
        :: "r"(dst), "l"((uint64_t)m), "r"(bar), "r"(row), "r"(chunk) : "memory");
}
__device__ __forceinline__ void tma3d_ef(uint32_t dst, const CUtensorMap* m, int row, int chunk, uint32_t bar, uint64_t pol) {
    asm volatile("cp.async.bulk.tensor.3d.shared::cluster.global.mbarrier::complete_tx::bytes.L2::cache_hint [%0], [%1, {0, %3, %4}], [%2], %5;"
        :: "r"(dst), "l"((uint64_t)m), "r"(bar), "r"(row), "r"(chunk), "l"(pol) : "memory");
}
__device__ __forceinline__ void tma3d_store(const CUtensorMap* m, int row, int chunk, uint32_t src, uint64_t pol, bool hint) {
    if (hint) asm volatile("cp.async.bulk.tensor.3d.global.shared::cta.bulk_group.L2::cache_hint [%0, {0, %2, %3}], [%1], %4;"
        :: "l"((uint64_t)m), "r"(src), "r"(row), "r"(chunk), "l"(pol) : "memory");
    else asm volatile("cp.async.bulk.tensor.3d.global.shared::cta.bulk_group [%0, {0, %2, %3}], [%1];"
        :: "l"((uint64_t)m), "r"(src), "r"(row), "r"(chunk) : "memory");
}
__device__ __forceinline__ bool elect() { uint32_t p; asm volatile("{ .reg .pred e; elect.sync _|e, -1; selp.u32 %0, 1, 0, e; }" : "=r"(p)); return p; }
__device__ __forceinline__ uint2 ld_ef(const void* p, uint64_t pol) {
    uint2 v; asm volatile("ld.relaxed.gpu.global.L2::cache_hint.v2.u32 {%0,%1}, [%2], %3;" : "=r"(v.x), "=r"(v.y) : "l"(p), "l"(pol)); return v;
}
__device__ __forceinline__ void st_ef(void* p, uint2 v, uint64_t pol) {
    asm volatile("st.global.L2::cache_hint.v2.u32 [%0], {%1,%2}, %3;" :: "l"(p), "r"(v.x), "r"(v.y), "l"(pol) : "memory");
}
__device__ __forceinline__ void tma2d_prefetch(const CUtensorMap* m, int c0, int c1) {
    asm volatile("cp.async.bulk.prefetch.tensor.2d.L2.global [%0, {%1, %2}];" :: "l"((uint64_t)m), "r"(c0), "r"(c1) : "memory");
}
__device__ __forceinline__ void mbar_arrive_remote(uint32_t bar) { asm volatile("mbarrier.arrive.relaxed.cluster.shared::cluster.b64 _, [%0];" :: "r"(bar) : "memory"); }
__device__ __forceinline__ void tma2d_store(const CUtensorMap* m, int c0, int c1, uint32_t src) {
    asm volatile("cp.async.bulk.tensor.2d.global.shared::cta.bulk_group [%0, {%2, %3}], [%1];"
        :: "l"((uint64_t)m), "r"(src), "r"(c0), "r"(c1) : "memory");
}
__device__ __forceinline__ void bulk_g2s(uint32_t dst, const void* src, int bytes, uint32_t bar) {
    asm volatile("cp.async.bulk.shared::cluster.global.mbarrier::complete_tx::bytes [%0], [%1], %2, [%3];" :: "r"(dst), "l"(src), "r"(bytes), "r"(bar) : "memory");
}
__device__ __forceinline__ void ldsm4(uint32_t (&r)[4], uint32_t a) {
    asm volatile("ldmatrix.sync.aligned.m8n8.x4.shared.b16 {%0,%1,%2,%3}, [%4];" : "=r"(r[0]), "=r"(r[1]), "=r"(r[2]), "=r"(r[3]) : "r"(a) : "memory");
}
__device__ __forceinline__ void ldsm4t(uint32_t (&r)[4], uint32_t a) {
    asm volatile("ldmatrix.sync.aligned.m8n8.x4.trans.shared.b16 {%0,%1,%2,%3}, [%4];" : "=r"(r[0]), "=r"(r[1]), "=r"(r[2]), "=r"(r[3]) : "r"(a) : "memory");
}
__device__ __forceinline__ void stsm4(uint32_t a, uint32_t r0, uint32_t r1, uint32_t r2, uint32_t r3) {
    asm volatile("stmatrix.sync.aligned.m8n8.x4.shared.b16 [%0], {%1,%2,%3,%4};" :: "r"(a), "r"(r0), "r"(r1), "r"(r2), "r"(r3) : "memory");
}
__device__ __forceinline__ void stsm4t(uint32_t a, uint32_t r0, uint32_t r1, uint32_t r2, uint32_t r3) {
    asm volatile("stmatrix.sync.aligned.m8n8.x4.trans.shared.b16 [%0], {%1,%2,%3,%4};" :: "r"(a), "r"(r0), "r"(r1), "r"(r2), "r"(r3) : "memory");
}
__device__ __forceinline__ void stsm2t(uint32_t a, uint32_t r0, uint32_t r1) {
    asm volatile("stmatrix.sync.aligned.m8n8.x2.trans.shared.b16 [%0], {%1,%2};" :: "r"(a), "r"(r0), "r"(r1) : "memory");
}
__device__ __forceinline__ uint32_t movm_t(uint32_t v) { uint32_t r; asm volatile("movmatrix.sync.aligned.m8n8.trans.b16 %0, %1;" : "=r"(r) : "r"(v)); return r; }
__device__ __forceinline__ void mma16(float (&d)[4], uint32_t a0, uint32_t a1, uint32_t a2, uint32_t a3, uint32_t b0, uint32_t b1) {
    asm volatile("mma.sync.aligned.m16n8k16.row.col.f32.bf16.bf16.f32 {%0,%1,%2,%3}, {%4,%5,%6,%7}, {%8,%9}, {%0,%1,%2,%3};"
        : "+f"(d[0]), "+f"(d[1]), "+f"(d[2]), "+f"(d[3]) : "r"(a0), "r"(a1), "r"(a2), "r"(a3), "r"(b0), "r"(b1));
}
__device__ __forceinline__ void mma8(float (&d)[4], uint32_t a0, uint32_t a1, uint32_t b0) {
    asm volatile("mma.sync.aligned.m16n8k8.row.col.f32.bf16.bf16.f32 {%0,%1,%2,%3}, {%4,%5}, {%6}, {%0,%1,%2,%3};"
        : "+f"(d[0]), "+f"(d[1]), "+f"(d[2]), "+f"(d[3]) : "r"(a0), "r"(a1), "r"(b0));
}
__device__ __forceinline__ uint32_t mapa(uint32_t a, uint32_t r) { uint32_t o; asm volatile("mapa.shared::cluster.u32 %0, %1, %2;" : "=r"(o) : "r"(a), "r"(r)); return o; }
__device__ __forceinline__ void bar_sync(int id, int n) { asm volatile("bar.sync %0, %1;" :: "r"(id), "r"(n) : "memory"); }
__device__ __forceinline__ void bar_arrive(int id, int n) { asm volatile("bar.arrive %0, %1;" :: "r"(id), "r"(n) : "memory"); }
__device__ __forceinline__ uint64_t mkdesc(uint32_t addr, uint32_t lbo, uint32_t sbo) {
    return (uint64_t)((addr & 0x3FFFF) >> 4) | ((uint64_t)(lbo >> 4) << 16) | ((uint64_t)(sbo >> 4) << 32) | (1ull << 62);
}
#define WG_FENCE()  asm volatile("wgmma.fence.sync.aligned;" ::: "memory")
#define WG_COMMIT() asm volatile("wgmma.commit_group.sync.aligned;" ::: "memory")
#define WG_WAIT(n)  asm volatile("wgmma.wait_group.sync.aligned %0;" :: "n"(n) : "memory")

__device__ __forceinline__ void wgmma_ss_n192_tb(float (&d)[96], uint64_t a, uint64_t b, int acc) {
    asm volatile("{ .reg .pred p; setp.ne.b32 p, %98, 0;\n"
        "wgmma.mma_async.sync.aligned.m64n192k16.f32.bf16.bf16 {%0,%1,%2,%3,%4,%5,%6,%7,%8,%9,%10,%11,%12,%13,%14,%15,%16,%17,%18,%19,%20,%21,%22,%23,%24,%25,%26,%27,%28,%29,%30,%31,%32,%33,%34,%35,%36,%37,%38,%39,%40,%41,%42,%43,%44,%45,%46,%47,%48,%49,%50,%51,%52,%53,%54,%55,%56,%57,%58,%59,%60,%61,%62,%63,%64,%65,%66,%67,%68,%69,%70,%71,%72,%73,%74,%75,%76,%77,%78,%79,%80,%81,%82,%83,%84,%85,%86,%87,%88,%89,%90,%91,%92,%93,%94,%95}, %96, %97, p, 1, 1, 0, 1; }"
        : "+f"(d[0]), "+f"(d[1]), "+f"(d[2]), "+f"(d[3]), "+f"(d[4]), "+f"(d[5]), "+f"(d[6]), "+f"(d[7]), "+f"(d[8]), "+f"(d[9]), "+f"(d[10]), "+f"(d[11]), "+f"(d[12]), "+f"(d[13]), "+f"(d[14]), "+f"(d[15]), "+f"(d[16]), "+f"(d[17]), "+f"(d[18]), "+f"(d[19]), "+f"(d[20]), "+f"(d[21]), "+f"(d[22]), "+f"(d[23]), "+f"(d[24]), "+f"(d[25]), "+f"(d[26]), "+f"(d[27]), "+f"(d[28]), "+f"(d[29]), "+f"(d[30]), "+f"(d[31]), "+f"(d[32]), "+f"(d[33]), "+f"(d[34]), "+f"(d[35]), "+f"(d[36]), "+f"(d[37]), "+f"(d[38]), "+f"(d[39]), "+f"(d[40]), "+f"(d[41]), "+f"(d[42]), "+f"(d[43]), "+f"(d[44]), "+f"(d[45]), "+f"(d[46]), "+f"(d[47]), "+f"(d[48]), "+f"(d[49]), "+f"(d[50]), "+f"(d[51]), "+f"(d[52]), "+f"(d[53]), "+f"(d[54]), "+f"(d[55]), "+f"(d[56]), "+f"(d[57]), "+f"(d[58]), "+f"(d[59]), "+f"(d[60]), "+f"(d[61]), "+f"(d[62]), "+f"(d[63]), "+f"(d[64]), "+f"(d[65]), "+f"(d[66]), "+f"(d[67]), "+f"(d[68]), "+f"(d[69]), "+f"(d[70]), "+f"(d[71]), "+f"(d[72]), "+f"(d[73]), "+f"(d[74]), "+f"(d[75]), "+f"(d[76]), "+f"(d[77]), "+f"(d[78]), "+f"(d[79]), "+f"(d[80]), "+f"(d[81]), "+f"(d[82]), "+f"(d[83]), "+f"(d[84]), "+f"(d[85]), "+f"(d[86]), "+f"(d[87]), "+f"(d[88]), "+f"(d[89]), "+f"(d[90]), "+f"(d[91]), "+f"(d[92]), "+f"(d[93]), "+f"(d[94]), "+f"(d[95])
        : "l"(a), "l"(b), "r"(acc));
}

__device__ __forceinline__ void wgmma_ss_n128_tb(float (&d)[64], uint64_t a, uint64_t b, int acc) {
    asm volatile("{ .reg .pred p; setp.ne.b32 p, %66, 0;\n"
        "wgmma.mma_async.sync.aligned.m64n128k16.f32.bf16.bf16 {%0,%1,%2,%3,%4,%5,%6,%7,%8,%9,%10,%11,%12,%13,%14,%15,%16,%17,%18,%19,%20,%21,%22,%23,%24,%25,%26,%27,%28,%29,%30,%31,%32,%33,%34,%35,%36,%37,%38,%39,%40,%41,%42,%43,%44,%45,%46,%47,%48,%49,%50,%51,%52,%53,%54,%55,%56,%57,%58,%59,%60,%61,%62,%63}, %64, %65, p, 1, 1, 0, 1; }"
        : "+f"(d[0]), "+f"(d[1]), "+f"(d[2]), "+f"(d[3]), "+f"(d[4]), "+f"(d[5]), "+f"(d[6]), "+f"(d[7]), "+f"(d[8]), "+f"(d[9]), "+f"(d[10]), "+f"(d[11]), "+f"(d[12]), "+f"(d[13]), "+f"(d[14]), "+f"(d[15]), "+f"(d[16]), "+f"(d[17]), "+f"(d[18]), "+f"(d[19]), "+f"(d[20]), "+f"(d[21]), "+f"(d[22]), "+f"(d[23]), "+f"(d[24]), "+f"(d[25]), "+f"(d[26]), "+f"(d[27]), "+f"(d[28]), "+f"(d[29]), "+f"(d[30]), "+f"(d[31]), "+f"(d[32]), "+f"(d[33]), "+f"(d[34]), "+f"(d[35]), "+f"(d[36]), "+f"(d[37]), "+f"(d[38]), "+f"(d[39]), "+f"(d[40]), "+f"(d[41]), "+f"(d[42]), "+f"(d[43]), "+f"(d[44]), "+f"(d[45]), "+f"(d[46]), "+f"(d[47]), "+f"(d[48]), "+f"(d[49]), "+f"(d[50]), "+f"(d[51]), "+f"(d[52]), "+f"(d[53]), "+f"(d[54]), "+f"(d[55]), "+f"(d[56]), "+f"(d[57]), "+f"(d[58]), "+f"(d[59]), "+f"(d[60]), "+f"(d[61]), "+f"(d[62]), "+f"(d[63])
        : "l"(a), "l"(b), "r"(acc));
}

__device__ __forceinline__ void wgmma_rs_n32(float (&d)[16], const uint32_t (&a)[4], uint64_t b, int acc) {
    asm volatile("{ .reg .pred p; setp.ne.b32 p, %21, 0;\n"
        "wgmma.mma_async.sync.aligned.m64n32k16.f32.bf16.bf16 {%0,%1,%2,%3,%4,%5,%6,%7,%8,%9,%10,%11,%12,%13,%14,%15}, {%16,%17,%18,%19}, %20, p, 1, 1, 0; }"
        : "+f"(d[0]), "+f"(d[1]), "+f"(d[2]), "+f"(d[3]), "+f"(d[4]), "+f"(d[5]), "+f"(d[6]), "+f"(d[7]), "+f"(d[8]), "+f"(d[9]), "+f"(d[10]), "+f"(d[11]), "+f"(d[12]), "+f"(d[13]), "+f"(d[14]), "+f"(d[15])
        : "r"(a[0]), "r"(a[1]), "r"(a[2]), "r"(a[3]), "l"(b), "r"(acc));
}

__device__ __forceinline__ float warp_sum(float v) {
#pragma unroll
    for (int o = 16; o; o >>= 1) v += __shfl_xor_sync(0xffffffffu, v, o);
    return v;
}
__device__ __forceinline__ uint32_t add2(uint32_t a, uint32_t b) { uint32_t r; asm("add.rn.bf16x2 %0, %1, %2;" : "=r"(r) : "r"(a), "r"(b)); return r; }
__device__ __forceinline__ uint32_t mul2(uint32_t a, uint32_t b) { uint32_t r; asm("mul.rn.bf16x2 %0, %1, %2;" : "=r"(r) : "r"(a), "r"(b)); return r; }
__device__ __forceinline__ uint32_t amax2(uint32_t m, uint32_t v) { uint32_t r; asm("max.u16x2 %0, %1, %2;" : "=r"(r) : "r"(m), "r"(v & 0x7fff7fffu)); return r; }
__device__ __forceinline__ uint32_t amax_warp(uint32_t m) { return __reduce_max_sync(0xffffffffu, max(m & 0xffffu, m >> 16)); }
__device__ __forceinline__ void ln_norm(const uint32_t (&xv)[10], uint32_t (&nv)[10]) {
    float s0 = 0, s1 = 0;
#pragma unroll
    for (int i = 0; i < 10; i++) { s0 += lo_f(xv[i]); s1 += hi_f(xv[i]); }
    const float mean = warp_sum(s0 + s1) * (1.f / DM);
    float q0 = 0, q1 = 0;
#pragma unroll
    for (int i = 0; i < 10; i++) { const float d0 = lo_f(xv[i]) - mean, d1 = hi_f(xv[i]) - mean; q0 += d0 * d0; q1 += d1 * d1; }
    const float inv = inv_std(warp_sum(q0 + q1) * (1.f / DM));
    const uint32_t mb = pack2(-mean, -mean);
#pragma unroll
    for (int i = 0; i < 10; i++) { const uint32_t d = add2(xv[i], mb); nv[i] = pack2(lo_f(d) * inv, hi_f(d) * inv); }
}
__device__ __forceinline__ void ln_mod(const uint32_t (&xv)[10], const uint32_t (&sv)[10], const uint32_t (&tv)[10], uint32_t (&hv)[10]) {
    ln_norm(xv, hv);
#pragma unroll
    for (int i = 0; i < 10; i++) hv[i] = add2(mul2(hv[i], add2(sv[i], 0x3f803f80u)), tv[i]);
}
__device__ __forceinline__ uint32_t ld_rlx(const uint32_t* f) { uint32_t v; asm volatile("ld.relaxed.gpu.global.u32 %0, [%1];" : "=r"(v) : "l"(f) : "memory"); return v; }
__device__ __forceinline__ void bump(uint32_t* f) { asm volatile("red.relaxed.gpu.global.add.u32 [%0], 1;" :: "l"(f) : "memory"); }
#define NAP 100
#define GPU_FENCE() asm volatile("fence.acq_rel.gpu;" ::: "memory")
__device__ __forceinline__ void flag_wait(const uint32_t* f, uint32_t target) {
    for (int n = 0;; n++) {
        uint32_t v; asm volatile("ld.relaxed.gpu.global.u32 %0, [%1];" : "=r"(v) : "l"(f) : "memory");
        if (v >= target) break;
        if (n > (1 << 22)) __trap();
        __nanosleep(NAP);
    }
}
__device__ __forceinline__ void flag_add(uint32_t* f, uint32_t v = 1) { asm volatile("red.release.gpu.global.add.u32 [%0], %1;" :: "l"(f), "r"(v) : "memory"); }
constexpr int N_SIDE = 36;
__device__ __forceinline__ void flags_release(int lane) {
    uint32_t old = 0;
    if (lane == 0) asm volatile("atom.relaxed.gpu.global.add.u32 %0, [%1], 1;" : "=r"(old) : "l"(&g_flags.done) : "memory");
    if (__shfl_sync(0xffffffffu, old, 0) == 96 + N_SIDE - 1)
#pragma unroll 1
        for (int i = lane; i < (int)(sizeof(Flags) / 16); i += 32) ((uint4*)&g_flags)[i] = make_uint4(0, 0, 0, 0);
}

struct ChainMaps { CUtensorMap wq, wk, wv, wo, h2, wo15, o15, slab2; };
struct ChainArgs { const bf16 *x, *mem0, *c, *wmod, *wgate, *wup, *wdown; bf16* out; int D1, D2, DG; };
constexpr uint32_t SM_BASE = 1024;
#define NRING 10
#define XORD 0
#define B5AT 38
#define QCUT 0x12
#define NCH 0
#define XA 2
#define VT 1
#define OSEND 1
#define SPOLL 0
#define BDEF 0
#define F61 1
#define IDLE 300
#define FW 2
#define RSEL 1
#define AIN 0
#define APRE 4
#define PBAR 0
#define WLATE 1
#define QDEL 300
#define STL 0
#define B7E 1
#define H24 0
#define NPRE 9
#define REG_P 208
#define REG_L (504 - 2 * REG_P)
constexpr int WO_BLK = 7 * 4096;
constexpr int C_WV = 0, C_WO = 81920, C_XR = 167936, C_VP = C_XR + 7 * 4096, C_VX = C_XR + 8 * 4096, C_QX = C_VX + 4096, C_KX = C_QX + 4096,
              C_MEM = C_KX + 4096, C_OX = C_MEM + 9216, C_VM = C_OX + 3072, C_QM = C_VM + 1024, C_KM = C_QM + 1024, C_SC = C_KM + 1024, C_BAR = C_SC + 3840;
constexpr int CB_W = C_BAR, CB_W2 = C_BAR + 8, CB_SC = C_BAR + 16, CB_XD = C_BAR + 24, CB_VX = C_BAR + 32, CB_W3 = C_BAR + 40, CB_XM = C_BAR + 48, CB_OX = C_BAR + 56,
              CB_XF = C_BAR + 64, C_LAG = C_BAR + 96, C_UN = C_BAR + 100, C_MX = C_BAR + 112;
constexpr int C_SMEM = C_BAR + 128;
#define PROF(i)
#define PROFG(i)
#define PROFV(i, v)
static_assert(C_SMEM <= 232448, "chain shared memory");
__device__ __forceinline__ uint32_t umax3(uint32_t a, uint32_t b, uint32_t c) { return max(max(a, b), c); }
__device__ __forceinline__ void wait_until(uint32_t t) {
    asm volatile("{ .reg .pred p; .reg .s32 c; .reg .u64 d;\nU_%=: mov.u64 d, %%clock64; cvt.u32.u64 c, d; sub.s32 c, c, %0; setp.lt.s32 p, c, 0; @p bra.uni U_%=; }" :: "r"(t) : "memory");
}
__device__ __forceinline__ uint32_t gtime() { uint32_t c; asm volatile("mov.u32 %0, %%globaltimer_lo;" : "=r"(c)); return c; }
__device__ __forceinline__ uint32_t opaque(uint32_t v) { uint32_t r; asm volatile("shfl.sync.bfly.b32 %0, %1, 0, 31, -1;" : "=r"(r) : "r"(v)); return r; }
__device__ __forceinline__ uint32_t lds32(uint32_t a) { uint32_t v; asm volatile("ld.shared.u32 %0, [%1];" : "=r"(v) : "r"(a) : "memory"); return v; }
__device__ __forceinline__ float2 lds64f(uint32_t a) { float2 v; asm volatile("ld.shared.v2.f32 {%0,%1}, [%2];" : "=f"(v.x), "=f"(v.y) : "r"(a) : "memory"); return v; }
__device__ __forceinline__ float4 lds128f(uint32_t a) { float4 v; asm volatile("ld.shared.v4.f32 {%0,%1,%2,%3}, [%4];" : "=f"(v.x), "=f"(v.y), "=f"(v.z), "=f"(v.w) : "r"(a) : "memory"); return v; }
__device__ __forceinline__ void sts128f(uint32_t a, float x, float y, float z, float w) { asm volatile("st.shared.v4.f32 [%0], {%1,%2,%3,%4};" :: "r"(a), "f"(x), "f"(y), "f"(z), "f"(w) : "memory"); }
__device__ __forceinline__ void lds64(uint32_t (&v)[2], uint32_t a) { asm volatile("ld.shared.v2.u32 {%0,%1}, [%2];" : "=r"(v[0]), "=r"(v[1]) : "r"(a) : "memory"); }
__device__ __forceinline__ void mma16q(float (&d)[4], const uint32_t (&a)[4], uint32_t b0, uint32_t b1) { mma16(d, a[0], a[1], a[2], a[3], b0, b1); }
__device__ __forceinline__ uint32_t f16_to_bf16(uint32_t v) {
    float lo, hi; asm("{ .reg .f16 l, h; mov.b32 {l, h}, %2; cvt.f32.f16 %0, l; cvt.f32.f16 %1, h; }" : "=f"(lo), "=f"(hi) : "r"(v));
    return pack2(lo, hi);
}
__device__ __forceinline__ uint32_t pack2h(float lo, float hi) { uint32_t r; asm("cvt.rn.f16x2.f32 %0, %1, %2;" : "=r"(r) : "f"(hi), "f"(lo)); return r; }
#define SPLIT 1
__device__ __forceinline__ void cut(uint32_t never, int n) {
    asm volatile("{ .reg .pred p; setp.ne.u32 p, %0, %1; @p bra.uni C_%=; trap; C_%=: }" :: "r"(never), "r"(n) : "memory");
}
__device__ __forceinline__ void pin(uint32_t never, uint32_t a, uint32_t b, uint32_t c, uint32_t d) {
    asm volatile("{ .reg .pred p; setp.eq.u32 p, %0, 0; @p st.shared.v4.u32 [%0], {%1,%2,%3,%4}; }" :: "r"(never), "r"(a), "r"(b), "r"(c), "r"(d) : "memory");
}
__device__ __forceinline__ void pin0(uint32_t never) {
    asm volatile("{ .reg .pred p; setp.eq.u32 p, %0, 0; @p st.shared.u32 [%0], 0; }" :: "r"(never) : "memory");
}
#define ELECTED(txt) "{ .reg .pred e; elect.sync _|e, -1; @e " txt " }"
__device__ __forceinline__ void w_bulk_s2g(void* dst, uint32_t src, int bytes) {
    asm volatile(ELECTED("cp.async.bulk.global.shared::cta.bulk_group [%0], [%1], %2;") :: "l"(dst), "r"(src), "r"(bytes) : "memory");
}
__device__ __forceinline__ void w_bump(uint32_t* f) { asm volatile(ELECTED("red.relaxed.gpu.global.add.u32 [%0], 1;") :: "l"(f) : "memory"); }
__device__ __forceinline__ void w_expect(uint32_t bar, int bytes) { asm volatile(ELECTED("mbarrier.arrive.expect_tx.shared::cta.b64 _, [%0], %1;") :: "r"(bar), "r"(bytes) : "memory"); }
__device__ __forceinline__ void w_flag_wait(const uint32_t* f, uint32_t target) {
    asm volatile("{ .reg .pred p; .reg .u32 n, v; mov.u32 n, 0;\n"
                 "F_%=: ld.relaxed.gpu.global.u32 v, [%0]; setp.ge.u32 p, v, %1; vote.sync.all.pred p, p, -1; @p bra.uni G_%=;\n"
                 "nanosleep.u32 %2; add.u32 n, n, 1; setp.lt.u32 p, n, 0x400000; @p bra.uni F_%=;\ntrap;\nG_%=: }" :: "l"(f), "r"(target), "n"(NAP) : "memory");
}
#define BULK_COMMIT()    asm volatile("cp.async.bulk.commit_group;" ::: "memory")
#define BULK_WAIT()      asm volatile("cp.async.bulk.wait_group 0;" ::: "memory")
#define BULK_WAIT_READ() asm volatile("cp.async.bulk.wait_group.read 0;" ::: "memory")
#define PROXY_FENCE()    asm volatile("fence.proxy.async.shared::cta;" ::: "memory")
__device__ __forceinline__ void send16(uint32_t dst, uint32_t bar, float a, float b, float c, float d) {
    asm volatile("st.async.shared::cluster.mbarrier::complete_tx::bytes.v4.f32 [%0], {%1,%2,%3,%4}, [%5];" :: "r"(dst), "f"(a), "f"(b), "f"(c), "f"(d), "r"(bar) : "memory");
}
__device__ __forceinline__ void send8(uint32_t dst, uint32_t bar, uint32_t a, uint32_t b) {
    asm volatile("st.async.shared::cluster.mbarrier::complete_tx::bytes.v2.b32 [%0], {%1,%2}, [%3];" :: "r"(dst), "r"(a), "r"(b), "r"(bar) : "memory");
}

__device__ __forceinline__ void seg_done(int n, int head) { GPU_FENCE(); w_bump(&g_flags.seg[(n - 60) * 32 + head]); }
__device__ __forceinline__ uint32_t x_base(int wg, uint32_t small, int sh) { return (uint32_t)mkdesc(SM_BASE + C_XR, 16, 1024) + wg * 256 + (small >> sh); }
__device__ __forceinline__ void x_chunk(float (&acc)[16], const uint32_t (&wa)[40][4], uint32_t xl, int a0, int i, int first) {
#pragma unroll
    for (int ks = 0; ks < 4; ks++)
        wgmma_rs_n32(acc, wa[a0 + 4 * i + ks], mkdesc(0, 0, 1024) | (uint32_t)(xl + (((i ? (i - 1) * 8192 : C_MEM - C_XR) + ks * 32) >> 4)), !(first && ks == 0));
}
template <typename F>
__device__ __forceinline__ void x_part(F aside, float (&acc)[16], const uint32_t (&wa)[40][4], uint32_t sm, int n, int wg, int w, uint32_t ln, uint32_t small) {
    const int s = n - 1; (void)s;
    uint32_t giv[12];
    auto chunk = [&](int a0, int i, int first) { x_chunk(acc, wa, x_base(wg, small, a0 ? 21 : 22), a0, i, first); };
    mbar_wait(sm + CB_XM, n & 1);
    if (n) bar_sync(5, 384);
    if (wg == 0 && w == 0) PROF(12);
    WG_FENCE();
#pragma unroll
    for (int i = 1 + XA; i < 5; i++) chunk(20, i, 0);
    chunk(20, 0, 0);
    WG_COMMIT();
    if (n) {
        if (wg == 1 && w == 1) BULK_WAIT();
        bar_sync(8, 256);
    }
    if (wg == 0 && w == 0) PROF(18);
    const uint32_t xb = sm + w * 512 + ln * 16, xw = xb + C_KX - wg * 4096, xr = xb + C_QX + wg * 4096;
    WG_WAIT(0);
#pragma unroll
    for (int i = 0; i < 8; i++) asm volatile("cvt.rn.bf16x2.f32 %0, %1, %2;" : "=r"(giv[i]) : "f"(acc[2 * i + 1]), "f"(acc[2 * i]));
#pragma unroll
    for (int p = 0; p < 2 + H24; p++)
        asm volatile("st.shared.v4.u32 [%0], {%1,%2,%3,%4};" :: "r"(p < 2 ? xw + p * 2048 : xb + (wg ? C_SC : C_OX + 1024)), "r"(giv[4 * p]), "r"(giv[4 * p + 1]), "r"(giv[4 * p + 2]), "r"(giv[4 * p + 3]) : "memory");
    bar_arrive(12 + wg, 256);
    WG_FENCE();
    chunk(0, 0, 1);
    WG_COMMIT();
    chunk(0, 1, 0);
    if (XORD) chunk(0, 2, 0);
    bar_sync(13 - wg, 256);
#pragma unroll
    for (int p = 0; p < 2 + H24; p++)
        asm volatile("ld.shared.v4.u32 {%0,%1,%2,%3}, [%4];" : "=r"(giv[4 * p]), "=r"(giv[4 * p + 1]), "=r"(giv[4 * p + 2]), "=r"(giv[4 * p + 3]) : "r"(p < 2 ? xr + p * 2048 : xb + (wg ? C_OX + 1024 : C_SC)) : "memory");
    WG_COMMIT(); WG_WAIT(1); bar_arrive(9, 384);
    WG_FENCE();
    if (!XORD) chunk(0, 2, 0);
    chunk(0, 3, 0); chunk(0, 4, 0);
    WG_COMMIT();
    const uint32_t r = ln & 7, mi = ln >> 3, dst = sm + (wg == 0 ? C_QX : C_KX) + ((mi >> 1) * 8 + r) * 128 + (((2 * w + (mi & 1)) ^ r) << 4);
    pin(xb, giv[0], giv[4], dst, 0);
    aside();
    bar_sync(10 + wg, 128);
    WG_WAIT(0);
    if (wg == 0 && w == 0) PROF(30);
    if (w == 0 && ln < 3) mbar_arrive_remote(mapa(sm + CB_XD, ln));
#pragma unroll
    for (int i = 0; i < 8; i++) { acc[2 * i] += lo_f(giv[i]); acc[2 * i + 1] += hi_f(giv[i]); }
#pragma unroll
    for (int p = 0; p < 2; p++)
        stsm4t(dst + p * 2048, pack2(acc[8 * p], acc[8 * p + 1]), pack2(acc[8 * p + 2], acc[8 * p + 3]), pack2(acc[8 * p + 4], acc[8 * p + 5]), pack2(acc[8 * p + 6], acc[8 * p + 7]));
    if (wg == 0 && w == 0) PROF(11);
}
__device__ __forceinline__ void x_fill(const ChainMaps& mp, uint32_t sm, int n, int j) {
    mbar_expect(sm + CB_XF, 24576);
    asm volatile("cp.async.bulk.tensor.3d.shared::cluster.global.mbarrier::complete_tx::bytes.multicast::cluster [%0], [%1, {0, %3, %4}], [%2], %5;"
        :: "r"(sm + C_XR + j * 8192), "l"((uint64_t)&mp.h2), "r"(sm + CB_XF), "r"(n * SEG), "r"(2 + 2 * j), "h"((uint16_t)7) : "memory");
}
__device__ __forceinline__ void x_rest(const ChainMaps& mp, uint32_t sm, int n) {
    mbar_expect(sm + CB_XM, 16384);
    tma3d(sm + C_XR + 6 * 4096, &mp.h2, n * SEG, 8, sm + CB_XM); tma3d(sm + C_MEM, &mp.h2, n * SEG, 0, sm + CB_XM);
}

#define WPOS 2
#define WP 4
#define SDEL 0
#define EORD 0
#define RPF 1
#define TDEL 2500
#define BPOS 2
#define TPF 1
#define B_LATE 13
constexpr int E_B = C_WO, E_STG = 196608, EB_A = 229376, EB_B = C_BAR + 80, EB_REL = C_BAR + 104;
__device__ __forceinline__ uint32_t e_slot(int wg, int c) { return wg && c == 2 ? E_B + 98304 : wg * 49152 + c * 16384; }
constexpr int T_WG = 0, T_WU = 20480, T_WD = 40960, T_X = 65536, T_RED = 77824, T_KEY = 86016;
__device__ __forceinline__ void wo_half(const ChainMaps& mp, uint32_t sm, int blk, int c) {
    if (blk < 80 && elect()) { mbar_expect(sm + EB_B + 8 * c, 49152); tma3d(sm + E_B + c * 49152, &mp.wo15, blk / 5 * 384 + c * 192, blk % 5 * 2, sm + EB_B + 8 * c); }
}
__device__ __forceinline__ void end_loads(const ChainMaps& mp, const ChainArgs& ar, uint32_t sm, int blk, int wg) {
    const uint32_t bar = sm + EB_A + wg * 48;
    const int kp = blk / 5;
    if (elect()) {
#pragma unroll 1
        for (int c = 0; c < 6; c++) mbar_init(bar + 8 * c, c < 3 ? 1 : 4);
        PROXY_FENCE();
    }
    __syncwarp();
    bar_arrive(5, 384);
    if (EORD) bar_sync(6, 96);
    if (blk >= 80) {
        if (TPF && elect()) {
#pragma unroll 1
            for (int c = 0; c < 3; c++) asm volatile("cp.async.bulk.prefetch.L2.global [%0], 61440;" :: "l"((c == 0 ? ar.wgate : c == 1 ? ar.wup : ar.wdown) + ((blk - 80) * 2 + wg) * 30720) : "memory");
        }
        return;
    }
    const uint64_t ef = policy_stream();
#pragma unroll 1
    for (int b = B_LATE; b < 16; b++) {
        w_flag_wait(b == 15 ? &g_flags.half[kp * 2 + wg] : &g_flags.pair[b * 16 + kp], b == 15 ? 2 : 4);
#pragma unroll 1
        for (int c = 0; c < 3; c++) {
            if (b > B_LATE) mbar_wait(bar + 24 + 8 * c, (b - B_LATE - 1) & 1);
            if (elect()) { mbar_expect(bar + 8 * c, 16384); tma3d_ef(sm + e_slot(wg, c), &mp.o15, b * 128 + wg * 64, kp * 6 + c * 2, bar + 8 * c, ef); }
            __syncwarp();
        }
    }
}
__device__ __forceinline__ void end_stores(const ChainMaps& mp, uint32_t sm, int blk, int wg) {
#pragma unroll 1
    for (int b = B_LATE; b < 16 && blk < 80; b++) {
        bar_sync(12 + wg, 160);
        if (elect()) tma3d_store(&mp.slab2, (b * KSPLIT + blk / 5) * 128 + wg * 64, blk % 5 * 2, sm + E_STG + wg * 16384, 0, false);
        BULK_COMMIT(); BULK_WAIT();
        if (b < 15) bar_arrive(10 + wg, 160);
        GPU_FENCE();
        w_bump(b < 14 ? &g_flags.o[b] : &g_flags.fin[((b - 14) * 2 + wg) * 32]);
    }
    bar_arrive(8, 320);
}
__device__ __forceinline__ void last_blocks(const ChainArgs& ar, uint32_t sm, int blk, int tid) {
    const int warp = __shfl_sync(0xffffffffu, tid >> 5, 0), lane = tid & 31, wg = warp >> 2, w = warp & 3;
    const uint32_t bar = sm + EB_A + wg * 48, stg = sm + E_STG + wg * 16384 + w * 2048;
    bar_sync(5, 384);
    EPT(tid == 128, 7);
    float acc[64];
#pragma unroll
    for (int n = 0; n < 64; n++) acc[n] = 0.f;
#pragma unroll 1
    for (int b = B_LATE; b < 16 && blk < 80; b++) {
#pragma unroll 1
        for (int c = 0; c < 6; c++) {
            mbar_wait(sm + EB_B + 8 * (c >= 3), 0); mbar_wait(bar + 8 * (c >> 1), (b - B_LATE) & 1);
            const uint64_t da = mkdesc(SM_BASE + e_slot(wg, c >> 1) + (c & 1) * 8192, 16, 1024), db = mkdesc(SM_BASE + E_B + (c >= 3 ? 24576 : 0) + c * 8192, 24576, 1024);
            WG_FENCE();
#pragma unroll
            for (int ks = 0; ks < 4; ks++) wgmma_ss_n128_tb(acc, da + ks * 2, db + ks * 128, c | ks);
            WG_COMMIT();
            WG_WAIT(1);
            if ((c & 1) == 0 && c && elect()) mbar_arrive(bar + 16 + 4 * c);
        }
        if (b > B_LATE) bar_sync(10 + wg, 160);
        WG_WAIT(0);
        if (elect()) mbar_arrive(bar + 40);
        EPT(tid == 128, 13 + 15 - b);
        const int r = lane & 7, mi = lane >> 3;
#pragma unroll
        for (int p = 0; p < 8; p++) {
            const int oc = 2 * p + (mi >> 1);
            stsm4(stg + (oc >> 3) * 8192 + ((mi & 1) * 8 + r) * 128 + (((oc & 7) ^ r) << 4), pack2(acc[8 * p], acc[8 * p + 1]), pack2(acc[8 * p + 2], acc[8 * p + 3]),
                  pack2(acc[8 * p + 4], acc[8 * p + 5]), pack2(acc[8 * p + 6], acc[8 * p + 7]));
        }
        PROXY_FENCE();
        bar_arrive(12 + wg, 160);
    }
    bar_sync(8, 320);
    if (TDEL && blk < 80) wait_until(clock() + TDEL);
    const int o = (tid >> 1) * FF + blk * 16 + (tid & 1) * 8;
    const bf16 *pg = ar.wgate + o, *pu = ar.wup + o, *pd = ar.wdown + tid * DM + (blk < 80 ? blk : 0) * 8;
#pragma unroll 1
    for (int i = 0; i < 6; i++) {
        const uint32_t d = sm + E_B + i * 4096 + tid * 16;
        if (i < 5) asm volatile("cp.async.cg.shared.global [%0], [%1], 16; cp.async.cg.shared.global [%0 + 20480], [%2], 16;" :: "r"(d), "l"(pg + i * 128 * FF), "l"(pu + i * 128 * FF) : "memory");
        asm volatile("cp.async.cg.shared.global [%0 + 40960], [%1], 16;" :: "r"(d), "l"(pd + i * 256 * DM) : "memory");
    }
    EPT(tid == 128, 8);
}
__device__ __forceinline__ void mod_tail(const ChainArgs& ar, const uint32_t tb, const uint32_t bar, const int blk, const int tid) {
#define TPROF(i) EPT(tid == 0, i)
    const int warp = __shfl_sync(0xffffffffu, tid >> 5, 0), lane = tid & 31, r = lane & 7, mi = lane >> 3;
    const uint32_t kb = tb + T_KEY;
    {
        uint32_t k[8];
        for (int n = 0;; n++) {
#pragma unroll
            for (int i = 0; i < 2; i++) asm volatile("ld.relaxed.gpu.global.v4.u32 {%0,%1,%2,%3}, [%4];" : "=r"(k[4 * i]), "=r"(k[4 * i + 1]), "=r"(k[4 * i + 2]), "=r"(k[4 * i + 3]) : "l"(g_key + warp * 256 + i * 128 + lane * 4) : "memory");
            if (__all_sync(0xffffffffu, (k[0] & k[1] & k[2] & k[3] & k[4] & k[5] & k[6] & k[7] & S_TOK) != 0)) break;
            if (n > (1 << 22)) __trap();
            __nanosleep(NAP);
        }
        const uint32_t m = __reduce_max_sync(0xffffffffu, max(umax3(k[0], k[1], k[2]), max(umax3(k[3], k[4], k[5]), max(k[6], k[7]))));
        asm volatile("st.shared.u32 [%0], %1; st.shared.u32 [%2], 0;" :: "r"(kb + warp * 4), "r"(m), "r"(kb + 32) : "memory");
        if (RPF && blk >= 93 && warp < 6) {
            uint32_t c = m;
#pragma unroll 1
            for (int it = 93; it < blk; it++) {
                uint32_t x = 0;
#pragma unroll
                for (int i = 0; i < 8; i++) x = max(x, k[i] < c ? k[i] : 0u);
                c = __reduce_max_sync(0xffffffffu, x);
            }
            if ((c & 2 * S_TOK) && lane < 2) asm volatile("cp.async.bulk.prefetch.L2.global [%0], 1280;" :: "l"((lane ? g_h2 : g_x1) + (~c & (S_TOK - 1)) * DM) : "memory");
        }
        asm volatile("cp.async.wait_all;" ::: "memory");
        bar_sync(1, 256);
        TPROF(1);
        const uint32_t low = __reduce_min_sync(0xffffffffu, lds32(kb + r * 4));
        uint32_t cnt = 0;
#pragma unroll
        for (int i = 0; i < 8; i++) cnt += k[i] >= low ? 4 : 0;
        if (cnt) {
            uint32_t a; asm volatile("atom.shared.add.u32 %0, [%1], %2;" : "=r"(a) : "r"(kb + 32), "r"(cnt) : "memory");
#pragma unroll
            for (int i = 0; i < 8; i++) if (k[i] >= low) { asm volatile("st.shared.u32 [%0], %1;" :: "r"(kb + 512 + a), "r"(k[i]) : "memory"); a += 4; }
        }
        if (tid == 0) mbar_arrive(bar);
        bar_sync(1, 256);
        const int nc = lds32(kb + 32);
#pragma unroll 1
        for (int c = lane * 4; c < nc; c += 128) {
            const uint32_t me = lds32(kb + 512 + c);
            int rank = 0;
#pragma unroll 2
            for (int e = 0; e < nc; e += 16) {
                const float4 z = lds128f(kb + 512 + e);
                rank += (__float_as_uint(z.x) > me) + (e + 4 < nc && __float_as_uint(z.y) > me) + (e + 8 < nc && __float_as_uint(z.z) > me) + (e + 12 < nc && __float_as_uint(z.w) > me);
            }
            if (rank < 8) asm volatile("st.shared.u32 [%0], %1;" :: "r"(kb + 64 + (warp * 8 + rank) * 4), "r"(me) : "memory");
        }
        __syncwarp();
    }
    const uint32_t k0 = lds32(kb + 64 + (warp * 8 + r) * 4), k1 = lds32(kb + 64 + (warp * 8 + (lane >> 2)) * 4);
    TPROF(2);
    const int trow = ~k1 & (S_TOK - 1), tcol = (blk < 80 ? blk : 0) * 8 + (lane & 3) * 2;
    uint2 xb[5];
#pragma unroll
    for (int h = 0; h < 5; h++) xb[h] = __ldcg((const uint2*)(g_h2 + trow * DM + (warp * 5 + h) * 16 + (lane & 3) * 4));
    const uint32_t fx1 = __ldcg((const uint32_t*)(g_x1 + trow * DM + tcol)), fh2 = __ldcg((const uint32_t*)(g_h2 + trow * DM + tcol)),
                   fgb = __ldcg((const uint32_t*)(g_mod + 5 * DM + tcol));
    const float fr = __uint_as_float(((int)k1 < 0 ? k1 ^ 0x80000000u : ~k1) & 0xffff0000u);
    {
        float dg[4] = {0, 0, 0, 0}, du[4] = {0, 0, 0, 0};
        uint32_t ag[5][4], au[5][4];
#pragma unroll
        for (int h = 0; h < 5; h++) {
            const uint32_t o = tb + ((warp * 5 + h) * 16 + (r >> 1) * 4 + (mi >> 1) * 2 + (r & 1)) * 32 + (mi & 1) * 16;
            ldsm4t(ag[h], o + T_WG); ldsm4t(au[h], o + T_WU);
        }
#pragma unroll
        for (int h = 0; h < 5; h++) { mma16q(dg, ag[h], xb[h].x, xb[h].y); mma16q(du, au[h], xb[h].x, xb[h].y); }
        TPROF(3);
        sts128f(tb + T_RED + warp * 1024 + lane * 16, dg[0], dg[1], dg[2], dg[3]); sts128f(tb + T_RED + warp * 1024 + 512 + lane * 16, du[0], du[1], du[2], du[3]);
    }
    bar_sync(1, 256);
    if (warp < 2) {
        float g2[2] = {0, 0}, u2[2] = {0, 0};
#pragma unroll
        for (int i = 0; i < 8; i++) {
            const float2 a = lds64f(tb + T_RED + i * 1024 + lane * 16 + warp * 8), b = lds64f(tb + T_RED + i * 1024 + 512 + lane * 16 + warp * 8);
            g2[0] += a.x; g2[1] += a.y; u2[0] += b.x; u2[1] += b.y;
        }
        float y[2];
#pragma unroll
        for (int i = 0; i < 2; i++) { const float gq = bfr(g2[i]); y[i] = bfr(__fdividef(gq, 1.f + __expf(-gq))) * bfr(u2[i]); }
        asm volatile("st.relaxed.gpu.global.u32 [%0], %1;" :: "l"(g_gu + (blk >> 1) * 128 + lane * 4 + warp * 2 + (blk & 1)), "r"(movm_t(pack2(y[0], y[1]))) : "memory");
    }
    TPROF(4);
    if (blk < 80) {
        uint32_t a[6][4], b[6][4];
#pragma unroll
        for (int k2 = 0; k2 < 6; k2++) ldsm4t(b[k2], tb + T_WD + (warp * 6 + k2) * 512 + lane * 16);
        for (int n = 0;; n++) {
            uint32_t m = 0;
#pragma unroll
            for (int k2 = 0; k2 < 6; k2++) asm volatile("ld.relaxed.gpu.global.v4.u32 {%0,%1,%2,%3}, [%4];" : "=r"(a[k2][0]), "=r"(a[k2][1]), "=r"(a[k2][2]), "=r"(a[k2][3]) : "l"(g_gu + (warp * 6 + k2) * 128 + lane * 4) : "memory");
#pragma unroll
            for (int k2 = 0; k2 < 6; k2++) m = umax3(umax3(m, a[k2][0], a[k2][1]), a[k2][2], a[k2][3]);
            if (!__any_sync(0xffffffffu, m == ~0u)) break;
            if (n > (1 << 22)) __trap();
        }
        TPROF(5);
        float d[2][4] = {{0, 0, 0, 0}, {0, 0, 0, 0}};
#pragma unroll
        for (int k2 = 0; k2 < 6; k2++) { mma16q(d[0], a[k2], b[k2][0], b[k2][1]); mma16q(d[1], a[k2], b[k2][2], b[k2][3]); }
        asm volatile("st.shared.v2.f32 [%0], {%1,%2};" :: "r"(tb + T_X + warp * 256 + lane * 8), "f"(d[0][0] + d[1][2]), "f"(d[0][1] + d[1][3]) : "memory");
        bar_sync(1, 256);
        if (warp == 0) {
            float y0 = 0, y1 = 0;
#pragma unroll
            for (int i = 0; i < 8; i++) { const float2 z = lds64f(tb + T_X + i * 256 + lane * 8); y0 += z.x; y1 += z.y; }
            const float sg = __fdividef(1.f, 1.f + __expf(-fr));
            *(uint32_t*)(ar.out + trow * DM + tcol) = add2(fx1, mul2(fgb, add2(fh2, mul2(pack2(y0, y1), pack2(sg, sg)))));
        }
    }
    TPROF(6);
}

__global__ void __cluster_dims__(3, 1, 1) __launch_bounds__(384, 1) k_chain(const __grid_constant__ ChainMaps mp, const __grid_constant__ ChainArgs ar) {
    const int D1 = ar.D1, DG = ar.DG;
    extern __shared__ __align__(1024) uint8_t smraw[];
    const uint32_t sm = SM_BASE + ((blockIdx.x % 3) << 24);
    if (smem_u32(smraw) != sm) __trap();
    uint32_t tid; asm volatile("mov.u32 %0, %%tid.x;" : "=r"(tid));
    const int warp = __shfl_sync(0xffffffffu, tid >> 5, 0), lane = tid & 31, wg = warp >> 2, w = warp & 3;
    const int blk = blockIdx.x, head = blk / 3, j = blk % 3;
    const int col0 = head * DH + j * 64;
    asm volatile("griddepcontrol.launch_dependents;");
#define PPROF(i)
    const int r = lane & 7, mi = lane >> 3;
    const uint32_t memrd = opaque(sm + C_MEM + lane * 16);
    if (wg < 2) {
        {
            uint32_t xv[3][10];
            const int row = blk * 8 + warp, nq = row < S_TOK - 1536 ? 3 : 2;
#pragma unroll
            for (int i = 0; i < 15; i++) {
                const uint2 v = __ldcs((const uint2*)(ar.x + (row + (i < 10 || nq == 3 ? i / 5 * 768 : 0)) * DM + lane * 4 + i % 5 * 128));
                xv[i / 5][i % 5 * 2] = v.x; xv[i / 5][i % 5 * 2 + 1] = v.y;
            }
            if (tid == 32) {
#pragma unroll 1
                for (int c = 0; c < 14; c++) if (c != 12) mbar_init(sm + C_BAR + 8 * c, c == 2 ? 5 : c == 3 ? 6 : 1);
                asm volatile("fence.mbarrier_init.release.cluster;" ::: "memory");
                mbar_expect(sm + CB_SC, 2560); mbar_expect(sm + CB_OX, 2048);
            }
            if (warp == 2) {
                const uint32_t f = blk >= 28 ? ~0u : 0u;
                ((uint4*)g_acc)[blk * 32 + lane] = make_uint4(0, 0, 0, 0);
                if (blk < 76) (blk < 12 ? (uint4*)g_stamp + blk * 32 : blk < 28 ? (uint4*)g_key + (blk - 12) * 32 : (uint4*)g_gu + (blk - 28) * 32)[lane] = make_uint4(f, f, f, f);
            }
            __syncwarp();
            asm volatile("barrier.cluster.arrive.relaxed.aligned;" ::: "memory");
            PPROF(8);
#pragma unroll 1
            for (int q = 0; q < 3; q++) {
                uint32_t nv[10];
                ln_norm(xv[0], nv);
#pragma unroll
                for (int i = 0; i < 10; i++) { xv[0][i] = xv[1][i]; xv[1][i] = xv[2][i]; xv[2][i] = nv[i]; }
            }
            PPROF(9);
            if (warp < 5) {
                uint4 u;
                for (int n = 0;; n++) {
                    asm volatile("ld.relaxed.gpu.global.v4.u32 {%0,%1,%2,%3}, [%4];" : "=r"(u.x), "=r"(u.y), "=r"(u.z), "=r"(u.w) : "l"(g_flags.mod1 + tid * 4) : "memory");
                    if (__all_sync(0xffffffffu, u.x && u.y && u.z && u.w)) break;
                    cut(n, 1 << 22);
                }
                asm volatile("st.shared.v4.u32 [%0], {%1,%2,%3,%4};" :: "r"(sm + C_KX + tid * 16), "r"(~u.x), "r"(~u.y), "r"(~u.z), "r"(~u.w) : "memory");
            }
            bar_sync(8, 256);
            PPROF(2);
            uint32_t m = 0;
#pragma unroll
            for (int i = 0; i < 5; i++) {
                uint32_t t[2], u[2];
                lds64(t, sm + C_KX + lane * 8 + i * 256); lds64(u, sm + C_KX + 1280 + lane * 8 + i * 256);
                u[0] = add2(u[0], 0x3f803f80u); u[1] = add2(u[1], 0x3f803f80u);
                m = amax2(amax2(amax2(amax2(m, t[0]), u[0]), t[1]), u[1]);
#pragma unroll
                for (int q = 0; q < 3; q++)
                    if (q < nq) *(uint2*)(g_h + (row + q * 768) * DM + lane * 4 + i * 128) = make_uint2(add2(mul2(xv[q][2 * i], u[0]), t[0]), add2(mul2(xv[q][2 * i + 1], u[1]), t[1]));
            }
            asm volatile("st.shared.u32 [%0], %1;" :: "r"(sm + C_LAG), "r"((amax_warp(m) >> 7) + 1) : "memory");
            bar_sync(8, 256);
            if (tid == 0) flag_add(&g_flags.h);
            __syncwarp();
            bar_arrive(2, 288);
            PPROF(3);
            asm volatile("barrier.cluster.wait.aligned;" ::: "memory");
        }
        asm volatile("setmaxnreg.inc.sync.aligned.u32 %0;" :: "n"(REG_P));
        uint32_t wa[40][4];
        mbar_wait(sm + CB_W, 0);
#pragma unroll
        for (int ks = 0; ks < 40; ks++)
            ldsm4t(wa[ks], sm + ((wg == 0) == (ks < 20) ? C_WV : C_WO) + ((mi >> 1) * 8 + r) * 128 + (((2 * w + (mi & 1)) ^ r) << 4) + (ks % 20 / 4 * 8 + 4 * wg + (ks & 3)) * 2048);
        PPROF(5);
        bar_arrive(1, 288);
        const uint32_t qst = opaque(sm + (wg == 0 ? C_QM : C_KM) + (2 * w + (mi & 1)) * 128 + r * 16);
        const uint32_t vrd = opaque(sm + C_WV + ((mi >> 1) * 8 + r) * 128 + (((2 * w + (mi & 1)) ^ r) << 4) + 4 * wg * 2048);
        const uint32_t mrd = opaque(memrd + wg * 1024);
        float acc[16];
        auto fb = [&](int n) { return mrd + (n >> 1) * 2048 + (n & 1) * 512; };
        auto fa = [&](int k) { return vrd + (k >> 2) * 16384 + (k & 3) * 2048; };
        auto qk_out = [&](int n) {
            uint8_t* rec = g_att + (n * NH + head) * AT_REC;
            w_bulk_s2g(rec + j * 8192, sm + C_QX, 8192); w_bulk_s2g(rec + AT_KM + j * 1024, sm + C_KM, 1024);
            BULK_COMMIT();
        };
        for (int s = -1;; s++) {
          if (s >= 0) {
            uint32_t b[3][4], a[4][4];
            x_part([&]() {
                if (AIN && s == 0) mbar_wait(sm + CB_W2, 0);
#pragma unroll
                for (int i = 0; i < AIN; i++) ldsm4t(a[i], fa(4 + i));
            }, acc, wa, sm, s, wg, w, opaque(mrd) >> 4 & 31, s + ar.D2);
            if (!AIN && s == 0) mbar_wait(sm + CB_W2, 0);
#pragma unroll
            for (int i = AIN; i < APRE; i++) ldsm4t(a[i], fa(4 + i));
            cut(s + ar.D2, 0);
            bar_sync(1, 384);
            if (warp == 0) { PROF(0); PROFG(24); }
            float dv[4] = {0, 0, 0, 0};
            const uint32_t xb = mrd - wg * 1024 - (C_MEM - C_VP) + w * 512;
            {
                float d[2][4] = {{0, 0, 0, 0}, {0, 0, 0, 0}}, g[2][4] = {{0, 0, 0, 0}, {0, 0, 0, 0}};
                ldsm4t(b[0], fb(0)); pin0(mrd); ldsm4t(b[1], fb(1)); pin0(mrd);
#pragma unroll
                for (int n = 0; n < 10; n++) {
                    const int c1 = n >= 10 - NCH;
                    if (n < 8) ldsm4t(b[(n + 2) % 3], fb(n + 2));
                    if (n < 2 && 2 * n >= APRE) { ldsm4t(a[2 * n], fa(4 + 2 * n)); ldsm4t(a[2 * n + 1], fa(5 + 2 * n)); }
#pragma unroll
                    for (int e = 0; e < 2; e++) {
                        mma16q(g[e & c1], wa[20 + 2 * n + e], b[n % 3][2 * e], b[n % 3][2 * e + 1]); mma16q(d[e & c1], wa[2 * n + e], b[n % 3][2 * e], b[n % 3][2 * e + 1]);
                        if (n >= 2 && n < 10 - VT) mma16q(dv, a[(2 * n + e) & 3], b[n % 3][2 * e], b[n % 3][2 * e + 1]);
                        if (n >= 2 && n < 8) ldsm4t(a[(2 * n + e) & 3], fa(2 * n + 4 + e));
                    }
                    if (QCUT >> n & 1) cut(s + ar.D2, 1 + n);
                }
                const float un = __uint_as_float(lds32(sm + C_UN));
                sts128f(xb - 4096 + wg * 2048, g[0][0] + g[1][0], g[0][1] + g[1][1], g[0][2] + g[1][2], g[0][3] + g[1][3]);
#pragma unroll
                for (int k = 20 - 2 * VT; k < 20; k++) mma16q(dv, a[k & 3], b[k / 2 % 3][2 * (k & 1)], b[k / 2 % 3][2 * (k & 1) + 1]);
                if (PBAR) bar_sync(10 + w, 64); else bar_sync(8, 256);
                const float4 z = lds128f(xb - 4096 + (wg ^ 1) * 2048);
                sts128f(xb + wg * 2048, dv[0], dv[1], dv[2], dv[3]);
                stsm2t(qst, pack2((d[0][0] + d[1][0] + z.x) * un, (d[0][1] + d[1][1] + z.y) * un), pack2((d[0][2] + d[1][2] + z.z) * un, (d[0][3] + d[1][3] + z.w) * un));
            }
            bar_arrive(2, 384);
            if (w == 0) PROF(1 + wg);
            if (s + 1 == NSEG) break;
          }
          if (!STL && warp == 3 && s >= 0)
              asm volatile(ELECTED("st.relaxed.gpu.global.u32 [%0], %1;") :: "l"(g_stamp + (s & 3) * 384 + (blk >> 3) * 32 + (blk & 7)), "r"((gtime() & ~31u) | ((s >> 2) + 1)) : "memory");
          PROXY_FENCE();
          mbar_wait(sm + CB_XF, (s + 1) & 1);
          if (s >= 0) bar_sync(7, 384);
          WG_FENCE();
#pragma unroll
          for (int i = 0; i < 16; i++) acc[i] = 0.f;
#pragma unroll
          for (int i = 1; i <= XA; i++) x_chunk(acc, wa, x_base(wg, s + ar.D2, 20), 20, i, i == 1);
          WG_COMMIT();
          if (warp == FW && s > 1) {
              if ((s & 3) == 0) { GPU_FENCE(); if (!BDEF) w_bump(&g_flags.qk[(s >> 2) - 1]); }
              if (BDEF && (s & 3) == 1) w_bump(&g_flags.qk[(s >> 2) - 1]);
              if (F61 && s == 62) seg_done(61, head);
          }
          if (!WLATE) WG_WAIT(0);
          if (s >= 0) {
            if (warp == 0) {
                PROF(7);
                if (elect()) x_rest(mp, sm, s + 1);
            } else {
                if (wg == 1) {
                    if (w == 1) {
                        if (QDEL) wait_until(clock() + QDEL);
                        qk_out(s);
                    }
                    if (w == 2 && blk < 20 && (s & 1) && s + 3 < NSEG)
                        asm volatile(ELECTED("cp.async.bulk.prefetch.L2.global [%0], 4096;") :: "l"((const uint8_t*)g_h + (s + 3) * (SEG * DM * 2) + blk * 4096) : "memory");
                } else if (w == 3) {
                    if (SPOLL) wait_until(clock() + SPOLL);
                    const uint32_t l = opaque(mrd) >> 4 & 31, tag = (s >> 2) + 1, now = gtime();
                    const uint32_t* sp = g_stamp + (s & 3) * 384 + (l >> 3) * 32 + (l & 7);
                    uint32_t t[3];
                    for (int n = 0;; n++) {
#pragma unroll
                        for (int i = 0; i < 3; i++) t[i] = ld_rlx(sp + i * 128);
                        if (!__any_sync(0xffffffffu, ((t[0] ^ tag) | (t[1] ^ tag) | (t[2] ^ tag)) & 31) || n > SPIN_LIMIT) break;
                    }
                    int all = -(1 << 30), own = all;
#pragma unroll
                    for (int i = 0; i < 3; i++) { const int d = t[i] - now; all = max(all, d); if ((i * 32 + l) / 3 == head) own = d; }
                    const int lag = min(__reduce_max_sync(0xffffffffu, all) - __reduce_max_sync(0xffffffffu, own), s || STL == 1 ? 8000 : 200);
                    PROFV(15, lag);
                    asm volatile("st.shared.u32 [%0], %1;" :: "r"(sm + C_LAG), "r"(D1 + ((lag * DG) >> 4)) : "memory");
                    bar_arrive(6, 160);
                } else if (w == 2) {
                    if ((s & 3) == 3) w_flag_wait(&g_flags.v[((s + 1) >> 2) * 32 + head], 2);
                    if (elect()) { mbar_expect(sm + CB_VX, 4096); bulk_g2s(sm + C_VX, g_att + ((s + 1) * NH + head) * AT_REC + AT_V + j * 4096, 4096, sm + CB_VX); }
                    if ((s & 3) == 1 && s + 3 < NSEG && blk == 20) asm volatile(ELECTED("cp.async.bulk.prefetch.L2.global [%0], 128;") :: "l"(&g_flags.v[((s + 3) >> 2) * 32]) : "memory");
                    if (s + 2 < NSEG && (s & 3) && ((s & 3) != 2 || __all_sync(0xffffffffu, ld_rlx(&g_flags.v[((s + 2) >> 2) * 32 + head]) >= 2))) {
                        const uint8_t* p = g_att + ((s + 2) * NH + head) * AT_REC + AT_V + j * 4096;
                        asm volatile(ELECTED("cp.async.bulk.prefetch.L2.global [%0], 4096;") :: "l"(p) : "memory");
                        if ((s & 3) == 3) asm volatile(ELECTED("cp.async.bulk.prefetch.L2.global [%0], 4096;") :: "l"(p + NH * AT_REC) : "memory");
                    }
                }
            }
          }
          if (WLATE) WG_WAIT(0);
        }
        PROXY_FENCE();
        bar_sync(8, 256);
        if (warp == 5) { qk_out(NSEG - 1); BULK_WAIT(); }
        if (warp == 7) { seg_done(NSEG - 2, head); if (!F61) w_bump(&g_flags.seg[32 + head]); }
        const int t2 = (opaque(mrd) >> 4 & 31) + warp * 32;
        EPT(t2 == 0, 0);
        last_blocks(ar, sm, blk, t2);
        mod_tail(ar, sm + E_B, sm + EB_REL, blk, t2);
    } else {
        asm volatile("setmaxnreg.dec.sync.aligned.u32 %0;" :: "n"(REG_L));
        asm volatile("barrier.cluster.arrive.relaxed.aligned;" ::: "memory");
        if (blk < 80) {
            const int t = tid - 256;
#pragma unroll 1
            for (int i = 0; i < 10; i++)
                asm volatile("cp.async.cg.shared.global.L2::128B [%0], [%1], 16;" :: "r"(sm + C_XR + i * 2048 + t * 16), "l"(ar.wmod + ((t >> 1) + 64 * i) * (6 * DM) + blk * 16 + (t & 1) * 8) : "memory");
            float cs[5];
#pragma unroll
            for (int i = 0; i < 5; i++) cs[i] = __uint_as_float((uint32_t)__ldg((const unsigned short*)ar.c + t + 128 * i) << 16);
#pragma unroll
            for (int i = 0; i < 5; i++) asm volatile("st.shared.f32 [%0], %1;" :: "r"(sm + C_QX + (t + 128 * i) * 4), "f"(bfr(__fdividef(cs[i], 1.f + __expf(-cs[i])))) : "memory");
            asm volatile("cp.async.wait_all;" ::: "memory");
            bar_sync(3, 128);
            float a0 = 0, a1 = 0;
#pragma unroll 8
            for (int i = 0; i < 40; i++) {
                const float f = __uint_as_float(lds32(sm + C_QX + (t >> 3) * 4 + i * 64));
                const uint32_t u = lds32(sm + C_XR + t * 4 + i * 512);
                a0 += f * lo_f(u); a1 += f * hi_f(u);
            }
#pragma unroll
            for (int o = 8; o < 32; o <<= 1) { a0 += __shfl_xor_sync(0xffffffffu, a0, o); a1 += __shfl_xor_sync(0xffffffffu, a1, o); }
            asm volatile("st.shared.v2.f32 [%0], {%1,%2};" :: "r"(sm + C_QM + w * 64 + (lane & 7) * 8), "f"(a0), "f"(a1) : "memory");
            bar_sync(3, 128);
            if (w == 0) {
#pragma unroll
                for (int i = 1; i < 4; i++) { const float2 z = lds64f(sm + C_QM + i * 64 + (lane & 7) * 8); a0 += z.x; a1 += z.y; }
                const uint32_t v = pack2(a0, a1);
                asm volatile("st.relaxed.gpu.global.u32 [%0], %1;" :: "l"(g_flags.mod1 + blk * 8 + (lane & 7)), "r"(~v) : "memory");
            }
        }
        uint32_t m0[5][4], mm = 0;
#pragma unroll
        for (int i = 0; i < 20; i++) {
            const unsigned short* p = (const unsigned short*)ar.mem0 + (i & 3) * 2 * DM + (i >> 2) * 128 + tid - 256;
            m0[i >> 2][i & 3] = __ldg(p) | (uint32_t)__ldg(p + DM) << 16;
        }
        {
            asm volatile("barrier.cluster.wait.aligned;" ::: "memory");
            if (w == 3) {
                w_flag_wait(&g_flags.h, 96);
                if (elect()) { x_fill(mp, sm, 0, j); x_rest(mp, sm, 0); }
                __syncwarp();
            }
            if (w == 1) {
                const uint64_t ef = policy_stream();
#pragma unroll 1
                for (int c = 0; c < 2 * WP + 2; c++) {
                    const uint32_t bar = sm + EB_B + 8 * (c & 1);
                    if (c == WPOS) bar_sync(2, 288);
                    if (c >= 2) mbar_wait(bar, (c / 2 - 1) & 1);
                    if (elect()) {
                        if (c < 2 * WP) { mbar_expect(bar, 81920 / WP); tma2d_ef(sm + C_WV + c * (81920 / WP), c < WP ? &mp.wq : &mp.wk, col0, c % WP * (640 / WP), bar, ef); }
                        if (c == 2 * WP + 1) mbar_arrive(sm + CB_W);
                    }
                    __syncwarp();
                }
                bar_sync(1, 288);
                if (elect()) {
                    mbar_expect(sm + CB_W2, 81920); mbar_expect(sm + CB_W3, 3 * WO_BLK);
#pragma unroll 1
                    for (int c = 0; c < 4; c++) tma2d(sm + C_WV + c * 20480, &mp.wv, col0, c * 160, sm + CB_W2);
#pragma unroll 1
                    for (int c = 0; c < 3; c++) tma3d(sm + C_WO + c * WO_BLK, &mp.wo, head * DH + (j + c) % 3 * 64, 7 * j, sm + CB_W3);
                }
                __syncwarp();
            } else {
                uint32_t mw = 0;
#pragma unroll 1
                for (int c = 0; c < 2; c++) {
                    mbar_wait(sm + (c ? CB_W3 : CB_W2), 0);
                    uint32_t m = 0;
                    const uint32_t end = sm + (c ? C_XR : C_WO);
#pragma unroll 1
                    for (uint32_t a = sm + c * C_WO + (w - (w > 0)) * 4096 + lane * 16; a < end; a += 3 * 4096) {
                        float4 z[8];
#pragma unroll
                        for (int i = 0; i < 8; i++) z[i] = lds128f(a + i * 512);
#pragma unroll
                        for (int i = 0; i < 8; i++) m = amax2(amax2(amax2(amax2(m, __float_as_uint(z[i].x)), __float_as_uint(z[i].y)), __float_as_uint(z[i].z)), __float_as_uint(z[i].w));
                    }
                    mw |= amax_warp(m) << (16 * c);
                }
                asm volatile("st.shared.u32 [%0], %1;" :: "r"(sm + C_KM + w * 4), "r"(mw) : "memory");
                bar_sync(3, 96);
                if (w == 0) asm volatile("st.relaxed.gpu.global.u32 [%0], %1;" :: "l"(g_flags.wmax + blk), "r"(amax2(amax2(mw, lds32(sm + C_KM + 8)), lds32(sm + C_KM + 12)) | 0x8000) : "memory");
            }
        }
        bar_sync(9, 384);
#pragma unroll
        for (int i = 0; i < 5; i++) {
            asm volatile("st.shared.v4.u32 [%0], {%1,%2,%3,%4};" :: "r"(sm + C_MEM + (tid - 256 + i * 128) * 16), "r"(m0[i][0]), "r"(m0[i][1]), "r"(m0[i][2]), "r"(m0[i][3]) : "memory");
            mm = amax2(amax2(amax2(amax2(mm, m0[i][0]), m0[i][1]), m0[i][2]), m0[i][3]);
        }
        asm volatile("st.shared.u32 [%0], %1; st.shared.u32 [%2], 0x3f800000;" :: "r"(sm + C_MX + w * 4), "r"(amax_warp(mm)), "r"(sm + C_UN) : "memory");
        int ew = __shfl_sync(0xffffffffu, lds32(sm + C_LAG), 0), es = 0;
        const uint32_t rb1 = (uint32_t)((j + 1) % 3 - j) << 24, rb2 = (uint32_t)((j + 2) % 3 - j) << 24;
        const float scale = 0.07216878364870322f;
        uint32_t va[8][4], mr = memrd;
#pragma unroll
        for (int i = 0; i < 8; i++) ldsm4t(va[i], sm + C_WV + ((mi >> 1) * 8 + r) * 128 + (((2 * w + (mi & 1)) ^ r) << 4) + i * 2048);
        bar_sync(1, 384);
        if (w == 0) {
            w_flag_wait(&g_flags.v[head], 2);
            if (elect()) { mbar_expect(sm + CB_VX, 4096); bulk_g2s(sm + C_VX, g_att + head * AT_REC + AT_V + j * 4096, 4096, sm + CB_VX); }
        }
        for (int s = 0; s < NSEG; s++) {
            const float un = __uint_as_float((127 - es) << 23);
            if (w == 1) {
                mbar_wait(sm + CB_XD, s & 1);
                if (s + 1 < NSEG) { if (elect()) x_fill(mp, sm, s + 1, j); }
                else { if (BPOS != 2) wo_half(mp, sm, blk, 0); if (BPOS != 0) wo_half(mp, sm, blk, 1); }
            }
            if (STL == 2 && w == 3) asm volatile(ELECTED("st.relaxed.gpu.global.u32 [%0], %1;") :: "l"(g_stamp + (s & 3) * 384 + (blk >> 3) * 32 + (blk & 7)), "r"((gtime() & ~31u) | ((s >> 2) + 1)) : "memory");
            const uint32_t l0 = mr >> 4 & 31, r0 = l0 & 7, m0 = l0 >> 3;
            float vd[4];
            {
                uint32_t c[4][4];
#pragma unroll
                for (int i = 0; i < 4; i++) ldsm4t(c[i], mr + i * 512);
                float d[2][4] = {{0, 0, 0, 0}, {0, 0, 0, 0}};
#pragma unroll
                for (int i = 0; i < 8; i++) mma16q(d[i & 1], va[i], c[i >> 1][2 * (i & 1)], c[i >> 1][2 * (i & 1) + 1]);
#pragma unroll
                for (int i = 0; i < 4; i++) vd[i] = d[0][i] + d[1][i];
            }
            uint32_t zr = 0;
            if (w == 2)
                asm volatile("atom.relaxed.gpu.global.exch.b32 %0, [%1], 0;" : "=r"(zr)
                    : "l"(g_acc + ((s & 2) ^ 2) * (ACC_PAIR / 2) + (s & 1) * 512 + (blk >> 2) * 1024 + (blk & 3) * 128 + l0 * 4) : "memory");
            __syncwarp();
            uint32_t kb[4][4] = {};
            {
                const uint32_t k7 = r0 ^ (m0 << 2 & 4), kxrd = sm + C_KX + (16 * (w & 1) + 8 * (m0 & 1) + k7) * 128 + (((m0 >> 1) ^ k7) << 4);
#pragma unroll
                for (int i = 0; i < 4; i++) if (w >= 2) ldsm4(kb[i], kxrd ^ (i << 5));
            }
            const uint32_t qrd = sm + C_QM + (w == 1 ? (m0 & 1) * 2 + (m0 >> 1) : m0) * 128 + r0 * 16;
            const uint32_t scdst = sm + C_SC + j * 1280 + (w == 1 ? 1024 + l0 * 8 : (w & 1) * 512 + (l0 & 2) * 128 + (l0 >> 2) * 32 + (l0 & 1) * 16);
            const uint32_t scrd = sm + C_SC + (l0 >> 4) * 256 + (l0 & 3) * 32 + (l0 >> 2 & 3) * 8;
            const uint32_t v7 = (4 * (m0 & 1) + (r0 >> 1)) ^ (r0 << 2 & 4), vxrd = sm + C_VX + (16 * (m0 >> 1) + 8 * (r0 & 1) + v7) * 128 + (((2 * w) ^ v7) << 4);
            if (s == 0) {
                uint32_t t[3];
                for (int n = 0;; n++) {
#pragma unroll
                    for (int i = 0; i < 3; i++) t[i] = ld_rlx(g_flags.wmax + l0 + 32 * i);
                    if (__all_sync(0xffffffffu, t[0] && t[1] && t[2])) break;
                    cut(n, 1 << 22);
                }
                const uint32_t m = amax2(amax2(amax2(0, t[0]), t[1]), t[2]);
                const int e = 371 - (int)(__reduce_max_sync(0xffffffffu, m & 0xffffu) >> 7) - (int)(__reduce_max_sync(0xffffffffu, m >> 16) >> 7);
                ew = e << 16 | (min(e - ew, 100) & 0xffff);
            }
            mbar_wait(sm + CB_VX, s & 1);
            uint32_t vb[2][4];
            ldsm4t(vb[0], vxrd); ldsm4t(vb[1], vxrd ^ 16);
            const uint32_t word = sm + C_WO + (m0 & 1) * 4096 + ((m0 >> 1) * 8 + r0) * 64 + ((w ^ (r0 >> 1)) << 4);
            const uint32_t word6 = word + 6 * 4096 - (m0 & 1) * 3072;
            const uint32_t oxrd = sm + C_OX + l0 * 8;
            const uint32_t ord = oxrd + w * 256;
            const uint32_t vp = mr - (C_MEM - C_VP) + w * 512, vmst = mr + (C_VM - C_MEM) + w * 256;
            pin(mr, scdst + rb1, sm + CB_SC + rb1, scdst + rb2, sm + CB_SC + rb2); pin(mr, qrd, scdst, scrd, vp); pin(mr, word, word6, oxrd, ord);
            pin(mr, __float_as_uint(vd[0]), __float_as_uint(vd[1]), __float_as_uint(vd[2]), __float_as_uint(vd[3]));
            bar_sync(2, 384);
            const bool odd = mr & 16;
            float4 y0, y1, mx4;
            if (s + 1 == NSEG) {
                y0 = lds128f(vp); y1 = lds128f(vp + 2048);
                stsm2t(vmst, pack2((vd[0] + y0.x + y1.x) * un, (vd[1] + y0.y + y1.y) * un), pack2((vd[2] + y0.z + y1.z) * un, (vd[3] + y0.w + y1.w) * un));
                PROXY_FENCE();
                bar_sync(3, 128);
                if (w == 1) { w_bulk_s2g(g_att + (s * NH + head) * AT_REC + AT_VM + j * 1024, sm + C_VM, 1024); BULK_COMMIT(); BULK_WAIT(); }
                break;
            }
            {
                uint32_t qa[2][4];
                ldsm4(qa[0], qrd); ldsm4(qa[1], qrd + 512);
                float sc[2][4] = {{0, 0, 0, 0}, {0, 0, 0, 0}};
                if (w == 1) {
                    ldsm4(kb[0], mr + (C_KM - C_MEM)); ldsm4(kb[1], mr + (C_KM - C_MEM) + 512);
                    pin0(mr); y0 = lds128f(vp); y1 = lds128f(vp + 2048); mx4 = lds128f(sm + C_MX);
#pragma unroll
                    for (int k = 0; k < 4; k++) mma16q(sc[k & 1], qa[k >> 1], kb[k >> 1][2 * (k & 1)], kb[k >> 1][2 * (k & 1) + 1]);
                    const uint32_t a0 = __float_as_uint(sc[0][0] + sc[1][2]), a1 = __float_as_uint(sc[0][1] + sc[1][3]);
                    if (B7E) { pin(mr, a0, a1, __float_as_uint(y1.x), 0); bar_arrive(7, 384); }
                    send8(scdst + rb1, sm + CB_SC + rb1, a0, a1); send8(scdst + rb2, sm + CB_SC + rb2, a0, a1);
                    asm volatile("st.shared.v2.u32 [%0], {%1,%2};" :: "r"(scdst), "r"(a0), "r"(a1) : "memory");
                } else {
                    pin0(mr); y0 = lds128f(vp); y1 = lds128f(vp + 2048); mx4 = lds128f(sm + C_MX);
                    if (!w) {
                        if (B7E) { pin(mr, __float_as_uint(y1.x), 0, 0, 0); bar_arrive(7, 384); }
                        if (STL == 1) asm volatile(ELECTED("st.relaxed.gpu.global.u32 [%0], %1;") :: "l"(g_stamp + (s & 3) * 384 + (blk >> 3) * 32 + (blk & 7)), "r"((gtime() & ~31u) | ((s >> 2) + 1)) : "memory");
                    } else {
#pragma unroll
                        for (int k = 0; k < 4; k++) mma16q(sc[k & 1], kb[k], qa[k >> 1][2 * (k & 1)], qa[k >> 1][2 * (k & 1) + 1]);
                        const float a0 = sc[0][0] + sc[1][0], a1 = sc[0][2] + sc[1][2], a2 = sc[0][1] + sc[1][1], a3 = sc[0][3] + sc[1][3];
                        if (B7E) { pin(mr, __float_as_uint(a0), __float_as_uint(y1.x), 0, 0); bar_arrive(7, 384); }
                        send16(scdst + rb1, sm + CB_SC + rb1, a0, a1, a2, a3); send16(scdst + rb2, sm + CB_SC + rb2, a0, a1, a2, a3);
                        sts128f(scdst, a0, a1, a2, a3);
                    }
                }
            }
            if (!B7E) bar_arrive(7, 384);
            __syncwarp();
            if (elect()) mbar_arrive(sm + CB_SC);
            {
                const float4 z = mx4;
                const int em = (int)(max(max(__float_as_uint(z.x), __float_as_uint(z.y)), max(__float_as_uint(z.z), __float_as_uint(z.w))) >> 7) - es;
                es = __shfl_sync(0xffffffffu, max(min((ew >> 16) - em, (int)(short)ew), -120), 0);
            }
            if (w == 0) PROF(4);
            const uint32_t vm0 = pack2((vd[0] + y0.x + y1.x) * un, (vd[1] + y0.y + y1.y) * un), vm1 = pack2((vd[2] + y0.z + y1.z) * un, (vd[3] + y0.w + y1.w) * un);
            stsm2t(vmst, vm0, vm1);
            cut(s + ar.D2, 0);
            mbar_wait(sm + CB_SC, s & 1);
            if (w == 0) PROF(8);
            float sv[10];
            {
                float2 z[5][3];
#pragma unroll
                for (int u = 0; u < 5; u++)
#pragma unroll
                    for (int p = 0; p < 3; p++) z[u][p] = lds64f((u < 4 ? scrd + (u >> 1) * 512 + (u & 1) * 128 : oxrd + (C_SC - C_OX) + 1024) + p * 1280);
#pragma unroll
                for (int u = 0; u < 5; u++) { sv[2 * u] = (z[u][0].x + z[u][1].x) + z[u][2].x; sv[2 * u + 1] = (z[u][0].y + z[u][1].y) + z[u][2].y; }
            }
            float mx = fmaxf(fmaxf(fmaxf(sv[0], sv[1]), fmaxf(sv[2], sv[3])), fmaxf(fmaxf(fmaxf(sv[4], sv[5]), fmaxf(sv[6], sv[7])), fmaxf(sv[8], sv[9])));
            uint32_t a[NRING][4];
            auto frag = [&](int i) { const int p = i / 7, u = i % 7, o = (p >> 1) * WO_BLK + (p & 1) * 2048;
                                     return u == 3 ? word6 + o : word + o + (u > 3 ? 1024 + (u - 4) * 8192 : u * 8192); };
            mx = fmaxf(fmaxf(mx, __shfl_xor_sync(0xffffffffu, mx, 1)), fmaxf(__shfl_xor_sync(0xffffffffu, mx, 2), __shfl_xor_sync(0xffffffffu, mx, 3)));
            pin(mr, __float_as_uint(mx), 0, 0, 0);
            {
#pragma unroll
                for (int i = 0; i < NPRE; i++) ldsm4t(a[i], frag(i));
                pin0(mr);
                const float sl2e = scale * 1.4426950408889634f, mxl = mx * sl2e;
#pragma unroll
                for (int i = 9; i >= 0; i--) asm volatile("ex2.approx.ftz.f32 %0, %1;" : "=f"(sv[i]) : "f"(fmaf(sv[i], sl2e, -mxl)));
                const uint32_t pq[4] = {pack2(sv[0], sv[1]), pack2(sv[4], sv[5]), pack2(sv[2], sv[3]), pack2(sv[6], sv[7])}, pm = pack2(sv[8], sv[9]);
                if (w == 0) PROF(6);
                float o[2][4] = {{0, 0, 0, 0}, {0, 0, 0, 0}}, o2[2][4] = {{0, 0, 0, 0}, {0, 0, 0, 0}}, sx[4] = {0, 0, 0, 0};
                mma8(sx, pm, 0, 0x3f803f80u); mma8(o[0], pm, 0, vm0); mma8(o[1], pm, 0, vm1);
                mma16q(sx, pq, 0x3f803f80u, 0x3f803f80u);
#pragma unroll
                for (int u = 0; u < 2; u++) { mma16q(o[u], pq, vb[u][0], vb[u][1]); mma16q(o2[u], pq, vb[u][2], vb[u][3]); }
                float inv; asm("rcp.approx.ftz.f32 %0, %1;" : "=f"(inv) : "f"((sx[0] + sx[2]) * __uint_as_float((127 - es) << 23)));
                const uint32_t f0 = pack2((o[0][0] + o2[0][2]) * inv, (o[0][1] + o2[0][3]) * inv), f1 = pack2((o[1][0] + o2[1][2]) * inv, (o[1][1] + o2[1][3]) * inv);
                send8(ord + 2048 + rb1, sm + CB_OX + rb1, f0, f1); send8(ord + 1024 + rb2, sm + CB_OX + rb2, f0, f1);
                asm volatile("st.shared.v2.u32 [%0], {%1,%2};" :: "r"(ord), "r"(f0), "r"(f1) : "memory");
            }
            if (w == 0) PROF(10);
#pragma unroll
            for (int i = NPRE; i < NRING; i++) ldsm4t(a[i], frag(i));
            bar_sync(3, 128);
            float e[5][4];
#pragma unroll
            for (int q = 0; q < 5; q++) e[q][0] = e[q][1] = e[q][2] = e[q][3] = 0.f;
            constexpr int LAG = 2;
            uint8_t* pdst = g_acc + ((s & 2) * (ACC_PAIR / 2) + (s & 1) * 512 + w * 2048 + j * 8192 - C_MEM - sm + mr);
#pragma unroll
            for (int h = 0; h < 3; h++) {
                uint32_t ob[4][2];
                if (h == 1) {
#pragma unroll
                    for (int i = 14 - LAG; i < 14; i++) ldsm4t(a[i % NRING], frag(i + NRING));
                    pin(mr, zr, (uint32_t)(uint64_t)pdst, (uint32_t)((uint64_t)pdst >> 32), 0);
                    mbar_wait(sm + CB_OX, s & 1);
                    if (w == 0) PROF(9);
                }
#pragma unroll
                for (int k = 0; k < 4; k++) lds64(ob[k], oxrd + h * 1024 + k * 256);
#pragma unroll
                for (int i = 14 * h; i < 14 * h + 14; i++) {
                    const int u = i % 7, k = 2 * (i / 7 & 1);
                    if (u == 3) { mma16q(e[3], a[i % NRING], ob[k][0], ob[k][1]); mma16q(e[4], a[i % NRING], ob[k + 1][0], ob[k + 1][1]); }
                    else mma16q(e[u & 3], a[i % NRING], ob[k + (u >> 2)][0], ob[k + (u >> 2)][1]);
                    if (i == B5AT) { pin(mr, a[i % NRING][0], a[i % NRING][1], a[i % NRING][2], a[i % NRING][3]); bar_arrive(5, 384); }
                    if (i >= LAG && !(i >= 14 && i < 14 + LAG) && i - LAG + NRING < 42) ldsm4t(a[(i - LAG) % NRING], frag(i - LAG + NRING));
                }
            }
            {
                const uint32_t w6 = pack2h(e[3][0] + e[4][2], e[3][1] + e[4][3]), one = 0x3c003c00u;
                asm volatile("red.relaxed.gpu.global.add.noftz.v4.f16x2 [%0], {%1,%2,%3,%4};"
                    :: "l"(pdst), "r"(pack2h(e[0][0], e[0][1])), "r"(pack2h(e[0][2], e[0][3])), "r"(pack2h(e[1][0], e[1][1])), "r"(odd ? w6 : one) : "memory");
                asm volatile("red.relaxed.gpu.global.add.noftz.v4.f16x2 [%0], {%1,%2,%3,%4};"
                    :: "l"(pdst + 1024), "r"(pack2h(e[1][2], e[1][3])), "r"(pack2h(e[2][0], e[2][1])), "r"(pack2h(e[2][2], e[2][3])), "r"(odd ? one : w6) : "memory");
            }
            const uint32_t tw = clock();
            if (w == 0) { PROF(14); PROFG(25); }
            PROXY_FENCE();
            bar_sync(6, 160);
            mr = opaque(mr);
            const uint32_t ln = mr >> 4 & 31, due = tw + lds32(sm + C_LAG);
            const uint32_t vr = sm + C_WV + ((ln >> 4) * 8 + (ln & 7)) * 128 + (((2 * w + (ln >> 3 & 1)) ^ (ln & 7)) << 4);
            const uint32_t ms0 = sm + C_MEM + w * 128 + (ln & 7) * 16 + (ln >> 3) * 512, ms1 = ms0 + (ln < 24 ? 2048 : 1536);
            if (BPOS == 2 && w == 0 && s + 2 == NSEG) wo_half(mp, sm, blk, 0);
            if (w == 2) { w_expect(sm + CB_SC, 2560); w_expect(sm + CB_OX, 2048); asm volatile("st.shared.u32 [%0], %1;" :: "r"(sm + C_UN), "r"((127 - es) << 23) : "memory"); }
            if (w == 0) { w_bulk_s2g(g_att + (s * NH + head) * AT_REC + AT_VM + j * 1024, sm + C_VM, 1024); BULK_COMMIT(); }
            const uint8_t* src = pdst - j * 8192;
            pin(mr, ms0, ms1, (uint32_t)(uint64_t)src, (uint32_t)((uint64_t)src >> 32));
            pin(mr, vr, due, 0, 0);
            cut(s + ar.D2, 1);
#pragma unroll
            for (int i = 0; i < 8; i++) ldsm4t(va[i], vr + i * 2048);
            wait_until(due);
            if (w == 0) { PROF(5); PROFG(26); }
            uint4 v[6];
            auto fetch = [&]() {
#pragma unroll
                for (int k = 0; k < 6; k++)
                    asm volatile("ld.relaxed.gpu.global.v4.u32 {%0,%1,%2,%3}, [%4];" : "=r"(v[k].x), "=r"(v[k].y), "=r"(v[k].z), "=r"(v[k].w) : "l"(src + (k >> 1) * 8192 + (k & 1) * 1024) : "memory");
            };
            fetch();
            PROFV(20 + w, 0);
            bar_sync(9, 384);
            uint32_t cv[3][7];
#pragma unroll 1
            for (int n = 0; __any_sync(0xffffffffu, ~((odd ? v[1].w & v[3].w & v[5].w : v[0].w & v[2].w & v[4].w)) & 0x50005000u); n++) {
                PROFV(20 + w, n + 1);
                cut(n, SPIN_LIMIT);
                uint32_t miss = 0;
#pragma unroll
                for (int k = 0; k < 3; k++) miss |= (~(odd ? v[2 * k + 1].w : v[2 * k].w) & 0x50005000u) ? (odd ? 2u : 1u) << (2 * k) : 0u;
                miss |= __shfl_xor_sync(0xffffffffu, miss, 1);
#pragma unroll
                for (int k = 0; k < 6; k++)
                    asm volatile("{ .reg .pred q; setp.ne.u32 q, %5, 0; @q ld.relaxed.gpu.global.v4.u32 {%0,%1,%2,%3}, [%4]; }" : "+r"(v[k].x), "+r"(v[k].y), "+r"(v[k].z), "+r"(v[k].w)
                        : "l"(src + (k >> 1) * 8192 + (k & 1) * 1024), "r"(miss & (1u << k)) : "memory");
            }
#pragma unroll
            for (int k = 0; k < 3; k++) {
                const uint4 x = v[2 * k], y = v[2 * k + 1];
                const uint32_t u[7] = {x.x, x.y, x.z, y.x, y.y, y.z, k < 2 ? (odd ? x.w : y.w) : 0u};
#pragma unroll
                for (int i = 0; i < 7; i++) cv[k][i] = f16_to_bf16(u[i]);
                stsm4(ms0 + k * 3584, cv[k][0], cv[k][1], cv[k][2], cv[k][3]);
                if (k < 2) stsm4(ms1 + k * 3584, cv[k][4], cv[k][5], cv[k][6], cv[k][6]);
                else asm volatile("stmatrix.sync.aligned.m8n8.x2.shared.b16 [%0], {%1,%2};" :: "r"(ms1 + k * 3584), "r"(cv[k][4]), "r"(cv[k][5]) : "memory");
            }
            if (w == 0) PROF(16);
            bar_sync(1, 384);
            if (w == 0) BULK_WAIT();
            cut(s + ar.D2, 2);
            uint32_t mc = 0;
#pragma unroll
            for (int i = 0; i < 20; i++) mc = amax2(mc, cv[i / 7][i % 7]);
            asm volatile("st.shared.u32 [%0], %1;" :: "r"(sm + C_MX + w * 4), "r"(amax_warp(mc)) : "memory");
        }
        if (w >= 2) end_loads(mp, ar, sm, blk, w - 2);
        else if (w == 1) { bar_sync(5, 384); seg_done(NSEG - 1, head); EPT(true, 9); if (EORD) bar_arrive(6, 96); if (BPOS == 0) wo_half(mp, sm, blk, 1); }
        else bar_arrive(5, 384);
        if (w < 2) end_stores(mp, sm, blk, w);
        if (w == 0) { mbar_wait(sm + EB_REL, 0); flags_release(mr >> 4 & 31); }
    }
}

struct SideMaps { CUtensorMap h, wv, ost, o, wo, slab, lnp[3]; };
constexpr int SD_ST = 14336, SD_NST = 12, SD_EPI = SD_NST * SD_ST, SD_PAR = SD_EPI + 2 * 24576, SD_BAR = SD_PAR + 6400, SD_SMEM = SD_BAR + 1024;
#define VLEAD 16
#define EARLY15 1
#define N_LIGHT 9
#define B_HELP 13
#define AUNR_ 2
constexpr int AUNR = AUNR_;
#define ADEF 1
#define SGP 400
#define SG0 0
#define KSV 4
#define KSO 8
#define KSA 3
#define B_8 10
#define B_16 13
__device__ __forceinline__ int o_shift(int b) { return b >= B_16 ? 4 : b >= B_8 ? 3 : 2; }
__device__ __forceinline__ int o_split(int b) { return 1 << o_shift(b); }
__device__ __forceinline__ uint32_t o_done(int b) { return b >= B_LATE ? 160 : 4 << o_shift(b); }
__device__ __forceinline__ int next_item(int lane) {
    const int b0 = lane & 15, hi = lane >> 4;
    for (int n = 0;; n++) {
        const uint32_t w0 = ld_rlx(g_flags.qk + lane), w1 = ld_rlx(g_flags.at + lane), w2 = ld_rlx(&g_flags.c[0][0] + lane), w3 = ld_rlx(&g_flags.c[2][0] + lane), w4 = ld_rlx(&g_flags.seg[32]);
        const uint32_t o01 = __ballot_sync(0xffffffffu, lane && w2 < 32), o23 = __ballot_sync(0xffffffffu, b0 < (hi ? 14 : B_LATE) && w3 < 2u * o_split(b0));
        uint32_t ra = __ballot_sync(0xffffffffu, w0 >= (hi ? 64u : 96u));
        const uint32_t rb = __ballot_sync(0xffffffffu, w1 >= (hi ? o_done(b0) : 64u));
        const int bv = __ffs(o01 | 0x10000) - 1, ba = __ffs(o01 >> 16 | 0x10000) - 1, bo = __ffs(o23 | 0x10000) - 1, bl = __ffs(o23 >> 16 | 0x10000) - 1;
        if (bl == 16 && ba == 16) return -1;
        const int bc = __ffs(~ra | 0x10000) - 1;
        const bool last = ba == 15 && (w4 >= 3 || (EARLY15 && bc == 15));
        const bool r1 = (ra & ra >> 16) >> ba & 1, r2 = (rb & 0xffff) >> bo & 1, r3 = rb >> 16 >> bl & 1;
        const int kind = ba == 16 ? (bo < 16 ? 2 : 3) : last ? 1 :
                         blockIdx.x < N_LIGHT ? (r1 ? 1 : r3 ? 3 : bv < 16 ? 0 : -1) :
                         bv < 16 && (bv <= bc + VLEAD || !r2) ? 0 : r1 && ba >= B_HELP ? 1 : r2 ? 2 : r1 ? 1 : r3 ? 3 : bo < ba ? 2 : -1;
        if (kind < 0) { if (n > (1 << 20)) __trap(); __nanosleep(IDLE); continue; }
        const int b = kind == 3 ? bl : kind == 2 ? bo : kind == 1 ? ba : bv;
        uint32_t i = 0;
        if (lane == 0) asm volatile("atom.relaxed.gpu.global.add.u32 %0, [%1], 1;" : "=r"(i) : "l"(&g_flags.c[kind][b]) : "memory");
        i = __shfl_sync(0xffffffffu, i, 0);
        if (i < (kind < 2 ? 32u : 2u * o_split(b))) return kind << 16 | b << 8 | i | ((kind == 1 ? r1 : kind == 2 ? r2 : r3) ? 128 : 0);
    }
}

template <int NP>
__device__ __forceinline__ void tile_out(const float (&acc)[8 * NP], uint32_t eb, uint32_t CH, uint32_t efull, uint32_t eempty, int& eph, int lane) {
    const int r = lane & 7, mi = lane >> 3, row = (mi & 1) * 8 + r;
    mbar_wait(eempty, eph); eph ^= 1;
#pragma unroll
    for (int p = 0; p < NP; p++) {
        const int oc = 2 * p + (mi >> 1);
        stsm4(eb + (oc >> 3) * CH + row * 128 + (((oc & 7) ^ r) << 4), pack2(acc[8 * p], acc[8 * p + 1]), pack2(acc[8 * p + 2], acc[8 * p + 3]),
              pack2(acc[8 * p + 4], acc[8 * p + 5]), pack2(acc[8 * p + 6], acc[8 * p + 7]));
    }
    asm volatile("fence.proxy.async.shared::cta;" ::: "memory");
    __syncwarp();
    if (lane == 0) mbar_arrive(efull);
}

template <int MT, typename F, typename G>
__device__ __forceinline__ void attn_tile(uint32_t base, uint32_t dst, int lane, F scores_done, G before_values) {
    constexpr int NK = MT ? 5 : 3;
    const int r = lane & 7, mi = lane >> 3, g = lane >> 2, t = lane & 3;
    float sc[NK][4];
#pragma unroll
    for (int n = 0; n < NK; n++) sc[n][0] = sc[n][1] = sc[n][2] = sc[n][3] = 0.f;
#pragma unroll AUNR
    for (int k2 = 0; k2 < 6; k2++) {
        const uint32_t cb = (k2 >> 1) * 8192, c0 = (k2 & 1) * 4;
        uint32_t a0[4], a1[4], bb[NK][4];
        ldsm4(a0, base + cb + (16 * MT + (mi & 1) * 8 + r) * 128 + (((c0 + (mi >> 1)) ^ r) << 4));
        ldsm4(a1, base + cb + (16 * MT + (mi & 1) * 8 + r) * 128 + (((c0 + 2 + (mi >> 1)) ^ r) << 4));
#pragma unroll
        for (int n = 0; n < NK; n++)
            ldsm4(bb[n], n < NK - 1 ? base + 4096 + cb + (8 * n + r) * 128 + (((c0 + mi) ^ r) << 4) : base + AT_KM + k2 * 512 + lane * 16);
#pragma unroll
        for (int n = 0; n < NK; n++) mma16(sc[n], a0[0], a0[1], a0[2], a0[3], bb[n][0], bb[n][1]);
#pragma unroll
        for (int n = 0; n < NK; n++) mma16(sc[n], a1[0], a1[1], a1[2], a1[3], bb[n][2], bb[n][3]);
    }
    scores_done();
    const float scale = 0.07216878364870322f, l2e = 1.4426950408889634f;
    float v[2][2 * NK], mx[2], sum[2];
#pragma unroll
    for (int hf = 0; hf < 2; hf++) {
        mx[hf] = -INFINITY;
#pragma unroll
        for (int n = 0; n < NK; n++) {
            uint32_t u = pack2(sc[n][2 * hf], sc[n][2 * hf + 1]);
            u = pack2(lo_f(u) * scale, hi_f(u) * scale);
            const int lim = 16 * MT + 8 * hf + g - 8 * n - 2 * t;
            v[hf][2 * n] = (n < NK - 1 && lim < 0) ? -1e9f : lo_f(u);
            v[hf][2 * n + 1] = (n < NK - 1 && lim < 1) ? -1e9f : hi_f(u);
            mx[hf] = fmaxf(mx[hf], fmaxf(v[hf][2 * n], v[hf][2 * n + 1]));
        }
    }
#pragma unroll
    for (int o = 1; o < 4; o <<= 1)
#pragma unroll
        for (int hf = 0; hf < 2; hf++) mx[hf] = fmaxf(mx[hf], __shfl_xor_sync(0xffffffffu, mx[hf], o));
#pragma unroll
    for (int hf = 0; hf < 2; hf++) {
        sum[hf] = 0;
#pragma unroll
        for (int q = 0; q < 2 * NK; q++) { asm("ex2.approx.ftz.f32 %0, %1;" : "=f"(v[hf][q]) : "f"((v[hf][q] - mx[hf]) * l2e)); sum[hf] += v[hf][q]; }
    }
#pragma unroll
    for (int o = 1; o < 4; o <<= 1)
#pragma unroll
        for (int hf = 0; hf < 2; hf++) sum[hf] += __shfl_xor_sync(0xffffffffu, sum[hf], o);
    uint32_t pa[NK][2];
#pragma unroll
    for (int hf = 0; hf < 2; hf++) {
        const float inv = __fdividef(1.f, sum[hf]);
#pragma unroll
        for (int n = 0; n < NK; n++) pa[n][hf] = pack2(v[hf][2 * n] * inv, v[hf][2 * n + 1] * inv);
    }
    before_values();
#pragma unroll AUNR
    for (int n4 = 0; n4 < 6; n4++) {
        const uint32_t cb = (n4 >> 1) * 4096, c0 = (n4 & 1) * 4;
        uint32_t bm[4], bb[2 + 2 * MT][4];
        ldsm4t(bm, base + AT_VM + n4 * 512 + lane * 16);
#pragma unroll
        for (int u = 0; u < 2 + 2 * MT; u++) ldsm4t(bb[u], base + AT_V + cb + (16 * (u >> 1) + 8 * (mi & 1) + r) * 128 + (((c0 + 2 * (u & 1) + (mi >> 1)) ^ r) << 4));
        float o[4][4];
#pragma unroll
        for (int u = 0; u < 4; u++) { o[u][0] = o[u][1] = o[u][2] = o[u][3] = 0.f; mma8(o[u], pa[NK - 1][0], pa[NK - 1][1], bm[u]); }
#pragma unroll
        for (int u = 0; u < 4 + 4 * MT; u++) mma16(o[u & 3], pa[u >> 2 << 1][0], pa[u >> 2 << 1][1], pa[(u >> 2 << 1) + 1][0], pa[(u >> 2 << 1) + 1][1], bb[u >> 1][2 * (u & 1)], bb[u >> 1][2 * (u & 1) + 1]);
#pragma unroll
        for (int p = 0; p < 2; p++)
            stsm4(dst + (n4 >> 1) * 2048 + ((mi & 1) * 8 + r) * 128 + (((c0 + 2 * p + (mi >> 1)) ^ r) << 4), pack2(o[2 * p][0], o[2 * p][1]), pack2(o[2 * p][2], o[2 * p][3]),
                  pack2(o[2 * p + 1][0], o[2 * p + 1][1]), pack2(o[2 * p + 1][2], o[2 * p + 1][3]));
    }
}

__device__ __forceinline__ uint32_t ln_row(const uint32_t (&as)[10], const uint2 (&xin)[5], int row, uint32_t par, uint32_t low, bf16* out, uint64_t ef, int lane) {
    const uint32_t pa = par + lane * 8;
    uint32_t xv[10], hv[10], sv[10], tv[10];
#pragma unroll
    for (int q = 0; q < 5; q++) {
        uint32_t ga[2], t[2], u[2];
        lds64(ga, pa + q * 256); lds64(t, pa + 1280 + q * 256); lds64(u, pa + 2560 + q * 256);
#pragma unroll
        for (int e = 0; e < 2; e++) {
            xv[2 * q + e] = add2(e ? xin[q].y : xin[q].x, mul2(ga[e], as[2 * q + e]));
            tv[2 * q + e] = t[e]; sv[2 * q + e] = u[e];
        }
    }
    ln_mod(xv, sv, tv, hv);
    float rs = 0;
#pragma unroll
    for (int q = 0; q < 5; q++) {
        const int c = row * DM + lane * 4 + q * 128;
        const uint32_t h0 = hv[2 * q], h1 = hv[2 * q + 1];
        uint32_t gb[2], wv[2];
        lds64(gb, pa + 3840 + q * 256); lds64(wv, pa + 5120 + q * 256);
        rs += (lo_f(h0) * lo_f(wv[0]) + hi_f(h0) * hi_f(wv[0])) + (lo_f(h1) * lo_f(wv[1]) + hi_f(h1) * hi_f(wv[1]));
        st_ef(out + c, make_uint2(add2(xv[2 * q], mul2(gb[0], h0)), add2(xv[2 * q + 1], mul2(gb[1], h1))), ef);
    }
    const uint32_t rb = pack2(0.f, warp_sum(rs));
    const uint32_t key = (((int)rb < 0 ? ~rb : rb | 0x80000000u) & 0xffff0000u) | (uint32_t)(4 * S_TOK - 1 - row);
    if (key < low) return key ^ (2 * S_TOK);
    {
#pragma unroll
        for (int q = 0; q < 5; q++) {
            *(uint2*)(g_x1 + row * DM + lane * 4 + q * 128) = make_uint2(xv[2 * q], xv[2 * q + 1]);
            *(uint2*)(g_h2 + row * DM + lane * 4 + q * 128) = make_uint2(hv[2 * q], hv[2 * q + 1]);
        }
    }
    return key;
}
__device__ __forceinline__ void key_out(uint32_t key) {
    __syncwarp();
    if (key) asm volatile("st.release.gpu.global.u32 [%0], %1;" :: "l"(g_key + (~key & (S_TOK - 1))), "r"(key) : "memory");
}

__global__ void __launch_bounds__(384, 1) k_side(const __grid_constant__ SideMaps mp, const bf16* __restrict__ x, const bf16* __restrict__ wr, const bf16* wmod, const bf16* cvec, bf16* __restrict__ out) {
    extern __shared__ __align__(1024) uint8_t smraw[];
    const uint32_t sm = smem_u32(smraw);
    if (sm & 1023) __trap();
    const uint32_t BARS = sm + SD_BAR, FULL = BARS + 768, EMPTY = FULL + 96, EFULL = BARS + 64, EEMPTY = BARS + 80, IFULL = BARS + 96, IEMPTY = BARS + 128, IQ = BARS + 160, SCHED = BARS + 176, PARAM = BARS + 184, ADONE = BARS + 192, LOW = BARS + 224, KEYS = BARS + 256;
    const int tid = opaque(threadIdx.x), warp = __shfl_sync(0xffffffffu, tid >> 5, 0), lane = tid & 31;
    const uint64_t ef = policy_stream();
    if (tid == 0) {
#pragma unroll 1
        for (int i = 0; i < SD_NST; i++) { mbar_init(FULL + 8 * i, 1); mbar_init(EMPTY + 8 * i, 2); }
        for (int i = 0; i < 2; i++) { mbar_init(EFULL + 8 * i, 4); mbar_init(EEMPTY + 8 * i, 1); }
        for (int i = 0; i < 4; i++) { mbar_init(IFULL + 8 * i, 1); mbar_init(IEMPTY + 8 * i, 11); }
        mbar_init(SCHED, 1); mbar_init(PARAM, 1);
        sts128f(ADONE, 0, 0, 0, 0); sts128f(ADONE + 16, 0, 0, 0, 0); sts128f(LOW, 0, 0, 0, 0);
        asm volatile("fence.mbarrier_init.release.cluster;" ::: "memory");
    }
    if (SDEL) __nanosleep(SDEL);
    __syncthreads();
    if (warp >= 8) {
      asm volatile("setmaxnreg.dec.sync.aligned.u32 40;");
      if (warp == 8) {
        int st = 0, ph = 1;
        int pk = -1;
        for (int q = 0;; q++) {
            mbar_wait(IFULL + 8 * (q & 3), (q >> 2) & 1);
            const int it = __shfl_sync(0xffffffffu, lds32(IQ + 4 * (q & 3)), 0);
            if (elect()) mbar_arrive(IEMPTY + 8 * (q & 3));
            if (it < 0) break;
            const int kind = it >> 16, b = (it >> 8) & 255, i = it & 63;
            const int nst = kind == 0 ? 10 : kind == 1 ? 4 : kind == 2 ? 192 >> o_shift(b) : b == 14 ? 4 : 2;
            const int ksched = kind == 0 ? KSV : kind == 2 ? nst - KSO : (it & 128) ? -1 : kind == 1 ? KSA : 0;
            if (ksched < 0 && elect()) mbar_arrive(SCHED);
            const bool look = !(it & 128);
            const int nu = kind == 2 ? 2 : 3;
            if (look && kind == 1) flag_wait(&g_flags.v[b * 32 + i], 2);
            if (look && kind == 3 && b < 14) flag_wait(&g_flags.o[b], o_done(b));
            if (kind == 1) {
#pragma unroll 1
                for (int u = 0; u < 8; u++) {
                    const int sec = look ? u & 1 : 0xd4 >> u & 1, sg = look ? u >> 1 : 0xed84 >> 2 * u & 3;
                    int p = st + 3 * sg, pp = ph; if (p >= SD_NST) { p -= SD_NST; pp ^= 1; }
                    if (sec || pk != 1) mbar_wait(EMPTY + 8 * p + 8, pp);
                    mbar_wait(EMPTY + 8 * p + 16 * sec, pp);
                    if (look && !sec) { flag_wait(&g_flags.seg[max(sg, 1) * 32 + i], 3); if (sg == ksched && elect()) mbar_arrive(SCHED); }
                    if (elect()) {
                        const uint32_t fb = FULL + 8 * p + 16 * sec, off = sec ? AT_VM : 0, n = sec ? AT_REC - AT_VM : AT_VM;
                        if (sec) mbar_arrive(fb - 8);
                        mbar_expect(fb, n);
                        asm volatile("cp.async.bulk.shared::cluster.global.mbarrier::complete_tx::bytes.L2::cache_hint [%0], [%1], %2, [%3], %4;"
                            :: "r"(sm + p * SD_ST + off), "l"(g_att + ((b * 4 + sg) * NH + i) * AT_REC + off), "r"(n), "r"(fb), "l"(ef) : "memory");
                    }
                    __syncwarp();
                }
                ph ^= 1; pk = 1;
                continue;
            }
            for (int kb = 0; kb < nst; kb++) {
                if (kb < 6 && (kind != pk || kind == 3)) mbar_wait(EMPTY + 8 * st, ph);
                mbar_wait(EMPTY + 8 * (st + nu - 1), ph);
                const uint32_t base = sm + st * SD_ST, fb = FULL + 8 * st;
                if (kb == ksched && elect()) mbar_arrive(SCHED);
                if (kind == 0) {
                    if (q == 0 && kb == 0) {
                        if (elect()) {
#pragma unroll 1
                            for (int c = 0; c < 4; c++) tma3d(sm + 3 * c * SD_ST + 16384, &mp.wv, c * 64, i * 3, FULL + 24 * c);
                        }
                        flag_wait(&g_flags.h, 96);
                    }
                    if (elect()) {
                        mbar_expect(fb, 40960);
                        if (q || kb >= 4) tma3d(base + 16384, &mp.wv, kb * 64, i * 3, fb);
                        tma2d(base, &mp.h, kb * 64, b * 128, fb);
                    }
                } else if (kind == 3) {
                    if (b == 14 && !(kb & 1)) flag_wait(&g_flags.fin[(kb + (i >> 4)) * 32], 80);
                    if (elect()) { mbar_expect(fb, 40960); tma3d_ef(base, &mp.lnp[o_shift(b) - 2], i * (160 >> o_shift(b)), b * KSPLIT + (kb << o_shift(b) >> 1), fb, ef); }
                } else {
                    const int k0 = ((i >> 1) * nst + kb) * 32;
                    if (elect()) { mbar_expect(fb, 28672); tma3d(base + 8192, &mp.wo, k0, (i & 1) * 5, fb); }
                    __syncwarp();
                    if (look && kb % 12 == 0) flag_wait(&g_flags.pair[b * 16 + k0 / 384], 4);
                    if (elect()) tma2d_ef(base, &mp.o, k0, b * 128, fb, ef);
                }
                __syncwarp();
                if (lane && lane < nu) mbar_arrive(fb + 8 * lane);
                st += nu; if (st == SD_NST) { st = 0; ph ^= 1; }
            }
            pk = kind;
        }
      } else if (warp == 11) {
        bool fin = false, par = false;
        for (int q = 0;; q++) {
            if (q) mbar_wait(SCHED, (q - 1) & 1);
            int it = fin ? -1 : q == 0 && blockIdx.x < 32 ? (int)blockIdx.x : next_item(lane);
            if (it < 0 && !fin && blockIdx.x < 32) { it = 3 << 16 | 14 << 8 | blockIdx.x; fin = true; }
            if (lane == 0) {
                if (it >> 16 == 3) {
                    const int b = (it >> 8) & 255, nr = 64 >> o_shift(b);
                    asm volatile("cp.async.bulk.prefetch.L2.global [%0], %1;" :: "l"(x + (b * 128 + (it & 63) * nr) * DM), "r"(nr * DM * 2) : "memory");
                }
                mbar_wait(IEMPTY + 8 * (q & 3), ((q >> 2) & 1) ^ 1);
                asm volatile("st.shared.u32 [%0], %1;" :: "r"(IQ + 4 * (q & 3)), "r"(it) : "memory");
                mbar_arrive(IFULL + 8 * (q & 3));
            }
            if (it >> 16 >= 2 && (it >> 8 & 255) >= 2) {
                const uint4* kp = (const uint4*)g_key + max((it >> 8 & 255) - ((it >> 16) == 2 ? 5 : 3), 0) * 32 + lane;
                const uint4 k1 = __ldcg(kp), k2 = __ldcg(kp + 32);
                uint32_t m = max(max(max(k1.x, k1.y), max(k1.z, k1.w)), max(max(k2.x, k2.y), max(k2.z, k2.w)));
                m = max(m, __shfl_xor_sync(0xffffffffu, m, 1)); m = max(m, __shfl_xor_sync(0xffffffffu, m, 2));
                asm volatile("red.shared.max.u32 [%0], %1;" :: "r"(LOW), "r"(__reduce_min_sync(0xffffffffu, m)) : "memory");
            }
            if (!par && it >> 16 == 3) {
                par = true;
                flag_wait(&g_flags.mod, 64);
                if (lane == 0) { mbar_expect(PARAM, 6400); bulk_g2s(sm + SD_PAR, g_mod + 2 * DM, 5120, PARAM); bulk_g2s(sm + SD_PAR + 5120, wr, 1280, PARAM); }
            }
            __syncwarp();
            if (it < 0) break;
        }
        flags_release(lane);
      } else {
        if (lane == 0) {
            const int wg = warp - 9; int ph = 0;
            for (int q = 0;; q++) {
                mbar_wait(IFULL + 8 * (q & 3), (q >> 2) & 1);
                const int it = lds32(IQ + 4 * (q & 3));
                mbar_arrive(IEMPTY + 8 * (q & 3));
                if (it < 0) break;
                const int kind = it >> 16, b = (it >> 8) & 255, i = it & 63;
                if (kind == 3 && b == 14) continue;
                if (kind & 1) {
                    for (int n = 0;; n++) {
                        uint32_t d0, d1, d2, d3;
                        asm volatile("ld.volatile.shared.v4.u32 {%0,%1,%2,%3}, [%4];" : "=r"(d0), "=r"(d1), "=r"(d2), "=r"(d3) : "r"(ADONE + wg * 16) : "memory");
                        if (min(min(d0, d1), min(d2, d3)) > q) break;
                        if (n > (1 << 24)) __trap();
                        __nanosleep(40);
                    }
                    GPU_FENCE();
                    EPT(kind == 1 && b == 15 && wg, 17);
                    if (kind == 1) { bump(b == 15 ? &g_flags.half[(i & 30) + wg] : &g_flags.pair[b * 16 + (i >> 1)]); bump(&g_flags.at[b]); }
                    else {
#pragma unroll 1
                        for (int c = 0; c < 8; c++) { const uint32_t key = lds32(KEYS + (q & 7) * 64 + wg * 32 + c * 4); if (key) asm volatile("st.relaxed.gpu.global.u32 [%0], %1;" :: "l"(g_key + (~key & (S_TOK - 1))), "r"(key) : "memory"); }
                    }
                    continue;
                }
#pragma unroll 1
                for (int rd = 0; rd < (kind == 2 ? 2 : 1); rd++) {
                    mbar_wait(EFULL + 8 * wg, ph); ph ^= 1;
                    const uint32_t src = sm + SD_EPI + wg * 24576;
#pragma unroll 1
                    for (int c = 0; c < (kind ? 2 + rd : 6); c++) {
                        if (c && q) __nanosleep(kind && !rd ? SG0 : kind ? 2 * SGP : SGP);
                        if (kind) tma2d_store(&mp.slab, ((i & 1) * 5 + (rd ? 0 : 3) + c) * 64, (b * KSPLIT + (i >> 1)) * 128 + wg * 64, src + c * 8192);
                        else asm volatile("cp.async.bulk.global.shared::cta.bulk_group.L2::cache_hint [%0], [%1], 4096, %2;"
                            :: "l"(g_att + ((b * 4 + wg * 2 + c / 3) * NH + i) * AT_REC + AT_V + c % 3 * 4096), "r"(src + c * 4096), "l"(ef) : "memory");
                    }
                    asm volatile("cp.async.bulk.commit_group;" ::: "memory");
                    asm volatile("cp.async.bulk.wait_group.read 0;" ::: "memory");
                    mbar_arrive(EEMPTY + 8 * wg);
                }
                asm volatile("cp.async.bulk.wait_group 0;" ::: "memory");
                GPU_FENCE();
                bump(kind == 0 ? &g_flags.v[b * 32 + i] : &g_flags.o[b]);
                if (kind == 0) bump(&g_flags.vb[b]);
            }
        }
      }
    } else {
        asm volatile("setmaxnreg.inc.sync.aligned.u32 232;");
        const int wg = warp >> 2, w = warp & 3;
        int st = 0, ph = 0, eph = 1;
        bool att = false;
        uint4 mz[4] = {}; uint2 mc = {}; float ma[8] = {0, 0, 0, 0, 0, 0, 0, 0};
        const uint32_t eb = sm + SD_EPI + wg * 24576;
        for (int q = 0;; q++) {
            mbar_wait(IFULL + 8 * (q & 3), (q >> 2) & 1);
            const int itc = __shfl_sync(0xffffffffu, lds32(IQ + 4 * (q & 3)), 0);
            __syncwarp();
            if (lane == 0) mbar_arrive(IEMPTY + 8 * (q & 3));
            if (itc < 0) break;
            const int kind = itc >> 16, b = (itc >> 8) & 255, i = itc & 63;
            if (q >= 1 && q <= 9 && blockIdx.x < 32) {
                const int t = min(tid, 199), k = t / 10 * 32 + (q - 1) * 4;
#pragma unroll
                for (int e = 0; e < 4; e++) {
                    const uint32_t cw = e & 2 ? mc.y : mc.x;
                    const float c = e & 1 ? hi_f(cw) : lo_f(cw), f = bfr(__fdividef(c, 1.f + __expf(-c)));
                    ma[0] += f * lo_f(mz[e].x); ma[1] += f * hi_f(mz[e].x); ma[2] += f * lo_f(mz[e].y); ma[3] += f * hi_f(mz[e].y);
                    ma[4] += f * lo_f(mz[e].z); ma[5] += f * hi_f(mz[e].z); ma[6] += f * lo_f(mz[e].w); ma[7] += f * hi_f(mz[e].w);
                }
                if (q < 9) {
#pragma unroll
                    for (int e = 0; e < 4; e++) mz[e] = __ldcs((const uint4*)(wmod + (k + e) * (6 * DM) + 2 * DM + blockIdx.x * 80 + t % 10 * 8));
                    mc = __ldg((const uint2*)(cvec + k));
                } else {
                    sts128f(sm + SD_PAR + t * 32, ma[0], ma[1], ma[2], ma[3]); sts128f(sm + SD_PAR + 16 + t * 32, ma[4], ma[5], ma[6], ma[7]);
                    bar_sync(1, 256);
                    if (tid < 40) {
                        float a0 = 0, a1 = 0;
#pragma unroll 4
                        for (int g = 0; g < 20; g++) { const float2 v = lds64f(sm + SD_PAR + g * 320 + tid * 8); a0 += v.x; a1 += v.y; }
                        ((uint32_t*)(g_mod + 2 * DM + blockIdx.x * 80))[tid] = pack2(a0, a1);
                    }
                    __syncwarp();
                    if (warp < 2 && lane == 0) flag_add(&g_flags.mod);
                }
            }
            if (att && kind != 1) { bar_sync(1, 256); att = false; }
            int prev = -1;
            auto next = [&](int nu) {
                WG_COMMIT();
                WG_WAIT(1);
                if (prev >= 0 && (tid & 127) < nu) mbar_arrive(EMPTY + 8 * (prev + (tid & 127)));
                prev = st;
                st += nu; if (st == SD_NST) { st = 0; ph ^= 1; }
            };
            auto desc = [](uint32_t lo, uint32_t hi) { return (uint64_t)hi << 32 | lo; };
            if (kind == 0) {
                float acc[96];
#pragma unroll
                for (int n = 0; n < 96; n++) acc[n] = 0.f;
                auto stage = [&](int more) {
                    mbar_wait(FULL + 8 * st, ph);
                    const uint32_t d0 = (sm + st * SD_ST) >> 4, da = d0 + wg * 512 + 0x10000, db = d0 + 1024 + 0x2000000;
                    WG_FENCE();
#pragma unroll
                    for (int ks = 0; ks < 4; ks++) wgmma_ss_n192_tb(acc, desc(da + ks * 2, 0x40000040), desc(db + ks * 128, 0x40000040), more | ks);
                    next(3);
                };
                stage(0);
#pragma unroll 1
                for (int kb = 1; kb < 10; kb++) stage(1);
                WG_WAIT(0);
                if ((tid & 127) < 3) mbar_arrive(EMPTY + 8 * (prev + (tid & 127)));
                tile_out<12>(acc, eb + (w >> 1) * 12288 + (w & 1) * 2048, 4096, EFULL + 8 * wg, EEMPTY + 8 * wg, eph, lane);
            } else if (kind == 2) {
                float acc[96], acc2[64];
#pragma unroll
                for (int n = 0; n < 96; n++) acc[n] = 0.f;
#pragma unroll
                for (int n = 0; n < 64; n++) acc2[n] = 0.f;
                auto stage = [&](int more) {
                    mbar_wait(FULL + 8 * st, ph);
                    const uint32_t d0 = (sm + st * SD_ST) >> 4, da = d0 + wg * 256 + 0x10000, db = d0 + 512 + 0x1000000;
                    WG_FENCE();
#pragma unroll
                    for (int ks = 0; ks < 2; ks++) {
                        wgmma_ss_n192_tb(acc, desc(da + ks * 2, 0x80000020), desc(db + ks * 128, 0x40000040), more | ks);
                        wgmma_ss_n128_tb(acc2, desc(da + ks * 2, 0x80000020), desc(db + 768 + ks * 128, 0x40000040), more | ks);
                    }
                    next(2);
                };
                stage(0);
                int kb = (192 >> o_shift(b)) - 1;
#pragma unroll 1
                do stage(1); while (--kb);
                WG_WAIT(0);
                if ((tid & 127) < 2) mbar_arrive(EMPTY + 8 * (prev + (tid & 127)));
                tile_out<8>(acc2, eb + w * 2048, 8192, EFULL + 8 * wg, EEMPTY + 8 * wg, eph, lane);
                tile_out<12>(acc, eb + w * 2048, 8192, EFULL + 8 * wg, EEMPTY + 8 * wg, eph, lane);
            } else if (kind == 1) {
                const int seg = warp >> 1, mt = warp & 1;
                int sst = st + 3 * seg, sph = ph; if (sst >= SD_NST) { sst -= SD_NST; sph ^= 1; }
                ph ^= 1;
                mbar_wait(FULL + 8 * sst, sph);
                EPT(tid == 224 && b == 15, 16);
                const uint32_t base = sm + sst * SD_ST;
                auto f1 = [&]() { __syncwarp(); if (lane == 0) mbar_arrive(EMPTY + 8 * sst); };
                auto f2 = [&]() {
                    mbar_wait(EEMPTY + 8 * wg, eph);
                    BULK_WAIT();
                    if (lane == 0) asm volatile("st.release.cta.shared.u32 [%0], %1;" :: "r"(ADONE + warp * 4), "r"(q) : "memory");
                    mbar_wait(FULL + 8 * sst + 16, sph);
                };
                if (mt) attn_tile<1>(base, eb + w * 6144, lane, f1, f2);
                else attn_tile<0>(base, eb + w * 6144, lane, f1, f2);
                asm volatile("fence.proxy.async.shared::cta;" ::: "memory");
                __syncwarp();
                if (lane < 2) mbar_arrive(EMPTY + 8 * (sst + 1 + lane));
                if (lane == 0) {
                    tma3d_store(&mp.ost, b * 128 + warp * 16, i * 3, eb + w * 6144, ef, false);
                    BULK_COMMIT();
                    if (!ADEF || !mbar_test(IFULL + 8 * (q + 1 & 3), (q + 1 >> 2) & 1) || (lds32(IQ + 4 * (q + 1 & 3)) & 0xffff0080u) != 0x10080u) {
                        BULK_WAIT();
                        asm volatile("st.release.cta.shared.u32 [%0], %1;" :: "r"(ADONE + warp * 4), "r"(q + 1) : "memory");
                    }
                }
                __syncwarp();
                att = true;
            } else {
                const int sh = o_shift(b), nr = 64 >> sh, fw = b == 14 ? wg : 0, row0 = (b + fw) * 128 + i * nr, lw = warp - 4 * fw;
                if (fw) { ph ^= st != 0; st ^= 6; }
                uint2 xin[2][5];
                uint32_t as[2][10] = {};
#pragma unroll
                for (int q2 = 0; q2 < 10; q2++) xin[q2 & 1][q2 >> 1] = ld_ef(x + (row0 + ((warp + 8 * (q2 & 1)) & (nr - 1))) * DM + lane * 4 + (q2 >> 1) * 128, ef);
                mbar_wait(PARAM, 0); mbar_wait(FULL + 8 * st, ph); mbar_wait(FULL + 8 * st + 24, ph);
                EPT((tid & 127) == 0 && b == 14, 18 + wg);
#pragma unroll 1
                for (int lrow = lw + (nr & 16) / 2; lrow >= 0 && lrow < nr; lrow -= 8) {
                    const uint32_t one = (lane >> 3) == (lane & 3) ? 0x3f80u << (lane << 2 & 16) : 0u;
                    float a[5][4] = {};
#pragma unroll 2
                    for (int k = 0; k < (1 << sh >> 1); k++) {
                        const uint32_t ad = sm + st * SD_ST + ((k << (6 - sh)) + lrow) * 1280 + lane * 8;
#pragma unroll
                        for (int q2 = 0; q2 < 5; q2++) {
                            uint32_t z0[2], z1[2];
                            lds64(z0, ad + q2 * 256); lds64(z1, ad + 3 * SD_ST + q2 * 256);
                            mma16(a[q2], z0[0], z0[1], z1[0], z1[1], one, one);
                        }
                    }
#pragma unroll
                    for (int q2 = 0; q2 < 10; q2++) { as[1][q2] = as[0][q2]; as[0][q2] = pack2(a[q2 >> 1][2 * (q2 & 1)], a[q2 >> 1][2 * (q2 & 1) + 1]); }
                }
                bar_sync(2 + wg, 128);
                if ((tid & 127) < 6) mbar_arrive(EMPTY + 8 * (st + (tid & 127)));
                uint32_t key = 0;
#pragma unroll 1
                for (int lrow = lw; lrow < nr; lrow += 8) {
                    const int row = row0 + lrow;
                    const uint32_t k1 = ln_row(as[0], xin[0], row, sm + SD_PAR, lds32(LOW), out, ef, lane);
                    if (lane == lrow >> 3) key = k1;
#pragma unroll
                    for (int q2 = 0; q2 < 5; q2++) { as[0][2 * q2] = as[1][2 * q2]; as[0][2 * q2 + 1] = as[1][2 * q2 + 1]; xin[0][q2] = xin[1][q2]; }
                }
                if (b == 14) { EPT(tid == 128, 20); key_out(key); EPT(tid == 128, 21); }
                else {
                    if (lane < 2) asm volatile("st.shared.u32 [%0], %1;" :: "r"(KEYS + (q & 7) * 64 + warp * 8 + lane * 4), "r"(key) : "memory");
                    __syncwarp();
                    if (lane == 0) asm volatile("st.release.cta.shared.u32 [%0], %1;" :: "r"(ADONE + warp * 4), "r"(q + 1) : "memory");
                }
                ph ^= st != 0; st ^= 6;
            }
        }
    }
    __syncwarp();
    asm volatile("griddepcontrol.wait;" ::: "memory");
}

#define P_D1 500
#define P_DL 700
#define P_DG 29
typedef CUresult (*EncodeFn)(CUtensorMap*, CUtensorMapDataType, cuuint32_t, void*, const cuuint64_t*, const cuuint64_t*, const cuuint32_t*, const cuuint32_t*,
                             CUtensorMapInterleave, CUtensorMapSwizzle, CUtensorMapL2promotion, CUtensorMapFloatOOBfill);
static EncodeFn s_encode = nullptr;
static void make_map(CUtensorMap* m, const void* p, int rows, int cols, int box_rows, int box_cols = 64) {
    cuuint64_t dims[2] = {(cuuint64_t)cols, (cuuint64_t)rows}, strides[1] = {(cuuint64_t)cols * 2};
    cuuint32_t box[2] = {(cuuint32_t)box_cols, (cuuint32_t)box_rows}, es[2] = {1, 1};
    s_encode(m, CU_TENSOR_MAP_DATA_TYPE_BFLOAT16, 2, (void*)p, dims, strides, box, es, CU_TENSOR_MAP_INTERLEAVE_NONE,
             box_cols == 64 ? CU_TENSOR_MAP_SWIZZLE_128B : box_cols == 32 ? CU_TENSOR_MAP_SWIZZLE_64B : CU_TENSOR_MAP_SWIZZLE_NONE, CU_TENSOR_MAP_L2_PROMOTION_L2_256B, CU_TENSOR_MAP_FLOAT_OOB_FILL_NONE);
}
static void make_map3(CUtensorMap* m, const void* p, int rows, int cols, int box_rows, int box_chunks, int cw = 64) {
    cuuint64_t dims[3] = {(cuuint64_t)cw, (cuuint64_t)rows, (cuuint64_t)(cols / cw)}, strides[2] = {(cuuint64_t)cols * 2, (cuuint64_t)cw * 2};
    cuuint32_t box[3] = {(cuuint32_t)cw, (cuuint32_t)box_rows, (cuuint32_t)box_chunks}, es[3] = {1, 1, 1};
    s_encode(m, CU_TENSOR_MAP_DATA_TYPE_BFLOAT16, 3, (void*)p, dims, strides, box, es, CU_TENSOR_MAP_INTERLEAVE_NONE,
             cw == 64 ? CU_TENSOR_MAP_SWIZZLE_128B : CU_TENSOR_MAP_SWIZZLE_64B, CU_TENSOR_MAP_L2_PROMOTION_L2_256B, CU_TENSOR_MAP_FLOAT_OOB_FILL_NONE);
}
template <typename T> static void* sym(T& s) { void* p = nullptr; cudaGetSymbolAddress(&p, s); return p; }

extern "C" void kernel_launch(void* const* d_in, const int* in_sizes, int n_in, void* d_out, int out_size) {
    const bf16 *x = (const bf16*)d_in[0], *mem0 = (const bf16*)d_in[1], *Wq = (const bf16*)d_in[2], *Wk = (const bf16*)d_in[3],
               *Wv = (const bf16*)d_in[4], *Wo = (const bf16*)d_in[5], *wr = (const bf16*)d_in[8], *wgate = (const bf16*)d_in[9],
               *wup = (const bf16*)d_in[10], *wdown = (const bf16*)d_in[11], *c = (const bf16*)d_in[12], *wmod = (const bf16*)d_in[13];
    bf16* out = (bf16*)d_out;
    if (!s_encode) {
        cudaDriverEntryPointQueryResult qr;
        cudaGetDriverEntryPoint("cuTensorMapEncodeTiled", (void**)&s_encode, cudaEnableDefault, &qr);
        cudaFuncSetAttribute(k_side, cudaFuncAttributeMaxDynamicSharedMemorySize, SD_SMEM);
        cudaFuncSetAttribute(k_chain, cudaFuncAttributeMaxDynamicSharedMemorySize, C_SMEM);
    }
    ChainMaps cm; SideMaps sd;
    make_map(&sd.h, sym(g_h), S_TOK, DM, 128); make_map3(&sd.wv, Wv, DM, HD, 64, 3);
    make_map3(&sd.ost, sym(g_o), S_TOK, HD, 16, 3); make_map(&sd.o, sym(g_o), S_TOK, HD, 128, 32); make_map3(&sd.wo, Wo, HD, DM, 32, 5);
    make_map(&sd.slab, sym(g_slab), 16 * KSPLIT * 128, DM, 64); make_map3(&cm.slab2, sym(g_slab), 16 * KSPLIT * 128, DM, 64, 2);
    make_map3(&cm.wo15, Wo, HD, DM, 192, 2); make_map3(&cm.o15, sym(g_o), S_TOK, HD, 64, 2);
    for (int i = 0; i < 3; i++) {
        cuuint64_t dims[3] = {256, 320, 16 * KSPLIT}, strides[2] = {512, 128 * DM * 2};
        cuuint32_t box[3] = {256, 40u >> i, 2u << i}, es[3] = {1, 1, 1};
        s_encode(&sd.lnp[i], CU_TENSOR_MAP_DATA_TYPE_BFLOAT16, 3, sym(g_slab), dims, strides, box, es, CU_TENSOR_MAP_INTERLEAVE_NONE,
                 CU_TENSOR_MAP_SWIZZLE_NONE, CU_TENSOR_MAP_L2_PROMOTION_L2_256B, CU_TENSOR_MAP_FLOAT_OOB_FILL_NONE);
    }
    make_map(&cm.wq, Wq, DM, HD, 640 / WP); make_map(&cm.wk, Wk, DM, HD, 640 / WP); make_map(&cm.wv, Wv, DM, HD, 160); make_map3(&cm.wo, Wo, HD, DM, 64, 7, 32);
    make_map3(&cm.h2, sym(g_h), S_TOK, DM, 32, 2);
    ChainArgs ar = {x, mem0, c, wmod, wgate, wup, wdown, out, P_D1, P_DL, P_DG};
    k_chain<<<96, 384, C_SMEM>>>(cm, ar);
    cudaLaunchConfig_t cfg = {};
    cfg.gridDim = dim3(N_SIDE); cfg.blockDim = dim3(384); cfg.dynamicSmemBytes = SD_SMEM; cfg.stream = cudaStreamPerThread;
    cudaLaunchAttribute at[1]; at[0].id = cudaLaunchAttributeProgrammaticStreamSerialization; at[0].val.programmaticStreamSerializationAllowed = 1;
    cfg.attrs = at; cfg.numAttrs = 1;
    cudaLaunchKernelEx(&cfg, k_side, sd, x, wr, wmod, c, out);
}
```
